```python
import torch

def _softmax(x, axis=-1):
    return torch.softmax(x, dim=axis)

def _gelu(x):
    return torch.nn.functional.gelu(x, approximate='tanh')

def _silu(x):
    return torch.nn.functional.silu(x)

def _sigmoid(x):
    return torch.sigmoid(x)

def _layernorm(x, axis=-1, eps=1e-05):
    m = x.mean(dim=axis, keepdim=True)
    v = x.var(dim=axis, keepdim=True, unbiased=False)
    return (x - m) / torch.sqrt(v + eps)

def _scatter_add(tgt, idx, src, axis=0):
    return tgt.clone().index_add_(axis, idx, src)

def _segment_sum(src, seg, n):
    out = torch.zeros((n,) + src.shape[1:], dtype=src.dtype)
    return out.index_add_(0, seg, src)

def _pad(x, pw):
    flat = tuple((v for pair in reversed(pw) for v in pair))
    return torch.nn.functional.pad(x, flat)
kernel_name = 'adaLN_cond__memory_aug_recurrent_mem_tr__dense_activation_silu__prompt'

def setup_inputs():

    _w = lambda a: (lambda t: t.to(torch.bfloat16) if t.is_floating_point() else t)(torch.as_tensor(a))

    def _A_setup():
        B, S, Dm = (1, 2048, 640)
        H, Dh = (32, 192)
        M, seg = (8, 32)
        seg = min(seg, S)
        S = S // seg * seg
        return {'x': _w((lambda *s: torch.randn(*s, dtype=torch.bfloat16) * 0.05)(B, S, Dm)), 'mem0': _w((lambda *s: torch.randn(*s, dtype=torch.bfloat16) * 0.8)(B, M, Dm)), 'Wq': _w((lambda *s: torch.randn(*s, dtype=torch.bfloat16) * 0.8)(Dm, H, Dh) * Dm ** (-0.5)), 'Wk': _w((lambda *s: torch.randn(*s, dtype=torch.bfloat16) * 0.8)(Dm, H, Dh) * Dm ** (-0.5)), 'Wv': _w((lambda *s: torch.randn(*s, dtype=torch.bfloat16) * 0.8)(Dm, H, Dh) * Dm ** (-0.5)), 'Wo': _w((lambda *s: torch.randn(*s, dtype=torch.bfloat16) * 0.8)(H, Dh, Dm) * (H * Dh) ** (-0.5)), 'seg_len': seg}
    _A_in = _A_setup()

    def _B_setup():
        B, S, D, F = (1, 2048, 640, 1536)
        return {'x': _w((lambda *s: torch.randn(*s, dtype=torch.bfloat16) * 0.05)(B, S, D)), 'w1': _w((lambda *s: torch.randn(*s, dtype=torch.bfloat16) * 0.8)(D, F) * D ** (-0.5)), 'w2': _w((lambda *s: torch.randn(*s, dtype=torch.bfloat16) * 0.2)(F, D) * F ** (-0.5))}
    _B_in = _B_setup()
    return {'A_x': _A_in['x'], 'A_mem0': _A_in['mem0'], 'A_Wq': _A_in['Wq'], 'A_Wk': _A_in['Wk'], 'A_Wv': _A_in['Wv'], 'A_Wo': _A_in['Wo'], 'A_seg_len': _A_in['seg_len'], 'B_x': _B_in['x'], 'B_w1': _B_in['w1'], 'B_w2': _B_in['w2'], 'c': _w((lambda *s: torch.randn(*s, dtype=torch.bfloat16) * 0.1)(1, 640) * 8.0), 'w_mod': _w((lambda *s: torch.randn(*s, dtype=torch.bfloat16) * 0.1)(640, 6 * 640) * 640 ** (-0.5) * 8.0)}

def reference(A_x, A_mem0, A_Wq, A_Wk, A_Wv, A_Wo, A_seg_len, B_x, B_w1, B_w2, c, w_mod):

    def _A_ref(x, mem0, Wq, Wk, Wv, Wo, seg_len):
        B, S, Dm = x.shape
        H, Dh = (Wq.shape[1], Wq.shape[2])
        M = mem0.shape[1]
        scale = Dh ** (-0.5)
        n_seg = S // seg_len
        L = M + seg_len
        idx = torch.arange(L)
        mask = (idx[:, None] < M) | (idx[:, None] >= idx[None, :])
        mem = mem0
        outs = []
        for s in range(n_seg):
            xs = x[:, s * seg_len:(s + 1) * seg_len, :].clone()
            h = torch.concatenate([mem, xs], axis=1)
            q = torch.einsum('btd,dhe->bhte', h, Wq)
            k = torch.einsum('btd,dhe->bhte', h, Wk)
            v = torch.einsum('btd,dhe->bhte', h, Wv)
            scores = torch.einsum('bhqe,bhke->bhqk', q, k) * scale
            scores = torch.where(mask[None, None], scores, -1000000000.0)
            p = _softmax(scores, axis=-1)
            o = torch.einsum('bhqk,bhke->bhqe', p, v)
            o = torch.einsum('bhte,hed->btd', o, Wo)
            mem = o[:, :M, :].clone()
            outs.append(o[:, M:, :])
        return torch.concatenate(outs, axis=1)

    def _B_ref(x, w1, w2):
        h = torch.einsum('bsd,df->bsf', x, w1)
        h = _silu(h)
        out = torch.einsum('bsf,fd->bsd', h, w2)
        return out
    x = A_x
    mod = (_silu(c) @ w_mod).reshape(c.shape[0], 6, 1, -1)
    sa, ca, ga, sb, cb, gb = (mod[:, 0].clone(), mod[:, 1].clone(), mod[:, 2].clone(), mod[:, 3].clone(), mod[:, 4].clone(), mod[:, 5].clone())
    h = _layernorm(x, axis=-1) * (1 + ca) + sa
    x = x + ga * _A_ref(h, A_mem0, A_Wq, A_Wk, A_Wv, A_Wo, A_seg_len)
    h = _layernorm(x, axis=-1) * (1 + cb) + sb
    x = x + gb * _B_ref(h, B_w1, B_w2)
    return x
```

```cpp
#include <cuda_runtime.h>
#include <cuda_bf16.h>
#include <cuda.h>
#include <stdint.h>

typedef __nv_bfloat16 bf16;

constexpr int SEQ = 2048, DM = 640, NH = 32, DH = 192, NSEG = 64, FF = 1536, HD = NH * DH;

__device__ float g_mod[6 * DM];
__device__ __align__(1024) bf16 g_ht[(size_t)SEQ * DM];
__device__ __align__(1024) bf16 g_ox[(size_t)SEQ * HD];
__device__ __align__(1024) bf16 g_x1[(size_t)SEQ * DM];
__device__ __align__(1024) bf16 g_h2[(size_t)SEQ * DM];
__device__ __align__(1024) bf16 g_act[(size_t)SEQ * FF];
__device__ __align__(8192) uint32_t g_buf1[80 * 2 * 2048];
__device__ __align__(8192) uint32_t g_buf2[4 * 3 * 2048];
__device__ uint32_t g_choice[128];
__device__ uint32_t g_epoch;

__device__ __forceinline__ float bfr(float x) { return __bfloat162float(__float2bfloat16_rn(x)); }
__device__ __forceinline__ uint32_t pack2(float a, float b) {
    uint32_t r; asm("cvt.rn.bf16x2.f32 %0, %1, %2;" : "=r"(r) : "f"(b), "f"(a)); return r;
}
__device__ __forceinline__ float bflo(uint32_t v) { return __uint_as_float(v << 16); }
__device__ __forceinline__ float bfhi(uint32_t v) { return __uint_as_float(v & 0xffff0000u); }
__device__ __forceinline__ uint32_t smem_u32(const void* p) { return (uint32_t)__cvta_generic_to_shared(p); }

__device__ __forceinline__ void mbar_init(uint32_t bar, uint32_t cnt) {
    asm volatile("mbarrier.init.shared::cta.b64 [%0], %1;" :: "r"(bar), "r"(cnt) : "memory");
}
__device__ __forceinline__ void mbar_arrive(uint32_t bar) {
    asm volatile("mbarrier.arrive.shared::cta.b64 _, [%0];" :: "r"(bar) : "memory");
}
__device__ __forceinline__ void mbar_expect(uint32_t bar, uint32_t bytes) {
    asm volatile("mbarrier.arrive.expect_tx.shared::cta.b64 _, [%0], %1;" :: "r"(bar), "r"(bytes) : "memory");
}
__device__ __forceinline__ bool mbar_try(uint32_t bar, uint32_t parity) {
    uint32_t ok;
    asm volatile("{\n\t.reg .pred p;\n\tmbarrier.try_wait.parity.shared::cta.b64 p, [%1], %2;\n\tselp.u32 %0, 1, 0, p;\n\t}"
                 : "=r"(ok) : "r"(bar), "r"(parity) : "memory");
    return ok != 0;
}
__device__ __forceinline__ bool mbar_try_cluster(uint32_t bar, uint32_t parity) {
    uint32_t ok;
    asm volatile("{\n\t.reg .pred p;\n\tmbarrier.try_wait.parity.acquire.cluster.shared::cta.b64 p, [%1], %2;\n\tselp.u32 %0, 1, 0, p;\n\t}"
                 : "=r"(ok) : "r"(bar), "r"(parity) : "memory");
    return ok != 0;
}
__device__ __forceinline__ void mbar_wait(uint32_t bar, uint32_t parity) {
    uint32_t guard = 0;
    while (!mbar_try(bar, parity)) { if (++guard > (1u << 22)) __trap(); }
}
__device__ __forceinline__ void mbar_wait_cluster(uint32_t bar, uint32_t parity) {
    uint32_t guard = 0;
    while (!mbar_try_cluster(bar, parity)) { if (++guard > (1u << 22)) __trap(); }
}
__device__ __forceinline__ void bar_sync(int id, int n) { asm volatile("bar.sync %0, %1;" :: "r"(id), "r"(n) : "memory"); }
__device__ __forceinline__ void fence_async() { asm volatile("fence.proxy.async.shared::cta;" ::: "memory"); }
__device__ __forceinline__ void cluster_sync() {
    asm volatile("barrier.cluster.arrive.release.aligned;\n\tbarrier.cluster.wait.acquire.aligned;" ::: "memory");
}
__device__ __forceinline__ uint32_t mapa(uint32_t a, uint32_t rank) {
    uint32_t r; asm("mapa.shared::cluster.u32 %0, %1, %2;" : "=r"(r) : "r"(a), "r"(rank)); return r;
}
__device__ __forceinline__ void st_async1(uint32_t a, uint32_t v, uint32_t bar) {
    asm volatile("st.async.weak.shared::cluster.mbarrier::complete_tx::bytes.b32 [%0], %1, [%2];" :: "r"(a), "r"(v), "r"(bar) : "memory");
}
__device__ __forceinline__ void st_async2(uint32_t a, float x, float y, uint32_t bar) {
    asm volatile("st.async.weak.shared::cluster.mbarrier::complete_tx::bytes.v2.f32 [%0], {%1,%2}, [%3];" :: "r"(a), "f"(x), "f"(y), "r"(bar) : "memory");
}
__device__ __forceinline__ void st_async4(uint32_t a, const float* c, uint32_t bar) {
    asm volatile("st.async.weak.shared::cluster.mbarrier::complete_tx::bytes.v4.f32 [%0], {%1,%2,%3,%4}, [%5];"
                 :: "r"(a), "f"(c[0]), "f"(c[1]), "f"(c[2]), "f"(c[3]), "r"(bar) : "memory");
}
__device__ __forceinline__ void bulk_g2s(uint32_t dst, const void* src, uint32_t bytes, uint32_t bar) {
    asm volatile("cp.async.bulk.shared::cluster.global.mbarrier::complete_tx::bytes [%0], [%1], %2, [%3];"
                 :: "r"(dst), "l"(src), "r"(bytes), "r"(bar) : "memory");
}
__device__ __forceinline__ void cpa16(uint32_t s, const void* g) {
    asm volatile("cp.async.cg.shared.global [%0], [%1], 16;" :: "r"(s), "l"(g) : "memory");
}
__device__ __forceinline__ void cpa_wait_all() { asm volatile("cp.async.wait_all;" ::: "memory"); }
__device__ __forceinline__ void ldsm4(uint32_t* r, uint32_t a) {
    asm volatile("ldmatrix.sync.aligned.m8n8.x4.shared.b16 {%0,%1,%2,%3}, [%4];" : "=r"(r[0]), "=r"(r[1]), "=r"(r[2]), "=r"(r[3]) : "r"(a) : "memory");
}
__device__ __forceinline__ void ldsm4t(uint32_t* r, uint32_t a) {
    asm volatile("ldmatrix.sync.aligned.m8n8.x4.trans.shared.b16 {%0,%1,%2,%3}, [%4];" : "=r"(r[0]), "=r"(r[1]), "=r"(r[2]), "=r"(r[3]) : "r"(a) : "memory");
}
__device__ __forceinline__ void stsm2t(uint32_t a, uint32_t r0, uint32_t r1) {
    asm volatile("stmatrix.sync.aligned.m8n8.x2.trans.shared.b16 [%0], {%1,%2};" :: "r"(a), "r"(r0), "r"(r1) : "memory");
}
__device__ __forceinline__ void stsm4t(uint32_t a, uint32_t r0, uint32_t r1, uint32_t r2, uint32_t r3) {
    asm volatile("stmatrix.sync.aligned.m8n8.x4.trans.shared.b16 [%0], {%1,%2,%3,%4};" :: "r"(a), "r"(r0), "r"(r1), "r"(r2), "r"(r3) : "memory");
}
__device__ __forceinline__ uint32_t movm(uint32_t v) {
    uint32_t r; asm volatile("movmatrix.sync.aligned.m8n8.trans.b16 %0, %1;" : "=r"(r) : "r"(v)); return r;
}
__device__ __forceinline__ void mma16(float* c, uint32_t a0, uint32_t a1, uint32_t a2, uint32_t a3, uint32_t b0, uint32_t b1) {
    asm volatile("mma.sync.aligned.m16n8k16.row.col.f32.bf16.bf16.f32 {%0,%1,%2,%3}, {%4,%5,%6,%7}, {%8,%9}, {%0,%1,%2,%3};"
                 : "+f"(c[0]), "+f"(c[1]), "+f"(c[2]), "+f"(c[3]) : "r"(a0), "r"(a1), "r"(a2), "r"(a3), "r"(b0), "r"(b1));
}
__device__ __forceinline__ void mma8(float* c, uint32_t a0, uint32_t a1, uint32_t b0) {
    asm volatile("mma.sync.aligned.m16n8k8.row.col.f32.bf16.bf16.f32 {%0,%1,%2,%3}, {%4,%5}, {%6}, {%0,%1,%2,%3};"
                 : "+f"(c[0]), "+f"(c[1]), "+f"(c[2]), "+f"(c[3]) : "r"(a0), "r"(a1), "r"(b0));
}
__device__ __forceinline__ uint64_t make_desc(uint32_t saddr, uint32_t lbo, uint32_t sbo, uint32_t layout) {
    return (uint64_t)((saddr & 0x3FFFF) >> 4) | ((uint64_t)(lbo >> 4) << 16) | ((uint64_t)(sbo >> 4) << 32) | ((uint64_t)layout << 62);
}
__device__ __forceinline__ void wg_fence() { asm volatile("wgmma.fence.sync.aligned;" ::: "memory"); }
__device__ __forceinline__ void wg_commit() { asm volatile("wgmma.commit_group.sync.aligned;" ::: "memory"); }
template <int N> __device__ __forceinline__ void wg_wait() { asm volatile("wgmma.wait_group.sync.aligned %0;" :: "n"(N) : "memory"); }

__device__ __forceinline__ void wg_rs32(float* d, const uint32_t* a, uint64_t db, int sc) {
    asm volatile("{\n\t.reg .pred p;\n\tsetp.ne.b32 p, %21, 0;\n\t"
        "wgmma.mma_async.sync.aligned.m64n32k16.f32.bf16.bf16 {%0,%1,%2,%3,%4,%5,%6,%7,%8,%9,%10,%11,%12,%13,%14,%15}, {%16,%17,%18,%19}, %20, p, 1, 1, 0;\n\t}"
        : "+f"(d[0]), "+f"(d[1]), "+f"(d[2]), "+f"(d[3]), "+f"(d[4]), "+f"(d[5]), "+f"(d[6]), "+f"(d[7]),
          "+f"(d[8]), "+f"(d[9]), "+f"(d[10]), "+f"(d[11]), "+f"(d[12]), "+f"(d[13]), "+f"(d[14]), "+f"(d[15])
        : "r"(a[0]), "r"(a[1]), "r"(a[2]), "r"(a[3]), "l"(db), "r"(sc));
}
__device__ __forceinline__ void wg_ss32(float* d, uint64_t da, uint64_t db, int sc) {
    asm volatile("{\n\t.reg .pred p;\n\tsetp.ne.b32 p, %18, 0;\n\t"
        "wgmma.mma_async.sync.aligned.m64n32k16.f32.bf16.bf16 {%0,%1,%2,%3,%4,%5,%6,%7,%8,%9,%10,%11,%12,%13,%14,%15}, %16, %17, p, 1, 1, 1, 0;\n\t}"
        : "+f"(d[0]), "+f"(d[1]), "+f"(d[2]), "+f"(d[3]), "+f"(d[4]), "+f"(d[5]), "+f"(d[6]), "+f"(d[7]),
          "+f"(d[8]), "+f"(d[9]), "+f"(d[10]), "+f"(d[11]), "+f"(d[12]), "+f"(d[13]), "+f"(d[14]), "+f"(d[15])
        : "l"(da), "l"(db), "r"(sc));
}
__device__ __forceinline__ void wg_ss8(float* d, uint64_t da, uint64_t db, int sc) {
    asm volatile("{\n\t.reg .pred p;\n\tsetp.ne.b32 p, %6, 0;\n\t"
        "wgmma.mma_async.sync.aligned.m64n8k16.f32.bf16.bf16 {%0,%1,%2,%3}, %4, %5, p, 1, 1, 1, 1;\n\t}"
        : "+f"(d[0]), "+f"(d[1]), "+f"(d[2]), "+f"(d[3]) : "l"(da), "l"(db), "r"(sc));
}

__device__ __forceinline__ uint4 ld_relaxed4(const void* p) {
    uint4 v;
    asm volatile("ld.relaxed.gpu.global.v4.u32 {%0,%1,%2,%3}, [%4];" : "=r"(v.x), "=r"(v.y), "=r"(v.z), "=r"(v.w) : "l"(p) : "memory");
    return v;
}
__device__ __forceinline__ void st_relaxed2(void* p, uint32_t a, uint32_t b) {
    asm volatile("st.relaxed.gpu.global.v2.u32 [%0], {%1,%2};" :: "l"(p), "r"(a), "r"(b) : "memory");
}
__device__ __forceinline__ void st_relaxed1(void* p, uint32_t a) {
    asm volatile("st.relaxed.gpu.global.u32 [%0], %1;" :: "l"(p), "r"(a) : "memory");
}
__device__ __forceinline__ uint32_t ld_acquire1(const uint32_t* p) {
    uint32_t v; asm volatile("ld.acquire.gpu.global.u32 %0, [%1];" : "=r"(v) : "l"(p) : "memory"); return v;
}
__device__ __forceinline__ void st_release1(uint32_t* p, uint32_t a) {
    asm volatile("st.release.gpu.global.u32 [%0], %1;" :: "l"(p), "r"(a) : "memory");
}
__device__ __forceinline__ uint4 lds4(uint32_t s) {
    uint4 v; asm volatile("ld.shared.v4.u32 {%0,%1,%2,%3}, [%4];" : "=r"(v.x), "=r"(v.y), "=r"(v.z), "=r"(v.w) : "r"(s) : "memory"); return v;
}
__device__ __forceinline__ float4 lds4f(uint32_t s) {
    float4 v; asm volatile("ld.shared.v4.f32 {%0,%1,%2,%3}, [%4];" : "=f"(v.x), "=f"(v.y), "=f"(v.z), "=f"(v.w) : "r"(s) : "memory"); return v;
}
__device__ __forceinline__ float2 lds2f(uint32_t s) {
    float2 v; asm volatile("ld.shared.v2.f32 {%0,%1}, [%2];" : "=f"(v.x), "=f"(v.y) : "r"(s) : "memory"); return v;
}
__device__ __forceinline__ uint32_t clk32() { uint32_t c; asm volatile("mov.u32 %0, %%clock;" : "=r"(c) :: "memory"); return c; }
__device__ __forceinline__ uint32_t tagw(float v, uint32_t tag) { return ((__float_as_uint(v) + 8u) & ~15u) | tag; }
__device__ __forceinline__ bool ok4(const uint4& v, uint32_t tag) { return (((v.x ^ tag) | (v.y ^ tag) | (v.z ^ tag) | (v.w ^ tag)) & 15u) == 0; }
__device__ __forceinline__ bool oks(const uint4& v) { return v.x != 0xFFFFFFFFu && v.y != 0xFFFFFFFFu && v.z != 0xFFFFFFFFu && v.w != 0xFFFFFFFFu; }
__device__ __forceinline__ float uf(uint32_t x) { return __uint_as_float(x & ~15u); }

__global__ void __launch_bounds__(256) k_mod(const bf16* __restrict__ c, const bf16* __restrict__ wmod) {
    __shared__ float sc[DM];
    __shared__ float red[8][64];
    const int tid = threadIdx.x;
    for (int i = tid; i < DM; i += 256) {
        float v = __bfloat162float(c[i]);
        sc[i] = bfr(v / (1.0f + __expf(-v)));
    }
    __syncthreads();
    const int cp = tid & 31, kg = tid >> 5;
    const int col = blockIdx.x * 64 + cp * 2;
    float a0 = 0.f, a1 = 0.f;
    #pragma unroll 8
    for (int k = kg * 80; k < kg * 80 + 80; k++) {
        uint32_t w = *(const uint32_t*)(wmod + (size_t)k * (6 * DM) + col);
        a0 += sc[k] * bflo(w); a1 += sc[k] * bfhi(w);
    }
    red[kg][cp * 2] = a0; red[kg][cp * 2 + 1] = a1;
    __syncthreads();
    if (tid < 64) {
        float s = 0.f;
        #pragma unroll
        for (int i = 0; i < 8; i++) s += red[i][tid];
        g_mod[blockIdx.x * 64 + tid] = bfr(s);
    }
    if (blockIdx.x == 0 && tid == 0) g_epoch = g_epoch + 1;
}

template <int MODE>
__global__ void __launch_bounds__(256) k_ln(const bf16* __restrict__ xin) {
    const int lane = threadIdx.x & 31, row = blockIdx.x * 8 + (threadIdx.x >> 5);
    const bf16* src = (MODE == 0 ? xin : g_x1) + (size_t)row * DM;
    const float* shift = g_mod + (MODE == 0 ? 0 : 3 * DM);
    const float* scale = g_mod + (MODE == 0 ? DM : 4 * DM);
    float v[3][8];
    float s = 0.f;
    #pragma unroll
    for (int i = 0; i < 3; i++) {
        int c = lane + 32 * i;
        if (c < 80) {
            uint4 u = *(const uint4*)(src + c * 8);
            v[i][0] = bflo(u.x); v[i][1] = bfhi(u.x); v[i][2] = bflo(u.y); v[i][3] = bfhi(u.y);
            v[i][4] = bflo(u.z); v[i][5] = bfhi(u.z); v[i][6] = bflo(u.w); v[i][7] = bfhi(u.w);
        } else {
            #pragma unroll
            for (int j = 0; j < 8; j++) v[i][j] = 0.f;
        }
        #pragma unroll
        for (int j = 0; j < 8; j++) s += v[i][j];
    }
    #pragma unroll
    for (int o = 16; o > 0; o >>= 1) s += __shfl_xor_sync(0xffffffffu, s, o);
    const float mean = s * (1.0f / DM);
    float q = 0.f;
    #pragma unroll
    for (int i = 0; i < 3; i++) {
        if (lane + 32 * i < 80) {
            #pragma unroll
            for (int j = 0; j < 8; j++) { float d = v[i][j] - mean; q += d * d; }
        }
    }
    #pragma unroll
    for (int o = 16; o > 0; o >>= 1) q += __shfl_xor_sync(0xffffffffu, q, o);
    const float mb = bfr(mean);
    const float var = bfr(q * (1.0f / DM));
    const float sd = bfr(sqrtf(bfr(var + 1e-5f)));
    #pragma unroll
    for (int i = 0; i < 3; i++) {
        int c = lane + 32 * i;
        if (c < 80) {
            float o[8];
            #pragma unroll
            for (int j = 0; j < 8; j++) {
                float n = bfr(bfr(v[i][j] - mb) / sd);
                float m1 = bfr(1.0f + scale[c * 8 + j]);
                o[j] = bfr(n * m1) + shift[c * 8 + j];
            }
            uint4 u = make_uint4(pack2(o[0], o[1]), pack2(o[2], o[3]), pack2(o[4], o[5]), pack2(o[6], o[7]));
            if (MODE == 0) {
                int seg = row >> 5, r = row & 31, blk = c >> 3, cc = c & 7;
                *(uint4*)(g_ht + (size_t)seg * 20480 + blk * 2048 + r * 64 + ((cc ^ (r & 7)) << 3)) = u;
            } else {
                *(uint4*)(g_h2 + (size_t)row * DM + c * 8) = u;
            }
        }
    }
}

constexpr int SM_WV = 0;
constexpr int SM_HB = 81920;
constexpr int SM_WO = SM_HB + 40960;
constexpr int SM_QX = SM_WO + 77824;
constexpr int SM_KS = SM_QX + 4096;
constexpr int SM_QM = SM_KS + 5120;
constexpr int SM_XS = SM_QM + 1024;
constexpr int SM_MS = SM_XS + 12288;
constexpr int SM_OS = SM_MS + 3840;
constexpr int SM_BAR = SM_OS + 3072;
constexpr int SM_CH = SM_BAR + 128;
constexpr int SM_TOTAL = SM_CH + 128;
static_assert(SM_TOTAL <= 232448 - 1024, "smem");

enum { B_MEM_FULL = 0, B_MEM_FREE, B_HLO_FULL, B_HHI_FULL, B_HLO_FREE, B_HHI_FREE, B_MS, B_O, B_XS };

__device__ __forceinline__ int probe_blk(uint32_t* blk) {
    uint32_t t0 = 0xffffffffu, t1 = 0xffffffffu, acc = 0;
    for (int rep = 0; rep < 5; rep++) {
        #pragma unroll
        for (int pg = 0; pg < 2; pg++) {
            uint32_t c0 = clk32();
            uint32_t v = atomicOr(blk + pg * 1024 + acc, 0u);
            acc = (v == 0x12345678u) ? 1u : 0u;
            asm volatile("" :: "r"(acc) : "memory");
            uint32_t c1 = clk32() + acc;
            uint32_t d = c1 - c0;
            if (rep > 0) { if (pg == 0) t0 = min(t0, d); else t1 = min(t1, d); }
        }
    }
    return t1 < t0 ? 1 : 0;
}

__device__ __forceinline__ uint32_t wo_tile_off(int w) {
    if (w < 8) return w * 6144;
    if (w < 12) return 8 * 6144 + (w - 8) * 4096 - 2048;
    return 8 * 6144 + 4 * 4096 + (w - 12) * 6144;
}

template <int NRES, int NPRE>
__device__ __forceinline__ void wo_phase(uint32_t sb, int w, int lane, const uint32_t (*res)[4], uint32_t parity,
                                         uint32_t tag, uint32_t off0, uint32_t off1) {
    const int er = (lane & 7) + 8 * (lane >> 4);
    const uint32_t aaddr = sb + SM_WO + wo_tile_off(w) + er * 32 + ((((lane >> 3) & 1) ^ ((er >> 2) & 1)) << 4);
    uint32_t pre[NPRE][4];
    #pragma unroll
    for (int i = 0; i < NPRE; i++) ldsm4t(pre[i], aaddr + (NRES + i) * 512);
    mbar_wait_cluster(sb + SM_BAR + B_O * 8, parity);
    float c0[4] = {0.f, 0.f, 0.f, 0.f}, c1[4] = {0.f, 0.f, 0.f, 0.f};
    const uint32_t baddr = sb + SM_OS + lane * 16;
    #pragma unroll
    for (int kp = 0; kp < 6; kp++) {
        uint32_t b[4];
        ldsm4t(b, baddr + kp * 512);
        #pragma unroll
        for (int hh = 0; hh < 2; hh++) {
            const int kt = kp * 2 + hh;
            float* c = hh ? c1 : c0;
            if (kt < NRES) mma16(c, res[kt][0], res[kt][1], res[kt][2], res[kt][3], b[hh * 2], b[hh * 2 + 1]);
            else if (kt < NRES + NPRE) mma16(c, pre[kt - NRES][0], pre[kt - NRES][1], pre[kt - NRES][2], pre[kt - NRES][3], b[hh * 2], b[hh * 2 + 1]);
            else {
                uint32_t a[4];
                ldsm4t(a, aaddr + kt * 512);
                mma16(c, a[0], a[1], a[2], a[3], b[hh * 2], b[hh * 2 + 1]);
            }
        }
    }
    char* base = (char*)g_buf1;
    st_relaxed2(base + off0, tagw(c0[0] + c1[0], tag), tagw(c0[1] + c1[1], tag));
    st_relaxed2(base + off1, tagw(c0[2] + c1[2], tag), tagw(c0[3] + c1[3], tag));
}

__device__ __forceinline__ uint32_t hop1_off(uint32_t sb, int col, int h, int t) {
    const int r = col >> 3, j = (col >> 2) & 1;
    uint32_t ch;
    asm volatile("ld.shared.u8 %0, [%1];" : "=r"(ch) : "r"(sb + SM_CH + r) : "memory");
    return (uint32_t)((r * 2 + j) * 8192 + ((ch >> j) & 1) * 4096 + (col & 3) * 1024 + h * 32 + t * 8);
}

__global__ void __launch_bounds__(512, 1)
k_rec(const bf16* __restrict__ mem0, const bf16* __restrict__ Wq, const bf16* __restrict__ Wk,
      const bf16* __restrict__ Wv, const bf16* __restrict__ Wo) {
    extern __shared__ uint8_t smem_raw[];
    const uint32_t sb = (smem_u32(smem_raw) + 1023u) & ~1023u;
    const int tid = threadIdx.x, lane = tid & 31, warp = tid >> 5, wg = tid >> 7;
    const int b = blockIdx.x, h = b / 3, p = b % 3;
    const int g = lane >> 2, t = lane & 3;
    const int tile0 = p == 0 ? 0 : (p == 1 ? 14 : 27);
    const int ntile = p == 0 ? 14 : 13;
    const uint32_t bar = sb + SM_BAR;

    if (tid == 0) {
        mbar_init(bar + B_MEM_FULL * 8, 4);
        mbar_init(bar + B_MEM_FREE * 8, 12);
        mbar_init(bar + B_HLO_FULL * 8, 1);
        mbar_init(bar + B_HHI_FULL * 8, 1);
        mbar_init(bar + B_HLO_FREE * 8, 12);
        mbar_init(bar + B_HHI_FREE * 8, 12);
        mbar_init(bar + B_MS * 8, 1);
        mbar_init(bar + B_O * 8, 1);
        mbar_init(bar + B_XS * 8, 1);
        asm volatile("fence.mbarrier_init.release.cluster;" ::: "memory");
        mbar_expect(bar + B_MS * 8, 3840);
        mbar_expect(bar + B_O * 8, 3072);
        mbar_expect(bar + B_XS * 8, 12288);
        mbar_expect(bar + B_HLO_FULL * 8, 12288);
        bulk_g2s(sb + SM_HB, g_ht, 12288, bar + B_HLO_FULL * 8);
        mbar_expect(bar + B_HHI_FULL * 8, 28672);
        bulk_g2s(sb + SM_HB + 12288, (const char*)g_ht + 12288, 28672, bar + B_HHI_FULL * 8);
    }
    cluster_sync();

    if (wg < 2) {
        asm volatile("setmaxnreg.inc.sync.aligned.u32 200;");
        const int w = warp & 3;
        uint32_t wa[40][4];
        {
            const bf16* W = (wg == 0 ? Wq : Wk) + (size_t)h * DH + p * 64 + w * 16 + t * 4;
            #pragma unroll
            for (int kt = 0; kt < 40; kt++) {
                uint2 l1 = __ldg((const uint2*)(W + (size_t)(kt * 16 + g) * HD));
                uint2 l2 = __ldg((const uint2*)(W + (size_t)(kt * 16 + 8 + g) * HD));
                wa[kt][0] = l1.x; wa[kt][1] = l1.y; wa[kt][2] = l2.x; wa[kt][3] = l2.y;
            }
            #pragma unroll
            for (int kt = 0; kt < 40; kt++) {
                #pragma unroll
                for (int i = 0; i < 4; i++) wa[kt][i] = movm(wa[kt][i]);
            }
        }
        bar_sync(0, 512);
        const uint32_t off0 = hop1_off(sb, (tile0 + warp) * 16 + g, h, t);
        const uint32_t off1 = hop1_off(sb, (tile0 + warp) * 16 + 8 + g, h, t);
        const uint32_t dstx = sb + (wg == 0 ? SM_QX : SM_KS + 1024);

        for (int s = -1; s < NSEG; s++) {
            const uint32_t par = s & 1;
            if (s >= 0) {
                mbar_wait(bar + B_MEM_FULL * 8, par);
                float c0[4] = {0.f, 0.f, 0.f, 0.f}, c1[4] = {0.f, 0.f, 0.f, 0.f};
                const uint32_t maddr = sb + SM_HB + lane * 16;
                #pragma unroll
                for (int kp = 0; kp < 20; kp++) {
                    uint32_t bb[4];
                    ldsm4t(bb, maddr + kp * 512);
                    mma16(c0, wa[2 * kp][0], wa[2 * kp][1], wa[2 * kp][2], wa[2 * kp][3], bb[0], bb[1]);
                    mma16(c1, wa[2 * kp + 1][0], wa[2 * kp + 1][1], wa[2 * kp + 1][2], wa[2 * kp + 1][3], bb[2], bb[3]);
                }
                {
                    const int tok = lane & 7, ch = 2 * w + ((lane >> 3) & 1);
                    stsm2t(sb + (wg == 0 ? SM_QM : SM_KS) + tok * 128 + ((ch ^ tok) << 4),
                           pack2(c0[0] + c1[0], c0[1] + c1[1]), pack2(c0[2] + c1[2], c0[3] + c1[3]));
                }
                __syncwarp();
                if (lane == 0) mbar_arrive(bar + B_MEM_FREE * 8);
                bar_sync(1, 384);
                if (warp < 5) {
                    const int r = lane & 7, cq = lane >> 3;
                    uint32_t a[8], kb[8];
                    ldsm4(a, sb + SM_QM + r * 128 + ((cq ^ r) << 4));
                    ldsm4(kb, sb + SM_KS + (warp * 8 + r) * 128 + ((cq ^ r) << 4));
                    ldsm4(a + 4, sb + SM_QM + r * 128 + (((cq + 4) ^ r) << 4));
                    ldsm4(kb + 4, sb + SM_KS + (warp * 8 + r) * 128 + (((cq + 4) ^ r) << 4));
                    float d0[4] = {0.f, 0.f, 0.f, 0.f}, d1[4] = {0.f, 0.f, 0.f, 0.f};
                    mma16(d0, a[0], 0u, a[1], 0u, kb[0], kb[1]);
                    mma16(d1, a[2], 0u, a[3], 0u, kb[2], kb[3]);
                    mma16(d0, a[4], 0u, a[5], 0u, kb[4], kb[5]);
                    mma16(d1, a[6], 0u, a[7], 0u, kb[6], kb[7]);
                    const uint32_t la = sb + SM_MS + p * 1280 + warp * 256 + lane * 8;
                    #pragma unroll
                    for (int rk = 0; rk < 3; rk++)
                        st_async2(mapa(la, rk), d0[0] + d1[0], d0[1] + d1[1], mapa(bar + B_MS * 8, rk));
                }
                if (s < NSEG - 1) wo_phase<0, 5>(sb, warp, lane, nullptr, par, (uint32_t)(s % 15) + 1u, off0, off1);
                else mbar_wait_cluster(bar + B_O * 8, par);
                {
                    const int mi = warp < 3 ? 0 : 1, j = warp < 3 ? warp : warp - 3;
                    const int r = lane & 7, cq = lane >> 3;
                    const int qrow = mi * 16 + r + 8 * (cq & 1);
                    uint32_t kb[8];
                    ldsm4(kb, sb + SM_KS + (j * 8 + r) * 128 + ((cq ^ r) << 4));
                    ldsm4(kb + 4, sb + SM_KS + (j * 8 + r) * 128 + (((cq + 4) ^ r) << 4));
                    float d0[4] = {0.f, 0.f, 0.f, 0.f};
                    #pragma unroll
                    for (int kt = 0; kt < 4; kt++) {
                        uint32_t a[4];
                        ldsm4(a, sb + SM_QX + qrow * 128 + (((2 * kt + (cq >> 1)) ^ r) << 4));
                        mma16(d0, a[0], a[1], a[2], a[3], kb[2 * kt], kb[2 * kt + 1]);
                    }
                    const uint32_t la = sb + SM_XS + p * 4096 + warp * 512 + lane * 16;
                    #pragma unroll
                    for (int rk = 0; rk < 3; rk++) st_async4(mapa(la, rk), d0, mapa(bar + B_XS * 8, rk));
                }
            }
            if (s < NSEG - 1) {
                const uint32_t hp = (s + 1) & 1;
                float d[16];
                #pragma unroll
                for (int i = 0; i < 16; i++) d[i] = 0.f;
                const uint64_t db0 = make_desc(sb + SM_HB, 16, 1024, 1);
                mbar_wait(bar + B_HLO_FULL * 8, hp);
                wg_fence();
                #pragma unroll
                for (int kt = 0; kt < 12; kt++) wg_rs32(d, wa[kt], db0 + (uint64_t)(((kt >> 2) * 4096 + (kt & 3) * 32) >> 4), kt > 0);
                wg_commit();
                mbar_wait(bar + B_HHI_FULL * 8, hp);
                #pragma unroll
                for (int kt = 12; kt < 40; kt++) wg_rs32(d, wa[kt], db0 + (uint64_t)(((kt >> 2) * 4096 + (kt & 3) * 32) >> 4), 1);
                wg_commit();
                wg_wait<1>();
                if (lane == 0) mbar_arrive(bar + B_HLO_FREE * 8);
                wg_wait<0>();
                if (lane == 0) mbar_arrive(bar + B_HHI_FREE * 8);
                bar_sync(2, 256);
                const int mi = lane >> 3, r = lane & 7;
                #pragma unroll
                for (int jj = 0; jj < 2; jj++) {
                    const int tok = 8 * (2 * jj + (mi >> 1)) + r, ch = 2 * w + (mi & 1);
                    stsm4t(dstx + tok * 128 + ((ch ^ r) << 4),
                           pack2(d[8 * jj + 0], d[8 * jj + 1]), pack2(d[8 * jj + 2], d[8 * jj + 3]),
                           pack2(d[8 * jj + 4], d[8 * jj + 5]), pack2(d[8 * jj + 6], d[8 * jj + 7]));
                }
            }
        }
    } else if (wg == 2) {
        asm volatile("setmaxnreg.dec.sync.aligned.u32 72;");
        const int w = warp & 3;
        {
            const int c = tid & 7;
            const bf16* src = Wv + (size_t)h * DH + p * 64 + c * 8;
            for (int k = (tid & 127) >> 3; k < DM; k += 16)
                cpa16(sb + SM_WV + k * 128 + ((c ^ (k & 7)) << 4), src + (size_t)k * HD);
        }
        uint32_t res[4][4];
        {
            const bf16* src = Wo + (size_t)h * DH * DM + (tile0 + warp) * 16 + 2 * t;
            #pragma unroll
            for (int kt = 0; kt < 4; kt++) {
                res[kt][0] = __ldg((const uint32_t*)(src + (size_t)(kt * 16 + g) * DM));
                res[kt][1] = __ldg((const uint32_t*)(src + (size_t)(kt * 16 + g) * DM + 8));
                res[kt][2] = __ldg((const uint32_t*)(src + (size_t)(kt * 16 + 8 + g) * DM));
                res[kt][3] = __ldg((const uint32_t*)(src + (size_t)(kt * 16 + 8 + g) * DM + 8));
            }
            #pragma unroll
            for (int kt = 0; kt < 4; kt++) {
                #pragma unroll
                for (int i = 0; i < 4; i++) res[kt][i] = movm(res[kt][i]);
            }
        }
        cpa_wait_all();
        fence_async();
        bar_sync(0, 512);
        const uint32_t off0 = hop1_off(sb, (tile0 + warp) * 16 + g, h, t);
        const uint32_t off1 = hop1_off(sb, (tile0 + warp) * 16 + 8 + g, h, t);
        const uint64_t da0 = make_desc(sb + SM_WV, 16, 1024, 1);
        const float SCALE = 0.07216878364870322f;
        const float L2E = 1.4426950408889634f;
        uint32_t vx[8];
        uint32_t vm0 = 0, vm1 = 0;
        #pragma unroll
        for (int i = 0; i < 8; i++) vx[i] = 0;

        for (int s = -1; s < NSEG; s++) {
            const uint32_t par = s & 1;
            if (s >= 0) {
                mbar_wait(bar + B_MEM_FULL * 8, par);
                bar_sync(1, 384);
                float dv[4] = {0.f, 0.f, 0.f, 0.f};
                {
                    const uint64_t dbm = make_desc(sb + SM_HB, 128, 128, 0);
                    wg_fence();
                    #pragma unroll
                    for (int kt = 0; kt < 40; kt++) wg_ss8(dv, da0 + (uint64_t)(kt * 128), dbm + (uint64_t)(kt * 16), kt > 0);
                    wg_commit();
                }
                mbar_wait_cluster(bar + B_MS * 8, par);
                if (tid == 256) mbar_expect(bar + B_MS * 8, 3840);
                float sc[10];
                #pragma unroll
                for (int j = 0; j < 5; j++) {
                    const uint32_t a = sb + SM_MS + j * 256 + lane * 8;
                    float2 v0 = lds2f(a), v1 = lds2f(a + 1280), v2 = lds2f(a + 2560);
                    sc[2 * j] = bfr(bfr(v0.x + v1.x + v2.x) * SCALE);
                    sc[2 * j + 1] = bfr(bfr(v0.y + v1.y + v2.y) * SCALE);
                }
                float mx = sc[0];
                #pragma unroll
                for (int i = 1; i < 10; i++) mx = fmaxf(mx, sc[i]);
                mx = fmaxf(mx, __shfl_xor_sync(0xffffffffu, mx, 1));
                mx = fmaxf(mx, __shfl_xor_sync(0xffffffffu, mx, 2));
                float sum = 0.f;
                #pragma unroll
                for (int i = 0; i < 10; i++) { sc[i] = exp2f((sc[i] - mx) * L2E); sum += sc[i]; }
                sum += __shfl_xor_sync(0xffffffffu, sum, 1);
                sum += __shfl_xor_sync(0xffffffffu, sum, 2);
                const float inv = 1.0f / sum;
                uint32_t pb[5];
                #pragma unroll
                for (int j = 0; j < 5; j++) pb[j] = pack2(sc[2 * j] * inv, sc[2 * j + 1] * inv);
                float o0[4] = {0.f, 0.f, 0.f, 0.f}, o1[4] = {0.f, 0.f, 0.f, 0.f};
                mma16(o0, vx[0], vx[1], vx[2], vx[3], pb[1], pb[2]);
                mma16(o1, vx[4], vx[5], vx[6], vx[7], pb[3], pb[4]);
                wg_wait<0>();
                if (lane == 0) mbar_arrive(bar + B_MEM_FREE * 8);
                vm0 = pack2(dv[0], dv[1]); vm1 = pack2(dv[2], dv[3]);
                mma8(o0, vm0, vm1, pb[0]);
                {
                    const uint32_t q0 = pack2(o0[0] + o1[0], o0[1] + o1[1]), q1 = pack2(o0[2] + o1[2], o0[3] + o1[3]);
                    const uint32_t la = sb + SM_OS + (p * 64 + w * 16 + g) * 16 + t * 4;
                    #pragma unroll
                    for (int rk = 0; rk < 3; rk++) {
                        const uint32_t ra = mapa(la, rk), rb = mapa(bar + B_O * 8, rk);
                        st_async1(ra, q0, rb);
                        st_async1(ra + 128, q1, rb);
                    }
                }
                if (s < NSEG - 1) wo_phase<4, 4>(sb, warp, lane, res, par, (uint32_t)(s % 15) + 1u, off0, off1);
                else mbar_wait_cluster(bar + B_O * 8, par);
                if (tid == 256) mbar_expect(bar + B_O * 8, 3072);
            }
            float d[16];
            #pragma unroll
            for (int i = 0; i < 16; i++) d[i] = 0.f;
            if (s < NSEG - 1) {
                const uint32_t hp = (s + 1) & 1;
                const uint64_t db0 = make_desc(sb + SM_HB, 16, 1024, 1);
                mbar_wait(bar + B_HLO_FULL * 8, hp);
                wg_fence();
                #pragma unroll
                for (int kt = 0; kt < 12; kt++) wg_ss32(d, da0 + (uint64_t)(kt * 128), db0 + (uint64_t)(((kt >> 2) * 4096 + (kt & 3) * 32) >> 4), kt > 0);
                wg_commit();
                mbar_wait(bar + B_HHI_FULL * 8, hp);
                #pragma unroll
                for (int kt = 12; kt < 40; kt++) wg_ss32(d, da0 + (uint64_t)(kt * 128), db0 + (uint64_t)(((kt >> 2) * 4096 + (kt & 3) * 32) >> 4), 1);
                wg_commit();
                wg_wait<1>();
                if (lane == 0) mbar_arrive(bar + B_HLO_FREE * 8);
            }
            if (s >= 0) {
                mbar_wait_cluster(bar + B_XS * 8, par);
                if (tid == 256) mbar_expect(bar + B_XS * 8, 12288);
                bf16* orow = g_ox + (size_t)(s * 32 + g) * HD + h * DH + p * 64 + w * 16 + 2 * t;
                #pragma unroll
                for (int mi = 0; mi < 2; mi++) {
                    const int nt = mi ? 5 : 3, tb = mi ? 3 : 0;
                    float sc[5][4];
                    #pragma unroll
                    for (int j = 0; j < 5; j++) {
                        if (j < nt) {
                            const uint32_t a = sb + SM_XS + (tb + j) * 512 + lane * 16;
                            float4 v0 = lds4f(a), v1 = lds4f(a + 4096), v2 = lds4f(a + 8192);
                            sc[j][0] = bfr(bfr(v0.x + v1.x + v2.x) * SCALE);
                            sc[j][1] = bfr(bfr(v0.y + v1.y + v2.y) * SCALE);
                            sc[j][2] = bfr(bfr(v0.z + v1.z + v2.z) * SCALE);
                            sc[j][3] = bfr(bfr(v0.w + v1.w + v2.w) * SCALE);
                            if (j > 0) {
                                const int kx = 8 * (j - 1) + 2 * t, qx = 16 * mi + g;
                                const float NEG = -999292928.0f;
                                if (kx > qx) sc[j][0] = NEG;
                                if (kx + 1 > qx) sc[j][1] = NEG;
                                if (kx > qx + 8) sc[j][2] = NEG;
                                if (kx + 1 > qx + 8) sc[j][3] = NEG;
                            }
                        }
                    }
                    float m0 = fmaxf(sc[0][0], sc[0][1]), m1 = fmaxf(sc[0][2], sc[0][3]);
                    #pragma unroll
                    for (int j = 1; j < 5; j++) if (j < nt) {
                        m0 = fmaxf(m0, fmaxf(sc[j][0], sc[j][1])); m1 = fmaxf(m1, fmaxf(sc[j][2], sc[j][3]));
                    }
                    m0 = fmaxf(m0, __shfl_xor_sync(0xffffffffu, m0, 1)); m1 = fmaxf(m1, __shfl_xor_sync(0xffffffffu, m1, 1));
                    m0 = fmaxf(m0, __shfl_xor_sync(0xffffffffu, m0, 2)); m1 = fmaxf(m1, __shfl_xor_sync(0xffffffffu, m1, 2));
                    float s0 = 0.f, s1 = 0.f;
                    #pragma unroll
                    for (int j = 0; j < 5; j++) if (j < nt) {
                        sc[j][0] = exp2f((sc[j][0] - m0) * L2E); sc[j][1] = exp2f((sc[j][1] - m0) * L2E);
                        sc[j][2] = exp2f((sc[j][2] - m1) * L2E); sc[j][3] = exp2f((sc[j][3] - m1) * L2E);
                        s0 += sc[j][0] + sc[j][1]; s1 += sc[j][2] + sc[j][3];
                    }
                    s0 += __shfl_xor_sync(0xffffffffu, s0, 1); s1 += __shfl_xor_sync(0xffffffffu, s1, 1);
                    s0 += __shfl_xor_sync(0xffffffffu, s0, 2); s1 += __shfl_xor_sync(0xffffffffu, s1, 2);
                    const float i0 = 1.0f / s0, i1 = 1.0f / s1;
                    #pragma unroll
                    for (int hf = 0; hf < 2; hf++) {
                        const float iv = hf ? i1 : i0;
                        uint32_t pb[5];
                        #pragma unroll
                        for (int j = 0; j < 5; j++) if (j < nt) pb[j] = pack2(sc[j][2 * hf] * iv, sc[j][2 * hf + 1] * iv);
                        float o[4] = {0.f, 0.f, 0.f, 0.f};
                        mma8(o, vm0, vm1, pb[0]);
                        mma16(o, vx[0], vx[1], vx[2], vx[3], pb[1], pb[2]);
                        if (mi) mma16(o, vx[4], vx[5], vx[6], vx[7], pb[3], pb[4]);
                        const uint32_t u0 = movm(pack2(o[0], o[1])), u1 = movm(pack2(o[2], o[3]));
                        bf16* dst = orow + (size_t)(16 * mi + 8 * hf) * HD;
                        *(uint32_t*)dst = u0;
                        *(uint32_t*)(dst + 8) = u1;
                    }
                }
            }
            if (s < NSEG - 1) {
                wg_wait<0>();
                if (lane == 0) mbar_arrive(bar + B_HHI_FREE * 8);
                #pragma unroll
                for (int i = 0; i < 8; i++) vx[i] = pack2(d[2 * i], d[2 * i + 1]);
            }
        }
    } else {
        asm volatile("setmaxnreg.dec.sync.aligned.u32 40;");
        const int w = warp & 3, lt = tid & 127;
        {
            const bf16* src0 = Wo + (size_t)h * DH * DM + tile0 * 16;
            const int nch = 2 * ntile;
            for (int i = lt; i < DH * nch; i += 128) {
                const int e = i / nch, c = i - e * nch, tl = c >> 1, cc = c & 1;
                if (tl >= 8 && tl < 12 && e < 64) continue;
                cpa16(sb + SM_WO + wo_tile_off(tl) + e * 32 + ((cc ^ ((e >> 2) & 1)) << 4), src0 + (size_t)e * DM + c * 8);
            }
        }
        const uint32_t epoch = *(volatile uint32_t*)&g_epoch;
        if (b < 80) {
            #pragma unroll
            for (int i = 0; i < 2; i++) {
                const int idx = lt + i * 128, sl = idx >> 6, pg = (idx >> 5) & 1, wd = idx & 31;
                st_relaxed1(g_buf2 + (sl * 3 + (b >> 5)) * 2048 + pg * 1024 + (b & 31) * 32 + wd, 0xFFFFFFFFu);
            }
            __threadfence();
        }
        if (lane == 0) {
            for (int i = w; i < 14; i += 4) {
                int c = 0;
                if (i < 12) c = probe_blk(g_buf2 + i * 2048 + 640 + (b & 31) * 8);
                else if (b < 80) c = probe_blk(g_buf1 + (b * 2 + (i - 12)) * 2048);
                asm volatile("st.shared.u8 [%0], %1;" :: "r"(sb + SM_CH + 96 + i), "r"(c) : "memory");
            }
        }
        bar_sync(3, 128);
        uint32_t selmask = 0;
        for (int i = 0; i < 14; i++) {
            uint32_t c; asm volatile("ld.shared.u8 %0, [%1];" : "=r"(c) : "r"(sb + SM_CH + 96 + i) : "memory");
            selmask |= c << i;
        }
        if (lt == 0 && b < 80) st_release1(&g_choice[b], (epoch << 2) | (selmask >> 12));
        if (lt < 80) {
            uint32_t v, guard = 0;
            do { v = ld_acquire1(&g_choice[lt]); if (++guard > (1u << 22)) __trap(); } while ((v >> 2) != (epoch & 0x3fffffffu));
            asm volatile("st.shared.u8 [%0], %1;" :: "r"(sb + SM_CH + lt), "r"(v & 3u) : "memory");
        }
        cpa_wait_all();
        bar_sync(0, 512);
        const bool has_tile = (12 + w) < ntile;
        uint32_t off0 = 0, off1 = 0;
        if (has_tile) {
            off0 = hop1_off(sb, (tile0 + warp) * 16 + g, h, t);
            off1 = hop1_off(sb, (tile0 + warp) * 16 + 8 + g, h, t);
        }
        const char* rin = (const char*)g_buf1 + (size_t)(b * 2 + (w >> 1)) * 8192 + ((selmask >> (12 + (w >> 1))) & 1) * 4096 + (w & 1) * 2048 + lane * 16;

        for (int s = 0; s < NSEG; s++) {
            const uint32_t par = s & 1;
            mbar_wait(bar + B_HLO_FREE * 8, par);
            if (s == 0) {
                for (int k = lt; k < DM; k += 128) {
                    uint32_t v[4];
                    #pragma unroll
                    for (int i = 0; i < 4; i++) {
                        uint32_t lo = *(const uint16_t*)(mem0 + (2 * i) * DM + k), hi = *(const uint16_t*)(mem0 + (2 * i + 1) * DM + k);
                        v[i] = lo | (hi << 16);
                    }
                    asm volatile("st.shared.v4.u32 [%0], {%1,%2,%3,%4};" :: "r"(sb + SM_HB + k * 16), "r"(v[0]), "r"(v[1]), "r"(v[2]), "r"(v[3]) : "memory");
                }
            } else {
                const int sl = s & 3;
                const char* q = (const char*)g_buf2 + sl * 3 * 8192 + lt * 16;
                const uint32_t sm = selmask >> (sl * 3);
                const uint32_t dst = sb + SM_HB + lt * 16;
                uint32_t guard = 0;
                while (true) {
                    #pragma unroll
                    for (int c = 0; c < 5; c++)
                        cpa16(dst + c * 2048, q + (c >> 1) * 8192 + ((sm >> (c >> 1)) & 1) * 4096 + (c & 1) * 2048);
                    cpa_wait_all();
                    bool ok = true;
                    #pragma unroll
                    for (int c = 0; c < 5; c++) { uint4 v = lds4(dst + c * 2048); ok = ok && oks(v); }
                    if (__all_sync(0xffffffffu, ok)) break;
                    if (++guard > (1u << 22)) __trap();
                }
            }
            fence_async();
            __syncwarp();
            if (lane == 0) mbar_arrive(bar + B_MEM_FULL * 8);
            if (s < NSEG - 1) {
                if (w == 3) {
                    if (lane == 0) {
                        const char* src = (const char*)g_ht + (size_t)(s + 1) * 40960;
                        mbar_wait(bar + B_HHI_FREE * 8, par);
                        mbar_expect(bar + B_HHI_FULL * 8, 28672);
                        bulk_g2s(sb + SM_HB + 12288, src + 12288, 28672, bar + B_HHI_FULL * 8);
                        mbar_wait(bar + B_MEM_FREE * 8, par);
                        mbar_expect(bar + B_HLO_FULL * 8, 12288);
                        bulk_g2s(sb + SM_HB, src, 12288, bar + B_HLO_FULL * 8);
                    }
                    __syncwarp();
                }
                const uint32_t tag = (uint32_t)(s % 15) + 1u;
                if (has_tile) wo_phase<0, 3>(sb, warp, lane, nullptr, par, tag, off0, off1);
                else mbar_wait_cluster(bar + B_O * 8, par);
                if (b < 80) {
                    uint4 v0, v1, v2, v3;
                    uint32_t guard = 0;
                    while (true) {
                        v0 = ld_relaxed4(rin); v1 = ld_relaxed4(rin + 512);
                        v2 = ld_relaxed4(rin + 1024); v3 = ld_relaxed4(rin + 1536);
                        if (__all_sync(0xffffffffu, ok4(v0, tag) && ok4(v1, tag) && ok4(v2, tag) && ok4(v3, tag))) break;
                        if (++guard > (1u << 22)) __trap();
                    }
                    float a0 = uf(v0.x) + uf(v1.x), a1 = uf(v0.y) + uf(v1.y), a2 = uf(v0.z) + uf(v1.z), a3 = uf(v0.w) + uf(v1.w);
                    float b0 = uf(v2.x) + uf(v3.x), b1 = uf(v2.y) + uf(v3.y), b2 = uf(v2.z) + uf(v3.z), b3 = uf(v2.w) + uf(v3.w);
                    const bool u16 = lane & 16;
                    float k0 = (u16 ? b0 : a0) + __shfl_xor_sync(0xffffffffu, u16 ? a0 : b0, 16);
                    float k1 = (u16 ? b1 : a1) + __shfl_xor_sync(0xffffffffu, u16 ? a1 : b1, 16);
                    float k2 = (u16 ? b2 : a2) + __shfl_xor_sync(0xffffffffu, u16 ? a2 : b2, 16);
                    float k3 = (u16 ? b3 : a3) + __shfl_xor_sync(0xffffffffu, u16 ? a3 : b3, 16);
                    const bool u8 = lane & 8;
                    float m0 = (u8 ? k2 : k0) + __shfl_xor_sync(0xffffffffu, u8 ? k0 : k2, 8);
                    float m1 = (u8 ? k3 : k1) + __shfl_xor_sync(0xffffffffu, u8 ? k1 : k3, 8);
                    m0 += __shfl_xor_sync(0xffffffffu, m0, 4); m1 += __shfl_xor_sync(0xffffffffu, m1, 4);
                    m0 += __shfl_xor_sync(0xffffffffu, m0, 2); m1 += __shfl_xor_sync(0xffffffffu, m1, 2);
                    const int col = b * 8 + 2 * w + (lane >> 4), wd = 2 * (lane & 1) + ((lane >> 3) & 1);
                    const int sl = (lane & 4) ? ((s + 3) & 3) : ((s + 1) & 3);
                    uint32_t* dst = g_buf2 + (sl * 3 + (col >> 8)) * 2048 + ((lane >> 1) & 1) * 1024 + (col & 255) * 4 + wd;
                    st_relaxed1(dst, (lane & 4) ? 0xFFFFFFFFu : pack2(m0, m1));
                }
            }
        }
    }
    cluster_sync();
}

constexpr int G_STAGES = 5;
constexpr int G_STAGE_BYTES = 32768;
constexpr int G_SMEM = G_STAGES * G_STAGE_BYTES + 1024 + 256;

__device__ __forceinline__ void tma2d(uint32_t dst, const CUtensorMap* map, int c0, int c1, uint32_t bar) {
    asm volatile("cp.async.bulk.tensor.2d.shared::cluster.global.mbarrier::complete_tx::bytes [%0], [%1, {%2, %3}], [%4];"
                 :: "r"(dst), "l"(map), "r"(c0), "r"(c1), "r"(bar) : "memory");
}
__device__ __forceinline__ void wg_ss128(float* d, uint64_t da, uint64_t db, int sc) {
    asm volatile("{\n\t.reg .pred p;\n\tsetp.ne.b32 p, %66, 0;\n\t"
        "wgmma.mma_async.sync.aligned.m64n128k16.f32.bf16.bf16 "
        "{%0,%1,%2,%3,%4,%5,%6,%7,%8,%9,%10,%11,%12,%13,%14,%15,%16,%17,%18,%19,%20,%21,%22,%23,%24,%25,%26,%27,%28,%29,%30,%31,"
        "%32,%33,%34,%35,%36,%37,%38,%39,%40,%41,%42,%43,%44,%45,%46,%47,%48,%49,%50,%51,%52,%53,%54,%55,%56,%57,%58,%59,%60,%61,%62,%63}, "
        "%64, %65, p, 1, 1, 0, 1;\n\t}"
        : "+f"(d[0]), "+f"(d[1]), "+f"(d[2]), "+f"(d[3]), "+f"(d[4]), "+f"(d[5]), "+f"(d[6]), "+f"(d[7]),
          "+f"(d[8]), "+f"(d[9]), "+f"(d[10]), "+f"(d[11]), "+f"(d[12]), "+f"(d[13]), "+f"(d[14]), "+f"(d[15]),
          "+f"(d[16]), "+f"(d[17]), "+f"(d[18]), "+f"(d[19]), "+f"(d[20]), "+f"(d[21]), "+f"(d[22]), "+f"(d[23]),
          "+f"(d[24]), "+f"(d[25]), "+f"(d[26]), "+f"(d[27]), "+f"(d[28]), "+f"(d[29]), "+f"(d[30]), "+f"(d[31]),
          "+f"(d[32]), "+f"(d[33]), "+f"(d[34]), "+f"(d[35]), "+f"(d[36]), "+f"(d[37]), "+f"(d[38]), "+f"(d[39]),
          "+f"(d[40]), "+f"(d[41]), "+f"(d[42]), "+f"(d[43]), "+f"(d[44]), "+f"(d[45]), "+f"(d[46]), "+f"(d[47]),
          "+f"(d[48]), "+f"(d[49]), "+f"(d[50]), "+f"(d[51]), "+f"(d[52]), "+f"(d[53]), "+f"(d[54]), "+f"(d[55]),
          "+f"(d[56]), "+f"(d[57]), "+f"(d[58]), "+f"(d[59]), "+f"(d[60]), "+f"(d[61]), "+f"(d[62]), "+f"(d[63])
        : "l"(da), "l"(db), "r"(sc));
}

template <int EPI>
__global__ void __launch_bounds__(384, 1)
k_gemm(const __grid_constant__ CUtensorMap mapA, const __grid_constant__ CUtensorMap mapB, int K,
       const bf16* __restrict__ xin, bf16* __restrict__ outp) {
    extern __shared__ uint8_t smem_raw[];
    const uint32_t sb = (smem_u32(smem_raw) + 1023u) & ~1023u;
    const uint32_t bars = sb + G_STAGES * G_STAGE_BYTES;
    const int tid = threadIdx.x, lane = tid & 31, wg = tid >> 7;
    const int n0 = blockIdx.x * 128, m0 = blockIdx.y * 128;
    const int nk = K / 64;
    if (tid == 0) {
        for (int i = 0; i < G_STAGES; i++) { mbar_init(bars + i * 8, 1); mbar_init(bars + 64 + i * 8, 8); }
        asm volatile("fence.mbarrier_init.release.cluster;" ::: "memory");
    }
    __syncthreads();
    if (wg == 0) {
        if (tid == 0) {
            for (int kb = 0; kb < nk; kb++) {
                const int st = kb % G_STAGES;
                if (kb >= G_STAGES) mbar_wait(bars + 64 + st * 8, ((kb / G_STAGES) - 1) & 1);
                const uint32_t a = sb + st * G_STAGE_BYTES;
                mbar_expect(bars + st * 8, G_STAGE_BYTES);
                tma2d(a, &mapA, kb * 64, m0, bars + st * 8);
                tma2d(a + 16384, &mapB, n0, kb * 64, bars + st * 8);
                tma2d(a + 16384 + 8192, &mapB, n0 + 64, kb * 64, bars + st * 8);
            }
        }
    } else {
        float d[64];
        #pragma unroll
        for (int i = 0; i < 64; i++) d[i] = 0.f;
        const int cw = wg - 1;
        for (int kb = 0; kb < nk; kb++) {
            const int st = kb % G_STAGES;
            mbar_wait(bars + st * 8, (kb / G_STAGES) & 1);
            const uint32_t a = sb + st * G_STAGE_BYTES;
            const uint64_t da = make_desc(a + cw * 8192, 16, 1024, 1);
            const uint64_t db = make_desc(a + 16384, 8192, 1024, 1);
            wg_fence();
            #pragma unroll
            for (int k = 0; k < 4; k++) wg_ss128(d, da + (uint64_t)(k * 2), db + (uint64_t)(k * 128), 1);
            wg_commit();
            if (kb > 0) {
                wg_wait<1>();
                if (lane == 0) mbar_arrive(bars + 64 + ((kb - 1) % G_STAGES) * 8);
            }
        }
        wg_wait<0>();
        const int g = lane >> 2, t = lane & 3, w = (tid >> 5) & 3;
        const int ldo = EPI == 1 ? FF : DM;
        #pragma unroll
        for (int hf = 0; hf < 2; hf++) {
            const int row = m0 + cw * 64 + w * 16 + g + 8 * hf;
            #pragma unroll
            for (int j = 0; j < 16; j++) {
                const int col = n0 + j * 8 + 2 * t;
                float a0 = bfr(d[4 * j + 2 * hf]), a1 = bfr(d[4 * j + 2 * hf + 1]);
                uint32_t o;
                if (EPI == 1) {
                    o = pack2(a0 / (1.0f + __expf(-a0)), a1 / (1.0f + __expf(-a1)));
                } else {
                    const float2 gm = *(const float2*)(g_mod + (EPI == 0 ? 2 : 5) * DM + col);
                    const uint32_t xv = *(const uint32_t*)(xin + (size_t)row * DM + col);
                    o = pack2(bflo(xv) + bfr(gm.x * a0), bfhi(xv) + bfr(gm.y * a1));
                }
                *(uint32_t*)(outp + (size_t)row * ldo + col) = o;
            }
        }
    }
}

typedef CUresult (*EncodeFn)(CUtensorMap*, CUtensorMapDataType, cuuint32_t, void*, const cuuint64_t*, const cuuint64_t*,
                             const cuuint32_t*, const cuuint32_t*, CUtensorMapInterleave, CUtensorMapSwizzle,
                             CUtensorMapL2promotion, CUtensorMapFloatOOBfill);

static void make_map(EncodeFn fn, CUtensorMap* m, const void* ptr, uint64_t inner, uint64_t outer, uint32_t bi, uint32_t bo) {
    cuuint64_t dims[2] = {inner, outer};
    cuuint64_t strides[1] = {inner * 2};
    cuuint32_t box[2] = {bi, bo};
    cuuint32_t es[2] = {1, 1};
    fn(m, CU_TENSOR_MAP_DATA_TYPE_BFLOAT16, 2, (void*)ptr, dims, strides, box, es, CU_TENSOR_MAP_INTERLEAVE_NONE,
       CU_TENSOR_MAP_SWIZZLE_128B, CU_TENSOR_MAP_L2_PROMOTION_L2_256B, CU_TENSOR_MAP_FLOAT_OOB_FILL_NONE);
}

extern "C" void kernel_launch(void* const* d_in, const int* in_sizes, int n_in, void* d_out, int out_size) {
    const bf16* x = (const bf16*)d_in[0];
    const bf16* mem0 = (const bf16*)d_in[1];
    const bf16* Wq = (const bf16*)d_in[2];
    const bf16* Wk = (const bf16*)d_in[3];
    const bf16* Wv = (const bf16*)d_in[4];
    const bf16* Wo = (const bf16*)d_in[5];
    const bf16* w1 = (const bf16*)d_in[8];
    const bf16* w2 = (const bf16*)d_in[9];
    const bf16* c = (const bf16*)d_in[10];
    const bf16* wmod = (const bf16*)d_in[11];
    bf16* out = (bf16*)d_out;

    static EncodeFn enc = nullptr;
    static void *p_ox, *p_x1, *p_h2, *p_act;
    if (!enc) {
        cudaDriverEntryPointQueryResult qr;
        void* f = nullptr;
        cudaGetDriverEntryPoint("cuTensorMapEncodeTiled", &f, cudaEnableDefault, &qr);
        enc = (EncodeFn)f;
        cudaGetSymbolAddress(&p_ox, g_ox);
        cudaGetSymbolAddress(&p_x1, g_x1);
        cudaGetSymbolAddress(&p_h2, g_h2);
        cudaGetSymbolAddress(&p_act, g_act);
        cudaFuncSetAttribute(k_rec, cudaFuncAttributeMaxDynamicSharedMemorySize, SM_TOTAL + 1024);
        cudaFuncSetAttribute(k_gemm<0>, cudaFuncAttributeMaxDynamicSharedMemorySize, G_SMEM);
        cudaFuncSetAttribute(k_gemm<1>, cudaFuncAttributeMaxDynamicSharedMemorySize, G_SMEM);
        cudaFuncSetAttribute(k_gemm<2>, cudaFuncAttributeMaxDynamicSharedMemorySize, G_SMEM);
    }
    CUtensorMap mOx, mWo, mH2, mW1, mAct, mW2;
    make_map(enc, &mOx, p_ox, HD, SEQ, 64, 128);
    make_map(enc, &mWo, Wo, DM, HD, 64, 64);
    make_map(enc, &mH2, p_h2, DM, SEQ, 64, 128);
    make_map(enc, &mW1, w1, FF, DM, 64, 64);
    make_map(enc, &mAct, p_act, FF, SEQ, 64, 128);
    make_map(enc, &mW2, w2, DM, FF, 64, 64);

    cudaStream_t st = cudaStreamPerThread;
    k_mod<<<60, 256, 0, st>>>(c, wmod);
    k_ln<0><<<SEQ / 8, 256, 0, st>>>(x);
    {
        cudaLaunchConfig_t cfg = {};
        cfg.gridDim = dim3(96); cfg.blockDim = dim3(512); cfg.dynamicSmemBytes = SM_TOTAL + 1024; cfg.stream = st;
        cudaLaunchAttribute at[1];
        at[0].id = cudaLaunchAttributeClusterDimension;
        at[0].val.clusterDim.x = 3; at[0].val.clusterDim.y = 1; at[0].val.clusterDim.z = 1;
        cfg.attrs = at; cfg.numAttrs = 1;
        cudaLaunchKernelEx(&cfg, k_rec, mem0, Wq, Wk, Wv, Wo);
    }
    k_gemm<0><<<dim3(5, 16), 384, G_SMEM, st>>>(mOx, mWo, HD, x, (bf16*)p_x1);
    k_ln<1><<<SEQ / 8, 256, 0, st>>>(nullptr);
    k_gemm<1><<<dim3(12, 16), 384, G_SMEM, st>>>(mH2, mW1, DM, nullptr, (bf16*)p_act);
    k_gemm<2><<<dim3(5, 16), 384, G_SMEM, st>>>(mAct, mW2, FF, (const bf16*)p_x1, out);
}
```

```cpp
#include <cuda_runtime.h>
#include <cuda_bf16.h>
#include <cuda.h>
#include <stdint.h>

typedef __nv_bfloat16 bf16;

constexpr int SEQ = 2048, DM = 640, NH = 32, DH = 192, NSEG = 64, FF = 1536, HD = NH * DH;

__device__ float g_mod[6 * DM];
__device__ __align__(1024) bf16 g_ht[(size_t)SEQ * DM];
__device__ __align__(1024) bf16 g_ox[(size_t)SEQ * HD];
__device__ __align__(1024) bf16 g_x1[(size_t)SEQ * DM];
__device__ __align__(1024) bf16 g_h2[(size_t)SEQ * DM];
__device__ __align__(1024) bf16 g_act[(size_t)SEQ * FF];
__device__ __align__(8192) uint32_t g_buf1[80 * 2 * 2048];
__device__ __align__(8192) uint32_t g_buf2[4 * 3 * 2048];
__device__ uint32_t g_choice[128];
__device__ uint32_t g_epoch;
#define TR(k)

__device__ __forceinline__ float bfr(float x) { return __bfloat162float(__float2bfloat16_rn(x)); }
__device__ __forceinline__ uint32_t pack2(float a, float b) {
    uint32_t r; asm("cvt.rn.bf16x2.f32 %0, %1, %2;" : "=r"(r) : "f"(b), "f"(a)); return r;
}
__device__ __forceinline__ float bflo(uint32_t v) { return __uint_as_float(v << 16); }
__device__ __forceinline__ float bfhi(uint32_t v) { return __uint_as_float(v & 0xffff0000u); }
__device__ __forceinline__ uint32_t smem_u32(const void* p) { return (uint32_t)__cvta_generic_to_shared(p); }

__device__ __forceinline__ void mbar_init(uint32_t bar, uint32_t cnt) {
    asm volatile("mbarrier.init.shared::cta.b64 [%0], %1;" :: "r"(bar), "r"(cnt) : "memory");
}
__device__ __forceinline__ void mbar_arrive(uint32_t bar) {
    asm volatile("mbarrier.arrive.shared::cta.b64 _, [%0];" :: "r"(bar) : "memory");
}
__device__ __forceinline__ void mbar_expect(uint32_t bar, uint32_t bytes) {
    asm volatile("mbarrier.arrive.expect_tx.shared::cta.b64 _, [%0], %1;" :: "r"(bar), "r"(bytes) : "memory");
}
__device__ __forceinline__ bool mbar_try(uint32_t bar, uint32_t parity) {
    uint32_t ok;
    asm volatile("{\n\t.reg .pred p;\n\tmbarrier.try_wait.parity.shared::cta.b64 p, [%1], %2;\n\tselp.u32 %0, 1, 0, p;\n\t}"
                 : "=r"(ok) : "r"(bar), "r"(parity) : "memory");
    return ok != 0;
}
__device__ __forceinline__ bool mbar_try_cluster(uint32_t bar, uint32_t parity) {
    uint32_t ok;
    asm volatile("{\n\t.reg .pred p;\n\tmbarrier.try_wait.parity.acquire.cluster.shared::cta.b64 p, [%1], %2;\n\tselp.u32 %0, 1, 0, p;\n\t}"
                 : "=r"(ok) : "r"(bar), "r"(parity) : "memory");
    return ok != 0;
}
__device__ __forceinline__ void mbar_wait(uint32_t bar, uint32_t parity) {
    uint32_t guard = 0;
    while (!mbar_try(bar, parity)) { if (++guard > (1u << 22)) __trap(); }
}
__device__ __forceinline__ void mbar_wait_cluster(uint32_t bar, uint32_t parity) {
    uint32_t guard = 0;
    while (!mbar_try_cluster(bar, parity)) { if (++guard > (1u << 22)) __trap(); }
}
__device__ __forceinline__ void bar_sync(int id, int n) { asm volatile("bar.sync %0, %1;" :: "r"(id), "r"(n) : "memory"); }
__device__ __forceinline__ void fence_async() { asm volatile("fence.proxy.async.shared::cta;" ::: "memory"); }
__device__ __forceinline__ void cluster_sync() {
    asm volatile("barrier.cluster.arrive.release.aligned;\n\tbarrier.cluster.wait.acquire.aligned;" ::: "memory");
}
__device__ __forceinline__ uint32_t mapa(uint32_t a, uint32_t rank) {
    uint32_t r; asm("mapa.shared::cluster.u32 %0, %1, %2;" : "=r"(r) : "r"(a), "r"(rank)); return r;
}
__device__ __forceinline__ void st_async1(uint32_t a, uint32_t v, uint32_t bar) {
    asm volatile("st.async.weak.shared::cluster.mbarrier::complete_tx::bytes.b32 [%0], %1, [%2];" :: "r"(a), "r"(v), "r"(bar) : "memory");
}
__device__ __forceinline__ void st_async2(uint32_t a, float x, float y, uint32_t bar) {
    asm volatile("st.async.weak.shared::cluster.mbarrier::complete_tx::bytes.v2.f32 [%0], {%1,%2}, [%3];" :: "r"(a), "f"(x), "f"(y), "r"(bar) : "memory");
}
__device__ __forceinline__ void st_async4(uint32_t a, const float* c, uint32_t bar) {
    asm volatile("st.async.weak.shared::cluster.mbarrier::complete_tx::bytes.v4.f32 [%0], {%1,%2,%3,%4}, [%5];"
                 :: "r"(a), "f"(c[0]), "f"(c[1]), "f"(c[2]), "f"(c[3]), "r"(bar) : "memory");
}
__device__ __forceinline__ void bulk_g2s(uint32_t dst, const void* src, uint32_t bytes, uint32_t bar) {
    asm volatile("cp.async.bulk.shared::cluster.global.mbarrier::complete_tx::bytes [%0], [%1], %2, [%3];"
                 :: "r"(dst), "l"(src), "r"(bytes), "r"(bar) : "memory");
}
__device__ __forceinline__ void cpa16(uint32_t s, const void* g) {
    asm volatile("cp.async.cg.shared.global [%0], [%1], 16;" :: "r"(s), "l"(g) : "memory");
}
__device__ __forceinline__ void cpa_wait_all() { asm volatile("cp.async.wait_all;" ::: "memory"); }
__device__ __forceinline__ void ldsm4(uint32_t* r, uint32_t a) {
    asm volatile("ldmatrix.sync.aligned.m8n8.x4.shared.b16 {%0,%1,%2,%3}, [%4];" : "=r"(r[0]), "=r"(r[1]), "=r"(r[2]), "=r"(r[3]) : "r"(a) : "memory");
}
__device__ __forceinline__ void ldsm4t(uint32_t* r, uint32_t a) {
    asm volatile("ldmatrix.sync.aligned.m8n8.x4.trans.shared.b16 {%0,%1,%2,%3}, [%4];" : "=r"(r[0]), "=r"(r[1]), "=r"(r[2]), "=r"(r[3]) : "r"(a) : "memory");
}
__device__ __forceinline__ void stsm2t(uint32_t a, uint32_t r0, uint32_t r1) {
    asm volatile("stmatrix.sync.aligned.m8n8.x2.trans.shared.b16 [%0], {%1,%2};" :: "r"(a), "r"(r0), "r"(r1) : "memory");
}
__device__ __forceinline__ void stsm4t(uint32_t a, uint32_t r0, uint32_t r1, uint32_t r2, uint32_t r3) {
    asm volatile("stmatrix.sync.aligned.m8n8.x4.trans.shared.b16 [%0], {%1,%2,%3,%4};" :: "r"(a), "r"(r0), "r"(r1), "r"(r2), "r"(r3) : "memory");
}
__device__ __forceinline__ uint32_t movm(uint32_t v) {
    uint32_t r; asm volatile("movmatrix.sync.aligned.m8n8.trans.b16 %0, %1;" : "=r"(r) : "r"(v)); return r;
}
__device__ __forceinline__ void mma16(float* c, uint32_t a0, uint32_t a1, uint32_t a2, uint32_t a3, uint32_t b0, uint32_t b1) {
    asm volatile("mma.sync.aligned.m16n8k16.row.col.f32.bf16.bf16.f32 {%0,%1,%2,%3}, {%4,%5,%6,%7}, {%8,%9}, {%0,%1,%2,%3};"
                 : "+f"(c[0]), "+f"(c[1]), "+f"(c[2]), "+f"(c[3]) : "r"(a0), "r"(a1), "r"(a2), "r"(a3), "r"(b0), "r"(b1));
}
__device__ __forceinline__ void mma8(float* c, uint32_t a0, uint32_t a1, uint32_t b0) {
    asm volatile("mma.sync.aligned.m16n8k8.row.col.f32.bf16.bf16.f32 {%0,%1,%2,%3}, {%4,%5}, {%6}, {%0,%1,%2,%3};"
                 : "+f"(c[0]), "+f"(c[1]), "+f"(c[2]), "+f"(c[3]) : "r"(a0), "r"(a1), "r"(b0));
}
__host__ __device__ constexpr uint64_t make_desc(uint32_t saddr, uint32_t lbo, uint32_t sbo, uint32_t layout) {
    return (uint64_t)((saddr & 0x3FFFF) >> 4) | ((uint64_t)(lbo >> 4) << 16) | ((uint64_t)(sbo >> 4) << 32) | ((uint64_t)layout << 62);
}
__device__ __forceinline__ void wg_fence() { asm volatile("wgmma.fence.sync.aligned;" ::: "memory"); }
__device__ __forceinline__ void wg_commit() { asm volatile("wgmma.commit_group.sync.aligned;" ::: "memory"); }
template <int N> __device__ __forceinline__ void wg_wait() { asm volatile("wgmma.wait_group.sync.aligned %0;" :: "n"(N) : "memory"); }

#define D16(C) C(d[0]), C(d[1]), C(d[2]), C(d[3]), C(d[4]), C(d[5]), C(d[6]), C(d[7]), \
               C(d[8]), C(d[9]), C(d[10]), C(d[11]), C(d[12]), C(d[13]), C(d[14]), C(d[15])
#define DREG16 "{%0,%1,%2,%3,%4,%5,%6,%7,%8,%9,%10,%11,%12,%13,%14,%15}"
__device__ __forceinline__ void wg_rs32(float* d, const uint32_t* a, uint64_t db, bool acc) {
    if (acc)
        asm volatile("wgmma.mma_async.sync.aligned.m64n32k16.f32.bf16.bf16 " DREG16 ", {%16,%17,%18,%19}, %20, 1, 1, 1, 0;"
            : D16("+f") : "r"(a[0]), "r"(a[1]), "r"(a[2]), "r"(a[3]), "l"(db));
    else
        asm volatile("wgmma.mma_async.sync.aligned.m64n32k16.f32.bf16.bf16 " DREG16 ", {%16,%17,%18,%19}, %20, 0, 1, 1, 0;"
            : D16("=f") : "r"(a[0]), "r"(a[1]), "r"(a[2]), "r"(a[3]), "l"(db));
}
__device__ __forceinline__ void wg_ss32(float* d, uint64_t da, uint64_t db, bool acc) {
    if (acc)
        asm volatile("wgmma.mma_async.sync.aligned.m64n32k16.f32.bf16.bf16 " DREG16 ", %16, %17, 1, 1, 1, 1, 0;"
            : D16("+f") : "l"(da), "l"(db));
    else
        asm volatile("wgmma.mma_async.sync.aligned.m64n32k16.f32.bf16.bf16 " DREG16 ", %16, %17, 0, 1, 1, 1, 0;"
            : D16("=f") : "l"(da), "l"(db));
}
__device__ __forceinline__ void wg_ss8(float* d, uint64_t da, uint64_t db, bool acc) {
    if (acc)
        asm volatile("wgmma.mma_async.sync.aligned.m64n8k16.f32.bf16.bf16 {%0,%1,%2,%3}, %4, %5, 1, 1, 1, 1, 1;"
            : "+f"(d[0]), "+f"(d[1]), "+f"(d[2]), "+f"(d[3]) : "l"(da), "l"(db));
    else
        asm volatile("wgmma.mma_async.sync.aligned.m64n8k16.f32.bf16.bf16 {%0,%1,%2,%3}, %4, %5, 0, 1, 1, 1, 1;"
            : "=f"(d[0]), "=f"(d[1]), "=f"(d[2]), "=f"(d[3]) : "l"(da), "l"(db));
}
template <int OFF> __device__ __forceinline__ void ldsm4t_i(uint32_t* r, uint32_t a) {
    asm volatile("ldmatrix.sync.aligned.m8n8.x4.trans.shared.b16 {%0,%1,%2,%3}, [%4+%5];"
                 : "=r"(r[0]), "=r"(r[1]), "=r"(r[2]), "=r"(r[3]) : "r"(a), "n"(OFF) : "memory");
}

__device__ __forceinline__ uint4 ld_relaxed4(const void* p) {
    uint4 v;
    asm volatile("ld.relaxed.gpu.global.v4.u32 {%0,%1,%2,%3}, [%4];" : "=r"(v.x), "=r"(v.y), "=r"(v.z), "=r"(v.w) : "l"(p) : "memory");
    return v;
}
__device__ __forceinline__ void st_relaxed2(void* p, uint32_t a, uint32_t b) {
    asm volatile("st.relaxed.gpu.global.v2.u32 [%0], {%1,%2};" :: "l"(p), "r"(a), "r"(b) : "memory");
}
__device__ __forceinline__ void st_relaxed2_off(void* base, uint32_t off, uint32_t a, uint32_t b) {
    asm volatile("{\n\t.reg .u64 ad;\n\tcvt.u64.u32 ad, %1;\n\tadd.u64 ad, ad, %0;\n\tst.relaxed.gpu.global.v2.u32 [ad], {%2,%3};\n\t}"
                 :: "l"(base), "r"(off), "r"(a), "r"(b) : "memory");
}
__device__ __forceinline__ void st_relaxed1(void* p, uint32_t a) {
    asm volatile("st.relaxed.gpu.global.u32 [%0], %1;" :: "l"(p), "r"(a) : "memory");
}
__device__ __forceinline__ uint32_t ld_acquire1(const uint32_t* p) {
    uint32_t v; asm volatile("ld.acquire.gpu.global.u32 %0, [%1];" : "=r"(v) : "l"(p) : "memory"); return v;
}
__device__ __forceinline__ void st_release1(uint32_t* p, uint32_t a) {
    asm volatile("st.release.gpu.global.u32 [%0], %1;" :: "l"(p), "r"(a) : "memory");
}
__device__ __forceinline__ uint4 lds4(uint32_t s) {
    uint4 v; asm volatile("ld.shared.v4.u32 {%0,%1,%2,%3}, [%4];" : "=r"(v.x), "=r"(v.y), "=r"(v.z), "=r"(v.w) : "r"(s) : "memory"); return v;
}
__device__ __forceinline__ float4 lds4f(uint32_t s) {
    float4 v; asm volatile("ld.shared.v4.f32 {%0,%1,%2,%3}, [%4];" : "=f"(v.x), "=f"(v.y), "=f"(v.z), "=f"(v.w) : "r"(s) : "memory"); return v;
}
__device__ __forceinline__ float2 lds2f(uint32_t s) {
    float2 v; asm volatile("ld.shared.v2.f32 {%0,%1}, [%2];" : "=f"(v.x), "=f"(v.y) : "r"(s) : "memory"); return v;
}
__device__ __forceinline__ uint32_t clk32() { uint32_t c; asm volatile("mov.u32 %0, %%clock;" : "=r"(c) :: "memory"); return c; }
__device__ __forceinline__ uint32_t tagw(float v, uint32_t tag) { return ((__float_as_uint(v) + 8u) & ~15u) | tag; }
__device__ __forceinline__ bool ok4(const uint4& v, uint32_t tag) { return (((v.x ^ tag) | (v.y ^ tag) | (v.z ^ tag) | (v.w ^ tag)) & 15u) == 0; }
__device__ __forceinline__ bool oks(const uint4& v) { return v.x != 0xFFFFFFFFu && v.y != 0xFFFFFFFFu && v.z != 0xFFFFFFFFu && v.w != 0xFFFFFFFFu; }
__device__ __forceinline__ float uf(uint32_t x) { return __uint_as_float(x & ~15u); }

__global__ void __launch_bounds__(256) k_mod(const bf16* __restrict__ c, const bf16* __restrict__ wmod) {
    __shared__ float sc[DM];
    __shared__ float red[8][64];
    const int tid = threadIdx.x;
    for (int i = tid; i < DM; i += 256) {
        float v = __bfloat162float(c[i]);
        sc[i] = bfr(v / (1.0f + __expf(-v)));
    }
    __syncthreads();
    const int cp = tid & 31, kg = tid >> 5;
    const int col = blockIdx.x * 64 + cp * 2;
    float a0 = 0.f, a1 = 0.f;
    #pragma unroll 8
    for (int k = kg * 80; k < kg * 80 + 80; k++) {
        uint32_t w = *(const uint32_t*)(wmod + (size_t)k * (6 * DM) + col);
        a0 += sc[k] * bflo(w); a1 += sc[k] * bfhi(w);
    }
    red[kg][cp * 2] = a0; red[kg][cp * 2 + 1] = a1;
    __syncthreads();
    if (tid < 64) {
        float s = 0.f;
        #pragma unroll
        for (int i = 0; i < 8; i++) s += red[i][tid];
        g_mod[blockIdx.x * 64 + tid] = bfr(s);
    }
    if (blockIdx.x == 0 && tid == 0) g_epoch = g_epoch + 1;
}

template <int MODE>
__global__ void __launch_bounds__(256) k_ln(const bf16* __restrict__ xin) {
    const int lane = threadIdx.x & 31, row = blockIdx.x * 8 + (threadIdx.x >> 5);
    const bf16* src = (MODE == 0 ? xin : g_x1) + (size_t)row * DM;
    const float* shift = g_mod + (MODE == 0 ? 0 : 3 * DM);
    const float* scale = g_mod + (MODE == 0 ? DM : 4 * DM);
    float v[3][8];
    float s = 0.f;
    #pragma unroll
    for (int i = 0; i < 3; i++) {
        int c = lane + 32 * i;
        if (c < 80) {
            uint4 u = *(const uint4*)(src + c * 8);
            v[i][0] = bflo(u.x); v[i][1] = bfhi(u.x); v[i][2] = bflo(u.y); v[i][3] = bfhi(u.y);
            v[i][4] = bflo(u.z); v[i][5] = bfhi(u.z); v[i][6] = bflo(u.w); v[i][7] = bfhi(u.w);
        } else {
            #pragma unroll
            for (int j = 0; j < 8; j++) v[i][j] = 0.f;
        }
        #pragma unroll
        for (int j = 0; j < 8; j++) s += v[i][j];
    }
    #pragma unroll
    for (int o = 16; o > 0; o >>= 1) s += __shfl_xor_sync(0xffffffffu, s, o);
    const float mean = s * (1.0f / DM);
    float q = 0.f;
    #pragma unroll
    for (int i = 0; i < 3; i++) {
        if (lane + 32 * i < 80) {
            #pragma unroll
            for (int j = 0; j < 8; j++) { float d = v[i][j] - mean; q += d * d; }
        }
    }
    #pragma unroll
    for (int o = 16; o > 0; o >>= 1) q += __shfl_xor_sync(0xffffffffu, q, o);
    const float mb = bfr(mean);
    const float var = bfr(q * (1.0f / DM));
    const float sd = bfr(sqrtf(bfr(var + 1e-5f)));
    #pragma unroll
    for (int i = 0; i < 3; i++) {
        int c = lane + 32 * i;
        if (c < 80) {
            float o[8];
            #pragma unroll
            for (int j = 0; j < 8; j++) {
                float n = bfr(bfr(v[i][j] - mb) / sd);
                float m1 = bfr(1.0f + scale[c * 8 + j]);
                o[j] = bfr(n * m1) + shift[c * 8 + j];
            }
            uint4 u = make_uint4(pack2(o[0], o[1]), pack2(o[2], o[3]), pack2(o[4], o[5]), pack2(o[6], o[7]));
            if (MODE == 0) {
                int seg = row >> 5, r = row & 31, blk = c >> 3, cc = c & 7;
                *(uint4*)(g_ht + (size_t)seg * 20480 + blk * 2048 + r * 64 + ((cc ^ (r & 7)) << 3)) = u;
            } else {
                *(uint4*)(g_h2 + (size_t)row * DM + c * 8) = u;
            }
        }
    }
}

constexpr int SM_WV = 0;
constexpr int SM_HB = 81920;
constexpr int SM_WO = SM_HB + 40960;
constexpr int SM_QX = SM_WO + 77824;
constexpr int SM_KS = SM_QX + 4096;
constexpr int SM_QM = SM_KS + 5120;
constexpr int SM_XS = SM_QM + 1024;
constexpr int SM_MS = SM_XS + 12288;
constexpr int SM_OS = SM_MS + 3840;
constexpr int SM_BAR = SM_OS + 3072;
constexpr int SM_CH = SM_BAR + 128;
constexpr int SM_TOTAL = SM_CH + 128;
static_assert(SM_TOTAL <= 232448, "smem");

enum { B_MEM_FULL = 0, B_MEM_FREE, B_HLO_FULL, B_HHI_FULL, B_HLO_FREE, B_HHI_FREE, B_MS, B_O, B_XS };

__device__ __forceinline__ int probe_blk(uint32_t* blk) {
    uint32_t t0 = 0xffffffffu, t1 = 0xffffffffu, acc = 0;
    for (int rep = 0; rep < 5; rep++) {
        #pragma unroll
        for (int pg = 0; pg < 2; pg++) {
            uint32_t c0 = clk32();
            uint32_t v = atomicOr(blk + pg * 1024 + acc, 0u);
            acc = (v == 0x12345678u) ? 1u : 0u;
            asm volatile("" :: "r"(acc) : "memory");
            uint32_t c1 = clk32() + acc;
            uint32_t d = c1 - c0;
            if (rep > 0) { if (pg == 0) t0 = min(t0, d); else t1 = min(t1, d); }
        }
    }
    return t1 < t0 ? 1 : 0;
}

__device__ __forceinline__ uint32_t wo_tile_off(int w) {
    if (w < 8) return w * 6144;
    if (w < 12) return 8 * 6144 + (w - 8) * 4096 - 2048;
    return 8 * 6144 + 4 * 4096 + (w - 12) * 6144;
}

template <int NRES, int NPRE>
__device__ __forceinline__ void wo_phase(uint32_t sb, int w, int lane, const uint32_t (*res)[4], uint32_t parity,
                                         uint32_t tag, uint32_t off0, uint32_t off1) {
    const int er = (lane & 7) + 8 * (lane >> 4);
    const uint32_t aaddr = sb + SM_WO + wo_tile_off(w) + er * 32 + ((((lane >> 3) & 1) ^ ((er >> 2) & 1)) << 4);
    uint32_t pre[NPRE][4];
    #pragma unroll
    for (int i = 0; i < NPRE; i++) ldsm4t(pre[i], aaddr + (NRES + i) * 512);
    mbar_wait(sb + SM_BAR + B_O * 8, parity);
    float c0[4] = {0.f, 0.f, 0.f, 0.f}, c1[4] = {0.f, 0.f, 0.f, 0.f};
    const uint32_t baddr = sb + SM_OS + lane * 16;
    #pragma unroll
    for (int kp = 0; kp < 6; kp++) {
        uint32_t b[4];
        ldsm4t(b, baddr + kp * 512);
        #pragma unroll
        for (int hh = 0; hh < 2; hh++) {
            const int kt = kp * 2 + hh;
            float* c = hh ? c1 : c0;
            if (kt < NRES) mma16(c, res[kt][0], res[kt][1], res[kt][2], res[kt][3], b[hh * 2], b[hh * 2 + 1]);
            else if (kt < NRES + NPRE) mma16(c, pre[kt - NRES][0], pre[kt - NRES][1], pre[kt - NRES][2], pre[kt - NRES][3], b[hh * 2], b[hh * 2 + 1]);
            else {
                uint32_t a[4];
                ldsm4t(a, aaddr + kt * 512);
                mma16(c, a[0], a[1], a[2], a[3], b[hh * 2], b[hh * 2 + 1]);
            }
        }
    }
    st_relaxed2_off(g_buf1, off0, tagw(c0[0] + c1[0], tag), tagw(c0[1] + c1[1], tag));
    st_relaxed2_off(g_buf1, off1, tagw(c0[2] + c1[2], tag), tagw(c0[3] + c1[3], tag));
}

__device__ __forceinline__ uint32_t hop1_off(uint32_t sb, int col, int h, int t) {
    const int r = col >> 3, j = (col >> 2) & 1;
    uint32_t ch;
    asm volatile("ld.shared.u8 %0, [%1];" : "=r"(ch) : "r"(sb + SM_CH + r) : "memory");
    return (uint32_t)((r * 2 + j) * 8192 + ((ch >> j) & 1) * 4096 + (col & 3) * 1024 + h * 32 + t * 8);
}

__global__ void __launch_bounds__(512, 1)
k_rec(const bf16* __restrict__ mem0, const bf16* __restrict__ Wq, const bf16* __restrict__ Wk,
      const bf16* __restrict__ Wv, const bf16* __restrict__ Wo) {
    extern __shared__ __align__(1024) uint8_t smem_raw[];
    constexpr uint32_t SBC = 1024;
    const uint32_t sb = smem_u32(smem_raw);
    if ((sb & 0xFFFFFFu) != SBC) __trap();
    const int tid = threadIdx.x, lane = tid & 31, warp = tid >> 5, wg = tid >> 7;
    const int b = blockIdx.x, h = b / 3, p = b % 3;
    const int g = lane >> 2, t = lane & 3;
    const int tile0 = p == 0 ? 0 : (p == 1 ? 14 : 27);
    const int ntile = p == 0 ? 14 : 13;
    const uint32_t bar = sb + SM_BAR;

    if (tid == 0) {
        mbar_init(bar + B_MEM_FULL * 8, 4);
        mbar_init(bar + B_MEM_FREE * 8, 12);
        mbar_init(bar + B_HLO_FULL * 8, 1);
        mbar_init(bar + B_HHI_FULL * 8, 1);
        mbar_init(bar + B_HLO_FREE * 8, 12);
        mbar_init(bar + B_HHI_FREE * 8, 12);
        mbar_init(bar + B_MS * 8, 1);
        mbar_init(bar + B_O * 8, 1);
        mbar_init(bar + B_XS * 8, 1);
        asm volatile("fence.mbarrier_init.release.cluster;" ::: "memory");
        mbar_expect(bar + B_MS * 8, 3840);
        mbar_expect(bar + B_O * 8, 3072);
        mbar_expect(bar + B_XS * 8, 12288);
        mbar_expect(bar + B_HLO_FULL * 8, 12288);
        bulk_g2s(sb + SM_HB, g_ht, 12288, sb + SM_BAR + B_HLO_FULL * 8);
        mbar_expect(bar + B_HHI_FULL * 8, 28672);
        bulk_g2s(sb + SM_HB + 12288, (const char*)g_ht + 12288, 28672, sb + SM_BAR + B_HHI_FULL * 8);
    }
    cluster_sync();

    if (wg < 2) {
        asm volatile("setmaxnreg.inc.sync.aligned.u32 200;");
        const int w = warp & 3;
        uint32_t wa[40][4];
        {
            const bf16* W = (wg == 0 ? Wq : Wk) + (size_t)h * DH + p * 64 + w * 16 + t * 4;
            #pragma unroll
            for (int kt = 0; kt < 40; kt++) {
                uint2 l1 = __ldg((const uint2*)(W + (size_t)(kt * 16 + g) * HD));
                uint2 l2 = __ldg((const uint2*)(W + (size_t)(kt * 16 + 8 + g) * HD));
                wa[kt][0] = l1.x; wa[kt][1] = l1.y; wa[kt][2] = l2.x; wa[kt][3] = l2.y;
            }
            #pragma unroll
            for (int kt = 0; kt < 40; kt++) {
                #pragma unroll
                for (int i = 0; i < 4; i++) wa[kt][i] = movm(wa[kt][i]);
            }
        }
        bar_sync(0, 512);
        const uint32_t off0 = hop1_off(sb, (tile0 + warp) * 16 + g, h, t);
        const uint32_t off1 = hop1_off(sb, (tile0 + warp) * 16 + 8 + g, h, t);
        const uint32_t dstx = sb + (wg == 0 ? SM_QX : SM_KS + 1024);

        for (int s = -1; s < NSEG; s++) {
            const uint32_t par = s & 1;
            if (s >= 0) {
                mbar_wait(bar + B_MEM_FULL * 8, par);
                TR(0);
                float c0[4] = {0.f, 0.f, 0.f, 0.f}, c1[4] = {0.f, 0.f, 0.f, 0.f};
                uint32_t maddr = sb + lane * 16;
                asm volatile("" : "+r"(maddr));
                #pragma unroll
                for (int kp = 0; kp < 20; kp++) {
                    uint32_t bb[4];
                    ldsm4t(bb, maddr + (SM_HB + kp * 512));
                    mma16(c0, wa[2 * kp][0], wa[2 * kp][1], wa[2 * kp][2], wa[2 * kp][3], bb[0], bb[1]);
                    mma16(c1, wa[2 * kp + 1][0], wa[2 * kp + 1][1], wa[2 * kp + 1][2], wa[2 * kp + 1][3], bb[2], bb[3]);
                }
                {
                    const int tok = lane & 7, ch = 2 * w + ((lane >> 3) & 1);
                    stsm2t(sb + (wg == 0 ? SM_QM : SM_KS) + tok * 128 + ((ch ^ tok) << 4),
                           pack2(c0[0] + c1[0], c0[1] + c1[1]), pack2(c0[2] + c1[2], c0[3] + c1[3]));
                }
                __syncwarp();
                if (lane == 0) mbar_arrive(bar + B_MEM_FREE * 8);
                TR(1);
                bar_sync(1, 384);
                if (warp < 5) {
                    const int r = lane & 7, cq = lane >> 3;
                    uint32_t a[8], kb[8];
                    ldsm4(a, sb + SM_QM + r * 128 + ((cq ^ r) << 4));
                    ldsm4(kb, sb + SM_KS + (warp * 8 + r) * 128 + ((cq ^ r) << 4));
                    ldsm4(a + 4, sb + SM_QM + r * 128 + (((cq + 4) ^ r) << 4));
                    ldsm4(kb + 4, sb + SM_KS + (warp * 8 + r) * 128 + (((cq + 4) ^ r) << 4));
                    float d0[4] = {0.f, 0.f, 0.f, 0.f}, d1[4] = {0.f, 0.f, 0.f, 0.f};
                    mma16(d0, a[0], 0u, a[1], 0u, kb[0], kb[1]);
                    mma16(d1, a[2], 0u, a[3], 0u, kb[2], kb[3]);
                    mma16(d0, a[4], 0u, a[5], 0u, kb[4], kb[5]);
                    mma16(d1, a[6], 0u, a[7], 0u, kb[6], kb[7]);
                    const uint32_t la = sb + SM_MS + p * 1280 + warp * 256 + lane * 8;
                    #pragma unroll
                    for (int rk = 0; rk < 3; rk++)
                        st_async2(mapa(la, rk), d0[0] + d1[0], d0[1] + d1[1], mapa(bar + B_MS * 8, rk));
                }
                TR(2);
                if (s < NSEG - 1) wo_phase<0, 4>(sb, warp, lane, nullptr, par, (uint32_t)(s % 15) + 1u, off0, off1);
                else mbar_wait(bar + B_O * 8, par);
                TR(4);
                {
                    const int mi = warp < 3 ? 0 : 1, j = warp < 3 ? warp : warp - 3;
                    const int r = lane & 7, cq = lane >> 3;
                    const int qrow = mi * 16 + r + 8 * (cq & 1);
                    uint32_t kb[8];
                    ldsm4(kb, sb + SM_KS + (j * 8 + r) * 128 + ((cq ^ r) << 4));
                    ldsm4(kb + 4, sb + SM_KS + (j * 8 + r) * 128 + (((cq + 4) ^ r) << 4));
                    float d0[4] = {0.f, 0.f, 0.f, 0.f};
                    #pragma unroll
                    for (int kt = 0; kt < 4; kt++) {
                        uint32_t a[4];
                        ldsm4(a, sb + SM_QX + qrow * 128 + (((2 * kt + (cq >> 1)) ^ r) << 4));
                        mma16(d0, a[0], a[1], a[2], a[3], kb[2 * kt], kb[2 * kt + 1]);
                    }
                    const uint32_t la = sb + SM_XS + p * 4096 + warp * 512 + lane * 16;
                    #pragma unroll
                    for (int rk = 0; rk < 3; rk++) st_async4(mapa(la, rk), d0, mapa(bar + B_XS * 8, rk));
                }
            }
            if (s < NSEG - 1) {
                const uint32_t hp = (s + 1) & 1;
                float d[16];
                const uint64_t db0 = make_desc(SBC + SM_HB, 16, 1024, 1);
                mbar_wait(bar + B_HHI_FULL * 8, hp);
                mbar_wait(bar + B_HLO_FULL * 8, hp);
                TR(6);
                wg_fence();
                #pragma unroll
                for (int kt = 0; kt < 12; kt++) wg_rs32(d, wa[kt], db0 + (uint64_t)(((kt >> 2) * 4096 + (kt & 3) * 32) >> 4), kt > 0);
                wg_commit();
                #pragma unroll
                for (int kt = 12; kt < 39; kt++) wg_rs32(d, wa[kt], db0 + (uint64_t)(((kt >> 2) * 4096 + (kt & 3) * 32) >> 4), 1);
                wg_commit();
                wg_wait<1>();
                if (lane == 0) mbar_arrive(bar + B_HLO_FREE * 8);
                {
                    const int r = lane & 7, mq = lane >> 3;
                    const uint32_t ha = sb + SM_HB + 9 * 4096 + (8 * (mq >> 1) + r) * 128 + (((6 + (mq & 1)) ^ r) << 4);
                    uint32_t b0[4], b1[4];
                    ldsm4(b0, ha);
                    ldsm4(b1, ha + 2048);
                    wg_wait<0>();
                    mma16(d + 0, wa[39][0], wa[39][1], wa[39][2], wa[39][3], b0[0], b0[1]);
                    mma16(d + 4, wa[39][0], wa[39][1], wa[39][2], wa[39][3], b0[2], b0[3]);
                    mma16(d + 8, wa[39][0], wa[39][1], wa[39][2], wa[39][3], b1[0], b1[1]);
                    mma16(d + 12, wa[39][0], wa[39][1], wa[39][2], wa[39][3], b1[2], b1[3]);
                }
                __syncwarp();
                if (lane == 0) mbar_arrive(bar + B_HHI_FREE * 8);
                TR(7);
                bar_sync(2, 256);
                const int mi = lane >> 3, r = lane & 7;
                #pragma unroll
                for (int jj = 0; jj < 2; jj++) {
                    const int tok = 8 * (2 * jj + (mi >> 1)) + r, ch = 2 * w + (mi & 1);
                    stsm4t(dstx + tok * 128 + ((ch ^ r) << 4),
                           pack2(d[8 * jj + 0], d[8 * jj + 1]), pack2(d[8 * jj + 2], d[8 * jj + 3]),
                           pack2(d[8 * jj + 4], d[8 * jj + 5]), pack2(d[8 * jj + 6], d[8 * jj + 7]));
                }
            }
        }
    } else if (wg == 2) {
        asm volatile("setmaxnreg.dec.sync.aligned.u32 72;");
        const int w = warp & 3;
        {
            const int c = tid & 7;
            const bf16* src = Wv + (size_t)h * DH + p * 64 + c * 8;
            for (int k = (tid & 127) >> 3; k < DM; k += 16)
                cpa16(sb + SM_WV + k * 128 + ((c ^ (k & 7)) << 4), src + (size_t)k * HD);
        }
        uint32_t res[4][4];
        {
            const bf16* src = Wo + (size_t)h * DH * DM + (tile0 + warp) * 16 + 2 * t;
            #pragma unroll
            for (int kt = 0; kt < 4; kt++) {
                res[kt][0] = __ldg((const uint32_t*)(src + (size_t)(kt * 16 + g) * DM));
                res[kt][1] = __ldg((const uint32_t*)(src + (size_t)(kt * 16 + g) * DM + 8));
                res[kt][2] = __ldg((const uint32_t*)(src + (size_t)(kt * 16 + 8 + g) * DM));
                res[kt][3] = __ldg((const uint32_t*)(src + (size_t)(kt * 16 + 8 + g) * DM + 8));
            }
            #pragma unroll
            for (int kt = 0; kt < 4; kt++) {
                #pragma unroll
                for (int i = 0; i < 4; i++) res[kt][i] = movm(res[kt][i]);
            }
        }
        cpa_wait_all();
        fence_async();
        bar_sync(0, 512);
        const uint32_t off0 = hop1_off(sb, (tile0 + warp) * 16 + g, h, t);
        const uint32_t off1 = hop1_off(sb, (tile0 + warp) * 16 + 8 + g, h, t);
        const uint64_t da0 = make_desc(SBC + SM_WV, 16, 1024, 1);
        const float SCALE = 0.07216878364870322f;
        const float L2E = 1.4426950408889634f;
        uint32_t vx[8];
        uint32_t vm0 = 0, vm1 = 0;
        #pragma unroll
        for (int i = 0; i < 8; i++) vx[i] = 0;

        auto crit = [&](const int s) {
                const uint32_t par = s & 1;
                mbar_wait(bar + B_MEM_FULL * 8, par);
                bar_sync(1, 384);
                TR(0);
                float dv[4];
                {
                    const uint64_t dbm = make_desc(SBC + SM_HB, 128, 128, 0);
                    wg_fence();
                    #pragma unroll
                    for (int kt = 0; kt < 40; kt++) wg_ss8(dv, da0 + (uint64_t)(kt * 128), dbm + (uint64_t)(kt * 16), kt > 0);
                    wg_commit();
                }
                mbar_wait(bar + B_MS * 8, par);
                TR(1);
                if (tid == 256) mbar_expect(bar + B_MS * 8, 3840);
                float sc[10];
                #pragma unroll
                for (int j = 0; j < 5; j++) {
                    const uint32_t a = sb + SM_MS + j * 256 + lane * 8;
                    float2 v0 = lds2f(a), v1 = lds2f(a + 1280), v2 = lds2f(a + 2560);
                    sc[2 * j] = bfr(bfr(v0.x + v1.x + v2.x) * SCALE);
                    sc[2 * j + 1] = bfr(bfr(v0.y + v1.y + v2.y) * SCALE);
                }
                float mx = sc[0];
                #pragma unroll
                for (int i = 1; i < 10; i++) mx = fmaxf(mx, sc[i]);
                mx = fmaxf(mx, __shfl_xor_sync(0xffffffffu, mx, 1));
                mx = fmaxf(mx, __shfl_xor_sync(0xffffffffu, mx, 2));
                float sum = 0.f;
                #pragma unroll
                for (int i = 0; i < 10; i++) { sc[i] = exp2f((sc[i] - mx) * L2E); sum += sc[i]; }
                sum += __shfl_xor_sync(0xffffffffu, sum, 1);
                sum += __shfl_xor_sync(0xffffffffu, sum, 2);
                const float inv = 1.0f / sum;
                uint32_t pb[5];
                #pragma unroll
                for (int j = 0; j < 5; j++) pb[j] = pack2(sc[2 * j] * inv, sc[2 * j + 1] * inv);
                float o0[4] = {0.f, 0.f, 0.f, 0.f}, o1[4] = {0.f, 0.f, 0.f, 0.f};
                mma16(o0, vx[0], vx[1], vx[2], vx[3], pb[1], pb[2]);
                mma16(o1, vx[4], vx[5], vx[6], vx[7], pb[3], pb[4]);
                TR(2);
                wg_wait<0>();
                TR(3);
                if (lane == 0) mbar_arrive(bar + B_MEM_FREE * 8);
                vm0 = pack2(dv[0], dv[1]); vm1 = pack2(dv[2], dv[3]);
                mma8(o0, vm0, vm1, pb[0]);
                {
                    const uint32_t q0 = pack2(o0[0] + o1[0], o0[1] + o1[1]), q1 = pack2(o0[2] + o1[2], o0[3] + o1[3]);
                    const uint32_t la = sb + SM_OS + (p * 64 + w * 16 + g) * 16 + t * 4;
                    #pragma unroll
                    for (int rk = 0; rk < 3; rk++) {
                        const uint32_t ra = mapa(la, rk), rb = mapa(bar + B_O * 8, rk);
                        st_async1(ra, q0, rb);
                        st_async1(ra + 128, q1, rb);
                    }
                }
                if (s < NSEG - 1) wo_phase<4, 4>(sb, warp, lane, res, par, (uint32_t)(s % 15) + 1u, off0, off1);
                else mbar_wait(bar + B_O * 8, par);
                TR(4);
                if (tid == 256) mbar_expect(bar + B_O * 8, 3072);
        };
        auto xatt = [&](const int s) {
                const uint32_t par = s & 1;
                mbar_wait(bar + B_XS * 8, par);
                TR(8);
                if (tid == 256) mbar_expect(bar + B_XS * 8, 12288);
                bf16* orow = g_ox + (size_t)(s * 32 + g) * HD + h * DH + p * 64 + w * 16 + 2 * t;
                #pragma unroll
                for (int qt = 0; qt < 4; qt++) {
                    const int mi = qt >> 1, hf = qt & 1;
                    const int nt = qt + 2, tb = mi ? 3 : 0;
                    float sc[5][2];
                    #pragma unroll
                    for (int j = 0; j < 5; j++) {
                        if (j < nt) {
                            const uint32_t a = sb + SM_XS + (tb + j) * 512 + lane * 16 + hf * 8;
                            float2 v0 = lds2f(a), v1 = lds2f(a + 4096), v2 = lds2f(a + 8192);
                            sc[j][0] = bfr(bfr(v0.x + v1.x + v2.x) * SCALE);
                            sc[j][1] = bfr(bfr(v0.y + v1.y + v2.y) * SCALE);
                            if (j == nt - 1) {
                                const float NEG = -999292928.0f;
                                if (2 * t > g) sc[j][0] = NEG;
                                if (2 * t + 1 > g) sc[j][1] = NEG;
                            }
                        }
                    }
                    float m0 = fmaxf(sc[0][0], sc[0][1]);
                    #pragma unroll
                    for (int j = 1; j < 5; j++) if (j < nt) m0 = fmaxf(m0, fmaxf(sc[j][0], sc[j][1]));
                    m0 = fmaxf(m0, __shfl_xor_sync(0xffffffffu, m0, 1));
                    m0 = fmaxf(m0, __shfl_xor_sync(0xffffffffu, m0, 2));
                    float s0 = 0.f;
                    #pragma unroll
                    for (int j = 0; j < 5; j++) if (j < nt) {
                        sc[j][0] = exp2f((sc[j][0] - m0) * L2E); sc[j][1] = exp2f((sc[j][1] - m0) * L2E);
                        s0 += sc[j][0] + sc[j][1];
                    }
                    s0 += __shfl_xor_sync(0xffffffffu, s0, 1);
                    s0 += __shfl_xor_sync(0xffffffffu, s0, 2);
                    const float iv = 1.0f / s0;
                    uint32_t pb[5];
                    #pragma unroll
                    for (int j = 0; j < 5; j++) pb[j] = j < nt ? pack2(sc[j][0] * iv, sc[j][1] * iv) : 0u;
                    float o[4] = {0.f, 0.f, 0.f, 0.f};
                    mma8(o, vm0, vm1, pb[0]);
                    mma16(o, vx[0], vx[1], vx[2], vx[3], pb[1], pb[2]);
                    if (mi) mma16(o, vx[4], vx[5], vx[6], vx[7], pb[3], pb[4]);
                    const uint32_t u0 = movm(pack2(o[0], o[1])), u1 = movm(pack2(o[2], o[3]));
                    bf16* dst = orow + (size_t)(8 * qt) * HD;
                    *(uint32_t*)dst = u0;
                    *(uint32_t*)(dst + 8) = u1;
                }
                TR(9);
        };
        for (int s = -1; s < NSEG - 1; s++) {
            if (s >= 0) crit(s);
            float d[16];
            const uint32_t hp = (s + 1) & 1;
            const uint64_t db0 = make_desc(SBC + SM_HB, 16, 1024, 1);
            mbar_wait(bar + B_HHI_FULL * 8, hp);
            mbar_wait(bar + B_HLO_FULL * 8, hp);
            TR(6);
            wg_fence();
            #pragma unroll
            for (int kt = 0; kt < 12; kt++) wg_ss32(d, da0 + (uint64_t)(kt * 128), db0 + (uint64_t)(((kt >> 2) * 4096 + (kt & 3) * 32) >> 4), kt > 0);
            wg_commit();
            #pragma unroll
            for (int kt = 12; kt < 40; kt++) wg_ss32(d, da0 + (uint64_t)(kt * 128), db0 + (uint64_t)(((kt >> 2) * 4096 + (kt & 3) * 32) >> 4), 1);
            wg_commit();
            TR(5);
            wg_wait<1>();
            if (lane == 0) mbar_arrive(bar + B_HLO_FREE * 8);
            if (s >= 0) xatt(s);
            wg_wait<0>();
            TR(7);
            if (lane == 0) mbar_arrive(bar + B_HHI_FREE * 8);
            #pragma unroll
            for (int i = 0; i < 8; i++) vx[i] = pack2(d[2 * i], d[2 * i + 1]);
        }
        crit(NSEG - 1);
        xatt(NSEG - 1);
    } else {
        asm volatile("setmaxnreg.dec.sync.aligned.u32 40;");
        const int w = warp & 3, lt = tid & 127;
        {
            const bf16* src0 = Wo + (size_t)h * DH * DM + tile0 * 16;
            const int nch = 2 * ntile;
            for (int i = lt; i < DH * nch; i += 128) {
                const int e = i / nch, c = i - e * nch, tl = c >> 1, cc = c & 1;
                if (tl >= 8 && tl < 12 && e < 64) continue;
                cpa16(sb + SM_WO + wo_tile_off(tl) + e * 32 + ((cc ^ ((e >> 2) & 1)) << 4), src0 + (size_t)e * DM + c * 8);
            }
        }
        const uint32_t epoch = *(volatile uint32_t*)&g_epoch;
        if (b < 80) {
            #pragma unroll
            for (int i = 0; i < 2; i++) {
                const int idx = lt + i * 128, sl = idx >> 6, pg = (idx >> 5) & 1, wd = idx & 31;
                st_relaxed1(g_buf2 + (sl * 3 + (b >> 5)) * 2048 + pg * 1024 + (b & 31) * 32 + wd, 0xFFFFFFFFu);
            }
            __threadfence();
        }
        if (lane == 0) {
            for (int i = w; i < 14; i += 4) {
                int c = 0;
                if (i < 12) c = probe_blk(g_buf2 + i * 2048 + 640 + (b & 31) * 8);
                else if (b < 80) c = probe_blk(g_buf1 + (b * 2 + (i - 12)) * 2048);
                asm volatile("st.shared.u8 [%0], %1;" :: "r"(sb + SM_CH + 96 + i), "r"(c) : "memory");
            }
        }
        bar_sync(3, 128);
        uint32_t selmask = 0;
        for (int i = 0; i < 14; i++) {
            uint32_t c; asm volatile("ld.shared.u8 %0, [%1];" : "=r"(c) : "r"(sb + SM_CH + 96 + i) : "memory");
            selmask |= c << i;
        }
        if (lt == 0 && b < 80) st_release1(&g_choice[b], (epoch << 2) | (selmask >> 12));
        if (lt < 80) {
            uint32_t v, guard = 0;
            do { v = ld_acquire1(&g_choice[lt]); if (++guard > (1u << 22)) __trap(); } while ((v >> 2) != (epoch & 0x3fffffffu));
            asm volatile("st.shared.u8 [%0], %1;" :: "r"(sb + SM_CH + lt), "r"(v & 3u) : "memory");
        }
        cpa_wait_all();
        bar_sync(0, 512);
        const bool has_tile = (12 + w) < ntile;
        uint32_t off0 = 0, off1 = 0;
        if (has_tile) {
            off0 = hop1_off(sb, (tile0 + warp) * 16 + g, h, t);
            off1 = hop1_off(sb, (tile0 + warp) * 16 + 8 + g, h, t);
        }
        const char* rin = (const char*)g_buf1 + (size_t)(b * 2 + (w >> 1)) * 8192 + ((selmask >> (12 + (w >> 1))) & 1) * 4096 + (w & 1) * 2048 + lane * 16;

        for (int s = 0; s < NSEG; s++) {
            const uint32_t par = s & 1;
            mbar_wait(bar + B_HLO_FREE * 8, par);
            TR(10);
            if (s == 0) {
                for (int k = lt; k < DM; k += 128) {
                    uint32_t v[4];
                    #pragma unroll
                    for (int i = 0; i < 4; i++) {
                        uint32_t lo = *(const uint16_t*)(mem0 + (2 * i) * DM + k), hi = *(const uint16_t*)(mem0 + (2 * i + 1) * DM + k);
                        v[i] = lo | (hi << 16);
                    }
                    asm volatile("st.shared.v4.u32 [%0], {%1,%2,%3,%4};" :: "r"(sb + SM_HB + k * 16), "r"(v[0]), "r"(v[1]), "r"(v[2]), "r"(v[3]) : "memory");
                }
            } else {
                const int sl = s & 3;
                const char* q = (const char*)g_buf2 + sl * 3 * 8192 + lt * 16;
                const uint32_t sm = selmask >> (sl * 3);
                const uint32_t dst = sb + SM_HB + lt * 16;
                uint32_t guard = 0;
                while (true) {
                    #pragma unroll
                    for (int c = 0; c < 5; c++)
                        cpa16(dst + c * 2048, q + (c >> 1) * 8192 + ((sm >> (c >> 1)) & 1) * 4096 + (c & 1) * 2048);
                    cpa_wait_all();
                    bool ok = true;
                    #pragma unroll
                    for (int c = 0; c < 5; c++) { uint4 v = lds4(dst + c * 2048); ok = ok && oks(v); }
                    if (__all_sync(0xffffffffu, ok)) break;
                    if (++guard > (1u << 22)) __trap();
                }
            }
            fence_async();
            __syncwarp();
            if (lane == 0) mbar_arrive(bar + B_MEM_FULL * 8);
            TR(0);
            if (s < NSEG - 1) {
                if (w == 3) {
                    if (lane == 0) {
                        const char* src = (const char*)g_ht + (size_t)(s + 1) * 40960;
                        mbar_wait(bar + B_HHI_FREE * 8, par);
                        mbar_expect(bar + B_HHI_FULL * 8, 28672);
                        bulk_g2s(sb + SM_HB + 12288, src + 12288, 28672, sb + SM_BAR + B_HHI_FULL * 8);
                        mbar_wait(bar + B_MEM_FREE * 8, par);
                        mbar_expect(bar + B_HLO_FULL * 8, 12288);
                        bulk_g2s(sb + SM_HB, src, 12288, sb + SM_BAR + B_HLO_FULL * 8);
                    }
                    __syncwarp();
                }
                const uint32_t tag = (uint32_t)(s % 15) + 1u;
                if (has_tile) wo_phase<0, 3>(sb, warp, lane, nullptr, par, tag, off0, off1);
                else mbar_wait(bar + B_O * 8, par);
                TR(4);
                if (b < 80) {
                    uint4 v0, v1, v2, v3;
                    uint32_t guard = 0;
                    while (true) {
                        v0 = ld_relaxed4(rin); v1 = ld_relaxed4(rin + 512);
                        v2 = ld_relaxed4(rin + 1024); v3 = ld_relaxed4(rin + 1536);
                        if (__all_sync(0xffffffffu, ok4(v0, tag) && ok4(v1, tag) && ok4(v2, tag) && ok4(v3, tag))) break;
                        if (++guard > (1u << 22)) __trap();
                    }
                    TR(11);
                    float a0 = uf(v0.x) + uf(v1.x), a1 = uf(v0.y) + uf(v1.y), a2 = uf(v0.z) + uf(v1.z), a3 = uf(v0.w) + uf(v1.w);
                    float b0 = uf(v2.x) + uf(v3.x), b1 = uf(v2.y) + uf(v3.y), b2 = uf(v2.z) + uf(v3.z), b3 = uf(v2.w) + uf(v3.w);
                    const bool u16 = lane & 16;
                    float k0 = (u16 ? b0 : a0) + __shfl_xor_sync(0xffffffffu, u16 ? a0 : b0, 16);
                    float k1 = (u16 ? b1 : a1) + __shfl_xor_sync(0xffffffffu, u16 ? a1 : b1, 16);
                    float k2 = (u16 ? b2 : a2) + __shfl_xor_sync(0xffffffffu, u16 ? a2 : b2, 16);
                    float k3 = (u16 ? b3 : a3) + __shfl_xor_sync(0xffffffffu, u16 ? a3 : b3, 16);
                    const bool u8 = lane & 8;
                    float m0 = (u8 ? k2 : k0) + __shfl_xor_sync(0xffffffffu, u8 ? k0 : k2, 8);
                    float m1 = (u8 ? k3 : k1) + __shfl_xor_sync(0xffffffffu, u8 ? k1 : k3, 8);
                    m0 += __shfl_xor_sync(0xffffffffu, m0, 4); m1 += __shfl_xor_sync(0xffffffffu, m1, 4);
                    m0 += __shfl_xor_sync(0xffffffffu, m0, 2); m1 += __shfl_xor_sync(0xffffffffu, m1, 2);
                    const int col = b * 8 + 2 * w + (lane >> 4), wd = 2 * (lane & 1) + ((lane >> 3) & 1);
                    const int sl = (lane & 4) ? ((s + 3) & 3) : ((s + 1) & 3);
                    uint32_t* dst = g_buf2 + (sl * 3 + (col >> 8)) * 2048 + ((lane >> 1) & 1) * 1024 + (col & 255) * 4 + wd;
                    st_relaxed1(dst, (lane & 4) ? 0xFFFFFFFFu : pack2(m0, m1));
                    TR(12);
                }
            }
        }
    }
    cluster_sync();
}

constexpr int G_STAGES = 5;
constexpr int G_STAGE_BYTES = 32768;
constexpr int G_SMEM = G_STAGES * G_STAGE_BYTES + 1024 + 256;

__device__ __forceinline__ void tma2d(uint32_t dst, const CUtensorMap* map, int c0, int c1, uint32_t bar) {
    asm volatile("cp.async.bulk.tensor.2d.shared::cluster.global.mbarrier::complete_tx::bytes [%0], [%1, {%2, %3}], [%4];"
                 :: "r"(dst), "l"(map), "r"(c0), "r"(c1), "r"(bar) : "memory");
}
__device__ __forceinline__ void wg_ss128(float* d, uint64_t da, uint64_t db, int sc) {
    asm volatile("{\n\t.reg .pred p;\n\tsetp.ne.b32 p, %66, 0;\n\t"
        "wgmma.mma_async.sync.aligned.m64n128k16.f32.bf16.bf16 "
        "{%0,%1,%2,%3,%4,%5,%6,%7,%8,%9,%10,%11,%12,%13,%14,%15,%16,%17,%18,%19,%20,%21,%22,%23,%24,%25,%26,%27,%28,%29,%30,%31,"
        "%32,%33,%34,%35,%36,%37,%38,%39,%40,%41,%42,%43,%44,%45,%46,%47,%48,%49,%50,%51,%52,%53,%54,%55,%56,%57,%58,%59,%60,%61,%62,%63}, "
        "%64, %65, p, 1, 1, 0, 1;\n\t}"
        : "+f"(d[0]), "+f"(d[1]), "+f"(d[2]), "+f"(d[3]), "+f"(d[4]), "+f"(d[5]), "+f"(d[6]), "+f"(d[7]),
          "+f"(d[8]), "+f"(d[9]), "+f"(d[10]), "+f"(d[11]), "+f"(d[12]), "+f"(d[13]), "+f"(d[14]), "+f"(d[15]),
          "+f"(d[16]), "+f"(d[17]), "+f"(d[18]), "+f"(d[19]), "+f"(d[20]), "+f"(d[21]), "+f"(d[22]), "+f"(d[23]),
          "+f"(d[24]), "+f"(d[25]), "+f"(d[26]), "+f"(d[27]), "+f"(d[28]), "+f"(d[29]), "+f"(d[30]), "+f"(d[31]),
          "+f"(d[32]), "+f"(d[33]), "+f"(d[34]), "+f"(d[35]), "+f"(d[36]), "+f"(d[37]), "+f"(d[38]), "+f"(d[39]),
          "+f"(d[40]), "+f"(d[41]), "+f"(d[42]), "+f"(d[43]), "+f"(d[44]), "+f"(d[45]), "+f"(d[46]), "+f"(d[47]),
          "+f"(d[48]), "+f"(d[49]), "+f"(d[50]), "+f"(d[51]), "+f"(d[52]), "+f"(d[53]), "+f"(d[54]), "+f"(d[55]),
          "+f"(d[56]), "+f"(d[57]), "+f"(d[58]), "+f"(d[59]), "+f"(d[60]), "+f"(d[61]), "+f"(d[62]), "+f"(d[63])
        : "l"(da), "l"(db), "r"(sc));
}

template <int EPI>
__global__ void __launch_bounds__(384, 1)
k_gemm(const __grid_constant__ CUtensorMap mapA, const __grid_constant__ CUtensorMap mapB, int K,
       const bf16* __restrict__ xin, bf16* __restrict__ outp) {
    extern __shared__ uint8_t smem_raw[];
    const uint32_t sb = (smem_u32(smem_raw) + 1023u) & ~1023u;
    const uint32_t bars = sb + G_STAGES * G_STAGE_BYTES;
    const int tid = threadIdx.x, lane = tid & 31, wg = tid >> 7;
    const int n0 = blockIdx.x * 128, m0 = blockIdx.y * 128;
    const int nk = K / 64;
    if (tid == 0) {
        for (int i = 0; i < G_STAGES; i++) { mbar_init(bars + i * 8, 1); mbar_init(bars + 64 + i * 8, 8); }
        asm volatile("fence.mbarrier_init.release.cluster;" ::: "memory");
    }
    __syncthreads();
    if (wg == 0) {
        if (tid == 0) {
            for (int kb = 0; kb < nk; kb++) {
                const int st = kb % G_STAGES;
                if (kb >= G_STAGES) mbar_wait(bars + 64 + st * 8, ((kb / G_STAGES) - 1) & 1);
                const uint32_t a = sb + st * G_STAGE_BYTES;
                mbar_expect(bars + st * 8, G_STAGE_BYTES);
                tma2d(a, &mapA, kb * 64, m0, bars + st * 8);
                tma2d(a + 16384, &mapB, n0, kb * 64, bars + st * 8);
                tma2d(a + 16384 + 8192, &mapB, n0 + 64, kb * 64, bars + st * 8);
            }
        }
    } else {
        float d[64];
        #pragma unroll
        for (int i = 0; i < 64; i++) d[i] = 0.f;
        const int cw = wg - 1;
        for (int kb = 0; kb < nk; kb++) {
            const int st = kb % G_STAGES;
            mbar_wait(bars + st * 8, (kb / G_STAGES) & 1);
            const uint32_t a = sb + st * G_STAGE_BYTES;
            const uint64_t da = make_desc(a + cw * 8192, 16, 1024, 1);
            const uint64_t db = make_desc(a + 16384, 8192, 1024, 1);
            wg_fence();
            #pragma unroll
            for (int k = 0; k < 4; k++) wg_ss128(d, da + (uint64_t)(k * 2), db + (uint64_t)(k * 128), 1);
            wg_commit();
            if (kb > 0) {
                wg_wait<1>();
                if (lane == 0) mbar_arrive(bars + 64 + ((kb - 1) % G_STAGES) * 8);
            }
        }
        wg_wait<0>();
        const int g = lane >> 2, t = lane & 3, w = (tid >> 5) & 3;
        const int ldo = EPI == 1 ? FF : DM;
        #pragma unroll
        for (int hf = 0; hf < 2; hf++) {
            const int row = m0 + cw * 64 + w * 16 + g + 8 * hf;
            #pragma unroll
            for (int j = 0; j < 16; j++) {
                const int col = n0 + j * 8 + 2 * t;
                float a0 = bfr(d[4 * j + 2 * hf]), a1 = bfr(d[4 * j + 2 * hf + 1]);
                uint32_t o;
                if (EPI == 1) {
                    o = pack2(a0 / (1.0f + __expf(-a0)), a1 / (1.0f + __expf(-a1)));
                } else {
                    const float2 gm = *(const float2*)(g_mod + (EPI == 0 ? 2 : 5) * DM + col);
                    const uint32_t xv = *(const uint32_t*)(xin + (size_t)row * DM + col);
                    o = pack2(bflo(xv) + bfr(gm.x * a0), bfhi(xv) + bfr(gm.y * a1));
                }
                *(uint32_t*)(outp + (size_t)row * ldo + col) = o;
            }
        }
    }
}

typedef CUresult (*EncodeFn)(CUtensorMap*, CUtensorMapDataType, cuuint32_t, void*, const cuuint64_t*, const cuuint64_t*,
                             const cuuint32_t*, const cuuint32_t*, CUtensorMapInterleave, CUtensorMapSwizzle,
                             CUtensorMapL2promotion, CUtensorMapFloatOOBfill);

static void make_map(EncodeFn fn, CUtensorMap* m, const void* ptr, uint64_t inner, uint64_t outer, uint32_t bi, uint32_t bo) {
    cuuint64_t dims[2] = {inner, outer};
    cuuint64_t strides[1] = {inner * 2};
    cuuint32_t box[2] = {bi, bo};
    cuuint32_t es[2] = {1, 1};
    fn(m, CU_TENSOR_MAP_DATA_TYPE_BFLOAT16, 2, (void*)ptr, dims, strides, box, es, CU_TENSOR_MAP_INTERLEAVE_NONE,
       CU_TENSOR_MAP_SWIZZLE_128B, CU_TENSOR_MAP_L2_PROMOTION_L2_256B, CU_TENSOR_MAP_FLOAT_OOB_FILL_NONE);
}

extern "C" void kernel_launch(void* const* d_in, const int* in_sizes, int n_in, void* d_out, int out_size) {
    const bf16* x = (const bf16*)d_in[0];
    const bf16* mem0 = (const bf16*)d_in[1];
    const bf16* Wq = (const bf16*)d_in[2];
    const bf16* Wk = (const bf16*)d_in[3];
    const bf16* Wv = (const bf16*)d_in[4];
    const bf16* Wo = (const bf16*)d_in[5];
    const bf16* w1 = (const bf16*)d_in[8];
    const bf16* w2 = (const bf16*)d_in[9];
    const bf16* c = (const bf16*)d_in[10];
    const bf16* wmod = (const bf16*)d_in[11];
    bf16* out = (bf16*)d_out;

    static EncodeFn enc = nullptr;
    static void *p_ox, *p_x1, *p_h2, *p_act;
    if (!enc) {
        cudaDriverEntryPointQueryResult qr;
        void* f = nullptr;
        cudaGetDriverEntryPoint("cuTensorMapEncodeTiled", &f, cudaEnableDefault, &qr);
        enc = (EncodeFn)f;
        cudaGetSymbolAddress(&p_ox, g_ox);
        cudaGetSymbolAddress(&p_x1, g_x1);
        cudaGetSymbolAddress(&p_h2, g_h2);
        cudaGetSymbolAddress(&p_act, g_act);
        cudaFuncSetAttribute(k_rec, cudaFuncAttributeMaxDynamicSharedMemorySize, SM_TOTAL);
        cudaFuncSetAttribute(k_gemm<0>, cudaFuncAttributeMaxDynamicSharedMemorySize, G_SMEM);
        cudaFuncSetAttribute(k_gemm<1>, cudaFuncAttributeMaxDynamicSharedMemorySize, G_SMEM);
        cudaFuncSetAttribute(k_gemm<2>, cudaFuncAttributeMaxDynamicSharedMemorySize, G_SMEM);
    }
    CUtensorMap mOx, mWo, mH2, mW1, mAct, mW2;
    make_map(enc, &mOx, p_ox, HD, SEQ, 64, 128);
    make_map(enc, &mWo, Wo, DM, HD, 64, 64);
    make_map(enc, &mH2, p_h2, DM, SEQ, 64, 128);
    make_map(enc, &mW1, w1, FF, DM, 64, 64);
    make_map(enc, &mAct, p_act, FF, SEQ, 64, 128);
    make_map(enc, &mW2, w2, DM, FF, 64, 64);

    cudaStream_t st = cudaStreamPerThread;
    k_mod<<<60, 256, 0, st>>>(c, wmod);
    k_ln<0><<<SEQ / 8, 256, 0, st>>>(x);
    {
        cudaLaunchConfig_t cfg = {};
        cfg.gridDim = dim3(96); cfg.blockDim = dim3(512); cfg.dynamicSmemBytes = SM_TOTAL; cfg.stream = st;
        cudaLaunchAttribute at[1];
        at[0].id = cudaLaunchAttributeClusterDimension;
        at[0].val.clusterDim.x = 3; at[0].val.clusterDim.y = 1; at[0].val.clusterDim.z = 1;
        cfg.attrs = at; cfg.numAttrs = 1;
        cudaLaunchKernelEx(&cfg, k_rec, mem0, Wq, Wk, Wv, Wo);
    }
    k_gemm<0><<<dim3(5, 16), 384, G_SMEM, st>>>(mOx, mWo, HD, x, (bf16*)p_x1);
    k_ln<1><<<SEQ / 8, 256, 0, st>>>(nullptr);
    k_gemm<1><<<dim3(12, 16), 384, G_SMEM, st>>>(mH2, mW1, DM, nullptr, (bf16*)p_act);
    k_gemm<2><<<dim3(5, 16), 384, G_SMEM, st>>>(mAct, mW2, FF, (const bf16*)p_x1, out);
}
```

```cpp
#include <cuda_runtime.h>
#include <cuda_bf16.h>
#include <cuda.h>
#include <stdint.h>

typedef __nv_bfloat16 bf16;

constexpr int SEQ = 2048, DM = 640, NH = 32, DH = 192, NSEG = 64, FF = 1536, HD = NH * DH;

__device__ float g_mod[6 * DM];
__device__ __align__(1024) bf16 g_ht[(size_t)SEQ * DM];
__device__ __align__(1024) bf16 g_ox[(size_t)SEQ * HD];
__device__ __align__(1024) bf16 g_x1[(size_t)SEQ * DM];
__device__ __align__(1024) bf16 g_h2[(size_t)SEQ * DM];
__device__ __align__(1024) bf16 g_act[(size_t)SEQ * FF];
__device__ __align__(8192) uint32_t g_buf1[80 * 2 * 2048];
__device__ __align__(8192) uint32_t g_buf2[4 * 3 * 2048];
__device__ uint32_t g_choice[128];
__device__ uint32_t g_epoch;
#define TR(k)

__device__ __forceinline__ float bfr(float x) { return __bfloat162float(__float2bfloat16_rn(x)); }
__device__ __forceinline__ uint32_t pack2(float a, float b) {
    uint32_t r; asm("cvt.rn.bf16x2.f32 %0, %1, %2;" : "=r"(r) : "f"(b), "f"(a)); return r;
}
__device__ __forceinline__ float bflo(uint32_t v) { return __uint_as_float(v << 16); }
__device__ __forceinline__ float bfhi(uint32_t v) { return __uint_as_float(v & 0xffff0000u); }
__device__ __forceinline__ float ex2(float x) { float r; asm("ex2.approx.ftz.f32 %0, %1;" : "=f"(r) : "f"(x)); return r; }
__device__ __forceinline__ float rcpf(float x) { float r; asm("rcp.approx.ftz.f32 %0, %1;" : "=f"(r) : "f"(x)); return r; }
__device__ __forceinline__ void score2(float& a, float& b) {
    const float SCALE = 0.07216878364870322f;
    uint32_t u = pack2(a, b);
    u = pack2(bflo(u) * SCALE, bfhi(u) * SCALE);
    a = bflo(u); b = bfhi(u);
}
__device__ __forceinline__ uint32_t smem_u32(const void* p) { return (uint32_t)__cvta_generic_to_shared(p); }

__device__ __forceinline__ void mbar_init(uint32_t bar, uint32_t cnt) {
    asm volatile("mbarrier.init.shared::cta.b64 [%0], %1;" :: "r"(bar), "r"(cnt) : "memory");
}
__device__ __forceinline__ void mbar_arrive(uint32_t bar) {
    asm volatile("mbarrier.arrive.shared::cta.b64 _, [%0];" :: "r"(bar) : "memory");
}
__device__ __forceinline__ void mbar_expect(uint32_t bar, uint32_t bytes) {
    asm volatile("mbarrier.arrive.expect_tx.shared::cta.b64 _, [%0], %1;" :: "r"(bar), "r"(bytes) : "memory");
}
__device__ __forceinline__ bool mbar_try(uint32_t bar, uint32_t parity) {
    uint32_t ok;
    asm volatile("{\n\t.reg .pred p;\n\tmbarrier.try_wait.parity.shared::cta.b64 p, [%1], %2;\n\tselp.u32 %0, 1, 0, p;\n\t}"
                 : "=r"(ok) : "r"(bar), "r"(parity) : "memory");
    return ok != 0;
}
__device__ __forceinline__ bool mbar_try_cluster(uint32_t bar, uint32_t parity) {
    uint32_t ok;
    asm volatile("{\n\t.reg .pred p;\n\tmbarrier.try_wait.parity.acquire.cluster.shared::cta.b64 p, [%1], %2;\n\tselp.u32 %0, 1, 0, p;\n\t}"
                 : "=r"(ok) : "r"(bar), "r"(parity) : "memory");
    return ok != 0;
}
__device__ __forceinline__ void mbar_wait(uint32_t bar, uint32_t parity) {
    uint32_t guard = 0;
    while (!mbar_try(bar, parity)) { if (++guard > (1u << 22)) __trap(); }
}
__device__ __forceinline__ void mbar_wait_cluster(uint32_t bar, uint32_t parity) {
    uint32_t guard = 0;
    while (!mbar_try_cluster(bar, parity)) { if (++guard > (1u << 22)) __trap(); }
}
__device__ __forceinline__ void bar_sync(int id, int n) { asm volatile("bar.sync %0, %1;" :: "r"(id), "r"(n) : "memory"); }
__device__ __forceinline__ void bar_arrive(int id, int n) { asm volatile("bar.arrive %0, %1;" :: "r"(id), "r"(n) : "memory"); }
__device__ __forceinline__ void sts1(uint32_t a, uint32_t v) { asm volatile("st.shared.u32 [%0], %1;" :: "r"(a), "r"(v) : "memory"); }
__device__ __forceinline__ uint32_t lds1(uint32_t a) { uint32_t v; asm volatile("ld.shared.u32 %0, [%1];" : "=r"(v) : "r"(a) : "memory"); return v; }
__device__ __forceinline__ void fence_async() { asm volatile("fence.proxy.async.shared::cta;" ::: "memory"); }
__device__ __forceinline__ void cluster_sync() {
    asm volatile("barrier.cluster.arrive.release.aligned;\n\tbarrier.cluster.wait.acquire.aligned;" ::: "memory");
}
__device__ __forceinline__ uint32_t mapa(uint32_t a, uint32_t rank) {
    uint32_t r; asm("mapa.shared::cluster.u32 %0, %1, %2;" : "=r"(r) : "r"(a), "r"(rank)); return r;
}
__device__ __forceinline__ void st_async1(uint32_t a, uint32_t v, uint32_t bar) {
    asm volatile("st.async.weak.shared::cluster.mbarrier::complete_tx::bytes.b32 [%0], %1, [%2];" :: "r"(a), "r"(v), "r"(bar) : "memory");
}
__device__ __forceinline__ void st_async2(uint32_t a, float x, float y, uint32_t bar) {
    asm volatile("st.async.weak.shared::cluster.mbarrier::complete_tx::bytes.v2.f32 [%0], {%1,%2}, [%3];" :: "r"(a), "f"(x), "f"(y), "r"(bar) : "memory");
}
__device__ __forceinline__ void st_async4(uint32_t a, const float* c, uint32_t bar) {
    asm volatile("st.async.weak.shared::cluster.mbarrier::complete_tx::bytes.v4.f32 [%0], {%1,%2,%3,%4}, [%5];"
                 :: "r"(a), "f"(c[0]), "f"(c[1]), "f"(c[2]), "f"(c[3]), "r"(bar) : "memory");
}
__device__ __forceinline__ void bulk_g2s(uint32_t dst, const void* src, uint32_t bytes, uint32_t bar) {
    asm volatile("cp.async.bulk.shared::cluster.global.mbarrier::complete_tx::bytes [%0], [%1], %2, [%3];"
                 :: "r"(dst), "l"(src), "r"(bytes), "r"(bar) : "memory");
}
__device__ __forceinline__ void cpa16(uint32_t s, const void* g) {
    asm volatile("cp.async.cg.shared.global [%0], [%1], 16;" :: "r"(s), "l"(g) : "memory");
}
__device__ __forceinline__ void cpa_wait_all() { asm volatile("cp.async.wait_all;" ::: "memory"); }
__device__ __forceinline__ void ldsm4(uint32_t* r, uint32_t a) {
    asm volatile("ldmatrix.sync.aligned.m8n8.x4.shared.b16 {%0,%1,%2,%3}, [%4];" : "=r"(r[0]), "=r"(r[1]), "=r"(r[2]), "=r"(r[3]) : "r"(a) : "memory");
}
__device__ __forceinline__ void ldsm4t(uint32_t* r, uint32_t a) {
    asm volatile("ldmatrix.sync.aligned.m8n8.x4.trans.shared.b16 {%0,%1,%2,%3}, [%4];" : "=r"(r[0]), "=r"(r[1]), "=r"(r[2]), "=r"(r[3]) : "r"(a) : "memory");
}
__device__ __forceinline__ void stsm2t(uint32_t a, uint32_t r0, uint32_t r1) {
    asm volatile("stmatrix.sync.aligned.m8n8.x2.trans.shared.b16 [%0], {%1,%2};" :: "r"(a), "r"(r0), "r"(r1) : "memory");
}
__device__ __forceinline__ void stsm4t(uint32_t a, uint32_t r0, uint32_t r1, uint32_t r2, uint32_t r3) {
    asm volatile("stmatrix.sync.aligned.m8n8.x4.trans.shared.b16 [%0], {%1,%2,%3,%4};" :: "r"(a), "r"(r0), "r"(r1), "r"(r2), "r"(r3) : "memory");
}
__device__ __forceinline__ uint32_t movm(uint32_t v) {
    uint32_t r; asm volatile("movmatrix.sync.aligned.m8n8.trans.b16 %0, %1;" : "=r"(r) : "r"(v)); return r;
}
__device__ __forceinline__ void mma16(float* c, uint32_t a0, uint32_t a1, uint32_t a2, uint32_t a3, uint32_t b0, uint32_t b1) {
    asm volatile("mma.sync.aligned.m16n8k16.row.col.f32.bf16.bf16.f32 {%0,%1,%2,%3}, {%4,%5,%6,%7}, {%8,%9}, {%0,%1,%2,%3};"
                 : "+f"(c[0]), "+f"(c[1]), "+f"(c[2]), "+f"(c[3]) : "r"(a0), "r"(a1), "r"(a2), "r"(a3), "r"(b0), "r"(b1));
}
__device__ __forceinline__ void mma8(float* c, uint32_t a0, uint32_t a1, uint32_t b0) {
    asm volatile("mma.sync.aligned.m16n8k8.row.col.f32.bf16.bf16.f32 {%0,%1,%2,%3}, {%4,%5}, {%6}, {%0,%1,%2,%3};"
                 : "+f"(c[0]), "+f"(c[1]), "+f"(c[2]), "+f"(c[3]) : "r"(a0), "r"(a1), "r"(b0));
}
__host__ __device__ constexpr uint64_t make_desc(uint32_t saddr, uint32_t lbo, uint32_t sbo, uint32_t layout) {
    return (uint64_t)((saddr & 0x3FFFF) >> 4) | ((uint64_t)(lbo >> 4) << 16) | ((uint64_t)(sbo >> 4) << 32) | ((uint64_t)layout << 62);
}
__device__ __forceinline__ void wg_fence() { asm volatile("wgmma.fence.sync.aligned;" ::: "memory"); }
__device__ __forceinline__ void wg_commit() { asm volatile("wgmma.commit_group.sync.aligned;" ::: "memory"); }
template <int N> __device__ __forceinline__ void wg_wait() { asm volatile("wgmma.wait_group.sync.aligned %0;" :: "n"(N) : "memory"); }

#define D16(C) C(d[0]), C(d[1]), C(d[2]), C(d[3]), C(d[4]), C(d[5]), C(d[6]), C(d[7]), \
               C(d[8]), C(d[9]), C(d[10]), C(d[11]), C(d[12]), C(d[13]), C(d[14]), C(d[15])
#define DREG16 "{%0,%1,%2,%3,%4,%5,%6,%7,%8,%9,%10,%11,%12,%13,%14,%15}"
__device__ __forceinline__ void wg_rs32(float* d, const uint32_t* a, uint64_t db, bool acc) {
    if (acc)
        asm volatile("wgmma.mma_async.sync.aligned.m64n32k16.f32.bf16.bf16 " DREG16 ", {%16,%17,%18,%19}, %20, 1, 1, 1, 0;"
            : D16("+f") : "r"(a[0]), "r"(a[1]), "r"(a[2]), "r"(a[3]), "l"(db));
    else
        asm volatile("wgmma.mma_async.sync.aligned.m64n32k16.f32.bf16.bf16 " DREG16 ", {%16,%17,%18,%19}, %20, 0, 1, 1, 0;"
            : D16("=f") : "r"(a[0]), "r"(a[1]), "r"(a[2]), "r"(a[3]), "l"(db));
}
__device__ __forceinline__ void wg_ss32(float* d, uint64_t da, uint64_t db, bool acc) {
    if (acc)
        asm volatile("wgmma.mma_async.sync.aligned.m64n32k16.f32.bf16.bf16 " DREG16 ", %16, %17, 1, 1, 1, 1, 0;"
            : D16("+f") : "l"(da), "l"(db));
    else
        asm volatile("wgmma.mma_async.sync.aligned.m64n32k16.f32.bf16.bf16 " DREG16 ", %16, %17, 0, 1, 1, 1, 0;"
            : D16("=f") : "l"(da), "l"(db));
}
__device__ __forceinline__ void wg_ss8(float* d, uint64_t da, uint64_t db, bool acc) {
    if (acc)
        asm volatile("wgmma.mma_async.sync.aligned.m64n8k16.f32.bf16.bf16 {%0,%1,%2,%3}, %4, %5, 1, 1, 1, 1, 1;"
            : "+f"(d[0]), "+f"(d[1]), "+f"(d[2]), "+f"(d[3]) : "l"(da), "l"(db));
    else
        asm volatile("wgmma.mma_async.sync.aligned.m64n8k16.f32.bf16.bf16 {%0,%1,%2,%3}, %4, %5, 0, 1, 1, 1, 1;"
            : "=f"(d[0]), "=f"(d[1]), "=f"(d[2]), "=f"(d[3]) : "l"(da), "l"(db));
}
template <int OFF> __device__ __forceinline__ void ldsm4t_i(uint32_t* r, uint32_t a) {
    asm volatile("ldmatrix.sync.aligned.m8n8.x4.trans.shared.b16 {%0,%1,%2,%3}, [%4+%5];"
                 : "=r"(r[0]), "=r"(r[1]), "=r"(r[2]), "=r"(r[3]) : "r"(a), "n"(OFF) : "memory");
}

__device__ __forceinline__ uint4 ld_relaxed4(const void* p) {
    uint4 v;
    asm volatile("ld.relaxed.gpu.global.v4.u32 {%0,%1,%2,%3}, [%4];" : "=r"(v.x), "=r"(v.y), "=r"(v.z), "=r"(v.w) : "l"(p) : "memory");
    return v;
}
__device__ __forceinline__ void st_relaxed2(void* p, uint32_t a, uint32_t b) {
    asm volatile("st.relaxed.gpu.global.v2.u32 [%0], {%1,%2};" :: "l"(p), "r"(a), "r"(b) : "memory");
}
__device__ __forceinline__ void st_relaxed2_off(void* base, uint32_t off, uint32_t a, uint32_t b) {
    asm volatile("{\n\t.reg .u64 ad;\n\tcvt.u64.u32 ad, %1;\n\tadd.u64 ad, ad, %0;\n\tst.relaxed.gpu.global.v2.u32 [ad], {%2,%3};\n\t}"
                 :: "l"(base), "r"(off), "r"(a), "r"(b) : "memory");
}
__device__ __forceinline__ void st_relaxed1(void* p, uint32_t a) {
    asm volatile("st.relaxed.gpu.global.u32 [%0], %1;" :: "l"(p), "r"(a) : "memory");
}
__device__ __forceinline__ uint32_t ld_acquire1(const uint32_t* p) {
    uint32_t v; asm volatile("ld.acquire.gpu.global.u32 %0, [%1];" : "=r"(v) : "l"(p) : "memory"); return v;
}
__device__ __forceinline__ void st_release1(uint32_t* p, uint32_t a) {
    asm volatile("st.release.gpu.global.u32 [%0], %1;" :: "l"(p), "r"(a) : "memory");
}
__device__ __forceinline__ uint4 lds4(uint32_t s) {
    uint4 v; asm volatile("ld.shared.v4.u32 {%0,%1,%2,%3}, [%4];" : "=r"(v.x), "=r"(v.y), "=r"(v.z), "=r"(v.w) : "r"(s) : "memory"); return v;
}
__device__ __forceinline__ float4 lds4f(uint32_t s) {
    float4 v; asm volatile("ld.shared.v4.f32 {%0,%1,%2,%3}, [%4];" : "=f"(v.x), "=f"(v.y), "=f"(v.z), "=f"(v.w) : "r"(s) : "memory"); return v;
}
__device__ __forceinline__ float2 lds2f(uint32_t s) {
    float2 v; asm volatile("ld.shared.v2.f32 {%0,%1}, [%2];" : "=f"(v.x), "=f"(v.y) : "r"(s) : "memory"); return v;
}
__device__ __forceinline__ uint32_t clk32() { uint32_t c; asm volatile("mov.u32 %0, %%clock;" : "=r"(c) :: "memory"); return c; }
__device__ __forceinline__ uint32_t tagw(float v, uint32_t tag) { return ((__float_as_uint(v) + 8u) & ~15u) | tag; }
__device__ __forceinline__ bool ok4(const uint4& v, uint32_t tag) { return (((v.x ^ tag) | (v.y ^ tag) | (v.z ^ tag) | (v.w ^ tag)) & 15u) == 0; }
__device__ __forceinline__ bool oks(const uint4& v) { return v.x != 0xFFFFFFFFu && v.y != 0xFFFFFFFFu && v.z != 0xFFFFFFFFu && v.w != 0xFFFFFFFFu; }
__device__ __forceinline__ float uf(uint32_t x) { return __uint_as_float(x & ~15u); }

__global__ void __launch_bounds__(256) k_mod(const bf16* __restrict__ c, const bf16* __restrict__ wmod) {
    __shared__ float sc[DM];
    __shared__ float red[8][64];
    const int tid = threadIdx.x;
    for (int i = tid; i < DM; i += 256) {
        float v = __bfloat162float(c[i]);
        sc[i] = bfr(v / (1.0f + __expf(-v)));
    }
    __syncthreads();
    const int cp = tid & 31, kg = tid >> 5;
    const int col = blockIdx.x * 64 + cp * 2;
    float a0 = 0.f, a1 = 0.f;
    #pragma unroll 8
    for (int k = kg * 80; k < kg * 80 + 80; k++) {
        uint32_t w = *(const uint32_t*)(wmod + (size_t)k * (6 * DM) + col);
        a0 += sc[k] * bflo(w); a1 += sc[k] * bfhi(w);
    }
    red[kg][cp * 2] = a0; red[kg][cp * 2 + 1] = a1;
    __syncthreads();
    if (tid < 64) {
        float s = 0.f;
        #pragma unroll
        for (int i = 0; i < 8; i++) s += red[i][tid];
        g_mod[blockIdx.x * 64 + tid] = bfr(s);
    }
    if (blockIdx.x == 0 && tid == 0) g_epoch = g_epoch + 1;
}

template <int MODE>
__global__ void __launch_bounds__(256) k_ln(const bf16* __restrict__ xin) {
    const int lane = threadIdx.x & 31, row = blockIdx.x * 8 + (threadIdx.x >> 5);
    const bf16* src = (MODE == 0 ? xin : g_x1) + (size_t)row * DM;
    const float* shift = g_mod + (MODE == 0 ? 0 : 3 * DM);
    const float* scale = g_mod + (MODE == 0 ? DM : 4 * DM);
    float v[3][8];
    float s = 0.f;
    #pragma unroll
    for (int i = 0; i < 3; i++) {
        int c = lane + 32 * i;
        if (c < 80) {
            uint4 u = *(const uint4*)(src + c * 8);
            v[i][0] = bflo(u.x); v[i][1] = bfhi(u.x); v[i][2] = bflo(u.y); v[i][3] = bfhi(u.y);
            v[i][4] = bflo(u.z); v[i][5] = bfhi(u.z); v[i][6] = bflo(u.w); v[i][7] = bfhi(u.w);
        } else {
            #pragma unroll
            for (int j = 0; j < 8; j++) v[i][j] = 0.f;
        }
        #pragma unroll
        for (int j = 0; j < 8; j++) s += v[i][j];
    }
    #pragma unroll
    for (int o = 16; o > 0; o >>= 1) s += __shfl_xor_sync(0xffffffffu, s, o);
    const float mean = s * (1.0f / DM);
    float q = 0.f;
    #pragma unroll
    for (int i = 0; i < 3; i++) {
        if (lane + 32 * i < 80) {
            #pragma unroll
            for (int j = 0; j < 8; j++) { float d = v[i][j] - mean; q += d * d; }
        }
    }
    #pragma unroll
    for (int o = 16; o > 0; o >>= 1) q += __shfl_xor_sync(0xffffffffu, q, o);
    const float mb = bfr(mean);
    const float var = bfr(q * (1.0f / DM));
    const float sd = bfr(sqrtf(bfr(var + 1e-5f)));
    #pragma unroll
    for (int i = 0; i < 3; i++) {
        int c = lane + 32 * i;
        if (c < 80) {
            float o[8];
            #pragma unroll
            for (int j = 0; j < 8; j++) {
                float n = bfr(bfr(v[i][j] - mb) / sd);
                float m1 = bfr(1.0f + scale[c * 8 + j]);
                o[j] = bfr(n * m1) + shift[c * 8 + j];
            }
            uint4 u = make_uint4(pack2(o[0], o[1]), pack2(o[2], o[3]), pack2(o[4], o[5]), pack2(o[6], o[7]));
            if (MODE == 0) {
                int seg = row >> 5, r = row & 31, blk = c >> 3, cc = c & 7;
                *(uint4*)(g_ht + (size_t)seg * 20480 + blk * 2048 + r * 64 + ((cc ^ (r & 7)) << 3)) = u;
            } else {
                *(uint4*)(g_h2 + (size_t)row * DM + c * 8) = u;
            }
        }
    }
}

constexpr int SM_WV = 0;
constexpr int SM_HB = 81920;
constexpr int SM_WO = SM_HB + 40960;
constexpr int SM_QX = SM_WO + 77824;
constexpr int SM_KS = SM_QX + 4096;
constexpr int SM_QM = SM_KS + 5120;
constexpr int SM_XS = SM_QM + 1024;
constexpr int SM_MS = SM_XS + 12288;
constexpr int SM_OS = SM_MS + 3840;
constexpr int SM_PM = SM_OS + 3072;
constexpr int SM_BAR = SM_PM + 640;
constexpr int SM_CH = SM_BAR + 128;
constexpr int SM_TOTAL = SM_CH + 128;
static_assert(SM_TOTAL <= 232448, "smem");

enum { B_MEM_FULL = 0, B_MEM_FREE, B_HLO_FULL, B_HHI_FULL, B_HLO_FREE, B_HHI_FREE, B_MS, B_O, B_XS };

__device__ __forceinline__ int probe_blk(uint32_t* blk) {
    uint32_t t0 = 0xffffffffu, t1 = 0xffffffffu, acc = 0;
    for (int rep = 0; rep < 5; rep++) {
        #pragma unroll
        for (int pg = 0; pg < 2; pg++) {
            uint32_t c0 = clk32();
            uint32_t v = atomicOr(blk + pg * 1024 + acc, 0u);
            acc = (v == 0x12345678u) ? 1u : 0u;
            asm volatile("" :: "r"(acc) : "memory");
            uint32_t c1 = clk32() + acc;
            uint32_t d = c1 - c0;
            if (rep > 0) { if (pg == 0) t0 = min(t0, d); else t1 = min(t1, d); }
        }
    }
    return t1 < t0 ? 1 : 0;
}

__device__ __forceinline__ uint32_t wo_tile_off(int w) {
    if (w < 8) return w * 6144;
    if (w < 12) return 8 * 6144 + (w - 8) * 4096 - 2048;
    return 8 * 6144 + 4 * 4096 + (w - 12) * 6144;
}

template <int NRES, int NPRE>
__device__ __forceinline__ void wo_phase(uint32_t sb, int w, int lane, const uint32_t (*res)[4], uint32_t parity,
                                         uint32_t tag, uint32_t off0, uint32_t off1) {
    const int er = (lane & 7) + 8 * (lane >> 4);
    const uint32_t aaddr = sb + SM_WO + wo_tile_off(w) + er * 32 + ((((lane >> 3) & 1) ^ ((er >> 2) & 1)) << 4);
    uint32_t pre[NPRE][4];
    #pragma unroll
    for (int i = 0; i < NPRE; i++) ldsm4t(pre[i], aaddr + (NRES + i) * 512);
    mbar_wait(sb + SM_BAR + B_O * 8, parity);
    float c0[4] = {0.f, 0.f, 0.f, 0.f}, c1[4] = {0.f, 0.f, 0.f, 0.f};
    const uint32_t baddr = sb + SM_OS + lane * 16;
    #pragma unroll
    for (int kp = 0; kp < 6; kp++) {
        uint32_t b[4];
        ldsm4t(b, baddr + kp * 512);
        #pragma unroll
        for (int hh = 0; hh < 2; hh++) {
            const int kt = kp * 2 + hh;
            float* c = hh ? c1 : c0;
            if (kt < NRES) mma16(c, res[kt][0], res[kt][1], res[kt][2], res[kt][3], b[hh * 2], b[hh * 2 + 1]);
            else if (kt < NRES + NPRE) mma16(c, pre[kt - NRES][0], pre[kt - NRES][1], pre[kt - NRES][2], pre[kt - NRES][3], b[hh * 2], b[hh * 2 + 1]);
            else {
                uint32_t a[4];
                ldsm4t(a, aaddr + kt * 512);
                mma16(c, a[0], a[1], a[2], a[3], b[hh * 2], b[hh * 2 + 1]);
            }
        }
    }
    st_relaxed2_off(g_buf1, off0, tagw(c0[0] + c1[0], tag), tagw(c0[1] + c1[1], tag));
    st_relaxed2_off(g_buf1, off1, tagw(c0[2] + c1[2], tag), tagw(c0[3] + c1[3], tag));
}

__device__ __forceinline__ uint32_t hop1_off(uint32_t sb, int col, int h, int t) {
    const int r = col >> 3, j = (col >> 2) & 1;
    uint32_t ch;
    asm volatile("ld.shared.u8 %0, [%1];" : "=r"(ch) : "r"(sb + SM_CH + r) : "memory");
    return (uint32_t)((r * 2 + j) * 8192 + ((ch >> j) & 1) * 4096 + (col & 3) * 1024 + h * 32 + t * 8);
}

template <int NT, bool MASK>
__device__ __forceinline__ void softmax_row(uint32_t a, uint32_t tile_stride, uint32_t src_stride, int g, int t, uint32_t* pb) {
    const float L2E = 1.4426950408889634f;
    float sc[NT][2];
    #pragma unroll
    for (int j = 0; j < NT; j++) {
        float2 v0 = lds2f(a + j * tile_stride), v1 = lds2f(a + j * tile_stride + src_stride), v2 = lds2f(a + j * tile_stride + 2 * src_stride);
        sc[j][0] = v0.x + v1.x + v2.x; sc[j][1] = v0.y + v1.y + v2.y;
    }
    #pragma unroll
    for (int j = 0; j < NT; j++) score2(sc[j][0], sc[j][1]);
    if (MASK) {
        const float NEG = -999292928.0f;
        if (2 * t > g) sc[NT - 1][0] = NEG;
        if (2 * t + 1 > g) sc[NT - 1][1] = NEG;
    }
    float m[NT];
    #pragma unroll
    for (int j = 0; j < NT; j++) m[j] = fmaxf(sc[j][0], sc[j][1]);
    float mx = m[0];
    #pragma unroll
    for (int j = 1; j < NT; j++) mx = fmaxf(mx, m[j]);
    mx = fmaxf(mx, __shfl_xor_sync(0xffffffffu, mx, 1));
    mx = fmaxf(mx, __shfl_xor_sync(0xffffffffu, mx, 2));
    float s0 = 0.f, s1 = 0.f;
    #pragma unroll
    for (int j = 0; j < NT; j++) {
        sc[j][0] = ex2((sc[j][0] - mx) * L2E); sc[j][1] = ex2((sc[j][1] - mx) * L2E);
        s0 += sc[j][0]; s1 += sc[j][1];
    }
    s0 += s1;
    s0 += __shfl_xor_sync(0xffffffffu, s0, 1);
    s0 += __shfl_xor_sync(0xffffffffu, s0, 2);
    const float iv = rcpf(s0);
    #pragma unroll
    for (int j = 0; j < NT; j++) pb[j] = pack2(sc[j][0] * iv, sc[j][1] * iv);
}

__global__ void __launch_bounds__(512, 1)
k_rec(const bf16* __restrict__ mem0, const bf16* __restrict__ Wq, const bf16* __restrict__ Wk,
      const bf16* __restrict__ Wv, const bf16* __restrict__ Wo) {
    extern __shared__ __align__(1024) uint8_t smem_raw[];
    constexpr uint32_t SBC = 1024;
    const uint32_t sb = smem_u32(smem_raw);
    if ((sb & 0xFFFFFFu) != SBC) __trap();
    const int tid = threadIdx.x, lane = tid & 31, warp = tid >> 5, wg = tid >> 7;
    const int b = blockIdx.x, h = b / 3, p = b % 3;
    const int g = lane >> 2, t = lane & 3;
    const int tile0 = p == 0 ? 0 : (p == 1 ? 14 : 27);
    const int ntile = p == 0 ? 14 : 13;
    const uint32_t bar = sb + SM_BAR;

    if (tid == 0) {
        mbar_init(bar + B_MEM_FULL * 8, 4);
        mbar_init(bar + B_MEM_FREE * 8, 12);
        mbar_init(bar + B_HLO_FULL * 8, 1);
        mbar_init(bar + B_HHI_FULL * 8, 1);
        mbar_init(bar + B_HLO_FREE * 8, 12);
        mbar_init(bar + B_HHI_FREE * 8, 12);
        mbar_init(bar + B_MS * 8, 1);
        mbar_init(bar + B_O * 8, 1);
        mbar_init(bar + B_XS * 8, 1);
        asm volatile("fence.mbarrier_init.release.cluster;" ::: "memory");
        mbar_expect(bar + B_MS * 8, 3840);
        mbar_expect(bar + B_O * 8, 3072);
        mbar_expect(bar + B_XS * 8, 12288);
        mbar_expect(bar + B_HLO_FULL * 8, 12288);
        bulk_g2s(sb + SM_HB, g_ht, 12288, sb + SM_BAR + B_HLO_FULL * 8);
        mbar_expect(bar + B_HHI_FULL * 8, 28672);
        bulk_g2s(sb + SM_HB + 12288, (const char*)g_ht + 12288, 28672, sb + SM_BAR + B_HHI_FULL * 8);
    }
    cluster_sync();

    if (wg < 2) {
        asm volatile("setmaxnreg.inc.sync.aligned.u32 200;");
        const int w = warp & 3;
        uint32_t wa[40][4];
        {
            const bf16* W = (wg == 0 ? Wq : Wk) + (size_t)h * DH + p * 64 + w * 16 + t * 4;
            #pragma unroll
            for (int kt = 0; kt < 40; kt++) {
                uint2 l1 = __ldg((const uint2*)(W + (size_t)(kt * 16 + g) * HD));
                uint2 l2 = __ldg((const uint2*)(W + (size_t)(kt * 16 + 8 + g) * HD));
                wa[kt][0] = l1.x; wa[kt][1] = l1.y; wa[kt][2] = l2.x; wa[kt][3] = l2.y;
            }
            #pragma unroll
            for (int kt = 0; kt < 40; kt++) {
                #pragma unroll
                for (int i = 0; i < 4; i++) wa[kt][i] = movm(wa[kt][i]);
            }
        }
        bar_sync(0, 512);
        const uint32_t off0 = hop1_off(sb, (tile0 + warp) * 16 + g, h, t);
        const uint32_t off1 = hop1_off(sb, (tile0 + warp) * 16 + 8 + g, h, t);
        const uint32_t dstx = sb + (wg == 0 ? SM_QX : SM_KS + 1024);

        for (int s = -1; s < NSEG; s++) {
            const uint32_t par = s & 1;
            if (s >= 0) {
                mbar_wait(bar + B_MEM_FULL * 8, par);
                TR(0);
                float c[4][4];
                #pragma unroll
                for (int i = 0; i < 4; i++) { c[i][0] = 0.f; c[i][1] = 0.f; c[i][2] = 0.f; c[i][3] = 0.f; }
                uint32_t maddr = sb + lane * 16;
                asm volatile("" : "+r"(maddr));
                #pragma unroll
                for (int kp = 0; kp < 20; kp++) {
                    uint32_t bb[4];
                    ldsm4t(bb, maddr + (SM_HB + kp * 512));
                    mma16(c[(kp & 1) * 2], wa[2 * kp][0], wa[2 * kp][1], wa[2 * kp][2], wa[2 * kp][3], bb[0], bb[1]);
                    mma16(c[(kp & 1) * 2 + 1], wa[2 * kp + 1][0], wa[2 * kp + 1][1], wa[2 * kp + 1][2], wa[2 * kp + 1][3], bb[2], bb[3]);
                }
                {
                    const int tok = lane & 7, ch = 2 * w + ((lane >> 3) & 1);
                    stsm2t(sb + (wg == 0 ? SM_QM : SM_KS) + tok * 128 + ((ch ^ tok) << 4),
                           pack2((c[0][0] + c[1][0]) + (c[2][0] + c[3][0]), (c[0][1] + c[1][1]) + (c[2][1] + c[3][1])),
                           pack2((c[0][2] + c[1][2]) + (c[2][2] + c[3][2]), (c[0][3] + c[1][3]) + (c[2][3] + c[3][3])));
                }
                __syncwarp();
                if (lane == 0) mbar_arrive(bar + B_MEM_FREE * 8);
                TR(1);
                bar_sync(1, 256);
                if (warp < 5) {
                    const int r = lane & 7, cq = lane >> 3;
                    uint32_t a[8], kb[8];
                    ldsm4(a, sb + SM_QM + r * 128 + ((cq ^ r) << 4));
                    ldsm4(kb, sb + SM_KS + (warp * 8 + r) * 128 + ((cq ^ r) << 4));
                    ldsm4(a + 4, sb + SM_QM + r * 128 + (((cq + 4) ^ r) << 4));
                    ldsm4(kb + 4, sb + SM_KS + (warp * 8 + r) * 128 + (((cq + 4) ^ r) << 4));
                    float d0[4] = {0.f, 0.f, 0.f, 0.f}, d1[4] = {0.f, 0.f, 0.f, 0.f};
                    mma16(d0, a[0], 0u, a[1], 0u, kb[0], kb[1]);
                    mma16(d1, a[2], 0u, a[3], 0u, kb[2], kb[3]);
                    mma16(d0, a[4], 0u, a[5], 0u, kb[4], kb[5]);
                    mma16(d1, a[6], 0u, a[7], 0u, kb[6], kb[7]);
                    const uint32_t la = sb + SM_MS + p * 1280 + warp * 256 + lane * 8;
                    #pragma unroll
                    for (int rk = 0; rk < 3; rk++)
                        st_async2(mapa(la, rk), d0[0] + d1[0], d0[1] + d1[1], mapa(bar + B_MS * 8, rk));
                    bar_arrive(4, 288);
                }
                TR(2);
                if (s < NSEG - 1) wo_phase<0, 4>(sb, warp, lane, nullptr, par, (uint32_t)(s % 15) + 1u, off0, off1);
                else mbar_wait(bar + B_O * 8, par);
                TR(4);
                {
                    const int mi = warp < 3 ? 0 : 1, j = warp < 3 ? warp : warp - 3;
                    const int r = lane & 7, cq = lane >> 3;
                    const int qrow = mi * 16 + r + 8 * (cq & 1);
                    uint32_t kb[8];
                    ldsm4(kb, sb + SM_KS + (j * 8 + r) * 128 + ((cq ^ r) << 4));
                    ldsm4(kb + 4, sb + SM_KS + (j * 8 + r) * 128 + (((cq + 4) ^ r) << 4));
                    float d0[4] = {0.f, 0.f, 0.f, 0.f};
                    #pragma unroll
                    for (int kt = 0; kt < 4; kt++) {
                        uint32_t a[4];
                        ldsm4(a, sb + SM_QX + qrow * 128 + (((2 * kt + (cq >> 1)) ^ r) << 4));
                        mma16(d0, a[0], a[1], a[2], a[3], kb[2 * kt], kb[2 * kt + 1]);
                    }
                    const uint32_t la = sb + SM_XS + p * 4096 + warp * 512 + lane * 16;
                    #pragma unroll
                    for (int rk = 0; rk < 3; rk++) st_async4(mapa(la, rk), d0, mapa(bar + B_XS * 8, rk));
                }
                TR(5);
                if (s < NSEG - 1) bar_sync(6, 448);
            }
            if (s < NSEG - 1) {
                const uint32_t hp = (s + 1) & 1;
                float d[16];
                const uint64_t db0 = make_desc(SBC + SM_HB, 16, 1024, 1);
                mbar_wait(bar + B_HHI_FULL * 8, hp);
                mbar_wait(bar + B_HLO_FULL * 8, hp);
                TR(6);
                wg_fence();
                #pragma unroll
                for (int kt = 0; kt < 12; kt++) wg_rs32(d, wa[kt], db0 + (uint64_t)(((kt >> 2) * 4096 + (kt & 3) * 32) >> 4), kt > 0);
                wg_commit();
                #pragma unroll
                for (int kt = 12; kt < 39; kt++) wg_rs32(d, wa[kt], db0 + (uint64_t)(((kt >> 2) * 4096 + (kt & 3) * 32) >> 4), 1);
                wg_commit();
                wg_wait<1>();
                if (lane == 0) mbar_arrive(bar + B_HLO_FREE * 8);
                {
                    const int r = lane & 7, mq = lane >> 3;
                    const uint32_t ha = sb + SM_HB + 9 * 4096 + (8 * (mq >> 1) + r) * 128 + (((6 + (mq & 1)) ^ r) << 4);
                    uint32_t b0[4], b1[4];
                    ldsm4(b0, ha);
                    ldsm4(b1, ha + 2048);
                    wg_wait<0>();
                    mma16(d + 0, wa[39][0], wa[39][1], wa[39][2], wa[39][3], b0[0], b0[1]);
                    mma16(d + 4, wa[39][0], wa[39][1], wa[39][2], wa[39][3], b0[2], b0[3]);
                    mma16(d + 8, wa[39][0], wa[39][1], wa[39][2], wa[39][3], b1[0], b1[1]);
                    mma16(d + 12, wa[39][0], wa[39][1], wa[39][2], wa[39][3], b1[2], b1[3]);
                }
                __syncwarp();
                if (lane == 0) mbar_arrive(bar + B_HHI_FREE * 8);
                TR(7);
                const int mi = lane >> 3, r = lane & 7;
                #pragma unroll
                for (int jj = 0; jj < 2; jj++) {
                    const int tok = 8 * (2 * jj + (mi >> 1)) + r, ch = 2 * w + (mi & 1);
                    stsm4t(dstx + tok * 128 + ((ch ^ r) << 4),
                           pack2(d[8 * jj + 0], d[8 * jj + 1]), pack2(d[8 * jj + 2], d[8 * jj + 3]),
                           pack2(d[8 * jj + 4], d[8 * jj + 5]), pack2(d[8 * jj + 6], d[8 * jj + 7]));
                }
            }
        }
    } else if (wg == 2) {
        asm volatile("setmaxnreg.dec.sync.aligned.u32 72;");
        const int w = warp & 3;
        {
            const int c = tid & 7;
            const bf16* src = Wv + (size_t)h * DH + p * 64 + c * 8;
            for (int k = (tid & 127) >> 3; k < DM; k += 16)
                cpa16(sb + SM_WV + k * 128 + ((c ^ (k & 7)) << 4), src + (size_t)k * HD);
        }
        uint32_t res[4][4];
        {
            const bf16* src = Wo + (size_t)h * DH * DM + (tile0 + warp) * 16 + 2 * t;
            #pragma unroll
            for (int kt = 0; kt < 4; kt++) {
                res[kt][0] = __ldg((const uint32_t*)(src + (size_t)(kt * 16 + g) * DM));
                res[kt][1] = __ldg((const uint32_t*)(src + (size_t)(kt * 16 + g) * DM + 8));
                res[kt][2] = __ldg((const uint32_t*)(src + (size_t)(kt * 16 + 8 + g) * DM));
                res[kt][3] = __ldg((const uint32_t*)(src + (size_t)(kt * 16 + 8 + g) * DM + 8));
            }
            #pragma unroll
            for (int kt = 0; kt < 4; kt++) {
                #pragma unroll
                for (int i = 0; i < 4; i++) res[kt][i] = movm(res[kt][i]);
            }
        }
        cpa_wait_all();
        fence_async();
        bar_sync(0, 512);
        const uint32_t off0 = hop1_off(sb, (tile0 + warp) * 16 + g, h, t);
        const uint32_t off1 = hop1_off(sb, (tile0 + warp) * 16 + 8 + g, h, t);
        const uint64_t da0 = make_desc(SBC + SM_WV, 16, 1024, 1);
        uint32_t vx[8];
        uint32_t vm0 = 0, vm1 = 0;
        #pragma unroll
        for (int i = 0; i < 8; i++) vx[i] = 0;

        auto crit = [&](const int s) {
                const uint32_t par = s & 1;
                mbar_wait(bar + B_MEM_FULL * 8, par);
                bar_sync(4, 288);
                TR(0);
                float dv[4];
                {
                    const uint64_t dbm = make_desc(SBC + SM_HB, 128, 128, 0);
                    wg_fence();
                    #pragma unroll
                    for (int kt = 0; kt < 40; kt++) wg_ss8(dv, da0 + (uint64_t)(kt * 128), dbm + (uint64_t)(kt * 16), kt > 0);
                    wg_commit();
                }
                TR(1);
                bar_sync(5, 160);
                TR(2);
                uint32_t pb[5];
                #pragma unroll
                for (int j = 0; j < 5; j++) pb[j] = lds1(sb + SM_PM + j * 128 + lane * 4);
                float o0[4] = {0.f, 0.f, 0.f, 0.f}, o1[4] = {0.f, 0.f, 0.f, 0.f};
                mma16(o0, vx[0], vx[1], vx[2], vx[3], pb[1], pb[2]);
                mma16(o1, vx[4], vx[5], vx[6], vx[7], pb[3], pb[4]);
                wg_wait<0>();
                TR(3);
                vm0 = pack2(dv[0], dv[1]); vm1 = pack2(dv[2], dv[3]);
                mma8(o0, vm0, vm1, pb[0]);
                {
                    const uint32_t q0 = pack2(o0[0] + o1[0], o0[1] + o1[1]), q1 = pack2(o0[2] + o1[2], o0[3] + o1[3]);
                    const uint32_t la = sb + SM_OS + (p * 64 + w * 16 + g) * 16 + t * 4;
                    #pragma unroll
                    for (int rk = 0; rk < 3; rk++) {
                        const uint32_t ra = mapa(la, rk), rb = mapa(bar + B_O * 8, rk);
                        st_async1(ra, q0, rb);
                        st_async1(ra + 128, q1, rb);
                    }
                }
                if (lane == 0) mbar_arrive(bar + B_MEM_FREE * 8);
                if (s < NSEG - 1) wo_phase<4, 4>(sb, warp, lane, res, par, (uint32_t)(s % 15) + 1u, off0, off1);
                else mbar_wait(bar + B_O * 8, par);
                TR(4);
                if (tid == 256) mbar_expect(bar + B_O * 8, 3072);
        };
        auto xatt = [&](const int s) {
                const uint32_t par = s & 1;
                mbar_wait(bar + B_XS * 8, par);
                TR(8);
                if (tid == 256) mbar_expect(bar + B_XS * 8, 12288);
                {
                    const uint32_t a = sb + SM_XS + (w >> 1) * 1536 + lane * 16 + (w & 1) * 8;
                    uint32_t pb[5];
                    if (w == 0) { softmax_row<2, true>(a, 512, 4096, g, t, pb); }
                    else if (w == 1) { softmax_row<3, true>(a, 512, 4096, g, t, pb); }
                    else if (w == 2) { softmax_row<4, true>(a, 512, 4096, g, t, pb); }
                    else { softmax_row<5, true>(a, 512, 4096, g, t, pb); }
                    #pragma unroll
                    for (int j = 0; j < 5; j++) if (j < w + 2) sts1(a + j * 512, pb[j]);
                }
                bar_sync(7, 128);
                bf16* orow = g_ox + (size_t)(s * 32 + g) * HD + h * DH + p * 64 + w * 16 + 2 * t;
                #pragma unroll
                for (int mi = 0; mi < 2; mi++) {
                    uint4 pv[5];
                    #pragma unroll
                    for (int j = 0; j < 5; j++) if (j < (mi ? 5 : 3)) pv[j] = lds4(sb + SM_XS + mi * 1536 + j * 512 + lane * 16);
                    float oa[4] = {0.f, 0.f, 0.f, 0.f}, ob[4] = {0.f, 0.f, 0.f, 0.f};
                    mma8(oa, vm0, vm1, pv[0].x);
                    mma8(ob, vm0, vm1, pv[0].z);
                    mma16(oa, vx[0], vx[1], vx[2], vx[3], pv[1].x, mi ? pv[2].x : 0u);
                    mma16(ob, vx[0], vx[1], vx[2], vx[3], pv[1].z, pv[2].z);
                    if (mi) {
                        mma16(oa, vx[4], vx[5], vx[6], vx[7], pv[3].x, 0u);
                        mma16(ob, vx[4], vx[5], vx[6], vx[7], pv[3].z, pv[4].z);
                    }
                    const uint32_t u0 = movm(pack2(oa[0], oa[1])), u1 = movm(pack2(oa[2], oa[3]));
                    const uint32_t u2 = movm(pack2(ob[0], ob[1])), u3 = movm(pack2(ob[2], ob[3]));
                    bf16* dst = orow + (size_t)(16 * mi) * HD;
                    *(uint32_t*)dst = u0;
                    *(uint32_t*)(dst + 8) = u1;
                    *(uint32_t*)(dst + 8 * HD) = u2;
                    *(uint32_t*)(dst + 8 * HD + 8) = u3;
                }
                TR(9);
        };
        for (int s = -1; s < NSEG - 1; s++) {
            if (s >= 0) { crit(s); bar_sync(6, 448); }
            float d[16];
            const uint32_t hp = (s + 1) & 1;
            const uint64_t db0 = make_desc(SBC + SM_HB, 16, 1024, 1);
            mbar_wait(bar + B_HHI_FULL * 8, hp);
            mbar_wait(bar + B_HLO_FULL * 8, hp);
            TR(6);
            wg_fence();
            #pragma unroll
            for (int kt = 0; kt < 12; kt++) wg_ss32(d, da0 + (uint64_t)(kt * 128), db0 + (uint64_t)(((kt >> 2) * 4096 + (kt & 3) * 32) >> 4), kt > 0);
            wg_commit();
            #pragma unroll
            for (int kt = 12; kt < 40; kt++) wg_ss32(d, da0 + (uint64_t)(kt * 128), db0 + (uint64_t)(((kt >> 2) * 4096 + (kt & 3) * 32) >> 4), 1);
            wg_commit();
            TR(5);
            wg_wait<1>();
            if (lane == 0) mbar_arrive(bar + B_HLO_FREE * 8);
            if (s >= 0) xatt(s);
            wg_wait<0>();
            TR(7);
            if (lane == 0) mbar_arrive(bar + B_HHI_FREE * 8);
            #pragma unroll
            for (int i = 0; i < 8; i++) vx[i] = pack2(d[2 * i], d[2 * i + 1]);
        }
        crit(NSEG - 1);
        xatt(NSEG - 1);
    } else {
        asm volatile("setmaxnreg.dec.sync.aligned.u32 40;");
        const int w = warp & 3, lt = tid & 127;
        {
            const bf16* src0 = Wo + (size_t)h * DH * DM + tile0 * 16;
            const int nch = 2 * ntile;
            for (int i = lt; i < DH * nch; i += 128) {
                const int e = i / nch, c = i - e * nch, tl = c >> 1, cc = c & 1;
                if (tl >= 8 && tl < 12 && e < 64) continue;
                cpa16(sb + SM_WO + wo_tile_off(tl) + e * 32 + ((cc ^ ((e >> 2) & 1)) << 4), src0 + (size_t)e * DM + c * 8);
            }
        }
        const uint32_t epoch = *(volatile uint32_t*)&g_epoch;
        if (b < 80) {
            #pragma unroll
            for (int i = 0; i < 2; i++) {
                const int idx = lt + i * 128, sl = idx >> 6, pg = (idx >> 5) & 1, wd = idx & 31;
                st_relaxed1(g_buf2 + (sl * 3 + (b >> 5)) * 2048 + pg * 1024 + (b & 31) * 32 + wd, 0xFFFFFFFFu);
            }
            __threadfence();
        }
        if (lane == 0) {
            for (int i = w; i < 14; i += 4) {
                int c = 0;
                if (i < 12) c = probe_blk(g_buf2 + i * 2048 + 640 + (b & 31) * 8);
                else if (b < 80) c = probe_blk(g_buf1 + (b * 2 + (i - 12)) * 2048);
                asm volatile("st.shared.u8 [%0], %1;" :: "r"(sb + SM_CH + 96 + i), "r"(c) : "memory");
            }
        }
        bar_sync(3, 128);
        uint32_t selmask = 0;
        for (int i = 0; i < 14; i++) {
            uint32_t c; asm volatile("ld.shared.u8 %0, [%1];" : "=r"(c) : "r"(sb + SM_CH + 96 + i) : "memory");
            selmask |= c << i;
        }
        if (lt == 0 && b < 80) st_release1(&g_choice[b], (epoch << 2) | (selmask >> 12));
        if (lt < 80) {
            uint32_t v, guard = 0;
            do { v = ld_acquire1(&g_choice[lt]); if (++guard > (1u << 22)) __trap(); } while ((v >> 2) != (epoch & 0x3fffffffu));
            asm volatile("st.shared.u8 [%0], %1;" :: "r"(sb + SM_CH + lt), "r"(v & 3u) : "memory");
        }
        cpa_wait_all();
        bar_sync(0, 512);
        const bool has_tile = (12 + w) < ntile;
        uint32_t off0 = 0, off1 = 0;
        if (has_tile) {
            off0 = hop1_off(sb, (tile0 + warp) * 16 + g, h, t);
            off1 = hop1_off(sb, (tile0 + warp) * 16 + 8 + g, h, t);
        }
        const char* rin = (const char*)g_buf1 + (size_t)(b * 2 + (w >> 1)) * 8192 + ((selmask >> (12 + (w >> 1))) & 1) * 4096 + (w & 1) * 2048 + lane * 16;

        for (int s = 0; s < NSEG; s++) {
            const uint32_t par = s & 1;
            mbar_wait(bar + B_HLO_FREE * 8, par);
            TR(10);
            if (s == 0) {
                for (int k = lt; k < DM; k += 128) {
                    uint32_t v[4];
                    #pragma unroll
                    for (int i = 0; i < 4; i++) {
                        uint32_t lo = *(const uint16_t*)(mem0 + (2 * i) * DM + k), hi = *(const uint16_t*)(mem0 + (2 * i + 1) * DM + k);
                        v[i] = lo | (hi << 16);
                    }
                    asm volatile("st.shared.v4.u32 [%0], {%1,%2,%3,%4};" :: "r"(sb + SM_HB + k * 16), "r"(v[0]), "r"(v[1]), "r"(v[2]), "r"(v[3]) : "memory");
                }
            } else {
                const int sl = s & 3;
                const char* q = (const char*)g_buf2 + sl * 3 * 8192 + lt * 16;
                const uint32_t sm = selmask >> (sl * 3);
                const uint32_t dst = sb + SM_HB + lt * 16;
                uint32_t guard = 0;
                while (true) {
                    #pragma unroll
                    for (int c = 0; c < 5; c++)
                        cpa16(dst + c * 2048, q + (c >> 1) * 8192 + ((sm >> (c >> 1)) & 1) * 4096 + (c & 1) * 2048);
                    cpa_wait_all();
                    bool ok = true;
                    #pragma unroll
                    for (int c = 0; c < 5; c++) { uint4 v = lds4(dst + c * 2048); ok = ok && oks(v); }
                    if (__all_sync(0xffffffffu, ok)) break;
                    if (++guard > (1u << 22)) __trap();
                }
            }
            fence_async();
            __syncwarp();
            if (lane == 0) mbar_arrive(bar + B_MEM_FULL * 8);
            TR(0);
            if (w == 2) {
                mbar_wait(bar + B_MS * 8, par);
                TR(1);
                if (lane == 0) mbar_expect(bar + B_MS * 8, 3840);
                uint32_t pb[5];
                softmax_row<5, false>(sb + SM_MS + lane * 8, 256, 1280, g, t, pb);
                #pragma unroll
                for (int j = 0; j < 5; j++) sts1(sb + SM_PM + j * 128 + lane * 4, pb[j]);
                bar_arrive(5, 160);
                TR(2);
            }
            if (s < NSEG - 1) {
                if (w == 3) {
                    if (lane == 0) {
                        const char* src = (const char*)g_ht + (size_t)(s + 1) * 40960;
                        mbar_wait(bar + B_HHI_FREE * 8, par);
                        mbar_expect(bar + B_HHI_FULL * 8, 28672);
                        bulk_g2s(sb + SM_HB + 12288, src + 12288, 28672, sb + SM_BAR + B_HHI_FULL * 8);
                        mbar_wait(bar + B_MEM_FREE * 8, par);
                        mbar_expect(bar + B_HLO_FULL * 8, 12288);
                        bulk_g2s(sb + SM_HB, src, 12288, sb + SM_BAR + B_HLO_FULL * 8);
                    }
                    __syncwarp();
                }
                const uint32_t tag = (uint32_t)(s % 15) + 1u;
                if (has_tile) wo_phase<0, 3>(sb, warp, lane, nullptr, par, tag, off0, off1);
                else mbar_wait(bar + B_O * 8, par);
                if (w < 2) bar_arrive(6, 448);
                TR(4);
                if (b < 80) {
                    uint4 v0, v1, v2, v3;
                    uint32_t guard = 0;
                    while (true) {
                        v0 = ld_relaxed4(rin); v1 = ld_relaxed4(rin + 512);
                        v2 = ld_relaxed4(rin + 1024); v3 = ld_relaxed4(rin + 1536);
                        if (__all_sync(0xffffffffu, ok4(v0, tag) && ok4(v1, tag) && ok4(v2, tag) && ok4(v3, tag))) break;
                        if (++guard > (1u << 22)) __trap();
                    }
                    TR(11);
                    float a0 = uf(v0.x) + uf(v1.x), a1 = uf(v0.y) + uf(v1.y), a2 = uf(v0.z) + uf(v1.z), a3 = uf(v0.w) + uf(v1.w);
                    float b0 = uf(v2.x) + uf(v3.x), b1 = uf(v2.y) + uf(v3.y), b2 = uf(v2.z) + uf(v3.z), b3 = uf(v2.w) + uf(v3.w);
                    const bool u16 = lane & 16;
                    float k0 = (u16 ? b0 : a0) + __shfl_xor_sync(0xffffffffu, u16 ? a0 : b0, 16);
                    float k1 = (u16 ? b1 : a1) + __shfl_xor_sync(0xffffffffu, u16 ? a1 : b1, 16);
                    float k2 = (u16 ? b2 : a2) + __shfl_xor_sync(0xffffffffu, u16 ? a2 : b2, 16);
                    float k3 = (u16 ? b3 : a3) + __shfl_xor_sync(0xffffffffu, u16 ? a3 : b3, 16);
                    const bool u8 = lane & 8;
                    float m0 = (u8 ? k2 : k0) + __shfl_xor_sync(0xffffffffu, u8 ? k0 : k2, 8);
                    float m1 = (u8 ? k3 : k1) + __shfl_xor_sync(0xffffffffu, u8 ? k1 : k3, 8);
                    m0 += __shfl_xor_sync(0xffffffffu, m0, 4); m1 += __shfl_xor_sync(0xffffffffu, m1, 4);
                    m0 += __shfl_xor_sync(0xffffffffu, m0, 2); m1 += __shfl_xor_sync(0xffffffffu, m1, 2);
                    const int col = b * 8 + 2 * w + (lane >> 4), wd = 2 * (lane & 1) + ((lane >> 3) & 1);
                    const int sl = (lane & 4) ? ((s + 3) & 3) : ((s + 1) & 3);
                    uint32_t* dst = g_buf2 + (sl * 3 + (col >> 8)) * 2048 + ((lane >> 1) & 1) * 1024 + (col & 255) * 4 + wd;
                    st_relaxed1(dst, (lane & 4) ? 0xFFFFFFFFu : pack2(m0, m1));
                    TR(12);
                }
            }
        }
    }
    cluster_sync();
}

constexpr int G_STAGES = 5;
constexpr int G_STAGE_BYTES = 32768;
constexpr int G_SMEM = G_STAGES * G_STAGE_BYTES + 1024 + 256;

__device__ __forceinline__ void tma2d(uint32_t dst, const CUtensorMap* map, int c0, int c1, uint32_t bar) {
    asm volatile("cp.async.bulk.tensor.2d.shared::cluster.global.mbarrier::complete_tx::bytes [%0], [%1, {%2, %3}], [%4];"
                 :: "r"(dst), "l"(map), "r"(c0), "r"(c1), "r"(bar) : "memory");
}
__device__ __forceinline__ void wg_ss128(float* d, uint64_t da, uint64_t db, int sc) {
    asm volatile("{\n\t.reg .pred p;\n\tsetp.ne.b32 p, %66, 0;\n\t"
        "wgmma.mma_async.sync.aligned.m64n128k16.f32.bf16.bf16 "
        "{%0,%1,%2,%3,%4,%5,%6,%7,%8,%9,%10,%11,%12,%13,%14,%15,%16,%17,%18,%19,%20,%21,%22,%23,%24,%25,%26,%27,%28,%29,%30,%31,"
        "%32,%33,%34,%35,%36,%37,%38,%39,%40,%41,%42,%43,%44,%45,%46,%47,%48,%49,%50,%51,%52,%53,%54,%55,%56,%57,%58,%59,%60,%61,%62,%63}, "
        "%64, %65, p, 1, 1, 0, 1;\n\t}"
        : "+f"(d[0]), "+f"(d[1]), "+f"(d[2]), "+f"(d[3]), "+f"(d[4]), "+f"(d[5]), "+f"(d[6]), "+f"(d[7]),
          "+f"(d[8]), "+f"(d[9]), "+f"(d[10]), "+f"(d[11]), "+f"(d[12]), "+f"(d[13]), "+f"(d[14]), "+f"(d[15]),
          "+f"(d[16]), "+f"(d[17]), "+f"(d[18]), "+f"(d[19]), "+f"(d[20]), "+f"(d[21]), "+f"(d[22]), "+f"(d[23]),
          "+f"(d[24]), "+f"(d[25]), "+f"(d[26]), "+f"(d[27]), "+f"(d[28]), "+f"(d[29]), "+f"(d[30]), "+f"(d[31]),
          "+f"(d[32]), "+f"(d[33]), "+f"(d[34]), "+f"(d[35]), "+f"(d[36]), "+f"(d[37]), "+f"(d[38]), "+f"(d[39]),
          "+f"(d[40]), "+f"(d[41]), "+f"(d[42]), "+f"(d[43]), "+f"(d[44]), "+f"(d[45]), "+f"(d[46]), "+f"(d[47]),
          "+f"(d[48]), "+f"(d[49]), "+f"(d[50]), "+f"(d[51]), "+f"(d[52]), "+f"(d[53]), "+f"(d[54]), "+f"(d[55]),
          "+f"(d[56]), "+f"(d[57]), "+f"(d[58]), "+f"(d[59]), "+f"(d[60]), "+f"(d[61]), "+f"(d[62]), "+f"(d[63])
        : "l"(da), "l"(db), "r"(sc));
}

template <int EPI>
__global__ void __launch_bounds__(384, 1)
k_gemm(const __grid_constant__ CUtensorMap mapA, const __grid_constant__ CUtensorMap mapB, int K,
       const bf16* __restrict__ xin, bf16* __restrict__ outp) {
    extern __shared__ uint8_t smem_raw[];
    const uint32_t sb = (smem_u32(smem_raw) + 1023u) & ~1023u;
    const uint32_t bars = sb + G_STAGES * G_STAGE_BYTES;
    const int tid = threadIdx.x, lane = tid & 31, wg = tid >> 7;
    const int n0 = blockIdx.x * 128, m0 = blockIdx.y * 128;
    const int nk = K / 64;
    if (tid == 0) {
        for (int i = 0; i < G_STAGES; i++) { mbar_init(bars + i * 8, 1); mbar_init(bars + 64 + i * 8, 8); }
        asm volatile("fence.mbarrier_init.release.cluster;" ::: "memory");
    }
    __syncthreads();
    if (wg == 0) {
        if (tid == 0) {
            for (int kb = 0; kb < nk; kb++) {
                const int st = kb % G_STAGES;
                if (kb >= G_STAGES) mbar_wait(bars + 64 + st * 8, ((kb / G_STAGES) - 1) & 1);
                const uint32_t a = sb + st * G_STAGE_BYTES;
                mbar_expect(bars + st * 8, G_STAGE_BYTES);
                tma2d(a, &mapA, kb * 64, m0, bars + st * 8);
                tma2d(a + 16384, &mapB, n0, kb * 64, bars + st * 8);
                tma2d(a + 16384 + 8192, &mapB, n0 + 64, kb * 64, bars + st * 8);
            }
        }
    } else {
        float d[64];
        #pragma unroll
        for (int i = 0; i < 64; i++) d[i] = 0.f;
        const int cw = wg - 1;
        for (int kb = 0; kb < nk; kb++) {
            const int st = kb % G_STAGES;
            mbar_wait(bars + st * 8, (kb / G_STAGES) & 1);
            const uint32_t a = sb + st * G_STAGE_BYTES;
            const uint64_t da = make_desc(a + cw * 8192, 16, 1024, 1);
            const uint64_t db = make_desc(a + 16384, 8192, 1024, 1);
            wg_fence();
            #pragma unroll
            for (int k = 0; k < 4; k++) wg_ss128(d, da + (uint64_t)(k * 2), db + (uint64_t)(k * 128), 1);
            wg_commit();
            if (kb > 0) {
                wg_wait<1>();
                if (lane == 0) mbar_arrive(bars + 64 + ((kb - 1) % G_STAGES) * 8);
            }
        }
        wg_wait<0>();
        const int g = lane >> 2, t = lane & 3, w = (tid >> 5) & 3;
        const int ldo = EPI == 1 ? FF : DM;
        #pragma unroll
        for (int hf = 0; hf < 2; hf++) {
            const int row = m0 + cw * 64 + w * 16 + g + 8 * hf;
            #pragma unroll
            for (int j = 0; j < 16; j++) {
                const int col = n0 + j * 8 + 2 * t;
                float a0 = bfr(d[4 * j + 2 * hf]), a1 = bfr(d[4 * j + 2 * hf + 1]);
                uint32_t o;
                if (EPI == 1) {
                    o = pack2(a0 / (1.0f + __expf(-a0)), a1 / (1.0f + __expf(-a1)));
                } else {
                    const float2 gm = *(const float2*)(g_mod + (EPI == 0 ? 2 : 5) * DM + col);
                    const uint32_t xv = *(const uint32_t*)(xin + (size_t)row * DM + col);
                    o = pack2(bflo(xv) + bfr(gm.x * a0), bfhi(xv) + bfr(gm.y * a1));
                }
                *(uint32_t*)(outp + (size_t)row * ldo + col) = o;
            }
        }
    }
}

typedef CUresult (*EncodeFn)(CUtensorMap*, CUtensorMapDataType, cuuint32_t, void*, const cuuint64_t*, const cuuint64_t*,
                             const cuuint32_t*, const cuuint32_t*, CUtensorMapInterleave, CUtensorMapSwizzle,
                             CUtensorMapL2promotion, CUtensorMapFloatOOBfill);

static void make_map(EncodeFn fn, CUtensorMap* m, const void* ptr, uint64_t inner, uint64_t outer, uint32_t bi, uint32_t bo) {
    cuuint64_t dims[2] = {inner, outer};
    cuuint64_t strides[1] = {inner * 2};
    cuuint32_t box[2] = {bi, bo};
    cuuint32_t es[2] = {1, 1};
    fn(m, CU_TENSOR_MAP_DATA_TYPE_BFLOAT16, 2, (void*)ptr, dims, strides, box, es, CU_TENSOR_MAP_INTERLEAVE_NONE,
       CU_TENSOR_MAP_SWIZZLE_128B, CU_TENSOR_MAP_L2_PROMOTION_L2_256B, CU_TENSOR_MAP_FLOAT_OOB_FILL_NONE);
}

extern "C" void kernel_launch(void* const* d_in, const int* in_sizes, int n_in, void* d_out, int out_size) {
    const bf16* x = (const bf16*)d_in[0];
    const bf16* mem0 = (const bf16*)d_in[1];
    const bf16* Wq = (const bf16*)d_in[2];
    const bf16* Wk = (const bf16*)d_in[3];
    const bf16* Wv = (const bf16*)d_in[4];
    const bf16* Wo = (const bf16*)d_in[5];
    const bf16* w1 = (const bf16*)d_in[8];
    const bf16* w2 = (const bf16*)d_in[9];
    const bf16* c = (const bf16*)d_in[10];
    const bf16* wmod = (const bf16*)d_in[11];
    bf16* out = (bf16*)d_out;

    static EncodeFn enc = nullptr;
    static void *p_ox, *p_x1, *p_h2, *p_act;
    if (!enc) {
        cudaDriverEntryPointQueryResult qr;
        void* f = nullptr;
        cudaGetDriverEntryPoint("cuTensorMapEncodeTiled", &f, cudaEnableDefault, &qr);
        enc = (EncodeFn)f;
        cudaGetSymbolAddress(&p_ox, g_ox);
        cudaGetSymbolAddress(&p_x1, g_x1);
        cudaGetSymbolAddress(&p_h2, g_h2);
        cudaGetSymbolAddress(&p_act, g_act);
        cudaFuncSetAttribute(k_rec, cudaFuncAttributeMaxDynamicSharedMemorySize, SM_TOTAL);
        cudaFuncSetAttribute(k_gemm<0>, cudaFuncAttributeMaxDynamicSharedMemorySize, G_SMEM);
        cudaFuncSetAttribute(k_gemm<1>, cudaFuncAttributeMaxDynamicSharedMemorySize, G_SMEM);
        cudaFuncSetAttribute(k_gemm<2>, cudaFuncAttributeMaxDynamicSharedMemorySize, G_SMEM);
    }
    CUtensorMap mOx, mWo, mH2, mW1, mAct, mW2;
    make_map(enc, &mOx, p_ox, HD, SEQ, 64, 128);
    make_map(enc, &mWo, Wo, DM, HD, 64, 64);
    make_map(enc, &mH2, p_h2, DM, SEQ, 64, 128);
    make_map(enc, &mW1, w1, FF, DM, 64, 64);
    make_map(enc, &mAct, p_act, FF, SEQ, 64, 128);
    make_map(enc, &mW2, w2, DM, FF, 64, 64);

    cudaStream_t st = cudaStreamPerThread;
    k_mod<<<60, 256, 0, st>>>(c, wmod);
    k_ln<0><<<SEQ / 8, 256, 0, st>>>(x);
    {
        cudaLaunchConfig_t cfg = {};
        cfg.gridDim = dim3(96); cfg.blockDim = dim3(512); cfg.dynamicSmemBytes = SM_TOTAL; cfg.stream = st;
        cudaLaunchAttribute at[1];
        at[0].id = cudaLaunchAttributeClusterDimension;
        at[0].val.clusterDim.x = 3; at[0].val.clusterDim.y = 1; at[0].val.clusterDim.z = 1;
        cfg.attrs = at; cfg.numAttrs = 1;
        cudaLaunchKernelEx(&cfg, k_rec, mem0, Wq, Wk, Wv, Wo);
    }
    k_gemm<0><<<dim3(5, 16), 384, G_SMEM, st>>>(mOx, mWo, HD, x, (bf16*)p_x1);
    k_ln<1><<<SEQ / 8, 256, 0, st>>>(nullptr);
    k_gemm<1><<<dim3(12, 16), 384, G_SMEM, st>>>(mH2, mW1, DM, nullptr, (bf16*)p_act);
    k_gemm<2><<<dim3(5, 16), 384, G_SMEM, st>>>(mAct, mW2, FF, (const bf16*)p_x1, out);
}
```

```cpp
#include <cuda_runtime.h>
#include <cuda_bf16.h>
#include <cuda.h>
#include <stdint.h>

typedef __nv_bfloat16 bf16;
#define VM_THROTTLE 1

constexpr int SEQ = 2048, DM = 640, NH = 32, DH = 192, NSEG = 64, FF = 1536, HD = NH * DH;

__device__ float g_mod[6 * DM];
__device__ __align__(1024) bf16 g_ht[(size_t)SEQ * DM];
__device__ __align__(1024) bf16 g_ox[(size_t)SEQ * HD];
__device__ __align__(1024) bf16 g_x1[(size_t)SEQ * DM];
__device__ __align__(1024) bf16 g_h2[(size_t)SEQ * DM];
__device__ __align__(1024) bf16 g_act[(size_t)SEQ * FF];
__device__ __align__(8192) uint32_t g_buf1[80 * 2 * 2048];
__device__ __align__(8192) uint32_t g_buf2[4 * 3 * 2048];
__device__ uint32_t g_choice[128];
__device__ uint32_t g_epoch;
#define TR(k)

__device__ __forceinline__ float bfr(float x) { return __bfloat162float(__float2bfloat16_rn(x)); }
__device__ __forceinline__ uint32_t pack2(float a, float b) {
    uint32_t r; asm("cvt.rn.bf16x2.f32 %0, %1, %2;" : "=r"(r) : "f"(b), "f"(a)); return r;
}
__device__ __forceinline__ float bflo(uint32_t v) { return __uint_as_float(v << 16); }
__device__ __forceinline__ float bfhi(uint32_t v) { return __uint_as_float(v & 0xffff0000u); }
__device__ __forceinline__ float ex2(float x) { float r; asm("ex2.approx.ftz.f32 %0, %1;" : "=f"(r) : "f"(x)); return r; }
__device__ __forceinline__ float rcpf(float x) { float r; asm("rcp.approx.ftz.f32 %0, %1;" : "=f"(r) : "f"(x)); return r; }
__device__ __forceinline__ void score2(float& a, float& b) {
    const float SCALE = 0.07216878364870322f;
    uint32_t u = pack2(a, b);
    u = pack2(bflo(u) * SCALE, bfhi(u) * SCALE);
    a = bflo(u); b = bfhi(u);
}
__device__ __forceinline__ uint32_t smem_u32(const void* p) { return (uint32_t)__cvta_generic_to_shared(p); }

__device__ __forceinline__ void mbar_init(uint32_t bar, uint32_t cnt) {
    asm volatile("mbarrier.init.shared::cta.b64 [%0], %1;" :: "r"(bar), "r"(cnt) : "memory");
}
__device__ __forceinline__ void mbar_arrive(uint32_t bar) {
    asm volatile("mbarrier.arrive.shared::cta.b64 _, [%0];" :: "r"(bar) : "memory");
}
__device__ __forceinline__ void mbar_expect(uint32_t bar, uint32_t bytes) {
    asm volatile("mbarrier.arrive.expect_tx.shared::cta.b64 _, [%0], %1;" :: "r"(bar), "r"(bytes) : "memory");
}
__device__ __forceinline__ bool mbar_try(uint32_t bar, uint32_t parity) {
    uint32_t ok;
    asm volatile("{\n\t.reg .pred p;\n\tmbarrier.try_wait.parity.shared::cta.b64 p, [%1], %2;\n\tselp.u32 %0, 1, 0, p;\n\t}"
                 : "=r"(ok) : "r"(bar), "r"(parity) : "memory");
    return ok != 0;
}
__device__ __forceinline__ bool mbar_try_cluster(uint32_t bar, uint32_t parity) {
    uint32_t ok;
    asm volatile("{\n\t.reg .pred p;\n\tmbarrier.try_wait.parity.acquire.cluster.shared::cta.b64 p, [%1], %2;\n\tselp.u32 %0, 1, 0, p;\n\t}"
                 : "=r"(ok) : "r"(bar), "r"(parity) : "memory");
    return ok != 0;
}
__device__ __forceinline__ void mbar_wait(uint32_t bar, uint32_t parity) {
    uint32_t guard = 0;
    while (!mbar_try(bar, parity)) { if (++guard > (1u << 22)) __trap(); }
}
__device__ __forceinline__ void mbar_wait_cluster(uint32_t bar, uint32_t parity) {
    uint32_t guard = 0;
    while (!mbar_try_cluster(bar, parity)) { if (++guard > (1u << 22)) __trap(); }
}
__device__ __forceinline__ void bar_sync(int id, int n) { asm volatile("bar.sync %0, %1;" :: "r"(id), "r"(n) : "memory"); }
__device__ __forceinline__ void bar_arrive(int id, int n) { asm volatile("bar.arrive %0, %1;" :: "r"(id), "r"(n) : "memory"); }
__device__ __forceinline__ void sts1(uint32_t a, uint32_t v) { asm volatile("st.shared.u32 [%0], %1;" :: "r"(a), "r"(v) : "memory"); }
__device__ __forceinline__ uint32_t lds1(uint32_t a) { uint32_t v; asm volatile("ld.shared.u32 %0, [%1];" : "=r"(v) : "r"(a) : "memory"); return v; }
__device__ __forceinline__ void fence_async() { asm volatile("fence.proxy.async.shared::cta;" ::: "memory"); }
__device__ __forceinline__ void cluster_sync() {
    asm volatile("barrier.cluster.arrive.release.aligned;\n\tbarrier.cluster.wait.acquire.aligned;" ::: "memory");
}
__device__ __forceinline__ uint32_t mapa(uint32_t a, uint32_t rank) {
    uint32_t r; asm("mapa.shared::cluster.u32 %0, %1, %2;" : "=r"(r) : "r"(a), "r"(rank)); return r;
}
__device__ __forceinline__ void st_async1(uint32_t a, uint32_t v, uint32_t bar) {
    asm volatile("st.async.weak.shared::cluster.mbarrier::complete_tx::bytes.b32 [%0], %1, [%2];" :: "r"(a), "r"(v), "r"(bar) : "memory");
}
__device__ __forceinline__ void st_async2(uint32_t a, float x, float y, uint32_t bar) {
    asm volatile("st.async.weak.shared::cluster.mbarrier::complete_tx::bytes.v2.f32 [%0], {%1,%2}, [%3];" :: "r"(a), "f"(x), "f"(y), "r"(bar) : "memory");
}
__device__ __forceinline__ void st_async4(uint32_t a, const float* c, uint32_t bar) {
    asm volatile("st.async.weak.shared::cluster.mbarrier::complete_tx::bytes.v4.f32 [%0], {%1,%2,%3,%4}, [%5];"
                 :: "r"(a), "f"(c[0]), "f"(c[1]), "f"(c[2]), "f"(c[3]), "r"(bar) : "memory");
}
__device__ __forceinline__ void bulk_g2s(uint32_t dst, const void* src, uint32_t bytes, uint32_t bar) {
    asm volatile("cp.async.bulk.shared::cluster.global.mbarrier::complete_tx::bytes [%0], [%1], %2, [%3];"
                 :: "r"(dst), "l"(src), "r"(bytes), "r"(bar) : "memory");
}
__device__ __forceinline__ void cpa16(uint32_t s, const void* g) {
    asm volatile("cp.async.cg.shared.global [%0], [%1], 16;" :: "r"(s), "l"(g) : "memory");
}
__device__ __forceinline__ void cpa_wait_all() { asm volatile("cp.async.wait_all;" ::: "memory"); }
__device__ __forceinline__ void ldsm4(uint32_t* r, uint32_t a) {
    asm volatile("ldmatrix.sync.aligned.m8n8.x4.shared.b16 {%0,%1,%2,%3}, [%4];" : "=r"(r[0]), "=r"(r[1]), "=r"(r[2]), "=r"(r[3]) : "r"(a) : "memory");
}
__device__ __forceinline__ void ldsm4t(uint32_t* r, uint32_t a) {
    asm volatile("ldmatrix.sync.aligned.m8n8.x4.trans.shared.b16 {%0,%1,%2,%3}, [%4];" : "=r"(r[0]), "=r"(r[1]), "=r"(r[2]), "=r"(r[3]) : "r"(a) : "memory");
}
__device__ __forceinline__ void stsm2t(uint32_t a, uint32_t r0, uint32_t r1) {
    asm volatile("stmatrix.sync.aligned.m8n8.x2.trans.shared.b16 [%0], {%1,%2};" :: "r"(a), "r"(r0), "r"(r1) : "memory");
}
__device__ __forceinline__ void stsm4t(uint32_t a, uint32_t r0, uint32_t r1, uint32_t r2, uint32_t r3) {
    asm volatile("stmatrix.sync.aligned.m8n8.x4.trans.shared.b16 [%0], {%1,%2,%3,%4};" :: "r"(a), "r"(r0), "r"(r1), "r"(r2), "r"(r3) : "memory");
}
__device__ __forceinline__ uint32_t movm(uint32_t v) {
    uint32_t r; asm volatile("movmatrix.sync.aligned.m8n8.trans.b16 %0, %1;" : "=r"(r) : "r"(v)); return r;
}
__device__ __forceinline__ void mma16(float* c, uint32_t a0, uint32_t a1, uint32_t a2, uint32_t a3, uint32_t b0, uint32_t b1) {
    asm volatile("mma.sync.aligned.m16n8k16.row.col.f32.bf16.bf16.f32 {%0,%1,%2,%3}, {%4,%5,%6,%7}, {%8,%9}, {%0,%1,%2,%3};"
                 : "+f"(c[0]), "+f"(c[1]), "+f"(c[2]), "+f"(c[3]) : "r"(a0), "r"(a1), "r"(a2), "r"(a3), "r"(b0), "r"(b1));
}
__device__ __forceinline__ void mma8(float* c, uint32_t a0, uint32_t a1, uint32_t b0) {
    asm volatile("mma.sync.aligned.m16n8k8.row.col.f32.bf16.bf16.f32 {%0,%1,%2,%3}, {%4,%5}, {%6}, {%0,%1,%2,%3};"
                 : "+f"(c[0]), "+f"(c[1]), "+f"(c[2]), "+f"(c[3]) : "r"(a0), "r"(a1), "r"(b0));
}
__host__ __device__ constexpr uint64_t make_desc(uint32_t saddr, uint32_t lbo, uint32_t sbo, uint32_t layout) {
    return (uint64_t)((saddr & 0x3FFFF) >> 4) | ((uint64_t)(lbo >> 4) << 16) | ((uint64_t)(sbo >> 4) << 32) | ((uint64_t)layout << 62);
}
__device__ __forceinline__ void wg_fence() { asm volatile("wgmma.fence.sync.aligned;" ::: "memory"); }
__device__ __forceinline__ void wg_commit() { asm volatile("wgmma.commit_group.sync.aligned;" ::: "memory"); }
template <int N> __device__ __forceinline__ void wg_wait() { asm volatile("wgmma.wait_group.sync.aligned %0;" :: "n"(N) : "memory"); }

#define D16(C) C(d[0]), C(d[1]), C(d[2]), C(d[3]), C(d[4]), C(d[5]), C(d[6]), C(d[7]), \
               C(d[8]), C(d[9]), C(d[10]), C(d[11]), C(d[12]), C(d[13]), C(d[14]), C(d[15])
#define DREG16 "{%0,%1,%2,%3,%4,%5,%6,%7,%8,%9,%10,%11,%12,%13,%14,%15}"
__device__ __forceinline__ void wg_rs32(float* d, const uint32_t* a, uint64_t db, bool acc) {
    if (acc)
        asm volatile("wgmma.mma_async.sync.aligned.m64n32k16.f32.bf16.bf16 " DREG16 ", {%16,%17,%18,%19}, %20, 1, 1, 1, 0;"
            : D16("+f") : "r"(a[0]), "r"(a[1]), "r"(a[2]), "r"(a[3]), "l"(db));
    else
        asm volatile("wgmma.mma_async.sync.aligned.m64n32k16.f32.bf16.bf16 " DREG16 ", {%16,%17,%18,%19}, %20, 0, 1, 1, 0;"
            : D16("=f") : "r"(a[0]), "r"(a[1]), "r"(a[2]), "r"(a[3]), "l"(db));
}
__device__ __forceinline__ void wg_ss32(float* d, uint64_t da, uint64_t db, bool acc) {
    if (acc)
        asm volatile("wgmma.mma_async.sync.aligned.m64n32k16.f32.bf16.bf16 " DREG16 ", %16, %17, 1, 1, 1, 1, 0;"
            : D16("+f") : "l"(da), "l"(db));
    else
        asm volatile("wgmma.mma_async.sync.aligned.m64n32k16.f32.bf16.bf16 " DREG16 ", %16, %17, 0, 1, 1, 1, 0;"
            : D16("=f") : "l"(da), "l"(db));
}
__device__ __forceinline__ void wg_ss8(float* d, uint64_t da, uint64_t db, bool acc) {
    if (acc)
        asm volatile("wgmma.mma_async.sync.aligned.m64n8k16.f32.bf16.bf16 {%0,%1,%2,%3}, %4, %5, 1, 1, 1, 1, 1;"
            : "+f"(d[0]), "+f"(d[1]), "+f"(d[2]), "+f"(d[3]) : "l"(da), "l"(db));
    else
        asm volatile("wgmma.mma_async.sync.aligned.m64n8k16.f32.bf16.bf16 {%0,%1,%2,%3}, %4, %5, 0, 1, 1, 1, 1;"
            : "=f"(d[0]), "=f"(d[1]), "=f"(d[2]), "=f"(d[3]) : "l"(da), "l"(db));
}
template <int OFF> __device__ __forceinline__ void ldsm4t_i(uint32_t* r, uint32_t a) {
    asm volatile("ldmatrix.sync.aligned.m8n8.x4.trans.shared.b16 {%0,%1,%2,%3}, [%4+%5];"
                 : "=r"(r[0]), "=r"(r[1]), "=r"(r[2]), "=r"(r[3]) : "r"(a), "n"(OFF) : "memory");
}

__device__ __forceinline__ uint4 ld_relaxed4(const void* p) {
    uint4 v;
    asm volatile("ld.relaxed.gpu.global.v4.u32 {%0,%1,%2,%3}, [%4];" : "=r"(v.x), "=r"(v.y), "=r"(v.z), "=r"(v.w) : "l"(p) : "memory");
    return v;
}
__device__ __forceinline__ void st_relaxed2(void* p, uint32_t a, uint32_t b) {
    asm volatile("st.relaxed.gpu.global.v2.u32 [%0], {%1,%2};" :: "l"(p), "r"(a), "r"(b) : "memory");
}
__device__ __forceinline__ void st_relaxed2_off(void* base, uint32_t off, uint32_t a, uint32_t b) {
    asm volatile("{\n\t.reg .u64 ad;\n\tcvt.u64.u32 ad, %1;\n\tadd.u64 ad, ad, %0;\n\tst.relaxed.gpu.global.v2.u32 [ad], {%2,%3};\n\t}"
                 :: "l"(base), "r"(off), "r"(a), "r"(b) : "memory");
}
__device__ __forceinline__ void st_relaxed1(void* p, uint32_t a) {
    asm volatile("st.relaxed.gpu.global.u32 [%0], %1;" :: "l"(p), "r"(a) : "memory");
}
__device__ __forceinline__ uint32_t ld_acquire1(const uint32_t* p) {
    uint32_t v; asm volatile("ld.acquire.gpu.global.u32 %0, [%1];" : "=r"(v) : "l"(p) : "memory"); return v;
}
__device__ __forceinline__ void st_release1(uint32_t* p, uint32_t a) {
    asm volatile("st.release.gpu.global.u32 [%0], %1;" :: "l"(p), "r"(a) : "memory");
}
__device__ __forceinline__ uint4 lds4(uint32_t s) {
    uint4 v; asm volatile("ld.shared.v4.u32 {%0,%1,%2,%3}, [%4];" : "=r"(v.x), "=r"(v.y), "=r"(v.z), "=r"(v.w) : "r"(s) : "memory"); return v;
}
__device__ __forceinline__ void sts4(uint32_t s, const uint4& v) {
    asm volatile("st.shared.v4.u32 [%0], {%1,%2,%3,%4};" :: "r"(s), "r"(v.x), "r"(v.y), "r"(v.z), "r"(v.w) : "memory");
}
__device__ __forceinline__ float4 lds4f(uint32_t s) {
    float4 v; asm volatile("ld.shared.v4.f32 {%0,%1,%2,%3}, [%4];" : "=f"(v.x), "=f"(v.y), "=f"(v.z), "=f"(v.w) : "r"(s) : "memory"); return v;
}
__device__ __forceinline__ float2 lds2f(uint32_t s) {
    float2 v; asm volatile("ld.shared.v2.f32 {%0,%1}, [%2];" : "=f"(v.x), "=f"(v.y) : "r"(s) : "memory"); return v;
}
__device__ __forceinline__ uint32_t clk32() { uint32_t c; asm volatile("mov.u32 %0, %%clock;" : "=r"(c) :: "memory"); return c; }
__device__ __forceinline__ uint32_t tagw(float v, uint32_t tag) { return ((__float_as_uint(v) + 8u) & ~15u) | tag; }
__device__ __forceinline__ bool ok4(const uint4& v, uint32_t tag) { return (((v.x ^ tag) | (v.y ^ tag) | (v.z ^ tag) | (v.w ^ tag)) & 15u) == 0; }
__device__ __forceinline__ bool oks(const uint4& v) { return v.x != 0xFFFFFFFFu && v.y != 0xFFFFFFFFu && v.z != 0xFFFFFFFFu && v.w != 0xFFFFFFFFu; }
__device__ __forceinline__ float uf(uint32_t x) { return __uint_as_float(x & ~15u); }

__global__ void __launch_bounds__(256) k_mod(const bf16* __restrict__ c, const bf16* __restrict__ wmod) {
    __shared__ float sc[DM];
    __shared__ float red[8][64];
    const int tid = threadIdx.x;
    for (int i = tid; i < DM; i += 256) {
        float v = __bfloat162float(c[i]);
        sc[i] = bfr(v / (1.0f + __expf(-v)));
    }
    __syncthreads();
    const int cp = tid & 31, kg = tid >> 5;
    const int col = blockIdx.x * 64 + cp * 2;
    float a0 = 0.f, a1 = 0.f;
    #pragma unroll 8
    for (int k = kg * 80; k < kg * 80 + 80; k++) {
        uint32_t w = *(const uint32_t*)(wmod + (size_t)k * (6 * DM) + col);
        a0 += sc[k] * bflo(w); a1 += sc[k] * bfhi(w);
    }
    red[kg][cp * 2] = a0; red[kg][cp * 2 + 1] = a1;
    __syncthreads();
    if (tid < 64) {
        float s = 0.f;
        #pragma unroll
        for (int i = 0; i < 8; i++) s += red[i][tid];
        g_mod[blockIdx.x * 64 + tid] = bfr(s);
    }
    if (blockIdx.x == 0 && tid == 0) g_epoch = g_epoch + 1;
}

template <int MODE>
__global__ void __launch_bounds__(256) k_ln(const bf16* __restrict__ xin) {
    const int lane = threadIdx.x & 31, row = blockIdx.x * 8 + (threadIdx.x >> 5);
    const bf16* src = (MODE == 0 ? xin : g_x1) + (size_t)row * DM;
    const float* shift = g_mod + (MODE == 0 ? 0 : 3 * DM);
    const float* scale = g_mod + (MODE == 0 ? DM : 4 * DM);
    float v[3][8];
    float s = 0.f;
    #pragma unroll
    for (int i = 0; i < 3; i++) {
        int c = lane + 32 * i;
        if (c < 80) {
            uint4 u = *(const uint4*)(src + c * 8);
            v[i][0] = bflo(u.x); v[i][1] = bfhi(u.x); v[i][2] = bflo(u.y); v[i][3] = bfhi(u.y);
            v[i][4] = bflo(u.z); v[i][5] = bfhi(u.z); v[i][6] = bflo(u.w); v[i][7] = bfhi(u.w);
        } else {
            #pragma unroll
            for (int j = 0; j < 8; j++) v[i][j] = 0.f;
        }
        #pragma unroll
        for (int j = 0; j < 8; j++) s += v[i][j];
    }
    #pragma unroll
    for (int o = 16; o > 0; o >>= 1) s += __shfl_xor_sync(0xffffffffu, s, o);
    const float mean = s * (1.0f / DM);
    float q = 0.f;
    #pragma unroll
    for (int i = 0; i < 3; i++) {
        if (lane + 32 * i < 80) {
            #pragma unroll
            for (int j = 0; j < 8; j++) { float d = v[i][j] - mean; q += d * d; }
        }
    }
    #pragma unroll
    for (int o = 16; o > 0; o >>= 1) q += __shfl_xor_sync(0xffffffffu, q, o);
    const float mb = bfr(mean);
    const float var = bfr(q * (1.0f / DM));
    const float sd = bfr(sqrtf(bfr(var + 1e-5f)));
    #pragma unroll
    for (int i = 0; i < 3; i++) {
        int c = lane + 32 * i;
        if (c < 80) {
            float o[8];
            #pragma unroll
            for (int j = 0; j < 8; j++) {
                float n = bfr(bfr(v[i][j] - mb) / sd);
                float m1 = bfr(1.0f + scale[c * 8 + j]);
                o[j] = bfr(n * m1) + shift[c * 8 + j];
            }
            uint4 u = make_uint4(pack2(o[0], o[1]), pack2(o[2], o[3]), pack2(o[4], o[5]), pack2(o[6], o[7]));
            if (MODE == 0) {
                int seg = row >> 5, r = row & 31, blk = c >> 3, cc = c & 7;
                *(uint4*)(g_ht + (size_t)seg * 20480 + blk * 2048 + r * 64 + ((cc ^ (r & 7)) << 3)) = u;
            } else {
                *(uint4*)(g_h2 + (size_t)row * DM + c * 8) = u;
            }
        }
    }
}

constexpr int SM_WV = 0;
constexpr int SM_HB = 81920;
constexpr int SM_WO = SM_HB + 40960;
constexpr int SM_QX = SM_WO + 77824;
constexpr int SM_KS = SM_QX + 4096;
constexpr int SM_QM = SM_KS + 5120;
constexpr int SM_XS = SM_QM + 1024;
constexpr int SM_MS = SM_XS + 12288;
constexpr int SM_OS = SM_MS + 4608;
constexpr int SM_PM = SM_OS + 3072;
constexpr int SM_BAR = SM_PM + 640;
constexpr int SM_CH = SM_BAR + 128;
constexpr int SM_TOTAL = SM_CH + 128;
static_assert(SM_TOTAL <= 232448, "smem");

enum { B_MEM_FULL = 0, B_MEM_FREE, B_HLO_FULL, B_HHI_FULL, B_HLO_FREE, B_HHI_FREE, B_MS, B_O, B_XS, B_O1, B_XSFREE };

__device__ __forceinline__ int probe_blk(uint32_t* blk) {
    uint32_t t0 = 0xffffffffu, t1 = 0xffffffffu, acc = 0;
    for (int rep = 0; rep < 5; rep++) {
        #pragma unroll
        for (int pg = 0; pg < 2; pg++) {
            uint32_t c0 = clk32();
            uint32_t v = atomicOr(blk + pg * 1024 + acc, 0u);
            acc = (v == 0x12345678u) ? 1u : 0u;
            asm volatile("" :: "r"(acc) : "memory");
            uint32_t c1 = clk32() + acc;
            uint32_t d = c1 - c0;
            if (rep > 0) { if (pg == 0) t0 = min(t0, d); else t1 = min(t1, d); }
        }
    }
    return t1 < t0 ? 1 : 0;
}

__device__ __forceinline__ uint32_t wo_tile_off(int w) {
    if (w < 8) return w * 6144;
    if (w < 12) return 8 * 6144 + (w - 8) * 4096;
    return 8 * 6144 + 4 * 4096 + (w - 12) * 6144;
}

template <int NRES, int NPRE>
__device__ __forceinline__ void wo_phase(uint32_t sb, int w, int lane, const uint32_t (*res)[4], uint32_t parity,
                                         uint32_t tag, uint32_t off0, uint32_t off1) {
    const int er = (lane & 7) + 8 * (lane >> 4);
    const uint32_t aaddr = sb + SM_WO + wo_tile_off(w) + er * 32 + ((((lane >> 3) & 1) ^ ((er >> 2) & 1)) << 4);
    const uint32_t baddr = sb + SM_OS + lane * 16;
    float c0[4] = {0.f, 0.f, 0.f, 0.f}, c1[4] = {0.f, 0.f, 0.f, 0.f};
    uint32_t pre[NPRE > 4 ? NPRE : 4][4];
    if (NPRE >= 4) {
        #pragma unroll
        for (int i = 0; i < 4; i++) ldsm4t(pre[i], aaddr + i * 512);
        mbar_wait(sb + SM_BAR + B_O1 * 8, parity);
        #pragma unroll
        for (int kp = 0; kp < 2; kp++) {
            uint32_t b[4];
            ldsm4t(b, baddr + kp * 512);
            mma16(c0, pre[2 * kp][0], pre[2 * kp][1], pre[2 * kp][2], pre[2 * kp][3], b[0], b[1]);
            mma16(c1, pre[2 * kp + 1][0], pre[2 * kp + 1][1], pre[2 * kp + 1][2], pre[2 * kp + 1][3], b[2], b[3]);
        }
    } else {
        #pragma unroll
        for (int i = 0; i < 2; i++) ldsm4t(pre[i], aaddr + i * 512);
        mbar_wait(sb + SM_BAR + B_O1 * 8, parity);
        #pragma unroll
        for (int kp = 0; kp < 2; kp++) {
            uint32_t b[4];
            ldsm4t(b, baddr + kp * 512);
            if (kp == 1) { ldsm4t(pre[0], aaddr + 2 * 512); ldsm4t(pre[1], aaddr + 3 * 512); }
            mma16(c0, pre[0][0], pre[0][1], pre[0][2], pre[0][3], b[0], b[1]);
            mma16(c1, pre[1][0], pre[1][1], pre[1][2], pre[1][3], b[2], b[3]);
        }
    }
    #pragma unroll
    for (int i = 0; i < NPRE; i++) ldsm4t(pre[i], aaddr + (4 + i) * 512);
    mbar_wait(sb + SM_BAR + B_O * 8, parity);
    #pragma unroll
    for (int kp = 2; kp < 6; kp++) {
        uint32_t b[4];
        ldsm4t(b, baddr + kp * 512);
        #pragma unroll
        for (int hh = 0; hh < 2; hh++) {
            const int k2 = kp * 2 + hh - 4;
            float* c = hh ? c1 : c0;
            if (k2 < NRES) mma16(c, res[k2][0], res[k2][1], res[k2][2], res[k2][3], b[hh * 2], b[hh * 2 + 1]);
            else if (k2 < NRES + NPRE) mma16(c, pre[k2 - NRES][0], pre[k2 - NRES][1], pre[k2 - NRES][2], pre[k2 - NRES][3], b[hh * 2], b[hh * 2 + 1]);
            else {
                uint32_t a[4];
                ldsm4t(a, aaddr + (4 + k2 - NRES) * 512);
                mma16(c, a[0], a[1], a[2], a[3], b[hh * 2], b[hh * 2 + 1]);
            }
        }
    }
    st_relaxed2_off(g_buf1, off0, tagw(c0[0] + c1[0], tag), tagw(c0[1] + c1[1], tag));
    st_relaxed2_off(g_buf1, off1, tagw(c0[2] + c1[2], tag), tagw(c0[3] + c1[3], tag));
}

__device__ __forceinline__ uint32_t hop1_off(uint32_t sb, int col, int h, int t) {
    const int r = col >> 3, j = (col >> 2) & 1;
    uint32_t ch;
    asm volatile("ld.shared.u8 %0, [%1];" : "=r"(ch) : "r"(sb + SM_CH + r) : "memory");
    return (uint32_t)((r * 2 + j) * 8192 + ((ch >> j) & 1) * 4096 + (col & 3) * 1024 + h * 32 + t * 8);
}

template <int NT, bool MASK>
__device__ __forceinline__ void softmax_core(float (*sc)[2], int g, int t, uint32_t* pb) {
    const float L2E = 1.4426950408889634f;
    #pragma unroll
    for (int j = 0; j < NT; j++) score2(sc[j][0], sc[j][1]);
    if (MASK) {
        const float NEG = -999292928.0f;
        if (2 * t > g) sc[NT - 1][0] = NEG;
        if (2 * t + 1 > g) sc[NT - 1][1] = NEG;
    }
    float m[NT];
    #pragma unroll
    for (int j = 0; j < NT; j++) m[j] = fmaxf(sc[j][0], sc[j][1]);
    float mx = m[0];
    #pragma unroll
    for (int j = 1; j < NT; j++) mx = fmaxf(mx, m[j]);
    mx = fmaxf(mx, __shfl_xor_sync(0xffffffffu, mx, 1));
    mx = fmaxf(mx, __shfl_xor_sync(0xffffffffu, mx, 2));
    float s0 = 0.f, s1 = 0.f;
    #pragma unroll
    for (int j = 0; j < NT; j++) {
        sc[j][0] = ex2((sc[j][0] - mx) * L2E); sc[j][1] = ex2((sc[j][1] - mx) * L2E);
        s0 += sc[j][0]; s1 += sc[j][1];
    }
    s0 += s1;
    s0 += __shfl_xor_sync(0xffffffffu, s0, 1);
    s0 += __shfl_xor_sync(0xffffffffu, s0, 2);
    const float iv = rcpf(s0);
    #pragma unroll
    for (int j = 0; j < NT; j++) pb[j] = pack2(sc[j][0] * iv, sc[j][1] * iv);
}
template <int NT>
__device__ __forceinline__ void xsoftmax(uint32_t a, int g, int t) {
    float sc[NT][2];
    #pragma unroll
    for (int j = 0; j < NT; j++) {
        float2 v0 = lds2f(a + j * 512), v1 = lds2f(a + j * 512 + 4096), v2 = lds2f(a + j * 512 + 8192);
        sc[j][0] = v0.x + v1.x + v2.x; sc[j][1] = v0.y + v1.y + v2.y;
    }
    uint32_t pb[NT];
    softmax_core<NT, true>(sc, g, t, pb);
    #pragma unroll
    for (int j = 0; j < NT; j++) sts1(a + j * 512, pb[j]);
}
template <int NJ>
__device__ __forceinline__ void xscores(uint32_t sb, int p, int mi, int j0, int lane) {
    const int r = lane & 7, cq = lane >> 3;
    const int qrow = mi * 16 + r + 8 * (cq & 1);
    uint32_t kb[NJ][8];
    float d[NJ][4];
    #pragma unroll
    for (int j = 0; j < NJ; j++) {
        ldsm4(kb[j], sb + SM_KS + ((j0 + j) * 8 + r) * 128 + ((cq ^ r) << 4));
        ldsm4(kb[j] + 4, sb + SM_KS + ((j0 + j) * 8 + r) * 128 + (((cq + 4) ^ r) << 4));
        d[j][0] = 0.f; d[j][1] = 0.f; d[j][2] = 0.f; d[j][3] = 0.f;
    }
    #pragma unroll
    for (int kt = 0; kt < 4; kt++) {
        uint32_t a[4];
        ldsm4(a, sb + SM_QX + qrow * 128 + (((2 * kt + (cq >> 1)) ^ r) << 4));
        #pragma unroll
        for (int j = 0; j < NJ; j++) mma16(d[j], a[0], a[1], a[2], a[3], kb[j][2 * kt], kb[j][2 * kt + 1]);
    }
    const uint32_t la = sb + SM_XS + p * 4096 + (mi * 3 + j0) * 512 + lane * 16;
    #pragma unroll
    for (int rk = 0; rk < 3; rk++) {
        const uint32_t ra = mapa(la, rk), rb = mapa(sb + SM_BAR + B_XS * 8, rk);
        #pragma unroll
        for (int j = 0; j < NJ; j++) st_async4(ra + j * 512, d[j], rb);
    }
}
__device__ __forceinline__ void mbar_arrive_remote(uint32_t bar) {
    asm volatile("mbarrier.arrive.relaxed.cluster.shared::cluster.b64 _, [%0];" :: "r"(bar) : "memory");
}

__global__ void __launch_bounds__(512, 1)
k_rec(const bf16* __restrict__ mem0, const bf16* __restrict__ Wq, const bf16* __restrict__ Wk,
      const bf16* __restrict__ Wv, const bf16* __restrict__ Wo) {
    extern __shared__ __align__(1024) uint8_t smem_raw[];
    constexpr uint32_t SBC = 1024;
    const uint32_t sb = smem_u32(smem_raw);
    if ((sb & 0xFFFFFFu) != SBC) __trap();
    const int tid = threadIdx.x, lane = tid & 31, warp = tid >> 5, wg = tid >> 7;
    const int b = blockIdx.x, h = b / 3, p = b % 3;
    const int g = lane >> 2, t = lane & 3;
    const int tile0 = p == 0 ? 0 : (p == 1 ? 14 : 27);
    const int ntile = p == 0 ? 14 : 13;
    const uint32_t bar = sb + SM_BAR;

    if (tid == 0) {
        mbar_init(bar + B_MEM_FULL * 8, 4);
        mbar_init(bar + B_MEM_FREE * 8, 12);
        mbar_init(bar + B_HLO_FULL * 8, 1);
        mbar_init(bar + B_HHI_FULL * 8, 1);
        mbar_init(bar + B_HLO_FREE * 8, 12);
        mbar_init(bar + B_HHI_FREE * 8, 12);
        mbar_init(bar + B_MS * 8, 1);
        mbar_init(bar + B_O * 8, 1);
        mbar_init(bar + B_XS * 8, 1);
        mbar_init(bar + B_O1 * 8, 4);
        mbar_init(bar + B_XSFREE * 8, 12);
        asm volatile("fence.mbarrier_init.release.cluster;" ::: "memory");
        mbar_expect(bar + B_MS * 8, 3840);
        mbar_expect(bar + B_O * 8, 2048);
        mbar_expect(bar + B_XS * 8, 12288);
        mbar_expect(bar + B_HLO_FULL * 8, 12288);
        bulk_g2s(sb + SM_HB, g_ht, 12288, sb + SM_BAR + B_HLO_FULL * 8);
        mbar_expect(bar + B_HHI_FULL * 8, 28672);
        bulk_g2s(sb + SM_HB + 12288, (const char*)g_ht + 12288, 28672, sb + SM_BAR + B_HHI_FULL * 8);
    }
    cluster_sync();

    if (wg < 2) {
        asm volatile("setmaxnreg.inc.sync.aligned.u32 200;");
        const int w = warp & 3;
        uint32_t wa[40][4];
        {
            const bf16* W = (wg == 0 ? Wq : Wk) + (size_t)h * DH + p * 64 + w * 16 + t * 4;
            #pragma unroll
            for (int kt = 0; kt < 40; kt++) {
                uint2 l1 = __ldg((const uint2*)(W + (size_t)(kt * 16 + g) * HD));
                uint2 l2 = __ldg((const uint2*)(W + (size_t)(kt * 16 + 8 + g) * HD));
                wa[kt][0] = l1.x; wa[kt][1] = l1.y; wa[kt][2] = l2.x; wa[kt][3] = l2.y;
            }
            #pragma unroll
            for (int kt = 0; kt < 40; kt++) {
                #pragma unroll
                for (int i = 0; i < 4; i++) wa[kt][i] = movm(wa[kt][i]);
            }
        }
        bar_sync(0, 512);
        const uint32_t off0 = hop1_off(sb, (tile0 + warp) * 16 + g, h, t);
        const uint32_t off1 = hop1_off(sb, (tile0 + warp) * 16 + 8 + g, h, t);
        const uint32_t dstx = sb + (wg == 0 ? SM_QX : SM_KS + 1024);

        for (int s = -1; s < NSEG; s++) {
            const uint32_t par = s & 1;
            if (s >= 0) {
                mbar_wait(bar + B_MEM_FULL * 8, par);
                TR(0);
                float c[4][4];
                #pragma unroll
                for (int i = 0; i < 4; i++) { c[i][0] = 0.f; c[i][1] = 0.f; c[i][2] = 0.f; c[i][3] = 0.f; }
                uint32_t maddr = sb + lane * 16;
                asm volatile("" : "+r"(maddr));
                #pragma unroll
                for (int kp = 0; kp < 20; kp++) {
                    uint32_t bb[4];
                    ldsm4t(bb, maddr + (SM_HB + kp * 512));
                    mma16(c[(kp & 1) * 2], wa[2 * kp][0], wa[2 * kp][1], wa[2 * kp][2], wa[2 * kp][3], bb[0], bb[1]);
                    mma16(c[(kp & 1) * 2 + 1], wa[2 * kp + 1][0], wa[2 * kp + 1][1], wa[2 * kp + 1][2], wa[2 * kp + 1][3], bb[2], bb[3]);
                }
                {
                    const int tok = lane & 7, ch = 2 * w + ((lane >> 3) & 1);
                    stsm2t(sb + (wg == 0 ? SM_QM : SM_KS) + tok * 128 + ((ch ^ tok) << 4),
                           pack2((c[0][0] + c[1][0]) + (c[2][0] + c[3][0]), (c[0][1] + c[1][1]) + (c[2][1] + c[3][1])),
                           pack2((c[0][2] + c[1][2]) + (c[2][2] + c[3][2]), (c[0][3] + c[1][3]) + (c[2][3] + c[3][3])));
                }
                __syncwarp();
                if (lane == 0) mbar_arrive(bar + B_MEM_FREE * 8);
                TR(1);
                bar_sync(1, 256);
                if (warp < 5) {
                    const int r = lane & 7, cq = lane >> 3;
                    uint32_t a[8], kb[8];
                    ldsm4(a, sb + SM_QM + r * 128 + ((cq ^ r) << 4));
                    ldsm4(kb, sb + SM_KS + (warp * 8 + r) * 128 + ((cq ^ r) << 4));
                    ldsm4(a + 4, sb + SM_QM + r * 128 + (((cq + 4) ^ r) << 4));
                    ldsm4(kb + 4, sb + SM_KS + (warp * 8 + r) * 128 + (((cq + 4) ^ r) << 4));
                    float d0[4] = {0.f, 0.f, 0.f, 0.f}, d1[4] = {0.f, 0.f, 0.f, 0.f};
                    mma16(d0, a[0], 0u, a[1], 0u, kb[0], kb[1]);
                    mma16(d1, a[2], 0u, a[3], 0u, kb[2], kb[3]);
                    mma16(d0, a[4], 0u, a[5], 0u, kb[4], kb[5]);
                    mma16(d1, a[6], 0u, a[7], 0u, kb[6], kb[7]);
                    const uint32_t la = sb + SM_MS + p * 1536 + lane * 48 + warp * 8;
                    #pragma unroll
                    for (int rk = 0; rk < 3; rk++)
                        st_async2(mapa(la, rk), d0[0] + d1[0], d0[1] + d1[1], mapa(bar + B_MS * 8, rk));
                    bar_arrive(4, 352);
                } else if (warp < 7) {
                    xscores<1>(sb, p, warp - 5, 0, lane);
                    bar_arrive(4, 352);
                }
                TR(2);
                if (wg == 1) {
                    mbar_wait(bar + B_XS * 8, par);
                    TR(8);
                    if (tid == 128) mbar_expect(bar + B_XS * 8, 12288);
                    const uint32_t a = sb + SM_XS + (w >> 1) * 1536 + lane * 16 + (w & 1) * 8;
                    if (w == 0) xsoftmax<2>(a, g, t);
                    else if (w == 1) xsoftmax<3>(a, g, t);
                    else if (w == 2) xsoftmax<4>(a, g, t);
                    else xsoftmax<5>(a, g, t);
                    bar_arrive(7, 256);
                    TR(9);
                }
                if (s < NSEG - 1) {
                    wo_phase<0, 4>(sb, warp, lane, nullptr, par, (uint32_t)(s % 15) + 1u, off0, off1);
                    TR(4);
                    bar_arrive(6, 448);
                }
            }
            if (s < NSEG - 1) {
                const uint32_t hp = (s + 1) & 1;
                float d[16];
                const uint64_t db0 = make_desc(SBC + SM_HB, 16, 1024, 1);
                mbar_wait(bar + B_HHI_FULL * 8, hp);
                mbar_wait(bar + B_HLO_FULL * 8, hp);
                bar_sync(9, 384);
                TR(6);
                wg_fence();
                #pragma unroll
                for (int kt = 0; kt < 12; kt++) wg_rs32(d, wa[kt], db0 + (uint64_t)(((kt >> 2) * 4096 + (kt & 3) * 32) >> 4), kt > 0);
                wg_commit();
                #pragma unroll
                for (int kt = 12; kt < 39; kt++) wg_rs32(d, wa[kt], db0 + (uint64_t)(((kt >> 2) * 4096 + (kt & 3) * 32) >> 4), 1);
                wg_commit();
                wg_wait<1>();
                if (lane == 0) mbar_arrive(bar + B_HLO_FREE * 8);
                {
                    const int r = lane & 7, mq = lane >> 3;
                    const uint32_t ha = sb + SM_HB + 9 * 4096 + (8 * (mq >> 1) + r) * 128 + (((6 + (mq & 1)) ^ r) << 4);
                    uint32_t b0[4], b1[4];
                    ldsm4(b0, ha);
                    ldsm4(b1, ha + 2048);
                    wg_wait<0>();
                    mma16(d + 0, wa[39][0], wa[39][1], wa[39][2], wa[39][3], b0[0], b0[1]);
                    mma16(d + 4, wa[39][0], wa[39][1], wa[39][2], wa[39][3], b0[2], b0[3]);
                    mma16(d + 8, wa[39][0], wa[39][1], wa[39][2], wa[39][3], b1[0], b1[1]);
                    mma16(d + 12, wa[39][0], wa[39][1], wa[39][2], wa[39][3], b1[2], b1[3]);
                }
                __syncwarp();
                if (lane == 0) mbar_arrive(bar + B_HHI_FREE * 8);
                TR(7);
                const int mi = lane >> 3, r = lane & 7;
                #pragma unroll
                for (int jj = 0; jj < 2; jj++) {
                    const int tok = 8 * (2 * jj + (mi >> 1)) + r, ch = 2 * w + (mi & 1);
                    stsm4t(dstx + tok * 128 + ((ch ^ r) << 4),
                           pack2(d[8 * jj + 0], d[8 * jj + 1]), pack2(d[8 * jj + 2], d[8 * jj + 3]),
                           pack2(d[8 * jj + 4], d[8 * jj + 5]), pack2(d[8 * jj + 6], d[8 * jj + 7]));
                }
                bar_arrive(8, 384);
            }
        }
    } else if (wg == 2) {
        asm volatile("setmaxnreg.dec.sync.aligned.u32 64;");
        const int w = warp & 3;
        {
            const int c = tid & 7;
            const bf16* src = Wv + (size_t)h * DH + p * 64 + c * 8;
            for (int k = (tid & 127) >> 3; k < DM; k += 16)
                cpa16(sb + SM_WV + k * 128 + ((c ^ (k & 7)) << 4), src + (size_t)k * HD);
        }
        uint32_t res[4][4];
        {
            const bf16* src = Wo + ((size_t)h * DH + ((p + 1) % 3) * 64) * DM + (tile0 + warp) * 16 + 2 * t;
            #pragma unroll
            for (int kt = 0; kt < 4; kt++) {
                res[kt][0] = __ldg((const uint32_t*)(src + (size_t)(kt * 16 + g) * DM));
                res[kt][1] = __ldg((const uint32_t*)(src + (size_t)(kt * 16 + g) * DM + 8));
                res[kt][2] = __ldg((const uint32_t*)(src + (size_t)(kt * 16 + 8 + g) * DM));
                res[kt][3] = __ldg((const uint32_t*)(src + (size_t)(kt * 16 + 8 + g) * DM + 8));
            }
            #pragma unroll
            for (int kt = 0; kt < 4; kt++) {
                #pragma unroll
                for (int i = 0; i < 4; i++) res[kt][i] = movm(res[kt][i]);
            }
        }
        cpa_wait_all();
        fence_async();
        bar_sync(0, 512);
        const uint32_t off0 = hop1_off(sb, (tile0 + warp) * 16 + g, h, t);
        const uint32_t off1 = hop1_off(sb, (tile0 + warp) * 16 + 8 + g, h, t);
        const uint64_t da0 = make_desc(SBC + SM_WV, 16, 1024, 1);
        uint32_t vx[8];
        #pragma unroll
        for (int i = 0; i < 8; i++) vx[i] = 0;

        for (int s = -1; s < NSEG; s++) {
            if (s >= 0) {
                const uint32_t par = s & 1;
                mbar_wait(bar + B_MEM_FULL * 8, par);
                bar_sync(4, 352);
                TR(0);
                float dv[4];
                {
                    const uint64_t dbm = make_desc(SBC + SM_HB, 128, 128, 0);
                    wg_fence();
                    #pragma unroll
                    for (int kt = 0; kt < 40; kt++) {
                        wg_ss8(dv, da0 + (uint64_t)(kt * 128), dbm + (uint64_t)(kt * 16), kt > 0);
                        wg_commit();
                        if (kt < 39) wg_wait<1>();
                    }
                    wg_commit();
                }
                TR(1);
                bar_sync(5, 160);
                TR(2);
                uint32_t pb[5];
                #pragma unroll
                for (int j = 0; j < 5; j++) pb[j] = lds1(sb + SM_PM + j * 128 + lane * 4);
                float o0[4] = {0.f, 0.f, 0.f, 0.f}, o1[4] = {0.f, 0.f, 0.f, 0.f}, o2[4] = {0.f, 0.f, 0.f, 0.f};
                wg_wait<0>();
                TR(3);
                mma16(o0, vx[0], vx[1], vx[2], vx[3], pb[1], pb[2]);
                mma16(o1, vx[4], vx[5], vx[6], vx[7], pb[3], pb[4]);
                const uint32_t vm0 = pack2(dv[0], dv[1]), vm1 = pack2(dv[2], dv[3]);
                mma8(o2, vm0, vm1, pb[0]);
                if (s < NSEG - 1) {
                    const uint32_t q0 = pack2(o0[0] + o1[0] + o2[0], o0[1] + o1[1] + o2[1]), q1 = pack2(o0[2] + o1[2] + o2[2], o0[3] + o1[3] + o2[3]);
                    const uint32_t la = sb + SM_OS + (w * 16 + g) * 16 + t * 4;
                    #pragma unroll
                    for (int i = 1; i < 3; i++) {
                        const uint32_t rk = (p + i) % 3;
                        const uint32_t ra = mapa(la + (3 - i) * 1024, rk), rb = mapa(bar + B_O * 8, rk);
                        st_async1(ra, q0, rb);
                        st_async1(ra + 128, q1, rb);
                    }
                    sts1(la, q0);
                    sts1(la + 128, q1);
                    __syncwarp();
                    if (lane == 0) { mbar_arrive(bar + B_O1 * 8); mbar_arrive(bar + B_MEM_FREE * 8); }
                }
                TR(5);
                bar_sync(7, 256);
                TR(8);
                bf16* orow = g_ox + (size_t)(s * 32 + g) * HD + h * DH + p * 64 + w * 16 + 2 * t;
                #pragma unroll
                for (int mi = 0; mi < 2; mi++) {
                    uint4 pv[5];
                    #pragma unroll
                    for (int j = 0; j < 5; j++) if (j < (mi ? 5 : 3)) pv[j] = lds4(sb + SM_XS + mi * 1536 + j * 512 + lane * 16);
                    float oa[4] = {0.f, 0.f, 0.f, 0.f}, ob[4] = {0.f, 0.f, 0.f, 0.f};
                    mma8(oa, vm0, vm1, pv[0].x);
                    mma8(ob, vm0, vm1, pv[0].z);
                    mma16(oa, vx[0], vx[1], vx[2], vx[3], pv[1].x, mi ? pv[2].x : 0u);
                    mma16(ob, vx[0], vx[1], vx[2], vx[3], pv[1].z, pv[2].z);
                    if (mi) {
                        mma16(oa, vx[4], vx[5], vx[6], vx[7], pv[3].x, 0u);
                        mma16(ob, vx[4], vx[5], vx[6], vx[7], pv[3].z, pv[4].z);
                    }
                    const uint32_t u0 = movm(pack2(oa[0], oa[1])), u1 = movm(pack2(oa[2], oa[3]));
                    const uint32_t u2 = movm(pack2(ob[0], ob[1])), u3 = movm(pack2(ob[2], ob[3]));
                    bf16* dst = orow + (size_t)(16 * mi) * HD;
                    *(uint32_t*)dst = u0;
                    *(uint32_t*)(dst + 8) = u1;
                    *(uint32_t*)(dst + 8 * HD) = u2;
                    *(uint32_t*)(dst + 8 * HD + 8) = u3;
                }
                TR(9);
                if (s == NSEG - 1) break;
                wo_phase<4, 4>(sb, warp, lane, res, par, (uint32_t)(s % 15) + 1u, off0, off1);
                TR(4);
                if (lane < 3) mbar_arrive_remote(mapa(bar + B_XSFREE * 8, lane));
                if (tid == 256) mbar_expect(bar + B_O * 8, 2048);
                bar_sync(6, 448);
            }
            float d[16];
            const uint32_t hp = (s + 1) & 1;
            const uint64_t db0 = make_desc(SBC + SM_HB, 16, 1024, 1);
            mbar_wait(bar + B_HHI_FULL * 8, hp);
            mbar_wait(bar + B_HLO_FULL * 8, hp);
            TR(6);
            wg_fence();
            #pragma unroll
            for (int kt = 0; kt < 36; kt++) wg_ss32(d, da0 + (uint64_t)(kt * 128), db0 + (uint64_t)(((kt >> 2) * 4096 + (kt & 3) * 32) >> 4), kt > 0);
            wg_commit();
            #pragma unroll
            for (int kt = 36; kt < 40; kt++) wg_ss32(d, da0 + (uint64_t)(kt * 128), db0 + (uint64_t)(((kt >> 2) * 4096 + (kt & 3) * 32) >> 4), 1);
            wg_commit();
            wg_wait<1>();
            bar_arrive(9, 384);
            if (lane == 0) mbar_arrive(bar + B_HLO_FREE * 8);
            wg_wait<0>();
            TR(7);
            if (lane == 0) mbar_arrive(bar + B_HHI_FREE * 8);
            #pragma unroll
            for (int i = 0; i < 8; i++) vx[i] = pack2(d[2 * i], d[2 * i + 1]);
            if (s >= 0) mbar_wait_cluster(bar + B_XSFREE * 8, s & 1);
            bar_sync(8, 384);
            TR(10);
            if (w < 3) xscores<2>(sb, p, w > 0, w == 2 ? 3 : 1, lane);
            TR(11);
        }
    } else {
        asm volatile("setmaxnreg.dec.sync.aligned.u32 48;");
        const int w = warp & 3, lt = tid & 127;
        {
            const bf16* src0 = Wo + (size_t)h * DH * DM + tile0 * 16;
            const int nch = 2 * ntile;
            for (int i = lt; i < DH * nch; i += 128) {
                const int e = i / nch, c = i - e * nch, tl = c >> 1, cc = c & 1;
                int es = e;
                if (tl >= 8 && tl < 12) { if (e >= 64 && e < 128) continue; if (e >= 128) es = e - 64; }
                int eg = e + p * 64; if (eg >= DH) eg -= DH;
                cpa16(sb + SM_WO + wo_tile_off(tl) + es * 32 + ((cc ^ ((e >> 2) & 1)) << 4), src0 + (size_t)eg * DM + c * 8);
            }
        }
        const uint32_t epoch = *(volatile uint32_t*)&g_epoch;
        if (b < 80) {
            #pragma unroll
            for (int i = 0; i < 2; i++) {
                const int idx = lt + i * 128, sl = idx >> 6, pg = (idx >> 5) & 1, wd = idx & 31;
                st_relaxed1(g_buf2 + (sl * 3 + (b >> 5)) * 2048 + pg * 1024 + (b & 31) * 32 + wd, 0xFFFFFFFFu);
            }
            __threadfence();
        }
        if (lane == 0) {
            for (int i = w; i < 14; i += 4) {
                int c = 0;
                if (i < 12) c = probe_blk(g_buf2 + i * 2048 + 640 + (b & 31) * 8);
                else if (b < 80) c = probe_blk(g_buf1 + (b * 2 + (i - 12)) * 2048);
                asm volatile("st.shared.u8 [%0], %1;" :: "r"(sb + SM_CH + 96 + i), "r"(c) : "memory");
            }
        }
        bar_sync(3, 128);
        uint32_t selmask = 0;
        for (int i = 0; i < 14; i++) {
            uint32_t c; asm volatile("ld.shared.u8 %0, [%1];" : "=r"(c) : "r"(sb + SM_CH + 96 + i) : "memory");
            selmask |= c << i;
        }
        if (lt == 0 && b < 80) st_release1(&g_choice[b], (epoch << 2) | (selmask >> 12));
        if (lt < 80) {
            uint32_t v, guard = 0;
            do { v = ld_acquire1(&g_choice[lt]); if (++guard > (1u << 22)) __trap(); } while ((v >> 2) != (epoch & 0x3fffffffu));
            asm volatile("st.shared.u8 [%0], %1;" :: "r"(sb + SM_CH + lt), "r"(v & 3u) : "memory");
        }
        cpa_wait_all();
        bar_sync(0, 512);
        const bool has_tile = (12 + w) < ntile;
        uint32_t off0 = 0, off1 = 0;
        if (has_tile) {
            off0 = hop1_off(sb, (tile0 + warp) * 16 + g, h, t);
            off1 = hop1_off(sb, (tile0 + warp) * 16 + 8 + g, h, t);
        }
        const char* rin = (const char*)g_buf1 + (size_t)(b * 2 + (w >> 1)) * 8192 + ((selmask >> (12 + (w >> 1))) & 1) * 4096 + (w & 1) * 2048 + lane * 16;

        for (int s = 0; s < NSEG; s++) {
            const uint32_t par = s & 1;
            if (s == 0) {
                mbar_wait(bar + B_HLO_FREE * 8, par);
                for (int k = lt; k < DM; k += 128) {
                    uint32_t v[4];
                    #pragma unroll
                    for (int i = 0; i < 4; i++) {
                        uint32_t lo = *(const uint16_t*)(mem0 + (2 * i) * DM + k), hi = *(const uint16_t*)(mem0 + (2 * i + 1) * DM + k);
                        v[i] = lo | (hi << 16);
                    }
                    asm volatile("st.shared.v4.u32 [%0], {%1,%2,%3,%4};" :: "r"(sb + SM_HB + k * 16), "r"(v[0]), "r"(v[1]), "r"(v[2]), "r"(v[3]) : "memory");
                }
            } else {
                const int sl = s & 3;
                const char* q = (const char*)g_buf2 + sl * 3 * 8192 + lt * 16;
                const uint32_t sm = selmask >> (sl * 3);
                const char* q0 = q + (sm & 1) * 4096;
                const char* q1 = q + 8192 + (sm & 2) * 2048;
                const char* q2 = q + 16384 + (sm & 4) * 1024;
                const uint32_t dst = sb + SM_HB + lt * 16;
                uint32_t guard = 0;
                mbar_wait(bar + B_HLO_FREE * 8, par);
                TR(10);
                while (true) {
                    const uint4 v0 = ld_relaxed4(q0), v1 = ld_relaxed4(q0 + 2048), v2 = ld_relaxed4(q1), v3 = ld_relaxed4(q1 + 2048), v4 = ld_relaxed4(q2);
                    sts4(dst, v0); sts4(dst + 2048, v1); sts4(dst + 4096, v2); sts4(dst + 6144, v3); sts4(dst + 8192, v4);
                    if (__all_sync(0xffffffffu, oks(v0) && oks(v1) && oks(v2) && oks(v3) && oks(v4))) break;
                    if (++guard > (1u << 22)) __trap();
                }
            }
            fence_async();
            __syncwarp();
            if (lane == 0) mbar_arrive(bar + B_MEM_FULL * 8);
            TR(0);
            if (w == 2) {
                mbar_wait(bar + B_MS * 8, par);
                TR(1);
                if (lane == 0) mbar_expect(bar + B_MS * 8, 3840);
                uint32_t pb[5];
                float sc[5][2];
                {
                    const uint32_t a = sb + SM_MS + lane * 48;
                    float4 u0 = lds4f(a), u1 = lds4f(a + 16), v0 = lds4f(a + 1536), v1 = lds4f(a + 1552);
                    float2 u2 = lds2f(a + 32), v2 = lds2f(a + 1568);
                    float4 w0 = lds4f(a + 3072), w1 = lds4f(a + 3088);
                    float2 w2 = lds2f(a + 3104);
                    sc[0][0] = u0.x + v0.x + w0.x; sc[0][1] = u0.y + v0.y + w0.y; sc[1][0] = u0.z + v0.z + w0.z; sc[1][1] = u0.w + v0.w + w0.w;
                    sc[2][0] = u1.x + v1.x + w1.x; sc[2][1] = u1.y + v1.y + w1.y; sc[3][0] = u1.z + v1.z + w1.z; sc[3][1] = u1.w + v1.w + w1.w;
                    sc[4][0] = u2.x + v2.x + w2.x; sc[4][1] = u2.y + v2.y + w2.y;
                }
                softmax_core<5, false>(sc, g, t, pb);
                #pragma unroll
                for (int j = 0; j < 5; j++) sts1(sb + SM_PM + j * 128 + lane * 4, pb[j]);
                bar_arrive(5, 160);
                TR(2);
            }
            if (s < NSEG - 1) {
                if (w == 3) {
                    if (lane == 0) {
                        const char* src = (const char*)g_ht + (size_t)(s + 1) * 40960;
                        mbar_wait(bar + B_HHI_FREE * 8, par);
                        mbar_expect(bar + B_HHI_FULL * 8, 28672);
                        bulk_g2s(sb + SM_HB + 12288, src + 12288, 28672, sb + SM_BAR + B_HHI_FULL * 8);
                        mbar_wait(bar + B_MEM_FREE * 8, par);
                        mbar_expect(bar + B_HLO_FULL * 8, 12288);
                        bulk_g2s(sb + SM_HB, src, 12288, sb + SM_BAR + B_HLO_FULL * 8);
                    }
                    __syncwarp();
                }
                const uint32_t tag = (uint32_t)(s % 15) + 1u;
                if (has_tile) wo_phase<0, 3>(sb, warp, lane, nullptr, par, tag, off0, off1);
                else mbar_wait(bar + B_O * 8, par);
                if (w < 2) bar_arrive(6, 448);
                TR(4);
                if (b < 80) {
                    uint4 v0, v1, v2, v3;
                    uint32_t guard = 0;
                    while (true) {
                        v0 = ld_relaxed4(rin); v1 = ld_relaxed4(rin + 512);
                        v2 = ld_relaxed4(rin + 1024); v3 = ld_relaxed4(rin + 1536);
                        if (__all_sync(0xffffffffu, ok4(v0, tag) && ok4(v1, tag) && ok4(v2, tag) && ok4(v3, tag))) break;
                        if (++guard > (1u << 22)) __trap();
                    }
                    TR(11);
                    float a0 = uf(v0.x) + uf(v1.x), a1 = uf(v0.y) + uf(v1.y), a2 = uf(v0.z) + uf(v1.z), a3 = uf(v0.w) + uf(v1.w);
                    float b0 = uf(v2.x) + uf(v3.x), b1 = uf(v2.y) + uf(v3.y), b2 = uf(v2.z) + uf(v3.z), b3 = uf(v2.w) + uf(v3.w);
                    const bool u16 = lane & 16;
                    float k0 = (u16 ? b0 : a0) + __shfl_xor_sync(0xffffffffu, u16 ? a0 : b0, 16);
                    float k1 = (u16 ? b1 : a1) + __shfl_xor_sync(0xffffffffu, u16 ? a1 : b1, 16);
                    float k2 = (u16 ? b2 : a2) + __shfl_xor_sync(0xffffffffu, u16 ? a2 : b2, 16);
                    float k3 = (u16 ? b3 : a3) + __shfl_xor_sync(0xffffffffu, u16 ? a3 : b3, 16);
                    const bool u8 = lane & 8;
                    float m0 = (u8 ? k2 : k0) + __shfl_xor_sync(0xffffffffu, u8 ? k0 : k2, 8);
                    float m1 = (u8 ? k3 : k1) + __shfl_xor_sync(0xffffffffu, u8 ? k1 : k3, 8);
                    m0 += __shfl_xor_sync(0xffffffffu, m0, 4); m1 += __shfl_xor_sync(0xffffffffu, m1, 4);
                    m0 += __shfl_xor_sync(0xffffffffu, m0, 2); m1 += __shfl_xor_sync(0xffffffffu, m1, 2);
                    const int col = b * 8 + 2 * w + (lane >> 4), wd = 2 * (lane & 1) + ((lane >> 3) & 1);
                    const int sl = (lane & 4) ? ((s + 3) & 3) : ((s + 1) & 3);
                    uint32_t* dst = g_buf2 + (sl * 3 + (col >> 8)) * 2048 + ((lane >> 1) & 1) * 1024 + (col & 255) * 4 + wd;
                    st_relaxed1(dst, (lane & 4) ? 0xFFFFFFFFu : pack2(m0, m1));
                    TR(12);
                }
            }
        }
    }
    cluster_sync();
}

constexpr int G_STAGES = 5;
constexpr int G_STAGE_BYTES = 32768;
constexpr int G_SMEM = G_STAGES * G_STAGE_BYTES + 1024 + 256;

__device__ __forceinline__ void tma2d(uint32_t dst, const CUtensorMap* map, int c0, int c1, uint32_t bar) {
    asm volatile("cp.async.bulk.tensor.2d.shared::cluster.global.mbarrier::complete_tx::bytes [%0], [%1, {%2, %3}], [%4];"
                 :: "r"(dst), "l"(map), "r"(c0), "r"(c1), "r"(bar) : "memory");
}
__device__ __forceinline__ void wg_ss128(float* d, uint64_t da, uint64_t db, int sc) {
    asm volatile("{\n\t.reg .pred p;\n\tsetp.ne.b32 p, %66, 0;\n\t"
        "wgmma.mma_async.sync.aligned.m64n128k16.f32.bf16.bf16 "
        "{%0,%1,%2,%3,%4,%5,%6,%7,%8,%9,%10,%11,%12,%13,%14,%15,%16,%17,%18,%19,%20,%21,%22,%23,%24,%25,%26,%27,%28,%29,%30,%31,"
        "%32,%33,%34,%35,%36,%37,%38,%39,%40,%41,%42,%43,%44,%45,%46,%47,%48,%49,%50,%51,%52,%53,%54,%55,%56,%57,%58,%59,%60,%61,%62,%63}, "
        "%64, %65, p, 1, 1, 0, 1;\n\t}"
        : "+f"(d[0]), "+f"(d[1]), "+f"(d[2]), "+f"(d[3]), "+f"(d[4]), "+f"(d[5]), "+f"(d[6]), "+f"(d[7]),
          "+f"(d[8]), "+f"(d[9]), "+f"(d[10]), "+f"(d[11]), "+f"(d[12]), "+f"(d[13]), "+f"(d[14]), "+f"(d[15]),
          "+f"(d[16]), "+f"(d[17]), "+f"(d[18]), "+f"(d[19]), "+f"(d[20]), "+f"(d[21]), "+f"(d[22]), "+f"(d[23]),
          "+f"(d[24]), "+f"(d[25]), "+f"(d[26]), "+f"(d[27]), "+f"(d[28]), "+f"(d[29]), "+f"(d[30]), "+f"(d[31]),
          "+f"(d[32]), "+f"(d[33]), "+f"(d[34]), "+f"(d[35]), "+f"(d[36]), "+f"(d[37]), "+f"(d[38]), "+f"(d[39]),
          "+f"(d[40]), "+f"(d[41]), "+f"(d[42]), "+f"(d[43]), "+f"(d[44]), "+f"(d[45]), "+f"(d[46]), "+f"(d[47]),
          "+f"(d[48]), "+f"(d[49]), "+f"(d[50]), "+f"(d[51]), "+f"(d[52]), "+f"(d[53]), "+f"(d[54]), "+f"(d[55]),
          "+f"(d[56]), "+f"(d[57]), "+f"(d[58]), "+f"(d[59]), "+f"(d[60]), "+f"(d[61]), "+f"(d[62]), "+f"(d[63])
        : "l"(da), "l"(db), "r"(sc));
}

template <int EPI>
__global__ void __launch_bounds__(384, 1)
k_gemm(const __grid_constant__ CUtensorMap mapA, const __grid_constant__ CUtensorMap mapB, int K,
       const bf16* __restrict__ xin, bf16* __restrict__ outp) {
    extern __shared__ uint8_t smem_raw[];
    const uint32_t sb = (smem_u32(smem_raw) + 1023u) & ~1023u;
    const uint32_t bars = sb + G_STAGES * G_STAGE_BYTES;
    const int tid = threadIdx.x, lane = tid & 31, wg = tid >> 7;
    const int n0 = blockIdx.x * 128, m0 = blockIdx.y * 128;
    const int nk = K / 64;
    if (tid == 0) {
        for (int i = 0; i < G_STAGES; i++) { mbar_init(bars + i * 8, 1); mbar_init(bars + 64 + i * 8, 8); }
        asm volatile("fence.mbarrier_init.release.cluster;" ::: "memory");
    }
    __syncthreads();
    if (wg == 0) {
        if (tid == 0) {
            for (int kb = 0; kb < nk; kb++) {
                const int st = kb % G_STAGES;
                if (kb >= G_STAGES) mbar_wait(bars + 64 + st * 8, ((kb / G_STAGES) - 1) & 1);
                const uint32_t a = sb + st * G_STAGE_BYTES;
                mbar_expect(bars + st * 8, G_STAGE_BYTES);
                tma2d(a, &mapA, kb * 64, m0, bars + st * 8);
                tma2d(a + 16384, &mapB, n0, kb * 64, bars + st * 8);
                tma2d(a + 16384 + 8192, &mapB, n0 + 64, kb * 64, bars + st * 8);
            }
        }
    } else {
        float d[64];
        #pragma unroll
        for (int i = 0; i < 64; i++) d[i] = 0.f;
        const int cw = wg - 1;
        for (int kb = 0; kb < nk; kb++) {
            const int st = kb % G_STAGES;
            mbar_wait(bars + st * 8, (kb / G_STAGES) & 1);
            const uint32_t a = sb + st * G_STAGE_BYTES;
            const uint64_t da = make_desc(a + cw * 8192, 16, 1024, 1);
            const uint64_t db = make_desc(a + 16384, 8192, 1024, 1);
            wg_fence();
            #pragma unroll
            for (int k = 0; k < 4; k++) wg_ss128(d, da + (uint64_t)(k * 2), db + (uint64_t)(k * 128), 1);
            wg_commit();
            if (kb > 0) {
                wg_wait<1>();
                if (lane == 0) mbar_arrive(bars + 64 + ((kb - 1) % G_STAGES) * 8);
            }
        }
        wg_wait<0>();
        const int g = lane >> 2, t = lane & 3, w = (tid >> 5) & 3;
        const int ldo = EPI == 1 ? FF : DM;
        #pragma unroll
        for (int hf = 0; hf < 2; hf++) {
            const int row = m0 + cw * 64 + w * 16 + g + 8 * hf;
            #pragma unroll
            for (int j = 0; j < 16; j++) {
                const int col = n0 + j * 8 + 2 * t;
                float a0 = bfr(d[4 * j + 2 * hf]), a1 = bfr(d[4 * j + 2 * hf + 1]);
                uint32_t o;
                if (EPI == 1) {
                    o = pack2(a0 / (1.0f + __expf(-a0)), a1 / (1.0f + __expf(-a1)));
                } else {
                    const float2 gm = *(const float2*)(g_mod + (EPI == 0 ? 2 : 5) * DM + col);
                    const uint32_t xv = *(const uint32_t*)(xin + (size_t)row * DM + col);
                    o = pack2(bflo(xv) + bfr(gm.x * a0), bfhi(xv) + bfr(gm.y * a1));
                }
                *(uint32_t*)(outp + (size_t)row * ldo + col) = o;
            }
        }
    }
}

typedef CUresult (*EncodeFn)(CUtensorMap*, CUtensorMapDataType, cuuint32_t, void*, const cuuint64_t*, const cuuint64_t*,
                             const cuuint32_t*, const cuuint32_t*, CUtensorMapInterleave, CUtensorMapSwizzle,
                             CUtensorMapL2promotion, CUtensorMapFloatOOBfill);

static void make_map(EncodeFn fn, CUtensorMap* m, const void* ptr, uint64_t inner, uint64_t outer, uint32_t bi, uint32_t bo) {
    cuuint64_t dims[2] = {inner, outer};
    cuuint64_t strides[1] = {inner * 2};
    cuuint32_t box[2] = {bi, bo};
    cuuint32_t es[2] = {1, 1};
    fn(m, CU_TENSOR_MAP_DATA_TYPE_BFLOAT16, 2, (void*)ptr, dims, strides, box, es, CU_TENSOR_MAP_INTERLEAVE_NONE,
       CU_TENSOR_MAP_SWIZZLE_128B, CU_TENSOR_MAP_L2_PROMOTION_L2_256B, CU_TENSOR_MAP_FLOAT_OOB_FILL_NONE);
}

extern "C" void kernel_launch(void* const* d_in, const int* in_sizes, int n_in, void* d_out, int out_size) {
    const bf16* x = (const bf16*)d_in[0];
    const bf16* mem0 = (const bf16*)d_in[1];
    const bf16* Wq = (const bf16*)d_in[2];
    const bf16* Wk = (const bf16*)d_in[3];
    const bf16* Wv = (const bf16*)d_in[4];
    const bf16* Wo = (const bf16*)d_in[5];
    const bf16* w1 = (const bf16*)d_in[8];
    const bf16* w2 = (const bf16*)d_in[9];
    const bf16* c = (const bf16*)d_in[10];
    const bf16* wmod = (const bf16*)d_in[11];
    bf16* out = (bf16*)d_out;

    static EncodeFn enc = nullptr;
    static void *p_ox, *p_x1, *p_h2, *p_act;
    if (!enc) {
        cudaDriverEntryPointQueryResult qr;
        void* f = nullptr;
        cudaGetDriverEntryPoint("cuTensorMapEncodeTiled", &f, cudaEnableDefault, &qr);
        enc = (EncodeFn)f;
        cudaGetSymbolAddress(&p_ox, g_ox);
        cudaGetSymbolAddress(&p_x1, g_x1);
        cudaGetSymbolAddress(&p_h2, g_h2);
        cudaGetSymbolAddress(&p_act, g_act);
        cudaFuncSetAttribute(k_rec, cudaFuncAttributeMaxDynamicSharedMemorySize, SM_TOTAL);
        cudaFuncSetAttribute(k_gemm<0>, cudaFuncAttributeMaxDynamicSharedMemorySize, G_SMEM);
        cudaFuncSetAttribute(k_gemm<1>, cudaFuncAttributeMaxDynamicSharedMemorySize, G_SMEM);
        cudaFuncSetAttribute(k_gemm<2>, cudaFuncAttributeMaxDynamicSharedMemorySize, G_SMEM);
    }
    CUtensorMap mOx, mWo, mH2, mW1, mAct, mW2;
    make_map(enc, &mOx, p_ox, HD, SEQ, 64, 128);
    make_map(enc, &mWo, Wo, DM, HD, 64, 64);
    make_map(enc, &mH2, p_h2, DM, SEQ, 64, 128);
    make_map(enc, &mW1, w1, FF, DM, 64, 64);
    make_map(enc, &mAct, p_act, FF, SEQ, 64, 128);
    make_map(enc, &mW2, w2, DM, FF, 64, 64);

    cudaStream_t st = cudaStreamPerThread;
    k_mod<<<60, 256, 0, st>>>(c, wmod);
    k_ln<0><<<SEQ / 8, 256, 0, st>>>(x);
    {
        cudaLaunchConfig_t cfg = {};
        cfg.gridDim = dim3(96); cfg.blockDim = dim3(512); cfg.dynamicSmemBytes = SM_TOTAL; cfg.stream = st;
        cudaLaunchAttribute at[1];
        at[0].id = cudaLaunchAttributeClusterDimension;
        at[0].val.clusterDim.x = 3; at[0].val.clusterDim.y = 1; at[0].val.clusterDim.z = 1;
        cfg.attrs = at; cfg.numAttrs = 1;
        cudaLaunchKernelEx(&cfg, k_rec, mem0, Wq, Wk, Wv, Wo);
    }
    k_gemm<0><<<dim3(5, 16), 384, G_SMEM, st>>>(mOx, mWo, HD, x, (bf16*)p_x1);
    k_ln<1><<<SEQ / 8, 256, 0, st>>>(nullptr);
    k_gemm<1><<<dim3(12, 16), 384, G_SMEM, st>>>(mH2, mW1, DM, nullptr, (bf16*)p_act);
    k_gemm<2><<<dim3(5, 16), 384, G_SMEM, st>>>(mAct, mW2, FF, (const bf16*)p_x1, out);
}
```

```cpp
#include <cuda_runtime.h>
#include <cuda_bf16.h>
#include <cuda.h>
#include <stdint.h>

typedef __nv_bfloat16 bf16;
#define VM_THROTTLE 1

constexpr int SEQ = 2048, DM = 640, NH = 32, DH = 192, NSEG = 64, FF = 1536, HD = NH * DH;

__device__ float g_mod[6 * DM];
__device__ __align__(1024) bf16 g_ht[(size_t)SEQ * DM];
__device__ __align__(1024) bf16 g_ox[(size_t)SEQ * HD];
__device__ __align__(1024) bf16 g_x1[(size_t)SEQ * DM];
__device__ __align__(1024) bf16 g_h2[(size_t)SEQ * DM];
__device__ __align__(1024) bf16 g_act[(size_t)SEQ * FF];
__device__ __align__(8192) uint32_t g_buf1[80 * 2 * 2048];
__device__ __align__(8192) uint32_t g_buf2[4 * 3 * 2048];
__device__ uint32_t g_choice[128];
__device__ uint32_t g_epoch;
#define TR(k)

#define FRESH(x) asm volatile("" : "+r"(x))
__device__ __forceinline__ float bfr(float x) { return __bfloat162float(__float2bfloat16_rn(x)); }
__device__ __forceinline__ uint32_t pack2(float a, float b) {
    uint32_t r; asm("cvt.rn.bf16x2.f32 %0, %1, %2;" : "=r"(r) : "f"(b), "f"(a)); return r;
}
__device__ __forceinline__ float bflo(uint32_t v) { return __uint_as_float(v << 16); }
__device__ __forceinline__ float bfhi(uint32_t v) { return __uint_as_float(v & 0xffff0000u); }
__device__ __forceinline__ float ex2(float x) { float r; asm("ex2.approx.ftz.f32 %0, %1;" : "=f"(r) : "f"(x)); return r; }
__device__ __forceinline__ float rcpf(float x) { float r; asm("rcp.approx.ftz.f32 %0, %1;" : "=f"(r) : "f"(x)); return r; }
__device__ __forceinline__ void score2(float& a, float& b) {
    const float SCALE = 0.07216878364870322f;
    uint32_t u = pack2(a, b);
    u = pack2(bflo(u) * SCALE, bfhi(u) * SCALE);
    a = bflo(u); b = bfhi(u);
}
__device__ __forceinline__ uint32_t smem_u32(const void* p) { return (uint32_t)__cvta_generic_to_shared(p); }

__device__ __forceinline__ void mbar_init(uint32_t bar, uint32_t cnt) {
    asm volatile("mbarrier.init.shared::cta.b64 [%0], %1;" :: "r"(bar), "r"(cnt) : "memory");
}
__device__ __forceinline__ void mbar_arrive(uint32_t bar) {
    asm volatile("mbarrier.arrive.shared::cta.b64 _, [%0];" :: "r"(bar) : "memory");
}
__device__ __forceinline__ void mbar_expect(uint32_t bar, uint32_t bytes) {
    asm volatile("mbarrier.arrive.expect_tx.shared::cta.b64 _, [%0], %1;" :: "r"(bar), "r"(bytes) : "memory");
}
__device__ __forceinline__ bool mbar_try(uint32_t bar, uint32_t parity) {
    uint32_t ok;
    asm volatile("{\n\t.reg .pred p;\n\tmbarrier.try_wait.parity.shared::cta.b64 p, [%1], %2;\n\tselp.u32 %0, 1, 0, p;\n\t}"
                 : "=r"(ok) : "r"(bar), "r"(parity) : "memory");
    return ok != 0;
}
__device__ __forceinline__ bool mbar_try_cluster(uint32_t bar, uint32_t parity) {
    uint32_t ok;
    asm volatile("{\n\t.reg .pred p;\n\tmbarrier.try_wait.parity.acquire.cluster.shared::cta.b64 p, [%1], %2;\n\tselp.u32 %0, 1, 0, p;\n\t}"
                 : "=r"(ok) : "r"(bar), "r"(parity) : "memory");
    return ok != 0;
}
__device__ __forceinline__ void mbar_wait(uint32_t bar, uint32_t parity) {
    uint32_t guard = 0;
    while (!mbar_try(bar, parity)) { if (++guard > (1u << 22)) __trap(); }
}
__device__ __forceinline__ void mbar_wait_cluster(uint32_t bar, uint32_t parity) {
    uint32_t guard = 0;
    while (!mbar_try_cluster(bar, parity)) { if (++guard > (1u << 22)) __trap(); }
}
__device__ __forceinline__ void bar_sync(int id, int n) { asm volatile("bar.sync %0, %1;" :: "r"(id), "r"(n) : "memory"); }
__device__ __forceinline__ void bar_arrive(int id, int n) { asm volatile("bar.arrive %0, %1;" :: "r"(id), "r"(n) : "memory"); }
__device__ __forceinline__ void sts1(uint32_t a, uint32_t v) { asm volatile("st.shared.u32 [%0], %1;" :: "r"(a), "r"(v) : "memory"); }
__device__ __forceinline__ uint32_t lds1(uint32_t a) { uint32_t v; asm volatile("ld.shared.u32 %0, [%1];" : "=r"(v) : "r"(a) : "memory"); return v; }
__device__ __forceinline__ void fence_async() { asm volatile("fence.proxy.async.shared::cta;" ::: "memory"); }
__device__ __forceinline__ void cluster_sync() {
    asm volatile("barrier.cluster.arrive.release.aligned;\n\tbarrier.cluster.wait.acquire.aligned;" ::: "memory");
}
__device__ __forceinline__ uint32_t mapa(uint32_t a, uint32_t rank) {
    uint32_t r; asm("mapa.shared::cluster.u32 %0, %1, %2;" : "=r"(r) : "r"(a), "r"(rank)); return r;
}
__device__ __forceinline__ void st_async1(uint32_t a, uint32_t v, uint32_t bar) {
    asm volatile("st.async.weak.shared::cluster.mbarrier::complete_tx::bytes.b32 [%0], %1, [%2];" :: "r"(a), "r"(v), "r"(bar) : "memory");
}
__device__ __forceinline__ void st_async2(uint32_t a, float x, float y, uint32_t bar) {
    asm volatile("st.async.weak.shared::cluster.mbarrier::complete_tx::bytes.v2.f32 [%0], {%1,%2}, [%3];" :: "r"(a), "f"(x), "f"(y), "r"(bar) : "memory");
}
__device__ __forceinline__ void st_async4(uint32_t a, const float* c, uint32_t bar) {
    asm volatile("st.async.weak.shared::cluster.mbarrier::complete_tx::bytes.v4.f32 [%0], {%1,%2,%3,%4}, [%5];"
                 :: "r"(a), "f"(c[0]), "f"(c[1]), "f"(c[2]), "f"(c[3]), "r"(bar) : "memory");
}
__device__ __forceinline__ void bulk_g2s(uint32_t dst, const void* src, uint32_t bytes, uint32_t bar) {
    asm volatile("cp.async.bulk.shared::cluster.global.mbarrier::complete_tx::bytes [%0], [%1], %2, [%3];"
                 :: "r"(dst), "l"(src), "r"(bytes), "r"(bar) : "memory");
}
__device__ __forceinline__ void cpa16(uint32_t s, const void* g) {
    asm volatile("cp.async.cg.shared.global [%0], [%1], 16;" :: "r"(s), "l"(g) : "memory");
}
__device__ __forceinline__ void cpa_wait_all() { asm volatile("cp.async.wait_all;" ::: "memory"); }
__device__ __forceinline__ void ldsm4(uint32_t* r, uint32_t a) {
    asm volatile("ldmatrix.sync.aligned.m8n8.x4.shared.b16 {%0,%1,%2,%3}, [%4];" : "=r"(r[0]), "=r"(r[1]), "=r"(r[2]), "=r"(r[3]) : "r"(a) : "memory");
}
__device__ __forceinline__ void ldsm4t(uint32_t* r, uint32_t a) {
    asm volatile("ldmatrix.sync.aligned.m8n8.x4.trans.shared.b16 {%0,%1,%2,%3}, [%4];" : "=r"(r[0]), "=r"(r[1]), "=r"(r[2]), "=r"(r[3]) : "r"(a) : "memory");
}
__device__ __forceinline__ void stsm2t(uint32_t a, uint32_t r0, uint32_t r1) {
    asm volatile("stmatrix.sync.aligned.m8n8.x2.trans.shared.b16 [%0], {%1,%2};" :: "r"(a), "r"(r0), "r"(r1) : "memory");
}
__device__ __forceinline__ void stsm4t(uint32_t a, uint32_t r0, uint32_t r1, uint32_t r2, uint32_t r3) {
    asm volatile("stmatrix.sync.aligned.m8n8.x4.trans.shared.b16 [%0], {%1,%2,%3,%4};" :: "r"(a), "r"(r0), "r"(r1), "r"(r2), "r"(r3) : "memory");
}
__device__ __forceinline__ uint32_t movm(uint32_t v) {
    uint32_t r; asm volatile("movmatrix.sync.aligned.m8n8.trans.b16 %0, %1;" : "=r"(r) : "r"(v)); return r;
}
__device__ __forceinline__ void mma16(float* c, uint32_t a0, uint32_t a1, uint32_t a2, uint32_t a3, uint32_t b0, uint32_t b1) {
    asm volatile("mma.sync.aligned.m16n8k16.row.col.f32.bf16.bf16.f32 {%0,%1,%2,%3}, {%4,%5,%6,%7}, {%8,%9}, {%0,%1,%2,%3};"
                 : "+f"(c[0]), "+f"(c[1]), "+f"(c[2]), "+f"(c[3]) : "r"(a0), "r"(a1), "r"(a2), "r"(a3), "r"(b0), "r"(b1));
}
__device__ __forceinline__ void mma8(float* c, uint32_t a0, uint32_t a1, uint32_t b0) {
    asm volatile("mma.sync.aligned.m16n8k8.row.col.f32.bf16.bf16.f32 {%0,%1,%2,%3}, {%4,%5}, {%6}, {%0,%1,%2,%3};"
                 : "+f"(c[0]), "+f"(c[1]), "+f"(c[2]), "+f"(c[3]) : "r"(a0), "r"(a1), "r"(b0));
}
__host__ __device__ constexpr uint64_t make_desc(uint32_t saddr, uint32_t lbo, uint32_t sbo, uint32_t layout) {
    return (uint64_t)((saddr & 0x3FFFF) >> 4) | ((uint64_t)(lbo >> 4) << 16) | ((uint64_t)(sbo >> 4) << 32) | ((uint64_t)layout << 62);
}
__device__ __forceinline__ void wg_fence() { asm volatile("wgmma.fence.sync.aligned;" ::: "memory"); }
__device__ __forceinline__ void wg_commit() { asm volatile("wgmma.commit_group.sync.aligned;" ::: "memory"); }
template <int N> __device__ __forceinline__ void wg_wait() { asm volatile("wgmma.wait_group.sync.aligned %0;" :: "n"(N) : "memory"); }

#define D16(C) C(d[0]), C(d[1]), C(d[2]), C(d[3]), C(d[4]), C(d[5]), C(d[6]), C(d[7]), \
               C(d[8]), C(d[9]), C(d[10]), C(d[11]), C(d[12]), C(d[13]), C(d[14]), C(d[15])
#define DREG16 "{%0,%1,%2,%3,%4,%5,%6,%7,%8,%9,%10,%11,%12,%13,%14,%15}"
__device__ __forceinline__ void wg_rs32(float* d, const uint32_t* a, uint64_t db, bool acc) {
    if (acc)
        asm volatile("wgmma.mma_async.sync.aligned.m64n32k16.f32.bf16.bf16 " DREG16 ", {%16,%17,%18,%19}, %20, 1, 1, 1, 0;"
            : D16("+f") : "r"(a[0]), "r"(a[1]), "r"(a[2]), "r"(a[3]), "l"(db));
    else
        asm volatile("wgmma.mma_async.sync.aligned.m64n32k16.f32.bf16.bf16 " DREG16 ", {%16,%17,%18,%19}, %20, 0, 1, 1, 0;"
            : D16("=f") : "r"(a[0]), "r"(a[1]), "r"(a[2]), "r"(a[3]), "l"(db));
}
__device__ __forceinline__ void wg_ss32(float* d, uint64_t da, uint64_t db, bool acc) {
    if (acc)
        asm volatile("wgmma.mma_async.sync.aligned.m64n32k16.f32.bf16.bf16 " DREG16 ", %16, %17, 1, 1, 1, 1, 0;"
            : D16("+f") : "l"(da), "l"(db));
    else
        asm volatile("wgmma.mma_async.sync.aligned.m64n32k16.f32.bf16.bf16 " DREG16 ", %16, %17, 0, 1, 1, 1, 0;"
            : D16("=f") : "l"(da), "l"(db));
}
__device__ __forceinline__ void wg_ss8(float* d, uint64_t da, uint64_t db, bool acc) {
    if (acc)
        asm volatile("wgmma.mma_async.sync.aligned.m64n8k16.f32.bf16.bf16 {%0,%1,%2,%3}, %4, %5, 1, 1, 1, 1, 1;"
            : "+f"(d[0]), "+f"(d[1]), "+f"(d[2]), "+f"(d[3]) : "l"(da), "l"(db));
    else
        asm volatile("wgmma.mma_async.sync.aligned.m64n8k16.f32.bf16.bf16 {%0,%1,%2,%3}, %4, %5, 0, 1, 1, 1, 1;"
            : "=f"(d[0]), "=f"(d[1]), "=f"(d[2]), "=f"(d[3]) : "l"(da), "l"(db));
}
template <int OFF> __device__ __forceinline__ void ldsm4t_i(uint32_t* r, uint32_t a) {
    asm volatile("ldmatrix.sync.aligned.m8n8.x4.trans.shared.b16 {%0,%1,%2,%3}, [%4+%5];"
                 : "=r"(r[0]), "=r"(r[1]), "=r"(r[2]), "=r"(r[3]) : "r"(a), "n"(OFF) : "memory");
}

__device__ __forceinline__ uint4 ld_relaxed4(const void* p) {
    uint4 v;
    asm volatile("ld.relaxed.gpu.global.v4.u32 {%0,%1,%2,%3}, [%4];" : "=r"(v.x), "=r"(v.y), "=r"(v.z), "=r"(v.w) : "l"(p) : "memory");
    return v;
}
__device__ __forceinline__ void st_relaxed2(void* p, uint32_t a, uint32_t b) {
    asm volatile("st.relaxed.gpu.global.v2.u32 [%0], {%1,%2};" :: "l"(p), "r"(a), "r"(b) : "memory");
}
__device__ __forceinline__ void st_relaxed2_off(void* base, uint32_t off, uint32_t a, uint32_t b) {
    asm volatile("{\n\t.reg .u64 ad;\n\tcvt.u64.u32 ad, %1;\n\tadd.u64 ad, ad, %0;\n\tst.relaxed.gpu.global.v2.u32 [ad], {%2,%3};\n\t}"
                 :: "l"(base), "r"(off), "r"(a), "r"(b) : "memory");
}
__device__ __forceinline__ void st_relaxed1(void* p, uint32_t a) {
    asm volatile("st.relaxed.gpu.global.u32 [%0], %1;" :: "l"(p), "r"(a) : "memory");
}
__device__ __forceinline__ uint32_t ld_acquire1(const uint32_t* p) {
    uint32_t v; asm volatile("ld.acquire.gpu.global.u32 %0, [%1];" : "=r"(v) : "l"(p) : "memory"); return v;
}
__device__ __forceinline__ void st_release1(uint32_t* p, uint32_t a) {
    asm volatile("st.release.gpu.global.u32 [%0], %1;" :: "l"(p), "r"(a) : "memory");
}
__device__ __forceinline__ uint4 lds4(uint32_t s) {
    uint4 v; asm volatile("ld.shared.v4.u32 {%0,%1,%2,%3}, [%4];" : "=r"(v.x), "=r"(v.y), "=r"(v.z), "=r"(v.w) : "r"(s) : "memory"); return v;
}
__device__ __forceinline__ void sts4(uint32_t s, const uint4& v) {
    asm volatile("st.shared.v4.u32 [%0], {%1,%2,%3,%4};" :: "r"(s), "r"(v.x), "r"(v.y), "r"(v.z), "r"(v.w) : "memory");
}
__device__ __forceinline__ float4 lds4f(uint32_t s) {
    float4 v; asm volatile("ld.shared.v4.f32 {%0,%1,%2,%3}, [%4];" : "=f"(v.x), "=f"(v.y), "=f"(v.z), "=f"(v.w) : "r"(s) : "memory"); return v;
}
__device__ __forceinline__ uint2 lds2(uint32_t s) {
    uint2 v; asm volatile("ld.shared.v2.u32 {%0,%1}, [%2];" : "=r"(v.x), "=r"(v.y) : "r"(s) : "memory"); return v;
}
__device__ __forceinline__ float2 lds2f(uint32_t s) {
    float2 v; asm volatile("ld.shared.v2.f32 {%0,%1}, [%2];" : "=f"(v.x), "=f"(v.y) : "r"(s) : "memory"); return v;
}
__device__ __forceinline__ uint32_t clk32() { uint32_t c; asm volatile("mov.u32 %0, %%clock;" : "=r"(c) :: "memory"); return c; }
__device__ __forceinline__ uint32_t tagw(float v, uint32_t tag) { return ((__float_as_uint(v) + 8u) & ~15u) | tag; }
__device__ __forceinline__ bool ok4(const uint4& v, uint32_t tag) { return (((v.x ^ tag) | (v.y ^ tag) | (v.z ^ tag) | (v.w ^ tag)) & 15u) == 0; }
__device__ __forceinline__ bool oks(const uint4& v) { return v.x != 0xFFFFFFFFu && v.y != 0xFFFFFFFFu && v.z != 0xFFFFFFFFu && v.w != 0xFFFFFFFFu; }
__device__ __forceinline__ float uf(uint32_t x) { return __uint_as_float(x & ~15u); }

__global__ void __launch_bounds__(256) k_mod(const bf16* __restrict__ c, const bf16* __restrict__ wmod) {
    __shared__ float sc[DM];
    __shared__ float red[8][64];
    const int tid = threadIdx.x;
    for (int i = tid; i < DM; i += 256) {
        float v = __bfloat162float(c[i]);
        sc[i] = bfr(v / (1.0f + __expf(-v)));
    }
    __syncthreads();
    const int cp = tid & 31, kg = tid >> 5;
    const int col = blockIdx.x * 64 + cp * 2;
    float a0 = 0.f, a1 = 0.f;
    #pragma unroll 8
    for (int k = kg * 80; k < kg * 80 + 80; k++) {
        uint32_t w = *(const uint32_t*)(wmod + (size_t)k * (6 * DM) + col);
        a0 += sc[k] * bflo(w); a1 += sc[k] * bfhi(w);
    }
    red[kg][cp * 2] = a0; red[kg][cp * 2 + 1] = a1;
    __syncthreads();
    if (tid < 64) {
        float s = 0.f;
        #pragma unroll
        for (int i = 0; i < 8; i++) s += red[i][tid];
        g_mod[blockIdx.x * 64 + tid] = bfr(s);
    }
    if (blockIdx.x == 0 && tid == 0) g_epoch = g_epoch + 1;
}

template <int MODE>
__global__ void __launch_bounds__(256) k_ln(const bf16* __restrict__ xin) {
    const int lane = threadIdx.x & 31, row = blockIdx.x * 8 + (threadIdx.x >> 5);
    const bf16* src = (MODE == 0 ? xin : g_x1) + (size_t)row * DM;
    const float* shift = g_mod + (MODE == 0 ? 0 : 3 * DM);
    const float* scale = g_mod + (MODE == 0 ? DM : 4 * DM);
    float v[3][8];
    float s = 0.f;
    #pragma unroll
    for (int i = 0; i < 3; i++) {
        int c = lane + 32 * i;
        if (c < 80) {
            uint4 u = *(const uint4*)(src + c * 8);
            v[i][0] = bflo(u.x); v[i][1] = bfhi(u.x); v[i][2] = bflo(u.y); v[i][3] = bfhi(u.y);
            v[i][4] = bflo(u.z); v[i][5] = bfhi(u.z); v[i][6] = bflo(u.w); v[i][7] = bfhi(u.w);
        } else {
            #pragma unroll
            for (int j = 0; j < 8; j++) v[i][j] = 0.f;
        }
        #pragma unroll
        for (int j = 0; j < 8; j++) s += v[i][j];
    }
    #pragma unroll
    for (int o = 16; o > 0; o >>= 1) s += __shfl_xor_sync(0xffffffffu, s, o);
    const float mean = s * (1.0f / DM);
    float q = 0.f;
    #pragma unroll
    for (int i = 0; i < 3; i++) {
        if (lane + 32 * i < 80) {
            #pragma unroll
            for (int j = 0; j < 8; j++) { float d = v[i][j] - mean; q += d * d; }
        }
    }
    #pragma unroll
    for (int o = 16; o > 0; o >>= 1) q += __shfl_xor_sync(0xffffffffu, q, o);
    const float mb = bfr(mean);
    const float var = bfr(q * (1.0f / DM));
    const float sd = bfr(sqrtf(bfr(var + 1e-5f)));
    #pragma unroll
    for (int i = 0; i < 3; i++) {
        int c = lane + 32 * i;
        if (c < 80) {
            float o[8];
            #pragma unroll
            for (int j = 0; j < 8; j++) {
                float n = bfr(bfr(v[i][j] - mb) / sd);
                float m1 = bfr(1.0f + scale[c * 8 + j]);
                o[j] = bfr(n * m1) + shift[c * 8 + j];
            }
            uint4 u = make_uint4(pack2(o[0], o[1]), pack2(o[2], o[3]), pack2(o[4], o[5]), pack2(o[6], o[7]));
            if (MODE == 0) {
                int seg = row >> 5, r = row & 31, blk = c >> 3, cc = c & 7;
                *(uint4*)(g_ht + (size_t)seg * 20480 + blk * 2048 + r * 64 + ((cc ^ (r & 7)) << 3)) = u;
            } else {
                *(uint4*)(g_h2 + (size_t)row * DM + c * 8) = u;
            }
        }
    }
}

constexpr int SM_WV = 0;
constexpr int SM_HB = 81920;
constexpr int SM_WO = SM_HB + 40960;
constexpr int SM_QX = SM_WO + 77824;
constexpr int SM_KS = SM_QX + 4096;
constexpr int SM_QM = SM_KS + 5120;
constexpr int SM_XS = SM_QM + 1024;
constexpr int SM_MS = SM_XS + 12288;
constexpr int SM_OS = SM_MS + 3840;
constexpr int SM_PM = SM_OS + 3072;
constexpr int SM_BAR = SM_PM + 640;
constexpr int SM_CH = SM_BAR + 128;
constexpr int SM_TOTAL = SM_CH + 128;
static_assert(SM_TOTAL <= 232448, "smem");

enum { B_MEM_FULL = 0, B_MEM_FREE, B_HLO_FULL, B_HHI_FULL, B_HLO_FREE, B_HHI_FREE, B_MS, B_O, B_XS, B_O1, B_XSFREE };

__device__ __forceinline__ int probe_blk(uint32_t* blk) {
    uint32_t t0 = 0xffffffffu, t1 = 0xffffffffu, acc = 0;
    for (int rep = 0; rep < 5; rep++) {
        #pragma unroll
        for (int pg = 0; pg < 2; pg++) {
            uint32_t c0 = clk32();
            uint32_t v = atomicOr(blk + pg * 1024 + acc, 0u);
            acc = (v == 0x12345678u) ? 1u : 0u;
            asm volatile("" :: "r"(acc) : "memory");
            uint32_t c1 = clk32() + acc;
            uint32_t d = c1 - c0;
            if (rep > 0) { if (pg == 0) t0 = min(t0, d); else t1 = min(t1, d); }
        }
    }
    return t1 < t0 ? 1 : 0;
}

__device__ __forceinline__ uint32_t wo_tile_off(int w) {
    if (w < 8) return w * 6144;
    if (w < 12) return 8 * 6144 + (w - 8) * 4096;
    return 8 * 6144 + 4 * 4096 + (w - 12) * 6144;
}

template <int NRES, int NPRE>
__device__ __forceinline__ void wo_phase(uint32_t sb, int w, int lane, const uint32_t (*res)[4], uint32_t parity,
                                         uint32_t tag, int tile, int h) {
    FRESH(lane);
    const int er = (lane & 7) + 8 * (lane >> 4);
    const uint32_t aaddr = sb + SM_WO + wo_tile_off(w) + er * 32 + ((((lane >> 3) & 1) ^ ((er >> 2) & 1)) << 4);
    const uint32_t baddr = sb + SM_OS + lane * 16;
    float c0[4] = {0.f, 0.f, 0.f, 0.f}, c1[4] = {0.f, 0.f, 0.f, 0.f};
    uint32_t pre[NPRE > 4 ? NPRE : 4][4];
    if (NPRE >= 4) {
        #pragma unroll
        for (int i = 0; i < 4; i++) ldsm4t(pre[i], aaddr + i * 512);
        mbar_wait(sb + SM_BAR + B_O1 * 8, parity);
        uint32_t b[2][4];
        ldsm4t(b[0], baddr);
        ldsm4t(b[1], baddr + 512);
        #pragma unroll
        for (int kp = 0; kp < 2; kp++) {
            mma16(c0, pre[2 * kp][0], pre[2 * kp][1], pre[2 * kp][2], pre[2 * kp][3], b[kp][0], b[kp][1]);
            mma16(c1, pre[2 * kp + 1][0], pre[2 * kp + 1][1], pre[2 * kp + 1][2], pre[2 * kp + 1][3], b[kp][2], b[kp][3]);
        }
    } else {
        #pragma unroll
        for (int i = 0; i < 2; i++) ldsm4t(pre[i], aaddr + i * 512);
        mbar_wait(sb + SM_BAR + B_O1 * 8, parity);
        #pragma unroll
        for (int kp = 0; kp < 2; kp++) {
            uint32_t b[4];
            ldsm4t(b, baddr + kp * 512);
            if (kp == 1) { ldsm4t(pre[0], aaddr + 2 * 512); ldsm4t(pre[1], aaddr + 3 * 512); }
            mma16(c0, pre[0][0], pre[0][1], pre[0][2], pre[0][3], b[0], b[1]);
            mma16(c1, pre[1][0], pre[1][1], pre[1][2], pre[1][3], b[2], b[3]);
        }
    }
    #pragma unroll
    for (int i = 0; i < NPRE; i++) ldsm4t(pre[i], aaddr + (4 + i) * 512);
    uint32_t off0, off1;
    {
        uint32_t ch;
        asm volatile("ld.shared.u16 %0, [%1];" : "=r"(ch) : "r"(sb + SM_CH + 2 * tile) : "memory");
        const int j = lane >> 4;
        const uint32_t base = (uint32_t)((tile * 4 + j) * 8192 + ((lane >> 2) & 3) * 1024 + h * 32 + (lane & 3) * 8);
        ch >>= j;
        off0 = base + (ch & 1) * 4096;
        off1 = base + 16384 + (ch & 256) * 16;
    }
    mbar_wait(sb + SM_BAR + B_O * 8, parity);
    if (NRES == 4) {
        uint32_t b[4][4];
        #pragma unroll
        for (int i = 0; i < 4; i++) ldsm4t(b[i], baddr + (2 + i) * 512);
        #pragma unroll
        for (int i = 0; i < 2; i++) {
            mma16(c0, res[2 * i][0], res[2 * i][1], res[2 * i][2], res[2 * i][3], b[i][0], b[i][1]);
            mma16(c1, res[2 * i + 1][0], res[2 * i + 1][1], res[2 * i + 1][2], res[2 * i + 1][3], b[i][2], b[i][3]);
        }
        #pragma unroll
        for (int i = 0; i < 2; i++) {
            mma16(c0, pre[2 * i][0], pre[2 * i][1], pre[2 * i][2], pre[2 * i][3], b[2 + i][0], b[2 + i][1]);
            mma16(c1, pre[2 * i + 1][0], pre[2 * i + 1][1], pre[2 * i + 1][2], pre[2 * i + 1][3], b[2 + i][2], b[2 + i][3]);
        }
    } else if (NPRE == 4) {
        uint32_t b[2][4];
        #pragma unroll
        for (int hh = 0; hh < 2; hh++) {
            ldsm4t(b[0], baddr + (2 + 2 * hh) * 512);
            ldsm4t(b[1], baddr + (3 + 2 * hh) * 512);
            if (hh) {
                #pragma unroll
                for (int i = 0; i < 4; i++) ldsm4t(pre[i], aaddr + (8 + i) * 512);
            }
            #pragma unroll
            for (int i = 0; i < 2; i++) {
                mma16(c0, pre[2 * i][0], pre[2 * i][1], pre[2 * i][2], pre[2 * i][3], b[i][0], b[i][1]);
                mma16(c1, pre[2 * i + 1][0], pre[2 * i + 1][1], pre[2 * i + 1][2], pre[2 * i + 1][3], b[i][2], b[i][3]);
            }
        }
    }
    st_relaxed2_off(g_buf1, off0, tagw(c0[0] + c1[0], tag), tagw(c0[1] + c1[1], tag));
    st_relaxed2_off(g_buf1, off1, tagw(c0[2] + c1[2], tag), tagw(c0[3] + c1[3], tag));
}

template <int NT, bool MASK>
__device__ __forceinline__ void softmax_core(float (*sc)[2], int g, int t, uint32_t* pb) {
    const float L2E = 1.4426950408889634f;
    #pragma unroll
    for (int j = 0; j < NT; j++) score2(sc[j][0], sc[j][1]);
    if (MASK) {
        const float NEG = -999292928.0f;
        if (2 * t > g) sc[NT - 1][0] = NEG;
        if (2 * t + 1 > g) sc[NT - 1][1] = NEG;
    }
    float m[NT];
    #pragma unroll
    for (int j = 0; j < NT; j++) m[j] = fmaxf(sc[j][0], sc[j][1]);
    float mx = m[0];
    #pragma unroll
    for (int j = 1; j < NT; j++) mx = fmaxf(mx, m[j]);
    mx = fmaxf(mx, __shfl_xor_sync(0xffffffffu, mx, 1));
    mx = fmaxf(mx, __shfl_xor_sync(0xffffffffu, mx, 2));
    float s0 = 0.f, s1 = 0.f;
    #pragma unroll
    for (int j = 0; j < NT; j++) {
        sc[j][0] = ex2((sc[j][0] - mx) * L2E); sc[j][1] = ex2((sc[j][1] - mx) * L2E);
        s0 += sc[j][0]; s1 += sc[j][1];
    }
    s0 += s1;
    s0 += __shfl_xor_sync(0xffffffffu, s0, 1);
    s0 += __shfl_xor_sync(0xffffffffu, s0, 2);
    const float iv = rcpf(s0);
    #pragma unroll
    for (int j = 0; j < NT; j++) pb[j] = pack2(sc[j][0] * iv, sc[j][1] * iv);
}
template <int NT>
__device__ __forceinline__ void xsoftmax(uint32_t a, uint32_t pa, int g, int t) {
    float sc[NT][2];
    #pragma unroll
    for (int j = 0; j < NT; j++) {
        float2 v0 = lds2f(a + j * 512), v1 = lds2f(a + j * 512 + 4096), v2 = lds2f(a + j * 512 + 8192);
        sc[j][0] = v0.x + v1.x + v2.x; sc[j][1] = v0.y + v1.y + v2.y;
    }
    uint32_t pb[NT];
    softmax_core<NT, true>(sc, g, t, pb);
    #pragma unroll
    for (int j = 0; j < NT; j++) sts1(pa + j * 256, pb[j]);
}
template <int NJ>
__device__ __forceinline__ void xscores(uint32_t sb, int p, int mi, int j0, int lane) {
    FRESH(lane);
    const int r = lane & 7, cq = lane >> 3;
    const int qrow = mi * 16 + r + 8 * (cq & 1);
    uint32_t kb[NJ][8];
    float d[NJ][4];
    #pragma unroll
    for (int j = 0; j < NJ; j++) {
        ldsm4(kb[j], sb + SM_KS + ((j0 + j) * 8 + r) * 128 + ((cq ^ r) << 4));
        ldsm4(kb[j] + 4, sb + SM_KS + ((j0 + j) * 8 + r) * 128 + (((cq + 4) ^ r) << 4));
        d[j][0] = 0.f; d[j][1] = 0.f; d[j][2] = 0.f; d[j][3] = 0.f;
    }
    #pragma unroll
    for (int kt = 0; kt < 4; kt++) {
        uint32_t a[4];
        ldsm4(a, sb + SM_QX + qrow * 128 + (((2 * kt + (cq >> 1)) ^ r) << 4));
        #pragma unroll
        for (int j = 0; j < NJ; j++) mma16(d[j], a[0], a[1], a[2], a[3], kb[j][2 * kt], kb[j][2 * kt + 1]);
    }
    const uint32_t la = sb + SM_XS + p * 4096 + (mi * 3 + j0) * 512 + lane * 16;
    #pragma unroll
    for (int rk = 0; rk < 3; rk++) {
        const uint32_t ra = mapa(la, rk), rb = mapa(sb + SM_BAR + B_XS * 8, rk);
        #pragma unroll
        for (int j = 0; j < NJ; j++) st_async4(ra + j * 512, d[j], rb);
    }
}
__device__ __forceinline__ void mbar_arrive_remote(uint32_t bar) {
    asm volatile("mbarrier.arrive.relaxed.cluster.shared::cluster.b64 _, [%0];" :: "r"(bar) : "memory");
}

__global__ void __launch_bounds__(512, 1)
k_rec(const bf16* __restrict__ mem0, const bf16* __restrict__ Wq, const bf16* __restrict__ Wk,
      const bf16* __restrict__ Wv, const bf16* __restrict__ Wo) {
    extern __shared__ __align__(1024) uint8_t smem_raw[];
    constexpr uint32_t SBC = 1024;
    const uint32_t sb = smem_u32(smem_raw);
    if ((sb & 0xFFFFFFu) != SBC) __trap();
    int lane = __shfl_sync(0xffffffffu, threadIdx.x & 31, threadIdx.x & 31);
    const int warp = __shfl_sync(0xffffffffu, threadIdx.x >> 5, 0), wg = warp >> 2;
    const int tid = warp * 32 + lane;
    const int b = blockIdx.x, h = b / 3, p = b % 3;
    const int g = lane >> 2, t = lane & 3;
    const int tile0 = p == 0 ? 0 : (p == 1 ? 14 : 27);
    const int ntile = p == 0 ? 14 : 13;
    const uint32_t bar = sb + SM_BAR;

    if (tid == 0) {
        mbar_init(bar + B_MEM_FULL * 8, 4);
        mbar_init(bar + B_MEM_FREE * 8, 12);
        mbar_init(bar + B_HLO_FULL * 8, 1);
        mbar_init(bar + B_HHI_FULL * 8, 1);
        mbar_init(bar + B_HLO_FREE * 8, 12);
        mbar_init(bar + B_HHI_FREE * 8, 12);
        mbar_init(bar + B_MS * 8, 1);
        mbar_init(bar + B_O * 8, 1);
        mbar_init(bar + B_XS * 8, 1);
        mbar_init(bar + B_O1 * 8, 4);
        mbar_init(bar + B_XSFREE * 8, 12);
        asm volatile("fence.mbarrier_init.release.cluster;" ::: "memory");
        mbar_expect(bar + B_MS * 8, 3840);
        mbar_expect(bar + B_O * 8, 2048);
        mbar_expect(bar + B_XS * 8, 12288);
        mbar_expect(bar + B_HLO_FULL * 8, 12288);
        bulk_g2s(sb + SM_HB, g_ht, 12288, sb + SM_BAR + B_HLO_FULL * 8);
        mbar_expect(bar + B_HHI_FULL * 8, 28672);
        bulk_g2s(sb + SM_HB + 12288, (const char*)g_ht + 12288, 28672, sb + SM_BAR + B_HHI_FULL * 8);
    }
    cluster_sync();

    if (wg < 2) {
        asm volatile("setmaxnreg.inc.sync.aligned.u32 200;");
        const int w = warp & 3;
        uint32_t wa[40][4];
        {
            const bf16* W = (wg == 0 ? Wq : Wk) + (size_t)h * DH + p * 64 + w * 16 + t * 4;
            #pragma unroll
            for (int kt = 0; kt < 40; kt++) {
                uint2 l1 = __ldg((const uint2*)(W + (size_t)(kt * 16 + g) * HD));
                uint2 l2 = __ldg((const uint2*)(W + (size_t)(kt * 16 + 8 + g) * HD));
                wa[kt][0] = l1.x; wa[kt][1] = l1.y; wa[kt][2] = l2.x; wa[kt][3] = l2.y;
            }
            #pragma unroll
            for (int kt = 0; kt < 40; kt++) {
                #pragma unroll
                for (int i = 0; i < 4; i++) wa[kt][i] = movm(wa[kt][i]);
            }
        }
        bar_sync(0, 512);
        const uint32_t dstx = sb + (wg == 0 ? SM_QX : SM_KS + 1024);

        for (int s = -1; s < NSEG; s++) {
            const uint32_t par = s & 1;
            FRESH(lane);
            const int g = lane >> 2, t = lane & 3, tid = warp * 32 + lane;
            if (s >= 0) {
                mbar_wait(bar + B_MEM_FULL * 8, par);
                TR(0);
                float c[4][4];
                #pragma unroll
                for (int i = 0; i < 4; i++) { c[i][0] = 0.f; c[i][1] = 0.f; c[i][2] = 0.f; c[i][3] = 0.f; }
                uint32_t maddr = sb + lane * 16;
                asm volatile("" : "+r"(maddr));
                #pragma unroll
                for (int kp = 0; kp < 20; kp++) {
                    uint32_t bb[4];
                    ldsm4t(bb, maddr + (SM_HB + kp * 512));
                    mma16(c[(kp & 1) * 2], wa[2 * kp][0], wa[2 * kp][1], wa[2 * kp][2], wa[2 * kp][3], bb[0], bb[1]);
                    mma16(c[(kp & 1) * 2 + 1], wa[2 * kp + 1][0], wa[2 * kp + 1][1], wa[2 * kp + 1][2], wa[2 * kp + 1][3], bb[2], bb[3]);
                }
                {
                    const int tok = lane & 7, ch = 2 * w + ((lane >> 3) & 1);
                    stsm2t(sb + (wg == 0 ? SM_QM : SM_KS) + tok * 128 + ((ch ^ tok) << 4),
                           pack2((c[0][0] + c[1][0]) + (c[2][0] + c[3][0]), (c[0][1] + c[1][1]) + (c[2][1] + c[3][1])),
                           pack2((c[0][2] + c[1][2]) + (c[2][2] + c[3][2]), (c[0][3] + c[1][3]) + (c[2][3] + c[3][3])));
                }
                __syncwarp();
                if (lane == 0) mbar_arrive(bar + B_MEM_FREE * 8);
                TR(1);
                bar_sync(1, 256);
                if (warp < 5) {
                    const int r = lane & 7, cq = lane >> 3;
                    uint32_t a[8], kb[8];
                    ldsm4(a, sb + SM_QM + r * 128 + ((cq ^ r) << 4));
                    ldsm4(kb, sb + SM_KS + (warp * 8 + r) * 128 + ((cq ^ r) << 4));
                    ldsm4(a + 4, sb + SM_QM + r * 128 + (((cq + 4) ^ r) << 4));
                    ldsm4(kb + 4, sb + SM_KS + (warp * 8 + r) * 128 + (((cq + 4) ^ r) << 4));
                    float d0[4] = {0.f, 0.f, 0.f, 0.f}, d1[4] = {0.f, 0.f, 0.f, 0.f};
                    mma16(d0, a[0], 0u, a[1], 0u, kb[0], kb[1]);
                    mma16(d1, a[2], 0u, a[3], 0u, kb[2], kb[3]);
                    mma16(d0, a[4], 0u, a[5], 0u, kb[4], kb[5]);
                    mma16(d1, a[6], 0u, a[7], 0u, kb[6], kb[7]);
                    const uint32_t la = sb + SM_MS + p * 1280 + warp * 256 + lane * 8;
                    #pragma unroll
                    for (int rk = 0; rk < 3; rk++)
                        st_async2(mapa(la, rk), d0[0] + d1[0], d0[1] + d1[1], mapa(bar + B_MS * 8, rk));
                    bar_arrive(4, 352);
                } else if (warp < 7) {
                    xscores<1>(sb, p, warp - 5, 0, lane);
                    bar_arrive(4, 352);
                }
                TR(2);
                if (wg == 1) {
                    mbar_wait(bar + B_XS * 8, par);
                    TR(8);
                    if (tid == 128) mbar_expect(bar + B_XS * 8, 12288);
                    const uint32_t a = sb + SM_XS + (w >> 1) * 1536 + lane * 16 + (w & 1) * 8;
                    const uint32_t pa = sb + SM_QX + (w >> 1) * 768 + lane * 8 + (w & 1) * 4;
                    if (w == 0) xsoftmax<2>(a, pa, g, t);
                    else if (w == 1) xsoftmax<3>(a, pa, g, t);
                    else if (w == 2) xsoftmax<4>(a, pa, g, t);
                    else xsoftmax<5>(a, pa, g, t);
                    bar_arrive(7, 256);
                    if (lane < 3) mbar_arrive_remote(mapa(bar + B_XSFREE * 8, lane));
                    TR(9);
                }
                if (s < NSEG - 1) {
                    wo_phase<0, 4>(sb, warp, lane, nullptr, par, (uint32_t)(s % 15) + 1u, tile0 + warp, h);
                    TR(4);
                    bar_arrive(6, 448);
                }
            }
            if (s < NSEG - 1) {
                FRESH(lane);
                const uint32_t hp = (s + 1) & 1;
                float d[16];
                const uint64_t db0 = make_desc(SBC + SM_HB, 16, 1024, 1);
                mbar_wait(bar + B_HHI_FULL * 8, hp);
                mbar_wait(bar + B_HLO_FULL * 8, hp);
                bar_sync(9, 384);
                TR(6);
                wg_fence();
                #pragma unroll
                for (int kt = 0; kt < 12; kt++) wg_rs32(d, wa[kt], db0 + (uint64_t)(((kt >> 2) * 4096 + (kt & 3) * 32) >> 4), kt > 0);
                wg_commit();
                #pragma unroll
                for (int kt = 12; kt < 39; kt++) wg_rs32(d, wa[kt], db0 + (uint64_t)(((kt >> 2) * 4096 + (kt & 3) * 32) >> 4), 1);
                wg_commit();
                wg_wait<1>();
                if (lane == 0) mbar_arrive(bar + B_HLO_FREE * 8);
                {
                    const int r = lane & 7, mq = lane >> 3;
                    const uint32_t ha = sb + SM_HB + 9 * 4096 + (8 * (mq >> 1) + r) * 128 + (((6 + (mq & 1)) ^ r) << 4);
                    uint32_t b0[4], b1[4];
                    ldsm4(b0, ha);
                    ldsm4(b1, ha + 2048);
                    wg_wait<0>();
                    mma16(d + 0, wa[39][0], wa[39][1], wa[39][2], wa[39][3], b0[0], b0[1]);
                    mma16(d + 4, wa[39][0], wa[39][1], wa[39][2], wa[39][3], b0[2], b0[3]);
                    mma16(d + 8, wa[39][0], wa[39][1], wa[39][2], wa[39][3], b1[0], b1[1]);
                    mma16(d + 12, wa[39][0], wa[39][1], wa[39][2], wa[39][3], b1[2], b1[3]);
                }
                __syncwarp();
                if (lane == 0) mbar_arrive(bar + B_HHI_FREE * 8);
                TR(7);
                const int mi = lane >> 3, r = lane & 7;
                #pragma unroll
                for (int jj = 0; jj < 2; jj++) {
                    const int tok = 8 * (2 * jj + (mi >> 1)) + r, ch = 2 * w + (mi & 1);
                    stsm4t(dstx + tok * 128 + ((ch ^ r) << 4),
                           pack2(d[8 * jj + 0], d[8 * jj + 1]), pack2(d[8 * jj + 2], d[8 * jj + 3]),
                           pack2(d[8 * jj + 4], d[8 * jj + 5]), pack2(d[8 * jj + 6], d[8 * jj + 7]));
                }
                bar_arrive(8, 384);
            }
        }
    } else if (wg == 2) {
        asm volatile("setmaxnreg.dec.sync.aligned.u32 64;");
        const int w = warp & 3;
        {
            const int c = tid & 7;
            const bf16* src = Wv + (size_t)h * DH + p * 64 + c * 8;
            for (int k = (tid & 127) >> 3; k < DM; k += 16)
                cpa16(sb + SM_WV + k * 128 + ((c ^ (k & 7)) << 4), src + (size_t)k * HD);
        }
        uint32_t res[4][4];
        {
            const bf16* src = Wo + ((size_t)h * DH + ((p + 1) % 3) * 64) * DM + (tile0 + warp) * 16 + 2 * t;
            #pragma unroll
            for (int kt = 0; kt < 4; kt++) {
                res[kt][0] = __ldg((const uint32_t*)(src + (size_t)(kt * 16 + g) * DM));
                res[kt][1] = __ldg((const uint32_t*)(src + (size_t)(kt * 16 + g) * DM + 8));
                res[kt][2] = __ldg((const uint32_t*)(src + (size_t)(kt * 16 + 8 + g) * DM));
                res[kt][3] = __ldg((const uint32_t*)(src + (size_t)(kt * 16 + 8 + g) * DM + 8));
            }
            #pragma unroll
            for (int kt = 0; kt < 4; kt++) {
                #pragma unroll
                for (int i = 0; i < 4; i++) res[kt][i] = movm(res[kt][i]);
            }
        }
        cpa_wait_all();
        fence_async();
        bar_sync(0, 512);
        const uint64_t da0 = make_desc(SBC + SM_WV, 16, 1024, 1);
        uint32_t vx[8];
        #pragma unroll
        for (int i = 0; i < 8; i++) vx[i] = 0;

        for (int s = -1; s < NSEG; s++) {
            FRESH(lane);
            const int g = lane >> 2, t = lane & 3, tid = warp * 32 + lane;
            if (s >= 0) {
                const uint32_t par = s & 1;
                mbar_wait(bar + B_MEM_FULL * 8, par);
                bar_sync(4, 352);
                TR(0);
                float dv[4];
                {
                    const uint64_t dbm = make_desc(SBC + SM_HB, 128, 128, 0);
                    wg_fence();
                    #pragma unroll
                    for (int kt = 0; kt < 40; kt++) {
                        wg_ss8(dv, da0 + (uint64_t)(kt * 128), dbm + (uint64_t)(kt * 16), kt > 0);
                        wg_commit();
                        if (kt < 39) wg_wait<1>();
                    }
                    wg_commit();
                }
                TR(1);
                bar_sync(5, 160);
                TR(2);
                uint32_t pb[5];
                #pragma unroll
                for (int j = 0; j < 5; j++) pb[j] = lds1(sb + SM_PM + j * 128 + lane * 4);
                float o0[4] = {0.f, 0.f, 0.f, 0.f}, o1[4] = {0.f, 0.f, 0.f, 0.f}, o2[4] = {0.f, 0.f, 0.f, 0.f};
                wg_wait<0>();
                TR(3);
                mma16(o0, vx[0], vx[1], vx[2], vx[3], pb[1], pb[2]);
                mma16(o1, vx[4], vx[5], vx[6], vx[7], pb[3], pb[4]);
                const uint32_t vm0 = pack2(dv[0], dv[1]), vm1 = pack2(dv[2], dv[3]);
                mma8(o2, vm0, vm1, pb[0]);
                if (s < NSEG - 1) {
                    const uint32_t q0 = pack2(o0[0] + o1[0] + o2[0], o0[1] + o1[1] + o2[1]), q1 = pack2(o0[2] + o1[2] + o2[2], o0[3] + o1[3] + o2[3]);
                    const uint32_t la = sb + SM_OS + (w * 16 + g) * 16 + t * 4;
                    #pragma unroll
                    for (int i = 1; i < 3; i++) {
                        const uint32_t rk = (p + i) % 3;
                        const uint32_t ra = mapa(la + (3 - i) * 1024, rk), rb = mapa(bar + B_O * 8, rk);
                        st_async1(ra, q0, rb);
                        st_async1(ra + 128, q1, rb);
                    }
                    sts1(la, q0);
                    sts1(la + 128, q1);
                    __syncwarp();
                    if (lane == 0) { mbar_arrive(bar + B_O1 * 8); mbar_arrive(bar + B_MEM_FREE * 8); }
                }
                TR(5);
                bar_sync(7, 256);
                TR(8);
                bf16* orow = g_ox + (size_t)(s * 32 + g) * HD + h * DH + p * 64 + w * 16 + 2 * t;
                {
                    uint2 pv[8];
                    #pragma unroll
                    for (int j = 0; j < 8; j++) pv[j] = lds2(sb + SM_QX + j * 256 + lane * 8);
                    float oa[4][4];
                    #pragma unroll
                    for (int i = 0; i < 4; i++) { oa[i][0] = 0.f; oa[i][1] = 0.f; oa[i][2] = 0.f; oa[i][3] = 0.f; }
                    mma8(oa[0], vm0, vm1, pv[0].x);
                    mma8(oa[1], vm0, vm1, pv[0].y);
                    mma8(oa[2], vm0, vm1, pv[3].x);
                    mma8(oa[3], vm0, vm1, pv[3].y);
                    mma16(oa[0], vx[0], vx[1], vx[2], vx[3], pv[1].x, 0u);
                    mma16(oa[1], vx[0], vx[1], vx[2], vx[3], pv[1].y, pv[2].y);
                    mma16(oa[2], vx[0], vx[1], vx[2], vx[3], pv[4].x, pv[5].x);
                    mma16(oa[3], vx[0], vx[1], vx[2], vx[3], pv[4].y, pv[5].y);
                    mma16(oa[2], vx[4], vx[5], vx[6], vx[7], pv[6].x, 0u);
                    mma16(oa[3], vx[4], vx[5], vx[6], vx[7], pv[6].y, pv[7].y);
                    uint32_t u[8];
                    #pragma unroll
                    for (int i = 0; i < 4; i++) { u[2 * i] = movm(pack2(oa[i][0], oa[i][1])); u[2 * i + 1] = movm(pack2(oa[i][2], oa[i][3])); }
                    #pragma unroll
                    for (int i = 0; i < 4; i++) {
                        *(uint32_t*)(orow + (size_t)(8 * i) * HD) = u[2 * i];
                        *(uint32_t*)(orow + (size_t)(8 * i) * HD + 8) = u[2 * i + 1];
                    }
                }
                TR(9);
                if (s == NSEG - 1) break;
                wo_phase<4, 4>(sb, warp, lane, res, par, (uint32_t)(s % 15) + 1u, tile0 + warp, h);
                TR(4);
                if (tid == 256) mbar_expect(bar + B_O * 8, 2048);
                bar_sync(6, 448);
            }
            float d[16];
            const uint32_t hp = (s + 1) & 1;
            const uint64_t db0 = make_desc(SBC + SM_HB, 16, 1024, 1);
            mbar_wait(bar + B_HHI_FULL * 8, hp);
            mbar_wait(bar + B_HLO_FULL * 8, hp);
            TR(6);
            wg_fence();
            #pragma unroll
            for (int kt = 0; kt < 36; kt++) wg_ss32(d, da0 + (uint64_t)(kt * 128), db0 + (uint64_t)(((kt >> 2) * 4096 + (kt & 3) * 32) >> 4), kt > 0);
            wg_commit();
            #pragma unroll
            for (int kt = 36; kt < 40; kt++) wg_ss32(d, da0 + (uint64_t)(kt * 128), db0 + (uint64_t)(((kt >> 2) * 4096 + (kt & 3) * 32) >> 4), 1);
            wg_commit();
            wg_wait<1>();
            bar_arrive(9, 384);
            if (lane == 0) mbar_arrive(bar + B_HLO_FREE * 8);
            wg_wait<0>();
            TR(7);
            if (lane == 0) mbar_arrive(bar + B_HHI_FREE * 8);
            #pragma unroll
            for (int i = 0; i < 8; i++) vx[i] = pack2(d[2 * i], d[2 * i + 1]);
            if (s >= 0) mbar_wait_cluster(bar + B_XSFREE * 8, s & 1);
            bar_sync(8, 384);
            TR(10);
            if (w < 3) xscores<2>(sb, p, w > 0, w == 2 ? 3 : 1, lane);
            TR(11);
        }
    } else {
        asm volatile("setmaxnreg.dec.sync.aligned.u32 48;");
        const int w = warp & 3, lt = tid & 127;
        {
            const bf16* src0 = Wo + (size_t)h * DH * DM + tile0 * 16;
            const int nch = 2 * ntile;
            for (int i = lt; i < DH * nch; i += 128) {
                const int e = i / nch, c = i - e * nch, tl = c >> 1, cc = c & 1;
                int es = e;
                if (tl >= 8 && tl < 12) { if (e >= 64 && e < 128) continue; if (e >= 128) es = e - 64; }
                int eg = e + p * 64; if (eg >= DH) eg -= DH;
                cpa16(sb + SM_WO + wo_tile_off(tl) + es * 32 + ((cc ^ ((e >> 2) & 1)) << 4), src0 + (size_t)eg * DM + c * 8);
            }
        }
        const uint32_t epoch = *(volatile uint32_t*)&g_epoch;
        if (b < 80) {
            #pragma unroll
            for (int i = 0; i < 2; i++) {
                const int idx = lt + i * 128, sl = idx >> 6, pg = (idx >> 5) & 1, wd = idx & 31;
                st_relaxed1(g_buf2 + (sl * 3 + (b >> 5)) * 2048 + pg * 1024 + (b & 31) * 32 + wd, 0xFFFFFFFFu);
            }
            __threadfence();
        }
        if (lane == 0) {
            for (int i = w; i < 14; i += 4) {
                int c = 0;
                if (i < 12) c = probe_blk(g_buf2 + i * 2048 + 640 + (b & 31) * 8);
                else if (b < 80) c = probe_blk(g_buf1 + (b * 2 + (i - 12)) * 2048);
                asm volatile("st.shared.u8 [%0], %1;" :: "r"(sb + SM_CH + 96 + i), "r"(c) : "memory");
            }
        }
        bar_sync(3, 128);
        uint32_t selmask = 0;
        for (int i = 0; i < 14; i++) {
            uint32_t c; asm volatile("ld.shared.u8 %0, [%1];" : "=r"(c) : "r"(sb + SM_CH + 96 + i) : "memory");
            selmask |= c << i;
        }
        if (lt == 0 && b < 80) st_release1(&g_choice[b], (epoch << 2) | (selmask >> 12));
        if (lt < 80) {
            uint32_t v, guard = 0;
            do { v = ld_acquire1(&g_choice[lt]); if (++guard > (1u << 22)) __trap(); } while ((v >> 2) != (epoch & 0x3fffffffu));
            asm volatile("st.shared.u8 [%0], %1;" :: "r"(sb + SM_CH + lt), "r"(v & 3u) : "memory");
        }
        cpa_wait_all();
        bar_sync(0, 512);
        const bool has_tile = (12 + w) < ntile;
        for (int s = 0; s < NSEG; s++) {
            const uint32_t par = s & 1;
            FRESH(lane);
            const int g = lane >> 2, t = lane & 3, lt = w * 32 + lane;
            if (s == 0) {
                mbar_wait(bar + B_HLO_FREE * 8, par);
                for (int k = lt; k < DM; k += 128) {
                    uint32_t v[4];
                    #pragma unroll
                    for (int i = 0; i < 4; i++) {
                        uint32_t lo = *(const uint16_t*)(mem0 + (2 * i) * DM + k), hi = *(const uint16_t*)(mem0 + (2 * i + 1) * DM + k);
                        v[i] = lo | (hi << 16);
                    }
                    asm volatile("st.shared.v4.u32 [%0], {%1,%2,%3,%4};" :: "r"(sb + SM_HB + k * 16), "r"(v[0]), "r"(v[1]), "r"(v[2]), "r"(v[3]) : "memory");
                }
            } else {
                const int sl = s & 3;
                const char* q = (const char*)g_buf2 + sl * 3 * 8192 + lt * 16;
                const uint32_t sm = selmask >> (sl * 3);
                const char* q0 = q + (sm & 1) * 4096;
                const char* q1 = q + 8192 + (sm & 2) * 2048;
                const char* q2 = q + 16384 + (sm & 4) * 1024;
                const uint32_t dst = sb + SM_HB + lt * 16;
                uint32_t guard = 0;
                mbar_wait(bar + B_HLO_FREE * 8, par);
                TR(10);
                while (true) {
                    const uint4 v0 = ld_relaxed4(q0), v1 = ld_relaxed4(q0 + 2048), v2 = ld_relaxed4(q1), v3 = ld_relaxed4(q1 + 2048), v4 = ld_relaxed4(q2);
                    sts4(dst, v0); sts4(dst + 2048, v1); sts4(dst + 4096, v2); sts4(dst + 6144, v3); sts4(dst + 8192, v4);
                    if (__all_sync(0xffffffffu, oks(v0) && oks(v1) && oks(v2) && oks(v3) && oks(v4))) break;
                    if (++guard > (1u << 22)) __trap();
                }
            }
            fence_async();
            __syncwarp();
            if (lane == 0) mbar_arrive(bar + B_MEM_FULL * 8);
            TR(0);
            if (w == 2) {
                mbar_wait(bar + B_MS * 8, par);
                TR(1);
                if (lane == 0) mbar_expect(bar + B_MS * 8, 3840);
                uint32_t pb[5];
                float sc[5][2];
                {
                    const uint32_t a = sb + SM_MS + lane * 8;
                    float2 u[5], v[5];
                    #pragma unroll
                    for (int j = 0; j < 5; j++) { u[j] = lds2f(a + j * 256); v[j] = lds2f(a + j * 256 + 1280); }
                    #pragma unroll
                    for (int j = 0; j < 5; j++) { sc[j][0] = u[j].x + v[j].x; sc[j][1] = u[j].y + v[j].y; }
                    #pragma unroll
                    for (int j = 0; j < 5; j++) u[j] = lds2f(a + j * 256 + 2560);
                    #pragma unroll
                    for (int j = 0; j < 5; j++) { sc[j][0] += u[j].x; sc[j][1] += u[j].y; }
                }
                softmax_core<5, false>(sc, g, t, pb);
                #pragma unroll
                for (int j = 0; j < 5; j++) sts1(sb + SM_PM + j * 128 + lane * 4, pb[j]);
                bar_arrive(5, 160);
                TR(2);
            }
            if (s < NSEG - 1) {
                if (w == 3) {
                    if (lane == 0) {
                        const char* src = (const char*)g_ht + (size_t)(s + 1) * 40960;
                        mbar_wait(bar + B_HHI_FREE * 8, par);
                        mbar_expect(bar + B_HHI_FULL * 8, 28672);
                        bulk_g2s(sb + SM_HB + 12288, src + 12288, 28672, sb + SM_BAR + B_HHI_FULL * 8);
                        mbar_wait(bar + B_MEM_FREE * 8, par);
                        mbar_expect(bar + B_HLO_FULL * 8, 12288);
                        bulk_g2s(sb + SM_HB, src, 12288, sb + SM_BAR + B_HLO_FULL * 8);
                    }
                    __syncwarp();
                }
                const uint32_t tag = (uint32_t)(s % 15) + 1u;
                if (has_tile) wo_phase<0, 4>(sb, warp, lane, nullptr, par, tag, tile0 + warp, h);
                else mbar_wait(bar + B_O * 8, par);
                if (w < 2) bar_arrive(6, 448);
                TR(4);
                if (b < 80) {
                    FRESH(lane);
                    const char* rin = (const char*)g_buf1 + (size_t)(b * 2 + (w >> 1)) * 8192 + ((selmask >> (12 + (w >> 1))) & 1) * 4096 + (w & 1) * 2048 + lane * 16;
                    const int col = b * 8 + 2 * w + (lane >> 4), wd = 2 * (lane & 1) + ((lane >> 3) & 1);
                    const int sl = (lane & 4) ? ((s + 3) & 3) : ((s + 1) & 3);
                    uint32_t* dst = g_buf2 + (sl * 3 + (col >> 8)) * 2048 + ((lane >> 1) & 1) * 1024 + (col & 255) * 4 + wd;
                    asm volatile("" : "+l"(dst));
                    uint4 v0, v1, v2, v3;
                    uint32_t guard = 0;
                    while (true) {
                        v0 = ld_relaxed4(rin); v1 = ld_relaxed4(rin + 512);
                        v2 = ld_relaxed4(rin + 1024); v3 = ld_relaxed4(rin + 1536);
                        if (__all_sync(0xffffffffu, ok4(v0, tag) && ok4(v1, tag) && ok4(v2, tag) && ok4(v3, tag))) break;
                        if (++guard > (1u << 22)) __trap();
                    }
                    TR(11);
                    float a0 = uf(v0.x) + uf(v1.x), a1 = uf(v0.y) + uf(v1.y), a2 = uf(v0.z) + uf(v1.z), a3 = uf(v0.w) + uf(v1.w);
                    float b0 = uf(v2.x) + uf(v3.x), b1 = uf(v2.y) + uf(v3.y), b2 = uf(v2.z) + uf(v3.z), b3 = uf(v2.w) + uf(v3.w);
                    const bool u16 = lane & 16;
                    float k0 = (u16 ? b0 : a0) + __shfl_xor_sync(0xffffffffu, u16 ? a0 : b0, 16);
                    float k1 = (u16 ? b1 : a1) + __shfl_xor_sync(0xffffffffu, u16 ? a1 : b1, 16);
                    float k2 = (u16 ? b2 : a2) + __shfl_xor_sync(0xffffffffu, u16 ? a2 : b2, 16);
                    float k3 = (u16 ? b3 : a3) + __shfl_xor_sync(0xffffffffu, u16 ? a3 : b3, 16);
                    const bool u8 = lane & 8;
                    float m0 = (u8 ? k2 : k0) + __shfl_xor_sync(0xffffffffu, u8 ? k0 : k2, 8);
                    float m1 = (u8 ? k3 : k1) + __shfl_xor_sync(0xffffffffu, u8 ? k1 : k3, 8);
                    m0 += __shfl_xor_sync(0xffffffffu, m0, 4); m1 += __shfl_xor_sync(0xffffffffu, m1, 4);
                    m0 += __shfl_xor_sync(0xffffffffu, m0, 2); m1 += __shfl_xor_sync(0xffffffffu, m1, 2);
                    st_relaxed1(dst, (lane & 4) ? 0xFFFFFFFFu : pack2(m0, m1));
                    TR(12);
                }
            }
        }
    }
    cluster_sync();
}

constexpr int G_STAGES = 5;
constexpr int G_STAGE_BYTES = 32768;
constexpr int G_SMEM = G_STAGES * G_STAGE_BYTES + 1024 + 256;

__device__ __forceinline__ void tma2d(uint32_t dst, const CUtensorMap* map, int c0, int c1, uint32_t bar) {
    asm volatile("cp.async.bulk.tensor.2d.shared::cluster.global.mbarrier::complete_tx::bytes [%0], [%1, {%2, %3}], [%4];"
                 :: "r"(dst), "l"(map), "r"(c0), "r"(c1), "r"(bar) : "memory");
}
__device__ __forceinline__ void wg_ss128(float* d, uint64_t da, uint64_t db, int sc) {
    asm volatile("{\n\t.reg .pred p;\n\tsetp.ne.b32 p, %66, 0;\n\t"
        "wgmma.mma_async.sync.aligned.m64n128k16.f32.bf16.bf16 "
        "{%0,%1,%2,%3,%4,%5,%6,%7,%8,%9,%10,%11,%12,%13,%14,%15,%16,%17,%18,%19,%20,%21,%22,%23,%24,%25,%26,%27,%28,%29,%30,%31,"
        "%32,%33,%34,%35,%36,%37,%38,%39,%40,%41,%42,%43,%44,%45,%46,%47,%48,%49,%50,%51,%52,%53,%54,%55,%56,%57,%58,%59,%60,%61,%62,%63}, "
        "%64, %65, p, 1, 1, 0, 1;\n\t}"
        : "+f"(d[0]), "+f"(d[1]), "+f"(d[2]), "+f"(d[3]), "+f"(d[4]), "+f"(d[5]), "+f"(d[6]), "+f"(d[7]),
          "+f"(d[8]), "+f"(d[9]), "+f"(d[10]), "+f"(d[11]), "+f"(d[12]), "+f"(d[13]), "+f"(d[14]), "+f"(d[15]),
          "+f"(d[16]), "+f"(d[17]), "+f"(d[18]), "+f"(d[19]), "+f"(d[20]), "+f"(d[21]), "+f"(d[22]), "+f"(d[23]),
          "+f"(d[24]), "+f"(d[25]), "+f"(d[26]), "+f"(d[27]), "+f"(d[28]), "+f"(d[29]), "+f"(d[30]), "+f"(d[31]),
          "+f"(d[32]), "+f"(d[33]), "+f"(d[34]), "+f"(d[35]), "+f"(d[36]), "+f"(d[37]), "+f"(d[38]), "+f"(d[39]),
          "+f"(d[40]), "+f"(d[41]), "+f"(d[42]), "+f"(d[43]), "+f"(d[44]), "+f"(d[45]), "+f"(d[46]), "+f"(d[47]),
          "+f"(d[48]), "+f"(d[49]), "+f"(d[50]), "+f"(d[51]), "+f"(d[52]), "+f"(d[53]), "+f"(d[54]), "+f"(d[55]),
          "+f"(d[56]), "+f"(d[57]), "+f"(d[58]), "+f"(d[59]), "+f"(d[60]), "+f"(d[61]), "+f"(d[62]), "+f"(d[63])
        : "l"(da), "l"(db), "r"(sc));
}

template <int EPI>
__global__ void __launch_bounds__(384, 1)
k_gemm(const __grid_constant__ CUtensorMap mapA, const __grid_constant__ CUtensorMap mapB, int K,
       const bf16* __restrict__ xin, bf16* __restrict__ outp) {
    extern __shared__ uint8_t smem_raw[];
    const uint32_t sb = (smem_u32(smem_raw) + 1023u) & ~1023u;
    const uint32_t bars = sb + G_STAGES * G_STAGE_BYTES;
    const int tid = threadIdx.x, lane = tid & 31, wg = tid >> 7;
    const int n0 = blockIdx.x * 128, m0 = blockIdx.y * 128;
    const int nk = K / 64;
    if (tid == 0) {
        for (int i = 0; i < G_STAGES; i++) { mbar_init(bars + i * 8, 1); mbar_init(bars + 64 + i * 8, 8); }
        asm volatile("fence.mbarrier_init.release.cluster;" ::: "memory");
    }
    __syncthreads();
    if (wg == 0) {
        if (tid == 0) {
            for (int kb = 0; kb < nk; kb++) {
                const int st = kb % G_STAGES;
                if (kb >= G_STAGES) mbar_wait(bars + 64 + st * 8, ((kb / G_STAGES) - 1) & 1);
                const uint32_t a = sb + st * G_STAGE_BYTES;
                mbar_expect(bars + st * 8, G_STAGE_BYTES);
                tma2d(a, &mapA, kb * 64, m0, bars + st * 8);
                tma2d(a + 16384, &mapB, n0, kb * 64, bars + st * 8);
                tma2d(a + 16384 + 8192, &mapB, n0 + 64, kb * 64, bars + st * 8);
            }
        }
    } else {
        float d[64];
        #pragma unroll
        for (int i = 0; i < 64; i++) d[i] = 0.f;
        const int cw = wg - 1;
        for (int kb = 0; kb < nk; kb++) {
            const int st = kb % G_STAGES;
            mbar_wait(bars + st * 8, (kb / G_STAGES) & 1);
            const uint32_t a = sb + st * G_STAGE_BYTES;
            const uint64_t da = make_desc(a + cw * 8192, 16, 1024, 1);
            const uint64_t db = make_desc(a + 16384, 8192, 1024, 1);
            wg_fence();
            #pragma unroll
            for (int k = 0; k < 4; k++) wg_ss128(d, da + (uint64_t)(k * 2), db + (uint64_t)(k * 128), 1);
            wg_commit();
            if (kb > 0) {
                wg_wait<1>();
                if (lane == 0) mbar_arrive(bars + 64 + ((kb - 1) % G_STAGES) * 8);
            }
        }
        wg_wait<0>();
        const int g = lane >> 2, t = lane & 3, w = (tid >> 5) & 3;
        const int ldo = EPI == 1 ? FF : DM;
        #pragma unroll
        for (int hf = 0; hf < 2; hf++) {
            const int row = m0 + cw * 64 + w * 16 + g + 8 * hf;
            #pragma unroll
            for (int j = 0; j < 16; j++) {
                const int col = n0 + j * 8 + 2 * t;
                float a0 = bfr(d[4 * j + 2 * hf]), a1 = bfr(d[4 * j + 2 * hf + 1]);
                uint32_t o;
                if (EPI == 1) {
                    o = pack2(a0 / (1.0f + __expf(-a0)), a1 / (1.0f + __expf(-a1)));
                } else {
                    const float2 gm = *(const float2*)(g_mod + (EPI == 0 ? 2 : 5) * DM + col);
                    const uint32_t xv = *(const uint32_t*)(xin + (size_t)row * DM + col);
                    o = pack2(bflo(xv) + bfr(gm.x * a0), bfhi(xv) + bfr(gm.y * a1));
                }
                *(uint32_t*)(outp + (size_t)row * ldo + col) = o;
            }
        }
    }
}

typedef CUresult (*EncodeFn)(CUtensorMap*, CUtensorMapDataType, cuuint32_t, void*, const cuuint64_t*, const cuuint64_t*,
                             const cuuint32_t*, const cuuint32_t*, CUtensorMapInterleave, CUtensorMapSwizzle,
                             CUtensorMapL2promotion, CUtensorMapFloatOOBfill);

static void make_map(EncodeFn fn, CUtensorMap* m, const void* ptr, uint64_t inner, uint64_t outer, uint32_t bi, uint32_t bo) {
    cuuint64_t dims[2] = {inner, outer};
    cuuint64_t strides[1] = {inner * 2};
    cuuint32_t box[2] = {bi, bo};
    cuuint32_t es[2] = {1, 1};
    fn(m, CU_TENSOR_MAP_DATA_TYPE_BFLOAT16, 2, (void*)ptr, dims, strides, box, es, CU_TENSOR_MAP_INTERLEAVE_NONE,
       CU_TENSOR_MAP_SWIZZLE_128B, CU_TENSOR_MAP_L2_PROMOTION_L2_256B, CU_TENSOR_MAP_FLOAT_OOB_FILL_NONE);
}

extern "C" void kernel_launch(void* const* d_in, const int* in_sizes, int n_in, void* d_out, int out_size) {
    const bf16* x = (const bf16*)d_in[0];
    const bf16* mem0 = (const bf16*)d_in[1];
    const bf16* Wq = (const bf16*)d_in[2];
    const bf16* Wk = (const bf16*)d_in[3];
    const bf16* Wv = (const bf16*)d_in[4];
    const bf16* Wo = (const bf16*)d_in[5];
    const bf16* w1 = (const bf16*)d_in[8];
    const bf16* w2 = (const bf16*)d_in[9];
    const bf16* c = (const bf16*)d_in[10];
    const bf16* wmod = (const bf16*)d_in[11];
    bf16* out = (bf16*)d_out;

    static EncodeFn enc = nullptr;
    static void *p_ox, *p_x1, *p_h2, *p_act;
    if (!enc) {
        cudaDriverEntryPointQueryResult qr;
        void* f = nullptr;
        cudaGetDriverEntryPoint("cuTensorMapEncodeTiled", &f, cudaEnableDefault, &qr);
        enc = (EncodeFn)f;
        cudaGetSymbolAddress(&p_ox, g_ox);
        cudaGetSymbolAddress(&p_x1, g_x1);
        cudaGetSymbolAddress(&p_h2, g_h2);
        cudaGetSymbolAddress(&p_act, g_act);
        cudaFuncSetAttribute(k_rec, cudaFuncAttributeMaxDynamicSharedMemorySize, SM_TOTAL);
        cudaFuncSetAttribute(k_gemm<0>, cudaFuncAttributeMaxDynamicSharedMemorySize, G_SMEM);
        cudaFuncSetAttribute(k_gemm<1>, cudaFuncAttributeMaxDynamicSharedMemorySize, G_SMEM);
        cudaFuncSetAttribute(k_gemm<2>, cudaFuncAttributeMaxDynamicSharedMemorySize, G_SMEM);
    }
    CUtensorMap mOx, mWo, mH2, mW1, mAct, mW2;
    make_map(enc, &mOx, p_ox, HD, SEQ, 64, 128);
    make_map(enc, &mWo, Wo, DM, HD, 64, 64);
    make_map(enc, &mH2, p_h2, DM, SEQ, 64, 128);
    make_map(enc, &mW1, w1, FF, DM, 64, 64);
    make_map(enc, &mAct, p_act, FF, SEQ, 64, 128);
    make_map(enc, &mW2, w2, DM, FF, 64, 64);

    cudaStream_t st = cudaStreamPerThread;
    k_mod<<<60, 256, 0, st>>>(c, wmod);
    k_ln<0><<<SEQ / 8, 256, 0, st>>>(x);
    {
        cudaLaunchConfig_t cfg = {};
        cfg.gridDim = dim3(96); cfg.blockDim = dim3(512); cfg.dynamicSmemBytes = SM_TOTAL; cfg.stream = st;
        cudaLaunchAttribute at[1];
        at[0].id = cudaLaunchAttributeClusterDimension;
        at[0].val.clusterDim.x = 3; at[0].val.clusterDim.y = 1; at[0].val.clusterDim.z = 1;
        cfg.attrs = at; cfg.numAttrs = 1;
        cudaLaunchKernelEx(&cfg, k_rec, mem0, Wq, Wk, Wv, Wo);
    }
    k_gemm<0><<<dim3(5, 16), 384, G_SMEM, st>>>(mOx, mWo, HD, x, (bf16*)p_x1);
    k_ln<1><<<SEQ / 8, 256, 0, st>>>(nullptr);
    k_gemm<1><<<dim3(12, 16), 384, G_SMEM, st>>>(mH2, mW1, DM, nullptr, (bf16*)p_act);
    k_gemm<2><<<dim3(5, 16), 384, G_SMEM, st>>>(mAct, mW2, FF, (const bf16*)p_x1, out);
}
```

```cpp
#include <cuda_runtime.h>
#include <cuda_bf16.h>
#include <cuda.h>
#include <stdint.h>

typedef __nv_bfloat16 bf16;
#define VX_THROTTLE 1
#define VM_THROTTLE 1

constexpr int SEQ = 2048, DM = 640, NH = 32, DH = 192, NSEG = 64, FF = 1536, HD = NH * DH;

__device__ float g_mod[6 * DM];
__device__ __align__(1024) bf16 g_ht[(size_t)SEQ * DM];
__device__ __align__(1024) bf16 g_ox[(size_t)SEQ * HD];
__device__ __align__(1024) bf16 g_x1[(size_t)SEQ * DM];
__device__ __align__(1024) bf16 g_h2[(size_t)SEQ * DM];
__device__ __align__(1024) bf16 g_act[(size_t)SEQ * FF];
__device__ __align__(8192) uint32_t g_buf1[80 * 2 * 2048];
__device__ __align__(8192) uint32_t g_buf2[4 * 3 * 2048];
__device__ uint32_t g_choice[128];
__device__ uint32_t g_epoch;
#define TR(k)

#define FRESH(x) asm volatile("" : "+r"(x))
__device__ __forceinline__ float bfr(float x) { return __bfloat162float(__float2bfloat16_rn(x)); }
__device__ __forceinline__ uint32_t pack2(float a, float b) {
    uint32_t r; asm("cvt.rn.bf16x2.f32 %0, %1, %2;" : "=r"(r) : "f"(b), "f"(a)); return r;
}
__device__ __forceinline__ float bflo(uint32_t v) { return __uint_as_float(v << 16); }
__device__ __forceinline__ float bfhi(uint32_t v) { return __uint_as_float(v & 0xffff0000u); }
__device__ __forceinline__ float ex2(float x) { float r; asm("ex2.approx.ftz.f32 %0, %1;" : "=f"(r) : "f"(x)); return r; }
__device__ __forceinline__ float rcpf(float x) { float r; asm("rcp.approx.ftz.f32 %0, %1;" : "=f"(r) : "f"(x)); return r; }
__device__ __forceinline__ void score2(float& a, float& b) {
    const float SCALE = 0.07216878364870322f;
    uint32_t u = pack2(a, b);
    u = pack2(bflo(u) * SCALE, bfhi(u) * SCALE);
    a = bflo(u); b = bfhi(u);
}
__device__ __forceinline__ uint32_t smem_u32(const void* p) { return (uint32_t)__cvta_generic_to_shared(p); }

__device__ __forceinline__ void mbar_init(uint32_t bar, uint32_t cnt) {
    asm volatile("mbarrier.init.shared::cta.b64 [%0], %1;" :: "r"(bar), "r"(cnt) : "memory");
}
__device__ __forceinline__ void mbar_arrive(uint32_t bar) {
    asm volatile("mbarrier.arrive.shared::cta.b64 _, [%0];" :: "r"(bar) : "memory");
}
__device__ __forceinline__ void mbar_expect(uint32_t bar, uint32_t bytes) {
    asm volatile("mbarrier.arrive.expect_tx.shared::cta.b64 _, [%0], %1;" :: "r"(bar), "r"(bytes) : "memory");
}
__device__ __forceinline__ bool mbar_try(uint32_t bar, uint32_t parity) {
    uint32_t ok;
    asm volatile("{\n\t.reg .pred p;\n\tmbarrier.try_wait.parity.shared::cta.b64 p, [%1], %2;\n\tselp.u32 %0, 1, 0, p;\n\t}"
                 : "=r"(ok) : "r"(bar), "r"(parity) : "memory");
    return ok != 0;
}
__device__ __forceinline__ bool mbar_try_cluster(uint32_t bar, uint32_t parity) {
    uint32_t ok;
    asm volatile("{\n\t.reg .pred p;\n\tmbarrier.try_wait.parity.acquire.cluster.shared::cta.b64 p, [%1], %2;\n\tselp.u32 %0, 1, 0, p;\n\t}"
                 : "=r"(ok) : "r"(bar), "r"(parity) : "memory");
    return ok != 0;
}
__device__ __forceinline__ void mbar_wait(uint32_t bar, uint32_t parity) {
    uint32_t guard = 0;
    while (!mbar_try(bar, parity)) { if (++guard > (1u << 22)) __trap(); }
}
__device__ __forceinline__ void mbar_wait_cluster(uint32_t bar, uint32_t parity) {
    uint32_t guard = 0;
    while (!mbar_try_cluster(bar, parity)) { if (++guard > (1u << 22)) __trap(); }
}
__device__ __forceinline__ void bar_sync(int id, int n) { asm volatile("bar.sync %0, %1;" :: "r"(id), "r"(n) : "memory"); }
__device__ __forceinline__ void bar_arrive(int id, int n) { asm volatile("bar.arrive %0, %1;" :: "r"(id), "r"(n) : "memory"); }
__device__ __forceinline__ void sts1(uint32_t a, uint32_t v) { asm volatile("st.shared.u32 [%0], %1;" :: "r"(a), "r"(v) : "memory"); }
__device__ __forceinline__ uint32_t lds1(uint32_t a) { uint32_t v; asm volatile("ld.shared.u32 %0, [%1];" : "=r"(v) : "r"(a) : "memory"); return v; }
__device__ __forceinline__ void fence_async() { asm volatile("fence.proxy.async.shared::cta;" ::: "memory"); }
__device__ __forceinline__ void cluster_sync() {
    asm volatile("barrier.cluster.arrive.release.aligned;\n\tbarrier.cluster.wait.acquire.aligned;" ::: "memory");
}
__device__ __forceinline__ uint32_t mapa(uint32_t a, uint32_t rank) {
    uint32_t r; asm("mapa.shared::cluster.u32 %0, %1, %2;" : "=r"(r) : "r"(a), "r"(rank)); return r;
}
__device__ __forceinline__ void st_async1(uint32_t a, uint32_t v, uint32_t bar) {
    asm volatile("st.async.weak.shared::cluster.mbarrier::complete_tx::bytes.b32 [%0], %1, [%2];" :: "r"(a), "r"(v), "r"(bar) : "memory");
}
__device__ __forceinline__ void st_async2(uint32_t a, float x, float y, uint32_t bar) {
    asm volatile("st.async.weak.shared::cluster.mbarrier::complete_tx::bytes.v2.f32 [%0], {%1,%2}, [%3];" :: "r"(a), "f"(x), "f"(y), "r"(bar) : "memory");
}
__device__ __forceinline__ void st_async4(uint32_t a, const float* c, uint32_t bar) {
    asm volatile("st.async.weak.shared::cluster.mbarrier::complete_tx::bytes.v4.f32 [%0], {%1,%2,%3,%4}, [%5];"
                 :: "r"(a), "f"(c[0]), "f"(c[1]), "f"(c[2]), "f"(c[3]), "r"(bar) : "memory");
}
__device__ __forceinline__ void bulk_g2s(uint32_t dst, const void* src, uint32_t bytes, uint32_t bar) {
    asm volatile("cp.async.bulk.shared::cluster.global.mbarrier::complete_tx::bytes [%0], [%1], %2, [%3];"
                 :: "r"(dst), "l"(src), "r"(bytes), "r"(bar) : "memory");
}
__device__ __forceinline__ void cpa16(uint32_t s, const void* g) {
    asm volatile("cp.async.cg.shared.global [%0], [%1], 16;" :: "r"(s), "l"(g) : "memory");
}
__device__ __forceinline__ void cpa_wait_all() { asm volatile("cp.async.wait_all;" ::: "memory"); }
__device__ __forceinline__ void ldsm4(uint32_t* r, uint32_t a) {
    asm volatile("ldmatrix.sync.aligned.m8n8.x4.shared.b16 {%0,%1,%2,%3}, [%4];" : "=r"(r[0]), "=r"(r[1]), "=r"(r[2]), "=r"(r[3]) : "r"(a) : "memory");
}
__device__ __forceinline__ void ldsm4t(uint32_t* r, uint32_t a) {
    asm volatile("ldmatrix.sync.aligned.m8n8.x4.trans.shared.b16 {%0,%1,%2,%3}, [%4];" : "=r"(r[0]), "=r"(r[1]), "=r"(r[2]), "=r"(r[3]) : "r"(a) : "memory");
}
__device__ __forceinline__ void stsm2t(uint32_t a, uint32_t r0, uint32_t r1) {
    asm volatile("stmatrix.sync.aligned.m8n8.x2.trans.shared.b16 [%0], {%1,%2};" :: "r"(a), "r"(r0), "r"(r1) : "memory");
}
__device__ __forceinline__ void stsm4t(uint32_t a, uint32_t r0, uint32_t r1, uint32_t r2, uint32_t r3) {
    asm volatile("stmatrix.sync.aligned.m8n8.x4.trans.shared.b16 [%0], {%1,%2,%3,%4};" :: "r"(a), "r"(r0), "r"(r1), "r"(r2), "r"(r3) : "memory");
}
__device__ __forceinline__ uint32_t movm(uint32_t v) {
    uint32_t r; asm volatile("movmatrix.sync.aligned.m8n8.trans.b16 %0, %1;" : "=r"(r) : "r"(v)); return r;
}
__device__ __forceinline__ void mma16(float* c, uint32_t a0, uint32_t a1, uint32_t a2, uint32_t a3, uint32_t b0, uint32_t b1) {
    asm volatile("mma.sync.aligned.m16n8k16.row.col.f32.bf16.bf16.f32 {%0,%1,%2,%3}, {%4,%5,%6,%7}, {%8,%9}, {%0,%1,%2,%3};"
                 : "+f"(c[0]), "+f"(c[1]), "+f"(c[2]), "+f"(c[3]) : "r"(a0), "r"(a1), "r"(a2), "r"(a3), "r"(b0), "r"(b1));
}
__device__ __forceinline__ void mma8(float* c, uint32_t a0, uint32_t a1, uint32_t b0) {
    asm volatile("mma.sync.aligned.m16n8k8.row.col.f32.bf16.bf16.f32 {%0,%1,%2,%3}, {%4,%5}, {%6}, {%0,%1,%2,%3};"
                 : "+f"(c[0]), "+f"(c[1]), "+f"(c[2]), "+f"(c[3]) : "r"(a0), "r"(a1), "r"(b0));
}
__host__ __device__ constexpr uint64_t make_desc(uint32_t saddr, uint32_t lbo, uint32_t sbo, uint32_t layout) {
    return (uint64_t)((saddr & 0x3FFFF) >> 4) | ((uint64_t)(lbo >> 4) << 16) | ((uint64_t)(sbo >> 4) << 32) | ((uint64_t)layout << 62);
}
__device__ __forceinline__ void wg_fence() { asm volatile("wgmma.fence.sync.aligned;" ::: "memory"); }
__device__ __forceinline__ void wg_commit() { asm volatile("wgmma.commit_group.sync.aligned;" ::: "memory"); }
template <int N> __device__ __forceinline__ void wg_wait() { asm volatile("wgmma.wait_group.sync.aligned %0;" :: "n"(N) : "memory"); }

#define D16(C) C(d[0]), C(d[1]), C(d[2]), C(d[3]), C(d[4]), C(d[5]), C(d[6]), C(d[7]), \
               C(d[8]), C(d[9]), C(d[10]), C(d[11]), C(d[12]), C(d[13]), C(d[14]), C(d[15])
#define DREG16 "{%0,%1,%2,%3,%4,%5,%6,%7,%8,%9,%10,%11,%12,%13,%14,%15}"
__device__ __forceinline__ void wg_rs32(float* d, const uint32_t* a, uint64_t db, bool acc) {
    if (acc)
        asm volatile("wgmma.mma_async.sync.aligned.m64n32k16.f32.bf16.bf16 " DREG16 ", {%16,%17,%18,%19}, %20, 1, 1, 1, 0;"
            : D16("+f") : "r"(a[0]), "r"(a[1]), "r"(a[2]), "r"(a[3]), "l"(db));
    else
        asm volatile("wgmma.mma_async.sync.aligned.m64n32k16.f32.bf16.bf16 " DREG16 ", {%16,%17,%18,%19}, %20, 0, 1, 1, 0;"
            : D16("=f") : "r"(a[0]), "r"(a[1]), "r"(a[2]), "r"(a[3]), "l"(db));
}
__device__ __forceinline__ void wg_ss32(float* d, uint64_t da, uint64_t db, bool acc) {
    if (acc)
        asm volatile("wgmma.mma_async.sync.aligned.m64n32k16.f32.bf16.bf16 " DREG16 ", %16, %17, 1, 1, 1, 1, 0;"
            : D16("+f") : "l"(da), "l"(db));
    else
        asm volatile("wgmma.mma_async.sync.aligned.m64n32k16.f32.bf16.bf16 " DREG16 ", %16, %17, 0, 1, 1, 1, 0;"
            : D16("=f") : "l"(da), "l"(db));
}
__device__ __forceinline__ void wg_ss8(float* d, uint64_t da, uint64_t db, bool acc) {
    if (acc)
        asm volatile("wgmma.mma_async.sync.aligned.m64n8k16.f32.bf16.bf16 {%0,%1,%2,%3}, %4, %5, 1, 1, 1, 1, 1;"
            : "+f"(d[0]), "+f"(d[1]), "+f"(d[2]), "+f"(d[3]) : "l"(da), "l"(db));
    else
        asm volatile("wgmma.mma_async.sync.aligned.m64n8k16.f32.bf16.bf16 {%0,%1,%2,%3}, %4, %5, 0, 1, 1, 1, 1;"
            : "=f"(d[0]), "=f"(d[1]), "=f"(d[2]), "=f"(d[3]) : "l"(da), "l"(db));
}
template <int OFF> __device__ __forceinline__ void ldsm4t_i(uint32_t* r, uint32_t a) {
    asm volatile("ldmatrix.sync.aligned.m8n8.x4.trans.shared.b16 {%0,%1,%2,%3}, [%4+%5];"
                 : "=r"(r[0]), "=r"(r[1]), "=r"(r[2]), "=r"(r[3]) : "r"(a), "n"(OFF) : "memory");
}

__device__ __forceinline__ uint4 ld_relaxed4(const void* p) {
    uint4 v;
    asm volatile("ld.relaxed.gpu.global.v4.u32 {%0,%1,%2,%3}, [%4];" : "=r"(v.x), "=r"(v.y), "=r"(v.z), "=r"(v.w) : "l"(p) : "memory");
    return v;
}
__device__ __forceinline__ void st_relaxed2(void* p, uint32_t a, uint32_t b) {
    asm volatile("st.relaxed.gpu.global.v2.u32 [%0], {%1,%2};" :: "l"(p), "r"(a), "r"(b) : "memory");
}
__device__ __forceinline__ void st_relaxed2_off(void* base, uint32_t off, uint32_t a, uint32_t b) {
    asm volatile("{\n\t.reg .u64 ad;\n\tcvt.u64.u32 ad, %1;\n\tadd.u64 ad, ad, %0;\n\tst.relaxed.gpu.global.v2.u32 [ad], {%2,%3};\n\t}"
                 :: "l"(base), "r"(off), "r"(a), "r"(b) : "memory");
}
__device__ __forceinline__ void st_relaxed1(void* p, uint32_t a) {
    asm volatile("st.relaxed.gpu.global.u32 [%0], %1;" :: "l"(p), "r"(a) : "memory");
}
__device__ __forceinline__ uint32_t ld_acquire1(const uint32_t* p) {
    uint32_t v; asm volatile("ld.acquire.gpu.global.u32 %0, [%1];" : "=r"(v) : "l"(p) : "memory"); return v;
}
__device__ __forceinline__ void st_release1(uint32_t* p, uint32_t a) {
    asm volatile("st.release.gpu.global.u32 [%0], %1;" :: "l"(p), "r"(a) : "memory");
}
__device__ __forceinline__ uint4 lds4(uint32_t s) {
    uint4 v; asm volatile("ld.shared.v4.u32 {%0,%1,%2,%3}, [%4];" : "=r"(v.x), "=r"(v.y), "=r"(v.z), "=r"(v.w) : "r"(s) : "memory"); return v;
}
__device__ __forceinline__ void sts4(uint32_t s, const uint4& v) {
    asm volatile("st.shared.v4.u32 [%0], {%1,%2,%3,%4};" :: "r"(s), "r"(v.x), "r"(v.y), "r"(v.z), "r"(v.w) : "memory");
}
__device__ __forceinline__ float4 lds4f(uint32_t s) {
    float4 v; asm volatile("ld.shared.v4.f32 {%0,%1,%2,%3}, [%4];" : "=f"(v.x), "=f"(v.y), "=f"(v.z), "=f"(v.w) : "r"(s) : "memory"); return v;
}
__device__ __forceinline__ uint2 lds2(uint32_t s) {
    uint2 v; asm volatile("ld.shared.v2.u32 {%0,%1}, [%2];" : "=r"(v.x), "=r"(v.y) : "r"(s) : "memory"); return v;
}
__device__ __forceinline__ float2 lds2f(uint32_t s) {
    float2 v; asm volatile("ld.shared.v2.f32 {%0,%1}, [%2];" : "=f"(v.x), "=f"(v.y) : "r"(s) : "memory"); return v;
}
__device__ __forceinline__ uint32_t clk32() { uint32_t c; asm volatile("mov.u32 %0, %%clock;" : "=r"(c) :: "memory"); return c; }
__device__ __forceinline__ uint32_t tagw(float v, uint32_t tag) { return ((__float_as_uint(v) + 8u) & ~15u) | tag; }
__device__ __forceinline__ bool ok4(const uint4& v, uint32_t tag) { return (((v.x ^ tag) | (v.y ^ tag) | (v.z ^ tag) | (v.w ^ tag)) & 15u) == 0; }
__device__ __forceinline__ bool oks(const uint4& v) { return v.x != 0xFFFFFFFFu && v.y != 0xFFFFFFFFu && v.z != 0xFFFFFFFFu && v.w != 0xFFFFFFFFu; }
__device__ __forceinline__ float uf(uint32_t x) { return __uint_as_float(x & ~15u); }

__global__ void __launch_bounds__(256) k_mod(const bf16* __restrict__ c, const bf16* __restrict__ wmod) {
    __shared__ float sc[DM];
    __shared__ float red[8][64];
    const int tid = threadIdx.x;
    for (int i = tid; i < DM; i += 256) {
        float v = __bfloat162float(c[i]);
        sc[i] = bfr(v / (1.0f + __expf(-v)));
    }
    __syncthreads();
    const int cp = tid & 31, kg = tid >> 5;
    const int col = blockIdx.x * 64 + cp * 2;
    float a0 = 0.f, a1 = 0.f;
    #pragma unroll 8
    for (int k = kg * 80; k < kg * 80 + 80; k++) {
        uint32_t w = *(const uint32_t*)(wmod + (size_t)k * (6 * DM) + col);
        a0 += sc[k] * bflo(w); a1 += sc[k] * bfhi(w);
    }
    red[kg][cp * 2] = a0; red[kg][cp * 2 + 1] = a1;
    __syncthreads();
    if (tid < 64) {
        float s = 0.f;
        #pragma unroll
        for (int i = 0; i < 8; i++) s += red[i][tid];
        g_mod[blockIdx.x * 64 + tid] = bfr(s);
    }
    if (blockIdx.x == 0 && tid == 0) g_epoch = g_epoch + 1;
}

template <int MODE>
__global__ void __launch_bounds__(256) k_ln(const bf16* __restrict__ xin) {
    const int lane = threadIdx.x & 31, row = blockIdx.x * 8 + (threadIdx.x >> 5);
    const bf16* src = (MODE == 0 ? xin : g_x1) + (size_t)row * DM;
    const float* shift = g_mod + (MODE == 0 ? 0 : 3 * DM);
    const float* scale = g_mod + (MODE == 0 ? DM : 4 * DM);
    float v[3][8];
    float s = 0.f;
    #pragma unroll
    for (int i = 0; i < 3; i++) {
        int c = lane + 32 * i;
        if (c < 80) {
            uint4 u = *(const uint4*)(src + c * 8);
            v[i][0] = bflo(u.x); v[i][1] = bfhi(u.x); v[i][2] = bflo(u.y); v[i][3] = bfhi(u.y);
            v[i][4] = bflo(u.z); v[i][5] = bfhi(u.z); v[i][6] = bflo(u.w); v[i][7] = bfhi(u.w);
        } else {
            #pragma unroll
            for (int j = 0; j < 8; j++) v[i][j] = 0.f;
        }
        #pragma unroll
        for (int j = 0; j < 8; j++) s += v[i][j];
    }
    #pragma unroll
    for (int o = 16; o > 0; o >>= 1) s += __shfl_xor_sync(0xffffffffu, s, o);
    const float mean = s * (1.0f / DM);
    float q = 0.f;
    #pragma unroll
    for (int i = 0; i < 3; i++) {
        if (lane + 32 * i < 80) {
            #pragma unroll
            for (int j = 0; j < 8; j++) { float d = v[i][j] - mean; q += d * d; }
        }
    }
    #pragma unroll
    for (int o = 16; o > 0; o >>= 1) q += __shfl_xor_sync(0xffffffffu, q, o);
    const float mb = bfr(mean);
    const float var = bfr(q * (1.0f / DM));
    const float sd = bfr(sqrtf(bfr(var + 1e-5f)));
    #pragma unroll
    for (int i = 0; i < 3; i++) {
        int c = lane + 32 * i;
        if (c < 80) {
            float o[8];
            #pragma unroll
            for (int j = 0; j < 8; j++) {
                float n = bfr(bfr(v[i][j] - mb) / sd);
                float m1 = bfr(1.0f + scale[c * 8 + j]);
                o[j] = bfr(n * m1) + shift[c * 8 + j];
            }
            uint4 u = make_uint4(pack2(o[0], o[1]), pack2(o[2], o[3]), pack2(o[4], o[5]), pack2(o[6], o[7]));
            if (MODE == 0) {
                int seg = row >> 5, r = row & 31, blk = c >> 3, cc = c & 7;
                *(uint4*)(g_ht + (size_t)seg * 20480 + blk * 2048 + r * 64 + ((cc ^ (r & 7)) << 3)) = u;
            } else {
                *(uint4*)(g_h2 + (size_t)row * DM + c * 8) = u;
            }
        }
    }
}

constexpr int SM_WV = 0;
constexpr int SM_HB = 81920;
constexpr int SM_WO = SM_HB + 40960;
constexpr int SM_QX = SM_WO + 77824;
constexpr int SM_KS = SM_QX + 4096;
constexpr int SM_QM = SM_KS + 5120;
constexpr int SM_XS = SM_QM + 1024;
constexpr int SM_MS = SM_XS + 12288;
constexpr int SM_OS = SM_MS + 3840;
constexpr int SM_PM = SM_OS + 3072;
constexpr int SM_BAR = SM_PM + 640;
constexpr int SM_CH = SM_BAR + 128;
constexpr int SM_TOTAL = SM_CH + 128;
static_assert(SM_TOTAL <= 232448, "smem");

enum { B_MEM_FULL = 0, B_MEM_FREE, B_HLO_FULL, B_HHI_FULL, B_HLO_FREE, B_HHI_FREE, B_MS, B_O, B_XS, B_O1, B_XSFREE };

__device__ __forceinline__ int probe_blk(uint32_t* blk) {
    uint32_t t0 = 0xffffffffu, t1 = 0xffffffffu, acc = 0;
    for (int rep = 0; rep < 3; rep++) {
        #pragma unroll
        for (int pg = 0; pg < 2; pg++) {
            uint32_t c0 = clk32();
            uint32_t v = atomicOr(blk + pg * 1024 + acc, 0u);
            acc = (v == 0x12345678u) ? 1u : 0u;
            asm volatile("" :: "r"(acc) : "memory");
            uint32_t c1 = clk32() + acc;
            uint32_t d = c1 - c0;
            if (rep > 0) { if (pg == 0) t0 = min(t0, d); else t1 = min(t1, d); }
        }
    }
    return t1 < t0 ? 1 : 0;
}

__device__ __forceinline__ uint32_t wo_tile_off(int w) {
    if (w < 8) return w * 6144;
    if (w < 12) return 8 * 6144 + (w - 8) * 4096;
    return 8 * 6144 + 4 * 4096 + (w - 12) * 6144;
}

template <int NRES, int NPRE>
__device__ __forceinline__ void wo_phase(uint32_t sb, int w, int lane, const uint32_t (*res)[4], uint32_t parity,
                                         uint32_t tag, int tile, int h) {
    FRESH(lane);
    const int er = (lane & 7) + 8 * (lane >> 4);
    const uint32_t aaddr = sb + SM_WO + wo_tile_off(w) + er * 32 + ((((lane >> 3) & 1) ^ ((er >> 2) & 1)) << 4);
    const uint32_t baddr = sb + SM_OS + lane * 16;
    float c0[4] = {0.f, 0.f, 0.f, 0.f}, c1[4] = {0.f, 0.f, 0.f, 0.f};
    uint32_t pre[NPRE > 4 ? NPRE : 4][4];
    if (NPRE >= 4) {
        #pragma unroll
        for (int i = 0; i < 4; i++) ldsm4t(pre[i], aaddr + i * 512);
        mbar_wait(sb + SM_BAR + B_O1 * 8, parity);
        uint32_t b[2][4];
        ldsm4t(b[0], baddr);
        ldsm4t(b[1], baddr + 512);
        #pragma unroll
        for (int kp = 0; kp < 2; kp++) {
            mma16(c0, pre[2 * kp][0], pre[2 * kp][1], pre[2 * kp][2], pre[2 * kp][3], b[kp][0], b[kp][1]);
            mma16(c1, pre[2 * kp + 1][0], pre[2 * kp + 1][1], pre[2 * kp + 1][2], pre[2 * kp + 1][3], b[kp][2], b[kp][3]);
        }
    } else {
        #pragma unroll
        for (int i = 0; i < 2; i++) ldsm4t(pre[i], aaddr + i * 512);
        mbar_wait(sb + SM_BAR + B_O1 * 8, parity);
        #pragma unroll
        for (int kp = 0; kp < 2; kp++) {
            uint32_t b[4];
            ldsm4t(b, baddr + kp * 512);
            if (kp == 1) { ldsm4t(pre[0], aaddr + 2 * 512); ldsm4t(pre[1], aaddr + 3 * 512); }
            mma16(c0, pre[0][0], pre[0][1], pre[0][2], pre[0][3], b[0], b[1]);
            mma16(c1, pre[1][0], pre[1][1], pre[1][2], pre[1][3], b[2], b[3]);
        }
    }
    #pragma unroll
    for (int i = 0; i < NPRE; i++) ldsm4t(pre[i], aaddr + (4 + i) * 512);
    uint32_t off0, off1;
    {
        uint32_t ch;
        asm volatile("ld.shared.u16 %0, [%1];" : "=r"(ch) : "r"(sb + SM_CH + 2 * tile) : "memory");
        const int j = lane >> 4;
        const uint32_t base = (uint32_t)((tile * 4 + j) * 8192 + ((lane >> 2) & 3) * 1024 + h * 32 + (lane & 3) * 8);
        ch >>= j;
        off0 = base + (ch & 1) * 4096;
        off1 = base + 16384 + (ch & 256) * 16;
    }
    mbar_wait(sb + SM_BAR + B_O * 8, parity);
    if (NRES == 4) {
        uint32_t b[4][4];
        #pragma unroll
        for (int i = 0; i < 4; i++) ldsm4t(b[i], baddr + (2 + i) * 512);
        #pragma unroll
        for (int i = 0; i < 2; i++) {
            mma16(c0, res[2 * i][0], res[2 * i][1], res[2 * i][2], res[2 * i][3], b[i][0], b[i][1]);
            mma16(c1, res[2 * i + 1][0], res[2 * i + 1][1], res[2 * i + 1][2], res[2 * i + 1][3], b[i][2], b[i][3]);
        }
        #pragma unroll
        for (int i = 0; i < 2; i++) {
            mma16(c0, pre[2 * i][0], pre[2 * i][1], pre[2 * i][2], pre[2 * i][3], b[2 + i][0], b[2 + i][1]);
            mma16(c1, pre[2 * i + 1][0], pre[2 * i + 1][1], pre[2 * i + 1][2], pre[2 * i + 1][3], b[2 + i][2], b[2 + i][3]);
        }
    } else if (NPRE == 4) {
        uint32_t b[2][4];
        #pragma unroll
        for (int hh = 0; hh < 2; hh++) {
            ldsm4t(b[0], baddr + (2 + 2 * hh) * 512);
            ldsm4t(b[1], baddr + (3 + 2 * hh) * 512);
            if (hh) {
                #pragma unroll
                for (int i = 0; i < 4; i++) ldsm4t(pre[i], aaddr + (8 + i) * 512);
            }
            #pragma unroll
            for (int i = 0; i < 2; i++) {
                mma16(c0, pre[2 * i][0], pre[2 * i][1], pre[2 * i][2], pre[2 * i][3], b[i][0], b[i][1]);
                mma16(c1, pre[2 * i + 1][0], pre[2 * i + 1][1], pre[2 * i + 1][2], pre[2 * i + 1][3], b[i][2], b[i][3]);
            }
        }
    }
    st_relaxed2_off(g_buf1, off0, tagw(c0[0] + c1[0], tag), tagw(c0[1] + c1[1], tag));
    st_relaxed2_off(g_buf1, off1, tagw(c0[2] + c1[2], tag), tagw(c0[3] + c1[3], tag));
}

template <int NT, bool MASK>
__device__ __forceinline__ void softmax_core(float (*sc)[2], int g, int t, uint32_t* pb) {
    const float L2E = 1.4426950408889634f;
    #pragma unroll
    for (int j = 0; j < NT; j++) score2(sc[j][0], sc[j][1]);
    if (MASK) {
        const float NEG = -999292928.0f;
        if (2 * t > g) sc[NT - 1][0] = NEG;
        if (2 * t + 1 > g) sc[NT - 1][1] = NEG;
    }
    float m[NT];
    #pragma unroll
    for (int j = 0; j < NT; j++) m[j] = fmaxf(sc[j][0], sc[j][1]);
    float mx = m[0];
    #pragma unroll
    for (int j = 1; j < NT; j++) mx = fmaxf(mx, m[j]);
    mx = fmaxf(mx, __shfl_xor_sync(0xffffffffu, mx, 1));
    mx = fmaxf(mx, __shfl_xor_sync(0xffffffffu, mx, 2));
    float s0 = 0.f, s1 = 0.f;
    #pragma unroll
    for (int j = 0; j < NT; j++) {
        sc[j][0] = ex2((sc[j][0] - mx) * L2E); sc[j][1] = ex2((sc[j][1] - mx) * L2E);
        s0 += sc[j][0]; s1 += sc[j][1];
    }
    s0 += s1;
    s0 += __shfl_xor_sync(0xffffffffu, s0, 1);
    s0 += __shfl_xor_sync(0xffffffffu, s0, 2);
    const float iv = rcpf(s0);
    #pragma unroll
    for (int j = 0; j < NT; j++) pb[j] = pack2(sc[j][0] * iv, sc[j][1] * iv);
}
template <int NT>
__device__ __forceinline__ void xsoftmax(uint32_t a, uint32_t pa, int g, int t) {
    float sc[NT][2];
    #pragma unroll
    for (int j = 0; j < NT; j++) {
        float2 v0 = lds2f(a + j * 512), v1 = lds2f(a + j * 512 + 4096), v2 = lds2f(a + j * 512 + 8192);
        sc[j][0] = v0.x + v1.x + v2.x; sc[j][1] = v0.y + v1.y + v2.y;
    }
    uint32_t pb[NT];
    softmax_core<NT, true>(sc, g, t, pb);
    #pragma unroll
    for (int j = 0; j < NT; j++) sts1(pa + j * 256, pb[j]);
}
template <int NJ>
__device__ __forceinline__ void xscores(uint32_t sb, int p, int mi, int j0, int lane) {
    FRESH(lane);
    const int r = lane & 7, cq = lane >> 3;
    const int qrow = mi * 16 + r + 8 * (cq & 1);
    uint32_t kb[NJ][8];
    float d[NJ][4];
    #pragma unroll
    for (int j = 0; j < NJ; j++) {
        ldsm4(kb[j], sb + SM_KS + ((j0 + j) * 8 + r) * 128 + ((cq ^ r) << 4));
        ldsm4(kb[j] + 4, sb + SM_KS + ((j0 + j) * 8 + r) * 128 + (((cq + 4) ^ r) << 4));
        d[j][0] = 0.f; d[j][1] = 0.f; d[j][2] = 0.f; d[j][3] = 0.f;
    }
    #pragma unroll
    for (int kt = 0; kt < 4; kt++) {
        uint32_t a[4];
        ldsm4(a, sb + SM_QX + qrow * 128 + (((2 * kt + (cq >> 1)) ^ r) << 4));
        #pragma unroll
        for (int j = 0; j < NJ; j++) mma16(d[j], a[0], a[1], a[2], a[3], kb[j][2 * kt], kb[j][2 * kt + 1]);
    }
    const uint32_t la = sb + SM_XS + p * 4096 + (mi * 3 + j0) * 512 + lane * 16;
    #pragma unroll
    for (int rk = 0; rk < 3; rk++) {
        const uint32_t ra = mapa(la, rk), rb = mapa(sb + SM_BAR + B_XS * 8, rk);
        #pragma unroll
        for (int j = 0; j < NJ; j++) st_async4(ra + j * 512, d[j], rb);
    }
}
__device__ __forceinline__ void mbar_arrive_remote(uint32_t bar) {
    asm volatile("mbarrier.arrive.relaxed.cluster.shared::cluster.b64 _, [%0];" :: "r"(bar) : "memory");
}

__global__ void __launch_bounds__(512, 1)
k_rec(const bf16* __restrict__ mem0, const bf16* __restrict__ Wq, const bf16* __restrict__ Wk,
      const bf16* __restrict__ Wv, const bf16* __restrict__ Wo) {
    extern __shared__ __align__(1024) uint8_t smem_raw[];
    constexpr uint32_t SBC = 1024;
    const uint32_t sb = smem_u32(smem_raw);
    if ((sb & 0xFFFFFFu) != SBC) __trap();
    int lane = __shfl_sync(0xffffffffu, threadIdx.x & 31, threadIdx.x & 31);
    const int warp = __shfl_sync(0xffffffffu, threadIdx.x >> 5, 0), wg = warp >> 2;
    const int tid = warp * 32 + lane;
    const int b = blockIdx.x, h = b / 3, p = b % 3;
    const int g = lane >> 2, t = lane & 3;
    const int tile0 = p == 0 ? 0 : (p == 1 ? 14 : 27);
    const int ntile = p == 0 ? 14 : 13;
    const uint32_t bar = sb + SM_BAR;

    if (tid == 0) {
        mbar_init(bar + B_MEM_FULL * 8, 4);
        mbar_init(bar + B_MEM_FREE * 8, 12);
        mbar_init(bar + B_HLO_FULL * 8, 1);
        mbar_init(bar + B_HHI_FULL * 8, 1);
        mbar_init(bar + B_HLO_FREE * 8, 12);
        mbar_init(bar + B_HHI_FREE * 8, 12);
        mbar_init(bar + B_MS * 8, 1);
        mbar_init(bar + B_O * 8, 1);
        mbar_init(bar + B_XS * 8, 1);
        mbar_init(bar + B_O1 * 8, 4);
        mbar_init(bar + B_XSFREE * 8, 12);
        asm volatile("fence.mbarrier_init.release.cluster;" ::: "memory");
        mbar_expect(bar + B_MS * 8, 3840);
        mbar_expect(bar + B_O * 8, 2048);
        mbar_expect(bar + B_XS * 8, 12288);
        mbar_expect(bar + B_HLO_FULL * 8, 12288);
        bulk_g2s(sb + SM_HB, g_ht, 12288, sb + SM_BAR + B_HLO_FULL * 8);
        mbar_expect(bar + B_HHI_FULL * 8, 28672);
        bulk_g2s(sb + SM_HB + 12288, (const char*)g_ht + 12288, 28672, sb + SM_BAR + B_HHI_FULL * 8);
    }
    cluster_sync();

    if (wg < 2) {
        asm volatile("setmaxnreg.inc.sync.aligned.u32 200;");
        const int w = warp & 3;
        uint32_t wa[40][4];
        {
            const bf16* W = (wg == 0 ? Wq : Wk) + (size_t)h * DH + p * 64 + w * 16 + t * 4;
            #pragma unroll
            for (int kt = 0; kt < 40; kt++) {
                uint2 l1 = __ldg((const uint2*)(W + (size_t)(kt * 16 + g) * HD));
                uint2 l2 = __ldg((const uint2*)(W + (size_t)(kt * 16 + 8 + g) * HD));
                wa[kt][0] = l1.x; wa[kt][1] = l1.y; wa[kt][2] = l2.x; wa[kt][3] = l2.y;
            }
            #pragma unroll
            for (int kt = 0; kt < 40; kt++) {
                #pragma unroll
                for (int i = 0; i < 4; i++) wa[kt][i] = movm(wa[kt][i]);
            }
        }

        const uint32_t dstx = sb + (wg == 0 ? SM_QX : SM_KS + 1024);

        for (int s = -1; s < NSEG; s++) {
            const uint32_t par = s & 1;
            FRESH(lane);
            const int g = lane >> 2, t = lane & 3, tid = warp * 32 + lane;
            if (s >= 0) {
                mbar_wait(bar + B_MEM_FULL * 8, par);
                TR(0);
                float c[4][4];
                #pragma unroll
                for (int i = 0; i < 4; i++) { c[i][0] = 0.f; c[i][1] = 0.f; c[i][2] = 0.f; c[i][3] = 0.f; }
                uint32_t maddr = sb + lane * 16;
                asm volatile("" : "+r"(maddr));
                #pragma unroll
                for (int kp = 0; kp < 20; kp++) {
                    uint32_t bb[4];
                    ldsm4t(bb, maddr + (SM_HB + kp * 512));
                    mma16(c[(kp & 1) * 2], wa[2 * kp][0], wa[2 * kp][1], wa[2 * kp][2], wa[2 * kp][3], bb[0], bb[1]);
                    mma16(c[(kp & 1) * 2 + 1], wa[2 * kp + 1][0], wa[2 * kp + 1][1], wa[2 * kp + 1][2], wa[2 * kp + 1][3], bb[2], bb[3]);
                }
                {
                    const int tok = lane & 7, ch = 2 * w + ((lane >> 3) & 1);
                    stsm2t(sb + (wg == 0 ? SM_QM : SM_KS) + tok * 128 + ((ch ^ tok) << 4),
                           pack2((c[0][0] + c[1][0]) + (c[2][0] + c[3][0]), (c[0][1] + c[1][1]) + (c[2][1] + c[3][1])),
                           pack2((c[0][2] + c[1][2]) + (c[2][2] + c[3][2]), (c[0][3] + c[1][3]) + (c[2][3] + c[3][3])));
                }
                __syncwarp();
                if (lane == 0) mbar_arrive(bar + B_MEM_FREE * 8);
                TR(1);
                bar_sync(1, 256);
                if (warp < 5) {
                    const int r = lane & 7, cq = lane >> 3;
                    uint32_t a[8], kb[8];
                    ldsm4(a, sb + SM_QM + r * 128 + ((cq ^ r) << 4));
                    ldsm4(kb, sb + SM_KS + (warp * 8 + r) * 128 + ((cq ^ r) << 4));
                    ldsm4(a + 4, sb + SM_QM + r * 128 + (((cq + 4) ^ r) << 4));
                    ldsm4(kb + 4, sb + SM_KS + (warp * 8 + r) * 128 + (((cq + 4) ^ r) << 4));
                    float d0[4] = {0.f, 0.f, 0.f, 0.f}, d1[4] = {0.f, 0.f, 0.f, 0.f};
                    mma16(d0, a[0], 0u, a[1], 0u, kb[0], kb[1]);
                    mma16(d1, a[2], 0u, a[3], 0u, kb[2], kb[3]);
                    mma16(d0, a[4], 0u, a[5], 0u, kb[4], kb[5]);
                    mma16(d1, a[6], 0u, a[7], 0u, kb[6], kb[7]);
                    const uint32_t la = sb + SM_MS + p * 1280 + warp * 256 + lane * 8;
                    #pragma unroll
                    for (int rk = 0; rk < 3; rk++)
                        st_async2(mapa(la, rk), d0[0] + d1[0], d0[1] + d1[1], mapa(bar + B_MS * 8, rk));
                    bar_arrive(4, 352);
                } else if (warp < 7) {
                    xscores<1>(sb, p, warp - 5, 0, lane);
                    bar_arrive(4, 352);
                }
                TR(2);
                if (wg == 1) {
                    mbar_wait(bar + B_XS * 8, par);
                    TR(8);
                    if (tid == 128) mbar_expect(bar + B_XS * 8, 12288);
                    const uint32_t a = sb + SM_XS + (w >> 1) * 1536 + lane * 16 + (w & 1) * 8;
                    const uint32_t pa = sb + SM_QX + (w >> 1) * 768 + lane * 8 + (w & 1) * 4;
                    if (w == 0) xsoftmax<2>(a, pa, g, t);
                    else if (w == 1) xsoftmax<3>(a, pa, g, t);
                    else if (w == 2) xsoftmax<4>(a, pa, g, t);
                    else xsoftmax<5>(a, pa, g, t);
                    bar_arrive(7, 256);
                    if (lane < 3) mbar_arrive_remote(mapa(bar + B_XSFREE * 8, lane));
                    TR(9);
                }
                if (s < NSEG - 1) {
                    wo_phase<0, 4>(sb, warp, lane, nullptr, par, (uint32_t)(s % 15) + 1u, tile0 + warp, h);
                    TR(4);
                    bar_sync(6, 448);
                }
            }
            if (s < NSEG - 1) {
                FRESH(lane);
                const uint32_t hp = (s + 1) & 1;
                float d[16];
                const uint64_t db0 = make_desc(SBC + SM_HB, 16, 1024, 1);
                mbar_wait(bar + B_HHI_FULL * 8, hp);
                mbar_wait(bar + B_HLO_FULL * 8, hp);
                TR(6);
                wg_fence();
                #pragma unroll
                for (int kt = 0; kt < 36; kt++) wg_rs32(d, wa[kt], db0 + (uint64_t)(((kt >> 2) * 4096 + (kt & 3) * 32) >> 4), kt > 0);
                wg_commit();
                #pragma unroll
                for (int kt = 36; kt < 39; kt++) wg_rs32(d, wa[kt], db0 + (uint64_t)(((kt >> 2) * 4096 + (kt & 3) * 32) >> 4), 1);
                wg_commit();
                wg_wait<1>();
                bar_arrive(9, 384);
                if (lane == 0) mbar_arrive(bar + B_HLO_FREE * 8);
                {
                    const int r = lane & 7, mq = lane >> 3;
                    const uint32_t ha = sb + SM_HB + 9 * 4096 + (8 * (mq >> 1) + r) * 128 + (((6 + (mq & 1)) ^ r) << 4);
                    uint32_t b0[4], b1[4];
                    ldsm4(b0, ha);
                    ldsm4(b1, ha + 2048);
                    wg_wait<0>();
                    mma16(d + 0, wa[39][0], wa[39][1], wa[39][2], wa[39][3], b0[0], b0[1]);
                    mma16(d + 4, wa[39][0], wa[39][1], wa[39][2], wa[39][3], b0[2], b0[3]);
                    mma16(d + 8, wa[39][0], wa[39][1], wa[39][2], wa[39][3], b1[0], b1[1]);
                    mma16(d + 12, wa[39][0], wa[39][1], wa[39][2], wa[39][3], b1[2], b1[3]);
                }
                __syncwarp();
                if (lane == 0) mbar_arrive(bar + B_HHI_FREE * 8);
                TR(7);
                const int mi = lane >> 3, r = lane & 7;
                #pragma unroll
                for (int jj = 0; jj < 2; jj++) {
                    const int tok = 8 * (2 * jj + (mi >> 1)) + r, ch = 2 * w + (mi & 1);
                    stsm4t(dstx + tok * 128 + ((ch ^ r) << 4),
                           pack2(d[8 * jj + 0], d[8 * jj + 1]), pack2(d[8 * jj + 2], d[8 * jj + 3]),
                           pack2(d[8 * jj + 4], d[8 * jj + 5]), pack2(d[8 * jj + 6], d[8 * jj + 7]));
                }
                bar_arrive(8, 384);
                if (s < 0) bar_sync(0, 512);
            }
        }
    } else if (wg == 2) {
        asm volatile("setmaxnreg.dec.sync.aligned.u32 64;");
        const int w = warp & 3;
        {
            const int c = tid & 7;
            const bf16* src = Wv + (size_t)h * DH + p * 64 + c * 8;
            for (int k = (tid & 127) >> 3; k < DM; k += 16)
                cpa16(sb + SM_WV + k * 128 + ((c ^ (k & 7)) << 4), src + (size_t)k * HD);
        }
        uint32_t res[4][4];
        {
            const bf16* src = Wo + ((size_t)h * DH + ((p + 1) % 3) * 64) * DM + (tile0 + warp) * 16 + 2 * t;
            #pragma unroll
            for (int kt = 0; kt < 4; kt++) {
                res[kt][0] = __ldg((const uint32_t*)(src + (size_t)(kt * 16 + g) * DM));
                res[kt][1] = __ldg((const uint32_t*)(src + (size_t)(kt * 16 + g) * DM + 8));
                res[kt][2] = __ldg((const uint32_t*)(src + (size_t)(kt * 16 + 8 + g) * DM));
                res[kt][3] = __ldg((const uint32_t*)(src + (size_t)(kt * 16 + 8 + g) * DM + 8));
            }
            #pragma unroll
            for (int kt = 0; kt < 4; kt++) {
                #pragma unroll
                for (int i = 0; i < 4; i++) res[kt][i] = movm(res[kt][i]);
            }
        }
        cpa_wait_all();
        fence_async();
        bar_sync(2, 128);
        const uint64_t da0 = make_desc(SBC + SM_WV, 16, 1024, 1);
        uint32_t vx[8];
        #pragma unroll
        for (int i = 0; i < 8; i++) vx[i] = 0;

        for (int s = -1; s < NSEG; s++) {
            FRESH(lane);
            const int g = lane >> 2, t = lane & 3, tid = warp * 32 + lane;
            if (s >= 0) {
                const uint32_t par = s & 1;
                mbar_wait(bar + B_MEM_FULL * 8, par);
                bar_sync(4, 352);
                TR(0);
                float dv[4];
                {
                    const uint64_t dbm = make_desc(SBC + SM_HB, 128, 128, 0);
                    wg_fence();
                    #pragma unroll
                    for (int kt = 0; kt < 40; kt++) {
                        wg_ss8(dv, da0 + (uint64_t)(kt * 128), dbm + (uint64_t)(kt * 16), kt > 0);
                        wg_commit();
                        if (kt < 39) wg_wait<1>();
                    }
                    wg_commit();
                }
                TR(1);
                bar_sync(5, 160);
                TR(2);
                uint32_t pb[5];
                #pragma unroll
                for (int j = 0; j < 5; j++) pb[j] = lds1(sb + SM_PM + j * 128 + lane * 4);
                float o0[4] = {0.f, 0.f, 0.f, 0.f}, o1[4] = {0.f, 0.f, 0.f, 0.f}, o2[4] = {0.f, 0.f, 0.f, 0.f};
                wg_wait<0>();
                TR(3);
                mma16(o0, vx[0], vx[1], vx[2], vx[3], pb[1], pb[2]);
                mma16(o1, vx[4], vx[5], vx[6], vx[7], pb[3], pb[4]);
                const uint32_t vm0 = pack2(dv[0], dv[1]), vm1 = pack2(dv[2], dv[3]);
                mma8(o2, vm0, vm1, pb[0]);
                if (s < NSEG - 1) {
                    const uint32_t q0 = pack2(o0[0] + o1[0] + o2[0], o0[1] + o1[1] + o2[1]), q1 = pack2(o0[2] + o1[2] + o2[2], o0[3] + o1[3] + o2[3]);
                    const uint32_t la = sb + SM_OS + (w * 16 + g) * 16 + t * 4;
                    #pragma unroll
                    for (int i = 1; i < 3; i++) {
                        const uint32_t rk = (p + i) % 3;
                        const uint32_t ra = mapa(la + (3 - i) * 1024, rk), rb = mapa(bar + B_O * 8, rk);
                        st_async1(ra, q0, rb);
                        st_async1(ra + 128, q1, rb);
                    }
                    sts1(la, q0);
                    sts1(la + 128, q1);
                    __syncwarp();
                    if (lane == 0) { mbar_arrive(bar + B_O1 * 8); mbar_arrive(bar + B_MEM_FREE * 8); }
                }
                TR(5);
                if (s < NSEG - 1) {
                    wo_phase<4, 4>(sb, warp, lane, res, par, (uint32_t)(s % 15) + 1u, tile0 + warp, h);
                    TR(4);
                    if (tid == 256) mbar_expect(bar + B_O * 8, 2048);
                }
                bar_sync(7, 256);
                TR(8);
                FRESH(lane);
                bf16* orow = g_ox + (size_t)(s * 32 + (lane >> 2)) * HD + h * DH + p * 64 + w * 16 + 2 * (lane & 3);
                {
                    uint2 pv[8];
                    #pragma unroll
                    for (int j = 0; j < 8; j++) pv[j] = lds2(sb + SM_QX + j * 256 + lane * 8);
                    float oa[4][4];
                    #pragma unroll
                    for (int i = 0; i < 4; i++) { oa[i][0] = 0.f; oa[i][1] = 0.f; oa[i][2] = 0.f; oa[i][3] = 0.f; }
                    mma8(oa[0], vm0, vm1, pv[0].x);
                    mma8(oa[1], vm0, vm1, pv[0].y);
                    mma8(oa[2], vm0, vm1, pv[3].x);
                    mma8(oa[3], vm0, vm1, pv[3].y);
                    asm volatile("" :: "r"(pv[7].y), "r"(pv[6].x), "r"(pv[5].x), "r"(pv[4].x), "r"(pv[2].y), "r"(pv[1].x) : "memory");
                    if (s < NSEG - 1) bar_arrive(6, 448);
                    mma16(oa[0], vx[0], vx[1], vx[2], vx[3], pv[1].x, 0u);
                    mma16(oa[1], vx[0], vx[1], vx[2], vx[3], pv[1].y, pv[2].y);
                    mma16(oa[2], vx[0], vx[1], vx[2], vx[3], pv[4].x, pv[5].x);
                    mma16(oa[3], vx[0], vx[1], vx[2], vx[3], pv[4].y, pv[5].y);
                    mma16(oa[2], vx[4], vx[5], vx[6], vx[7], pv[6].x, 0u);
                    mma16(oa[3], vx[4], vx[5], vx[6], vx[7], pv[6].y, pv[7].y);
                    uint32_t u[8];
                    #pragma unroll
                    for (int i = 0; i < 4; i++) { u[2 * i] = movm(pack2(oa[i][0], oa[i][1])); u[2 * i + 1] = movm(pack2(oa[i][2], oa[i][3])); }
                    #pragma unroll
                    for (int i = 0; i < 4; i++) {
                        *(uint32_t*)(orow + (size_t)(8 * i) * HD) = u[2 * i];
                        *(uint32_t*)(orow + (size_t)(8 * i) * HD + 8) = u[2 * i + 1];
                    }
                }
                TR(9);
                if (s == NSEG - 1) break;
            }
            float d[16];
            const uint32_t hp = (s + 1) & 1;
            const uint64_t db0 = make_desc(SBC + SM_HB, 16, 1024, 1);
            mbar_wait(bar + B_HHI_FULL * 8, hp);
            mbar_wait(bar + B_HLO_FULL * 8, hp);
            bar_sync(9, 384);
            TR(6);
            wg_fence();
            #pragma unroll
            for (int kt = 0; kt < 40; kt++) {
                wg_ss32(d, da0 + (uint64_t)(kt * 128), db0 + (uint64_t)(((kt >> 2) * 4096 + (kt & 3) * 32) >> 4), kt > 0);
                wg_commit();
                if (kt < 39) wg_wait<1>();
                if (kt == 12 && lane == 0) mbar_arrive(bar + B_HLO_FREE * 8);
            }
            wg_wait<0>();
            TR(7);
            if (lane == 0) mbar_arrive(bar + B_HHI_FREE * 8);
            #pragma unroll
            for (int i = 0; i < 8; i++) vx[i] = pack2(d[2 * i], d[2 * i + 1]);
            if (s >= 0) mbar_wait_cluster(bar + B_XSFREE * 8, s & 1);
            bar_sync(8, 384);
            TR(10);
            if (w < 3) xscores<2>(sb, p, w > 0, w == 2 ? 3 : 1, lane);
            TR(11);
            if (s < 0) bar_sync(0, 512);
        }
    } else {
        asm volatile("setmaxnreg.dec.sync.aligned.u32 48;");
        const int w = warp & 3, lt = tid & 127;
        {
            const bf16* src0 = Wo + (size_t)h * DH * DM + tile0 * 16;
            const int nch = 2 * ntile;
            for (int i = lt; i < DH * nch; i += 128) {
                const int e = i / nch, c = i - e * nch, tl = c >> 1, cc = c & 1;
                int es = e;
                if (tl >= 8 && tl < 12) { if (e >= 64 && e < 128) continue; if (e >= 128) es = e - 64; }
                int eg = e + p * 64; if (eg >= DH) eg -= DH;
                cpa16(sb + SM_WO + wo_tile_off(tl) + es * 32 + ((cc ^ ((e >> 2) & 1)) << 4), src0 + (size_t)eg * DM + c * 8);
            }
        }
        const uint32_t epoch = *(volatile uint32_t*)&g_epoch;
        if (b < 80) {
            #pragma unroll
            for (int i = 0; i < 2; i++) {
                const int idx = lt + i * 128, sl = idx >> 6, pg = (idx >> 5) & 1, wd = idx & 31;
                st_relaxed1(g_buf2 + (sl * 3 + (b >> 5)) * 2048 + pg * 1024 + (b & 31) * 32 + wd, 0xFFFFFFFFu);
            }
            __threadfence();
        }
        if (lane == 0) {
            for (int i = w; i < 14; i += 4) {
                int c = 0;
                if (i < 12) c = probe_blk(g_buf2 + i * 2048 + 640 + (b & 31) * 8);
                else if (b < 80) c = probe_blk(g_buf1 + (b * 2 + (i - 12)) * 2048);
                asm volatile("st.shared.u8 [%0], %1;" :: "r"(sb + SM_CH + 96 + i), "r"(c) : "memory");
            }
        }
        bar_sync(3, 128);
        uint32_t selmask = 0;
        for (int i = 0; i < 14; i++) {
            uint32_t c; asm volatile("ld.shared.u8 %0, [%1];" : "=r"(c) : "r"(sb + SM_CH + 96 + i) : "memory");
            selmask |= c << i;
        }
        if (lt == 0 && b < 80) st_release1(&g_choice[b], (epoch << 2) | (selmask >> 12));
        if (lt < 80) {
            uint32_t v, guard = 0;
            do { v = ld_acquire1(&g_choice[lt]); if (++guard > (1u << 22)) __trap(); } while ((v >> 2) != (epoch & 0x3fffffffu));
            asm volatile("st.shared.u8 [%0], %1;" :: "r"(sb + SM_CH + lt), "r"(v & 3u) : "memory");
        }
        cpa_wait_all();
        bar_sync(0, 512);
        const bool has_tile = (12 + w) < ntile;
        for (int s = 0; s < NSEG; s++) {
            const uint32_t par = s & 1;
            FRESH(lane);
            const int g = lane >> 2, t = lane & 3, lt = w * 32 + lane;
            if (s == 0) {
                mbar_wait(bar + B_HLO_FREE * 8, par);
                for (int k = lt; k < DM; k += 128) {
                    uint32_t v[4];
                    #pragma unroll
                    for (int i = 0; i < 4; i++) {
                        uint32_t lo = *(const uint16_t*)(mem0 + (2 * i) * DM + k), hi = *(const uint16_t*)(mem0 + (2 * i + 1) * DM + k);
                        v[i] = lo | (hi << 16);
                    }
                    asm volatile("st.shared.v4.u32 [%0], {%1,%2,%3,%4};" :: "r"(sb + SM_HB + k * 16), "r"(v[0]), "r"(v[1]), "r"(v[2]), "r"(v[3]) : "memory");
                }
            } else {
                const int sl = s & 3;
                const char* q = (const char*)g_buf2 + sl * 3 * 8192 + lt * 16;
                const uint32_t sm = selmask >> (sl * 3);
                const char* q0 = q + (sm & 1) * 4096;
                const char* q1 = q + 8192 + (sm & 2) * 2048;
                const char* q2 = q + 16384 + (sm & 4) * 1024;
                const uint32_t dst = sb + SM_HB + lt * 16;
                uint32_t guard = 0;
                mbar_wait(bar + B_HLO_FREE * 8, par);
                TR(10);
                while (true) {
                    const uint4 v0 = ld_relaxed4(q0), v1 = ld_relaxed4(q0 + 2048), v2 = ld_relaxed4(q1), v3 = ld_relaxed4(q1 + 2048), v4 = ld_relaxed4(q2);
                    sts4(dst, v0); sts4(dst + 2048, v1); sts4(dst + 4096, v2); sts4(dst + 6144, v3); sts4(dst + 8192, v4);
                    if (__all_sync(0xffffffffu, oks(v0) && oks(v1) && oks(v2) && oks(v3) && oks(v4))) break;
                    if (++guard > (1u << 22)) __trap();
                }
            }
            fence_async();
            __syncwarp();
            if (lane == 0) mbar_arrive(bar + B_MEM_FULL * 8);
            TR(0);
            if (w == 2) {
                mbar_wait(bar + B_MS * 8, par);
                TR(1);
                if (lane == 0) mbar_expect(bar + B_MS * 8, 3840);
                uint32_t pb[5];
                float sc[5][2];
                {
                    const uint32_t a = sb + SM_MS + lane * 8;
                    float2 u[5], v[5];
                    #pragma unroll
                    for (int j = 0; j < 5; j++) { u[j] = lds2f(a + j * 256); v[j] = lds2f(a + j * 256 + 1280); }
                    #pragma unroll
                    for (int j = 0; j < 5; j++) { sc[j][0] = u[j].x + v[j].x; sc[j][1] = u[j].y + v[j].y; }
                    #pragma unroll
                    for (int j = 0; j < 5; j++) u[j] = lds2f(a + j * 256 + 2560);
                    #pragma unroll
                    for (int j = 0; j < 5; j++) { sc[j][0] += u[j].x; sc[j][1] += u[j].y; }
                }
                softmax_core<5, false>(sc, g, t, pb);
                #pragma unroll
                for (int j = 0; j < 5; j++) sts1(sb + SM_PM + j * 128 + lane * 4, pb[j]);
                bar_arrive(5, 160);
                TR(2);
            }
            if (s < NSEG - 1) {
                if (w == 3) {
                    if (lane == 0) {
                        const char* src = (const char*)g_ht + (size_t)(s + 1) * 40960;
                        mbar_wait(bar + B_HHI_FREE * 8, par);
                        mbar_expect(bar + B_HHI_FULL * 8, 28672);
                        bulk_g2s(sb + SM_HB + 12288, src + 12288, 28672, sb + SM_BAR + B_HHI_FULL * 8);
                        mbar_wait(bar + B_MEM_FREE * 8, par);
                        mbar_expect(bar + B_HLO_FULL * 8, 12288);
                        bulk_g2s(sb + SM_HB, src, 12288, sb + SM_BAR + B_HLO_FULL * 8);
                    }
                    __syncwarp();
                }
                const uint32_t tag = (uint32_t)(s % 15) + 1u;
                if (has_tile) wo_phase<0, 4>(sb, warp, lane, nullptr, par, tag, tile0 + warp, h);
                else mbar_wait(bar + B_O * 8, par);
                if (w < 2) bar_arrive(6, 448);
                TR(4);
                if (b < 80) {
                    FRESH(lane);
                    const char* rin = (const char*)g_buf1 + (size_t)(b * 2 + (w >> 1)) * 8192 + ((selmask >> (12 + (w >> 1))) & 1) * 4096 + (w & 1) * 2048 + lane * 16;
                    const int col = b * 8 + 2 * w + (lane >> 4), wd = 2 * (lane & 1) + ((lane >> 3) & 1);
                    const int sl = (lane & 4) ? ((s + 3) & 3) : ((s + 1) & 3);
                    uint32_t* dst = g_buf2 + (sl * 3 + (col >> 8)) * 2048 + ((lane >> 1) & 1) * 1024 + (col & 255) * 4 + wd;
                    asm volatile("" : "+l"(dst));
                    uint4 v0, v1, v2, v3;
                    uint32_t guard = 0;
                    while (true) {
                        v0 = ld_relaxed4(rin); v1 = ld_relaxed4(rin + 512);
                        v2 = ld_relaxed4(rin + 1024); v3 = ld_relaxed4(rin + 1536);
                        if (__all_sync(0xffffffffu, ok4(v0, tag) && ok4(v1, tag) && ok4(v2, tag) && ok4(v3, tag))) break;
                        if (++guard > (1u << 22)) __trap();
                    }
                    TR(11);
                    float a0 = uf(v0.x) + uf(v1.x), a1 = uf(v0.y) + uf(v1.y), a2 = uf(v0.z) + uf(v1.z), a3 = uf(v0.w) + uf(v1.w);
                    float b0 = uf(v2.x) + uf(v3.x), b1 = uf(v2.y) + uf(v3.y), b2 = uf(v2.z) + uf(v3.z), b3 = uf(v2.w) + uf(v3.w);
                    const bool u16 = lane & 16;
                    float k0 = (u16 ? b0 : a0) + __shfl_xor_sync(0xffffffffu, u16 ? a0 : b0, 16);
                    float k1 = (u16 ? b1 : a1) + __shfl_xor_sync(0xffffffffu, u16 ? a1 : b1, 16);
                    float k2 = (u16 ? b2 : a2) + __shfl_xor_sync(0xffffffffu, u16 ? a2 : b2, 16);
                    float k3 = (u16 ? b3 : a3) + __shfl_xor_sync(0xffffffffu, u16 ? a3 : b3, 16);
                    const bool u8 = lane & 8;
                    float m0 = (u8 ? k2 : k0) + __shfl_xor_sync(0xffffffffu, u8 ? k0 : k2, 8);
                    float m1 = (u8 ? k3 : k1) + __shfl_xor_sync(0xffffffffu, u8 ? k1 : k3, 8);
                    m0 += __shfl_xor_sync(0xffffffffu, m0, 4); m1 += __shfl_xor_sync(0xffffffffu, m1, 4);
                    m0 += __shfl_xor_sync(0xffffffffu, m0, 2); m1 += __shfl_xor_sync(0xffffffffu, m1, 2);
                    st_relaxed1(dst, (lane & 4) ? 0xFFFFFFFFu : pack2(m0, m1));
                    TR(12);
                }
            }
        }
    }
    cluster_sync();
}

constexpr int G_STAGES = 5;
constexpr int G_STAGE_BYTES = 32768;
constexpr int G_SMEM = G_STAGES * G_STAGE_BYTES + 1024 + 256;

__device__ __forceinline__ void tma2d(uint32_t dst, const CUtensorMap* map, int c0, int c1, uint32_t bar) {
    asm volatile("cp.async.bulk.tensor.2d.shared::cluster.global.mbarrier::complete_tx::bytes [%0], [%1, {%2, %3}], [%4];"
                 :: "r"(dst), "l"(map), "r"(c0), "r"(c1), "r"(bar) : "memory");
}
__device__ __forceinline__ void wg_ss128(float* d, uint64_t da, uint64_t db, int sc) {
    asm volatile("{\n\t.reg .pred p;\n\tsetp.ne.b32 p, %66, 0;\n\t"
        "wgmma.mma_async.sync.aligned.m64n128k16.f32.bf16.bf16 "
        "{%0,%1,%2,%3,%4,%5,%6,%7,%8,%9,%10,%11,%12,%13,%14,%15,%16,%17,%18,%19,%20,%21,%22,%23,%24,%25,%26,%27,%28,%29,%30,%31,"
        "%32,%33,%34,%35,%36,%37,%38,%39,%40,%41,%42,%43,%44,%45,%46,%47,%48,%49,%50,%51,%52,%53,%54,%55,%56,%57,%58,%59,%60,%61,%62,%63}, "
        "%64, %65, p, 1, 1, 0, 1;\n\t}"
        : "+f"(d[0]), "+f"(d[1]), "+f"(d[2]), "+f"(d[3]), "+f"(d[4]), "+f"(d[5]), "+f"(d[6]), "+f"(d[7]),
          "+f"(d[8]), "+f"(d[9]), "+f"(d[10]), "+f"(d[11]), "+f"(d[12]), "+f"(d[13]), "+f"(d[14]), "+f"(d[15]),
          "+f"(d[16]), "+f"(d[17]), "+f"(d[18]), "+f"(d[19]), "+f"(d[20]), "+f"(d[21]), "+f"(d[22]), "+f"(d[23]),
          "+f"(d[24]), "+f"(d[25]), "+f"(d[26]), "+f"(d[27]), "+f"(d[28]), "+f"(d[29]), "+f"(d[30]), "+f"(d[31]),
          "+f"(d[32]), "+f"(d[33]), "+f"(d[34]), "+f"(d[35]), "+f"(d[36]), "+f"(d[37]), "+f"(d[38]), "+f"(d[39]),
          "+f"(d[40]), "+f"(d[41]), "+f"(d[42]), "+f"(d[43]), "+f"(d[44]), "+f"(d[45]), "+f"(d[46]), "+f"(d[47]),
          "+f"(d[48]), "+f"(d[49]), "+f"(d[50]), "+f"(d[51]), "+f"(d[52]), "+f"(d[53]), "+f"(d[54]), "+f"(d[55]),
          "+f"(d[56]), "+f"(d[57]), "+f"(d[58]), "+f"(d[59]), "+f"(d[60]), "+f"(d[61]), "+f"(d[62]), "+f"(d[63])
        : "l"(da), "l"(db), "r"(sc));
}

template <int EPI>
__global__ void __launch_bounds__(384, 1)
k_gemm(const __grid_constant__ CUtensorMap mapA, const __grid_constant__ CUtensorMap mapB, int K,
       const bf16* __restrict__ xin, bf16* __restrict__ outp) {
    extern __shared__ uint8_t smem_raw[];
    const uint32_t sb = (smem_u32(smem_raw) + 1023u) & ~1023u;
    const uint32_t bars = sb + G_STAGES * G_STAGE_BYTES;
    const int tid = threadIdx.x, lane = tid & 31, wg = tid >> 7;
    const int n0 = blockIdx.x * 128, m0 = blockIdx.y * 128;
    const int nk = K / 64;
    if (tid == 0) {
        for (int i = 0; i < G_STAGES; i++) { mbar_init(bars + i * 8, 1); mbar_init(bars + 64 + i * 8, 8); }
        asm volatile("fence.mbarrier_init.release.cluster;" ::: "memory");
    }
    __syncthreads();
    if (wg == 0) {
        if (tid == 0) {
            for (int kb = 0; kb < nk; kb++) {
                const int st = kb % G_STAGES;
                if (kb >= G_STAGES) mbar_wait(bars + 64 + st * 8, ((kb / G_STAGES) - 1) & 1);
                const uint32_t a = sb + st * G_STAGE_BYTES;
                mbar_expect(bars + st * 8, G_STAGE_BYTES);
                tma2d(a, &mapA, kb * 64, m0, bars + st * 8);
                tma2d(a + 16384, &mapB, n0, kb * 64, bars + st * 8);
                tma2d(a + 16384 + 8192, &mapB, n0 + 64, kb * 64, bars + st * 8);
            }
        }
    } else {
        float d[64];
        #pragma unroll
        for (int i = 0; i < 64; i++) d[i] = 0.f;
        const int cw = wg - 1;
        for (int kb = 0; kb < nk; kb++) {
            const int st = kb % G_STAGES;
            mbar_wait(bars + st * 8, (kb / G_STAGES) & 1);
            const uint32_t a = sb + st * G_STAGE_BYTES;
            const uint64_t da = make_desc(a + cw * 8192, 16, 1024, 1);
            const uint64_t db = make_desc(a + 16384, 8192, 1024, 1);
            wg_fence();
            #pragma unroll
            for (int k = 0; k < 4; k++) wg_ss128(d, da + (uint64_t)(k * 2), db + (uint64_t)(k * 128), 1);
            wg_commit();
            if (kb > 0) {
                wg_wait<1>();
                if (lane == 0) mbar_arrive(bars + 64 + ((kb - 1) % G_STAGES) * 8);
            }
        }
        wg_wait<0>();
        const int g = lane >> 2, t = lane & 3, w = (tid >> 5) & 3;
        const int ldo = EPI == 1 ? FF : DM;
        #pragma unroll
        for (int hf = 0; hf < 2; hf++) {
            const int row = m0 + cw * 64 + w * 16 + g + 8 * hf;
            #pragma unroll
            for (int j = 0; j < 16; j++) {
                const int col = n0 + j * 8 + 2 * t;
                float a0 = bfr(d[4 * j + 2 * hf]), a1 = bfr(d[4 * j + 2 * hf + 1]);
                uint32_t o;
                if (EPI == 1) {
                    o = pack2(a0 / (1.0f + __expf(-a0)), a1 / (1.0f + __expf(-a1)));
                } else {
                    const float2 gm = *(const float2*)(g_mod + (EPI == 0 ? 2 : 5) * DM + col);
                    const uint32_t xv = *(const uint32_t*)(xin + (size_t)row * DM + col);
                    o = pack2(bflo(xv) + bfr(gm.x * a0), bfhi(xv) + bfr(gm.y * a1));
                }
                *(uint32_t*)(outp + (size_t)row * ldo + col) = o;
            }
        }
    }
}

typedef CUresult (*EncodeFn)(CUtensorMap*, CUtensorMapDataType, cuuint32_t, void*, const cuuint64_t*, const cuuint64_t*,
                             const cuuint32_t*, const cuuint32_t*, CUtensorMapInterleave, CUtensorMapSwizzle,
                             CUtensorMapL2promotion, CUtensorMapFloatOOBfill);

static void make_map(EncodeFn fn, CUtensorMap* m, const void* ptr, uint64_t inner, uint64_t outer, uint32_t bi, uint32_t bo) {
    cuuint64_t dims[2] = {inner, outer};
    cuuint64_t strides[1] = {inner * 2};
    cuuint32_t box[2] = {bi, bo};
    cuuint32_t es[2] = {1, 1};
    fn(m, CU_TENSOR_MAP_DATA_TYPE_BFLOAT16, 2, (void*)ptr, dims, strides, box, es, CU_TENSOR_MAP_INTERLEAVE_NONE,
       CU_TENSOR_MAP_SWIZZLE_128B, CU_TENSOR_MAP_L2_PROMOTION_L2_256B, CU_TENSOR_MAP_FLOAT_OOB_FILL_NONE);
}

extern "C" void kernel_launch(void* const* d_in, const int* in_sizes, int n_in, void* d_out, int out_size) {
    const bf16* x = (const bf16*)d_in[0];
    const bf16* mem0 = (const bf16*)d_in[1];
    const bf16* Wq = (const bf16*)d_in[2];
    const bf16* Wk = (const bf16*)d_in[3];
    const bf16* Wv = (const bf16*)d_in[4];
    const bf16* Wo = (const bf16*)d_in[5];
    const bf16* w1 = (const bf16*)d_in[8];
    const bf16* w2 = (const bf16*)d_in[9];
    const bf16* c = (const bf16*)d_in[10];
    const bf16* wmod = (const bf16*)d_in[11];
    bf16* out = (bf16*)d_out;

    static EncodeFn enc = nullptr;
    static void *p_ox, *p_x1, *p_h2, *p_act;
    if (!enc) {
        cudaDriverEntryPointQueryResult qr;
        void* f = nullptr;
        cudaGetDriverEntryPoint("cuTensorMapEncodeTiled", &f, cudaEnableDefault, &qr);
        enc = (EncodeFn)f;
        cudaGetSymbolAddress(&p_ox, g_ox);
        cudaGetSymbolAddress(&p_x1, g_x1);
        cudaGetSymbolAddress(&p_h2, g_h2);
        cudaGetSymbolAddress(&p_act, g_act);
        cudaFuncSetAttribute(k_rec, cudaFuncAttributeMaxDynamicSharedMemorySize, SM_TOTAL);
        cudaFuncSetAttribute(k_gemm<0>, cudaFuncAttributeMaxDynamicSharedMemorySize, G_SMEM);
        cudaFuncSetAttribute(k_gemm<1>, cudaFuncAttributeMaxDynamicSharedMemorySize, G_SMEM);
        cudaFuncSetAttribute(k_gemm<2>, cudaFuncAttributeMaxDynamicSharedMemorySize, G_SMEM);
    }
    CUtensorMap mOx, mWo, mH2, mW1, mAct, mW2;
    make_map(enc, &mOx, p_ox, HD, SEQ, 64, 128);
    make_map(enc, &mWo, Wo, DM, HD, 64, 64);
    make_map(enc, &mH2, p_h2, DM, SEQ, 64, 128);
    make_map(enc, &mW1, w1, FF, DM, 64, 64);
    make_map(enc, &mAct, p_act, FF, SEQ, 64, 128);
    make_map(enc, &mW2, w2, DM, FF, 64, 64);

    cudaStream_t st = cudaStreamPerThread;
    k_mod<<<60, 256, 0, st>>>(c, wmod);
    k_ln<0><<<SEQ / 8, 256, 0, st>>>(x);
    {
        cudaLaunchConfig_t cfg = {};
        cfg.gridDim = dim3(96); cfg.blockDim = dim3(512); cfg.dynamicSmemBytes = SM_TOTAL; cfg.stream = st;
        cudaLaunchAttribute at[1];
        at[0].id = cudaLaunchAttributeClusterDimension;
        at[0].val.clusterDim.x = 3; at[0].val.clusterDim.y = 1; at[0].val.clusterDim.z = 1;
        cfg.attrs = at; cfg.numAttrs = 1;
        cudaLaunchKernelEx(&cfg, k_rec, mem0, Wq, Wk, Wv, Wo);
    }
    k_gemm<0><<<dim3(5, 16), 384, G_SMEM, st>>>(mOx, mWo, HD, x, (bf16*)p_x1);
    k_ln<1><<<SEQ / 8, 256, 0, st>>>(nullptr);
    k_gemm<1><<<dim3(12, 16), 384, G_SMEM, st>>>(mH2, mW1, DM, nullptr, (bf16*)p_act);
    k_gemm<2><<<dim3(5, 16), 384, G_SMEM, st>>>(mAct, mW2, FF, (const bf16*)p_x1, out);
}
```

```cpp
#include <cuda_runtime.h>
#include <cuda_bf16.h>
#include <cuda.h>
#include <stdint.h>

typedef __nv_bfloat16 bf16;
#define VX_THROTTLE 1
#define VM_THROTTLE 1

constexpr int SEQ = 2048, DM = 640, NH = 32, DH = 192, NSEG = 64, FF = 1536, HD = NH * DH;

__device__ float g_mod[6 * DM];
__device__ __align__(1024) bf16 g_ht[(size_t)SEQ * DM];
__device__ __align__(1024) bf16 g_ox[(size_t)SEQ * HD];
__device__ __align__(1024) bf16 g_x1[(size_t)SEQ * DM];
__device__ __align__(1024) bf16 g_h2[(size_t)SEQ * DM];
__device__ __align__(1024) bf16 g_act[(size_t)SEQ * FF];
__device__ __align__(8192) uint32_t g_buf1[80 * 2 * 2048];
__device__ __align__(8192) uint32_t g_buf2[4 * 3 * 2048];
__device__ uint32_t g_choice[128];
__device__ uint32_t g_epoch;
#define TR(k)

#define FRESH(x) asm volatile("" : "+r"(x))
__device__ __forceinline__ float bfr(float x) { return __bfloat162float(__float2bfloat16_rn(x)); }
__device__ __forceinline__ uint32_t pack2(float a, float b) {
    uint32_t r; asm("cvt.rn.bf16x2.f32 %0, %1, %2;" : "=r"(r) : "f"(b), "f"(a)); return r;
}
__device__ __forceinline__ float bflo(uint32_t v) { return __uint_as_float(v << 16); }
__device__ __forceinline__ float bfhi(uint32_t v) { return __uint_as_float(v & 0xffff0000u); }
__device__ __forceinline__ float ex2(float x) { float r; asm("ex2.approx.ftz.f32 %0, %1;" : "=f"(r) : "f"(x)); return r; }
__device__ __forceinline__ float rcpf(float x) { float r; asm("rcp.approx.ftz.f32 %0, %1;" : "=f"(r) : "f"(x)); return r; }
__device__ __forceinline__ void score2(float& a, float& b) {
    const float SCALE = 0.07216878364870322f;
    uint32_t u = pack2(a, b);
    u = pack2(bflo(u) * SCALE, bfhi(u) * SCALE);
    a = bflo(u); b = bfhi(u);
}
__device__ __forceinline__ uint32_t smem_u32(const void* p) { return (uint32_t)__cvta_generic_to_shared(p); }

__device__ __forceinline__ void mbar_init(uint32_t bar, uint32_t cnt) {
    asm volatile("mbarrier.init.shared::cta.b64 [%0], %1;" :: "r"(bar), "r"(cnt) : "memory");
}
__device__ __forceinline__ void mbar_arrive(uint32_t bar) {
    asm volatile("mbarrier.arrive.shared::cta.b64 _, [%0];" :: "r"(bar) : "memory");
}
__device__ __forceinline__ void mbar_expect(uint32_t bar, uint32_t bytes) {
    asm volatile("mbarrier.arrive.expect_tx.shared::cta.b64 _, [%0], %1;" :: "r"(bar), "r"(bytes) : "memory");
}
__device__ __forceinline__ bool mbar_try(uint32_t bar, uint32_t parity) {
    uint32_t ok;
    asm volatile("{\n\t.reg .pred p;\n\tmbarrier.try_wait.parity.shared::cta.b64 p, [%1], %2;\n\tselp.u32 %0, 1, 0, p;\n\t}"
                 : "=r"(ok) : "r"(bar), "r"(parity) : "memory");
    return ok != 0;
}
__device__ __forceinline__ bool mbar_try_cluster(uint32_t bar, uint32_t parity) {
    uint32_t ok;
    asm volatile("{\n\t.reg .pred p;\n\tmbarrier.try_wait.parity.acquire.cluster.shared::cta.b64 p, [%1], %2;\n\tselp.u32 %0, 1, 0, p;\n\t}"
                 : "=r"(ok) : "r"(bar), "r"(parity) : "memory");
    return ok != 0;
}
__device__ __forceinline__ void mbar_wait(uint32_t bar, uint32_t parity) {
    uint32_t guard = 0;
    while (!mbar_try(bar, parity)) { if (++guard > (1u << 22)) __trap(); }
}
__device__ __forceinline__ void mbar_wait_cluster(uint32_t bar, uint32_t parity) {
    uint32_t guard = 0;
    while (!mbar_try_cluster(bar, parity)) { if (++guard > (1u << 22)) __trap(); }
}
__device__ __forceinline__ void bar_sync(int id, int n) { asm volatile("bar.sync %0, %1;" :: "r"(id), "r"(n) : "memory"); }
__device__ __forceinline__ void bar_arrive(int id, int n) { asm volatile("bar.arrive %0, %1;" :: "r"(id), "r"(n) : "memory"); }
__device__ __forceinline__ void sts1(uint32_t a, uint32_t v) { asm volatile("st.shared.u32 [%0], %1;" :: "r"(a), "r"(v) : "memory"); }
__device__ __forceinline__ uint32_t lds1(uint32_t a) { uint32_t v; asm volatile("ld.shared.u32 %0, [%1];" : "=r"(v) : "r"(a) : "memory"); return v; }
__device__ __forceinline__ void fence_async() { asm volatile("fence.proxy.async.shared::cta;" ::: "memory"); }
__device__ __forceinline__ void cluster_sync() {
    asm volatile("barrier.cluster.arrive.release.aligned;\n\tbarrier.cluster.wait.acquire.aligned;" ::: "memory");
}
__device__ __forceinline__ uint32_t mapa(uint32_t a, uint32_t rank) {
    uint32_t r; asm("mapa.shared::cluster.u32 %0, %1, %2;" : "=r"(r) : "r"(a), "r"(rank)); return r;
}
__device__ __forceinline__ void st_async1(uint32_t a, uint32_t v, uint32_t bar) {
    asm volatile("st.async.weak.shared::cluster.mbarrier::complete_tx::bytes.b32 [%0], %1, [%2];" :: "r"(a), "r"(v), "r"(bar) : "memory");
}
__device__ __forceinline__ void st_async2(uint32_t a, float x, float y, uint32_t bar) {
    asm volatile("st.async.weak.shared::cluster.mbarrier::complete_tx::bytes.v2.f32 [%0], {%1,%2}, [%3];" :: "r"(a), "f"(x), "f"(y), "r"(bar) : "memory");
}
__device__ __forceinline__ void st_async4(uint32_t a, const float* c, uint32_t bar) {
    asm volatile("st.async.weak.shared::cluster.mbarrier::complete_tx::bytes.v4.f32 [%0], {%1,%2,%3,%4}, [%5];"
                 :: "r"(a), "f"(c[0]), "f"(c[1]), "f"(c[2]), "f"(c[3]), "r"(bar) : "memory");
}
__device__ __forceinline__ void bulk_g2s(uint32_t dst, const void* src, uint32_t bytes, uint32_t bar) {
    asm volatile("cp.async.bulk.shared::cluster.global.mbarrier::complete_tx::bytes [%0], [%1], %2, [%3];"
                 :: "r"(dst), "l"(src), "r"(bytes), "r"(bar) : "memory");
}
__device__ __forceinline__ void cpa16(uint32_t s, const void* g) {
    asm volatile("cp.async.cg.shared.global [%0], [%1], 16;" :: "r"(s), "l"(g) : "memory");
}
__device__ __forceinline__ void cpa_wait_all() { asm volatile("cp.async.wait_all;" ::: "memory"); }
__device__ __forceinline__ void ldsm4(uint32_t* r, uint32_t a) {
    asm volatile("ldmatrix.sync.aligned.m8n8.x4.shared.b16 {%0,%1,%2,%3}, [%4];" : "=r"(r[0]), "=r"(r[1]), "=r"(r[2]), "=r"(r[3]) : "r"(a) : "memory");
}
__device__ __forceinline__ void ldsm4t(uint32_t* r, uint32_t a) {
    asm volatile("ldmatrix.sync.aligned.m8n8.x4.trans.shared.b16 {%0,%1,%2,%3}, [%4];" : "=r"(r[0]), "=r"(r[1]), "=r"(r[2]), "=r"(r[3]) : "r"(a) : "memory");
}
__device__ __forceinline__ void stsm2t(uint32_t a, uint32_t r0, uint32_t r1) {
    asm volatile("stmatrix.sync.aligned.m8n8.x2.trans.shared.b16 [%0], {%1,%2};" :: "r"(a), "r"(r0), "r"(r1) : "memory");
}
__device__ __forceinline__ void stsm4t(uint32_t a, uint32_t r0, uint32_t r1, uint32_t r2, uint32_t r3) {
    asm volatile("stmatrix.sync.aligned.m8n8.x4.trans.shared.b16 [%0], {%1,%2,%3,%4};" :: "r"(a), "r"(r0), "r"(r1), "r"(r2), "r"(r3) : "memory");
}
__device__ __forceinline__ uint32_t movm(uint32_t v) {
    uint32_t r; asm volatile("movmatrix.sync.aligned.m8n8.trans.b16 %0, %1;" : "=r"(r) : "r"(v)); return r;
}
__device__ __forceinline__ void mma16(float* c, uint32_t a0, uint32_t a1, uint32_t a2, uint32_t a3, uint32_t b0, uint32_t b1) {
    asm volatile("mma.sync.aligned.m16n8k16.row.col.f32.bf16.bf16.f32 {%0,%1,%2,%3}, {%4,%5,%6,%7}, {%8,%9}, {%0,%1,%2,%3};"
                 : "+f"(c[0]), "+f"(c[1]), "+f"(c[2]), "+f"(c[3]) : "r"(a0), "r"(a1), "r"(a2), "r"(a3), "r"(b0), "r"(b1));
}
__device__ __forceinline__ void mma8(float* c, uint32_t a0, uint32_t a1, uint32_t b0) {
    asm volatile("mma.sync.aligned.m16n8k8.row.col.f32.bf16.bf16.f32 {%0,%1,%2,%3}, {%4,%5}, {%6}, {%0,%1,%2,%3};"
                 : "+f"(c[0]), "+f"(c[1]), "+f"(c[2]), "+f"(c[3]) : "r"(a0), "r"(a1), "r"(b0));
}
__host__ __device__ constexpr uint64_t make_desc(uint32_t saddr, uint32_t lbo, uint32_t sbo, uint32_t layout) {
    return (uint64_t)((saddr & 0x3FFFF) >> 4) | ((uint64_t)(lbo >> 4) << 16) | ((uint64_t)(sbo >> 4) << 32) | ((uint64_t)layout << 62);
}
__device__ __forceinline__ void wg_fence() { asm volatile("wgmma.fence.sync.aligned;" ::: "memory"); }
__device__ __forceinline__ void wg_commit() { asm volatile("wgmma.commit_group.sync.aligned;" ::: "memory"); }
template <int N> __device__ __forceinline__ void wg_wait() { asm volatile("wgmma.wait_group.sync.aligned %0;" :: "n"(N) : "memory"); }

#define D16(C) C(d[0]), C(d[1]), C(d[2]), C(d[3]), C(d[4]), C(d[5]), C(d[6]), C(d[7]), \
               C(d[8]), C(d[9]), C(d[10]), C(d[11]), C(d[12]), C(d[13]), C(d[14]), C(d[15])
#define DREG16 "{%0,%1,%2,%3,%4,%5,%6,%7,%8,%9,%10,%11,%12,%13,%14,%15}"
__device__ __forceinline__ void wg_rs32(float* d, const uint32_t* a, uint64_t db, bool acc) {
    if (acc)
        asm volatile("wgmma.mma_async.sync.aligned.m64n32k16.f32.bf16.bf16 " DREG16 ", {%16,%17,%18,%19}, %20, 1, 1, 1, 0;"
            : D16("+f") : "r"(a[0]), "r"(a[1]), "r"(a[2]), "r"(a[3]), "l"(db));
    else
        asm volatile("wgmma.mma_async.sync.aligned.m64n32k16.f32.bf16.bf16 " DREG16 ", {%16,%17,%18,%19}, %20, 0, 1, 1, 0;"
            : D16("=f") : "r"(a[0]), "r"(a[1]), "r"(a[2]), "r"(a[3]), "l"(db));
}
__device__ __forceinline__ void wg_ss32(float* d, uint64_t da, uint64_t db, bool acc) {
    if (acc)
        asm volatile("wgmma.mma_async.sync.aligned.m64n32k16.f32.bf16.bf16 " DREG16 ", %16, %17, 1, 1, 1, 1, 0;"
            : D16("+f") : "l"(da), "l"(db));
    else
        asm volatile("wgmma.mma_async.sync.aligned.m64n32k16.f32.bf16.bf16 " DREG16 ", %16, %17, 0, 1, 1, 1, 0;"
            : D16("=f") : "l"(da), "l"(db));
}
__device__ __forceinline__ void wg_ss8(float* d, uint64_t da, uint64_t db, bool acc) {
    if (acc)
        asm volatile("wgmma.mma_async.sync.aligned.m64n8k16.f32.bf16.bf16 {%0,%1,%2,%3}, %4, %5, 1, 1, 1, 1, 1;"
            : "+f"(d[0]), "+f"(d[1]), "+f"(d[2]), "+f"(d[3]) : "l"(da), "l"(db));
    else
        asm volatile("wgmma.mma_async.sync.aligned.m64n8k16.f32.bf16.bf16 {%0,%1,%2,%3}, %4, %5, 0, 1, 1, 1, 1;"
            : "=f"(d[0]), "=f"(d[1]), "=f"(d[2]), "=f"(d[3]) : "l"(da), "l"(db));
}
template <int OFF> __device__ __forceinline__ void ldsm4t_i(uint32_t* r, uint32_t a) {
    asm volatile("ldmatrix.sync.aligned.m8n8.x4.trans.shared.b16 {%0,%1,%2,%3}, [%4+%5];"
                 : "=r"(r[0]), "=r"(r[1]), "=r"(r[2]), "=r"(r[3]) : "r"(a), "n"(OFF) : "memory");
}

__device__ __forceinline__ uint4 ld_relaxed4(const void* p) {
    uint4 v;
    asm volatile("ld.relaxed.gpu.global.v4.u32 {%0,%1,%2,%3}, [%4];" : "=r"(v.x), "=r"(v.y), "=r"(v.z), "=r"(v.w) : "l"(p) : "memory");
    return v;
}
__device__ __forceinline__ void st_relaxed2(void* p, uint32_t a, uint32_t b) {
    asm volatile("st.relaxed.gpu.global.v2.u32 [%0], {%1,%2};" :: "l"(p), "r"(a), "r"(b) : "memory");
}
__device__ __forceinline__ void st_relaxed2_off(void* base, uint32_t off, uint32_t a, uint32_t b) {
    asm volatile("{\n\t.reg .u64 ad;\n\tcvt.u64.u32 ad, %1;\n\tadd.u64 ad, ad, %0;\n\tst.relaxed.gpu.global.v2.u32 [ad], {%2,%3};\n\t}"
                 :: "l"(base), "r"(off), "r"(a), "r"(b) : "memory");
}
__device__ __forceinline__ void st_relaxed1(void* p, uint32_t a) {
    asm volatile("st.relaxed.gpu.global.u32 [%0], %1;" :: "l"(p), "r"(a) : "memory");
}
__device__ __forceinline__ uint32_t ld_acquire1(const uint32_t* p) {
    uint32_t v; asm volatile("ld.acquire.gpu.global.u32 %0, [%1];" : "=r"(v) : "l"(p) : "memory"); return v;
}
__device__ __forceinline__ void st_release1(uint32_t* p, uint32_t a) {
    asm volatile("st.release.gpu.global.u32 [%0], %1;" :: "l"(p), "r"(a) : "memory");
}
__device__ __forceinline__ uint4 lds4(uint32_t s) {
    uint4 v; asm volatile("ld.shared.v4.u32 {%0,%1,%2,%3}, [%4];" : "=r"(v.x), "=r"(v.y), "=r"(v.z), "=r"(v.w) : "r"(s) : "memory"); return v;
}
__device__ __forceinline__ void sts4(uint32_t s, const uint4& v) {
    asm volatile("st.shared.v4.u32 [%0], {%1,%2,%3,%4};" :: "r"(s), "r"(v.x), "r"(v.y), "r"(v.z), "r"(v.w) : "memory");
}
__device__ __forceinline__ float4 lds4f(uint32_t s) {
    float4 v; asm volatile("ld.shared.v4.f32 {%0,%1,%2,%3}, [%4];" : "=f"(v.x), "=f"(v.y), "=f"(v.z), "=f"(v.w) : "r"(s) : "memory"); return v;
}
__device__ __forceinline__ uint2 lds2(uint32_t s) {
    uint2 v; asm volatile("ld.shared.v2.u32 {%0,%1}, [%2];" : "=r"(v.x), "=r"(v.y) : "r"(s) : "memory"); return v;
}
__device__ __forceinline__ float2 lds2f(uint32_t s) {
    float2 v; asm volatile("ld.shared.v2.f32 {%0,%1}, [%2];" : "=f"(v.x), "=f"(v.y) : "r"(s) : "memory"); return v;
}
__device__ __forceinline__ uint32_t clk32() { uint32_t c; asm volatile("mov.u32 %0, %%clock;" : "=r"(c) :: "memory"); return c; }
__device__ __forceinline__ uint32_t tagw(float v, uint32_t tag) { return ((__float_as_uint(v) + 8u) & ~15u) | tag; }
__device__ __forceinline__ bool ok4(const uint4& v, uint32_t tag) { return (((v.x ^ tag) | (v.y ^ tag) | (v.z ^ tag) | (v.w ^ tag)) & 15u) == 0; }
__device__ __forceinline__ bool oks(const uint4& v) { return v.x != 0xFFFFFFFFu && v.y != 0xFFFFFFFFu && v.z != 0xFFFFFFFFu && v.w != 0xFFFFFFFFu; }
__device__ __forceinline__ float uf(uint32_t x) { return __uint_as_float(x & ~15u); }

__global__ void __launch_bounds__(256) k_mod(const bf16* __restrict__ c, const bf16* __restrict__ wmod) {
    __shared__ float sc[DM];
    __shared__ float red[8][64];
    const int tid = threadIdx.x;
    for (int i = tid; i < DM; i += 256) {
        float v = __bfloat162float(c[i]);
        sc[i] = bfr(v / (1.0f + __expf(-v)));
    }
    __syncthreads();
    const int cp = tid & 31, kg = tid >> 5;
    const int col = blockIdx.x * 64 + cp * 2;
    float a0 = 0.f, a1 = 0.f;
    #pragma unroll 8
    for (int k = kg * 80; k < kg * 80 + 80; k++) {
        uint32_t w = *(const uint32_t*)(wmod + (size_t)k * (6 * DM) + col);
        a0 += sc[k] * bflo(w); a1 += sc[k] * bfhi(w);
    }
    red[kg][cp * 2] = a0; red[kg][cp * 2 + 1] = a1;
    __syncthreads();
    if (tid < 64) {
        float s = 0.f;
        #pragma unroll
        for (int i = 0; i < 8; i++) s += red[i][tid];
        g_mod[blockIdx.x * 64 + tid] = bfr(s);
    }
    if (blockIdx.x == 0 && tid == 0) g_epoch = g_epoch + 1;
}

template <int MODE>
__global__ void __launch_bounds__(256) k_ln(const bf16* __restrict__ xin) {
    const int lane = threadIdx.x & 31, row = blockIdx.x * 8 + (threadIdx.x >> 5);
    const bf16* src = (MODE == 0 ? xin : g_x1) + (size_t)row * DM;
    const float* shift = g_mod + (MODE == 0 ? 0 : 3 * DM);
    const float* scale = g_mod + (MODE == 0 ? DM : 4 * DM);
    float v[3][8];
    float s = 0.f;
    #pragma unroll
    for (int i = 0; i < 3; i++) {
        int c = lane + 32 * i;
        if (c < 80) {
            uint4 u = *(const uint4*)(src + c * 8);
            v[i][0] = bflo(u.x); v[i][1] = bfhi(u.x); v[i][2] = bflo(u.y); v[i][3] = bfhi(u.y);
            v[i][4] = bflo(u.z); v[i][5] = bfhi(u.z); v[i][6] = bflo(u.w); v[i][7] = bfhi(u.w);
        } else {
            #pragma unroll
            for (int j = 0; j < 8; j++) v[i][j] = 0.f;
        }
        #pragma unroll
        for (int j = 0; j < 8; j++) s += v[i][j];
    }
    #pragma unroll
    for (int o = 16; o > 0; o >>= 1) s += __shfl_xor_sync(0xffffffffu, s, o);
    const float mean = s * (1.0f / DM);
    float q = 0.f;
    #pragma unroll
    for (int i = 0; i < 3; i++) {
        if (lane + 32 * i < 80) {
            #pragma unroll
            for (int j = 0; j < 8; j++) { float d = v[i][j] - mean; q += d * d; }
        }
    }
    #pragma unroll
    for (int o = 16; o > 0; o >>= 1) q += __shfl_xor_sync(0xffffffffu, q, o);
    const float mb = bfr(mean);
    const float var = bfr(q * (1.0f / DM));
    const float sd = bfr(sqrtf(bfr(var + 1e-5f)));
    #pragma unroll
    for (int i = 0; i < 3; i++) {
        int c = lane + 32 * i;
        if (c < 80) {
            float o[8];
            #pragma unroll
            for (int j = 0; j < 8; j++) {
                float n = bfr(bfr(v[i][j] - mb) / sd);
                float m1 = bfr(1.0f + scale[c * 8 + j]);
                o[j] = bfr(n * m1) + shift[c * 8 + j];
            }
            uint4 u = make_uint4(pack2(o[0], o[1]), pack2(o[2], o[3]), pack2(o[4], o[5]), pack2(o[6], o[7]));
            if (MODE == 0) {
                int seg = row >> 5, r = row & 31, blk = c >> 3, cc = c & 7;
                *(uint4*)(g_ht + (size_t)seg * 20480 + blk * 2048 + r * 64 + ((cc ^ (r & 7)) << 3)) = u;
            } else {
                *(uint4*)(g_h2 + (size_t)row * DM + c * 8) = u;
            }
        }
    }
}

constexpr int SM_WV = 0;
constexpr int SM_HB = 81920;
constexpr int SM_WO = SM_HB + 40960;
constexpr int SM_QX = SM_WO + 77824;
constexpr int SM_KS = SM_QX + 4096;
constexpr int SM_QM = SM_KS + 5120;
constexpr int SM_XS = SM_QM + 1024;
constexpr int SM_MS = SM_XS + 12288;
constexpr int SM_OS = SM_MS + 3840;
constexpr int SM_PM = SM_OS + 3072;
constexpr int SM_BAR = SM_PM + 640;
constexpr int SM_CH = SM_BAR + 128;
constexpr int SM_TOTAL = SM_CH + 128;
static_assert(SM_TOTAL <= 232448, "smem");

enum { B_MEM_FULL = 0, B_MEM_FREE, B_HLO_FULL, B_HHI_FULL, B_HLO_FREE, B_HHI_FREE, B_MS, B_O, B_XS, B_O1, B_XSFREE };

__device__ __forceinline__ int probe_blk(uint32_t* blk) {
    uint32_t t0 = 0xffffffffu, t1 = 0xffffffffu, acc = 0;
    for (int rep = 0; rep < 3; rep++) {
        #pragma unroll
        for (int pg = 0; pg < 2; pg++) {
            uint32_t c0 = clk32();
            uint32_t v = atomicOr(blk + pg * 1024 + acc, 0u);
            acc = (v == 0x12345678u) ? 1u : 0u;
            asm volatile("" :: "r"(acc) : "memory");
            uint32_t c1 = clk32() + acc;
            uint32_t d = c1 - c0;
            if (rep > 0) { if (pg == 0) t0 = min(t0, d); else t1 = min(t1, d); }
        }
    }
    return t1 < t0 ? 1 : 0;
}

__device__ __forceinline__ uint32_t wo_tile_off(int w) {
    if (w < 8) return w * 6144;
    if (w < 12) return 8 * 6144 + (w - 8) * 4096;
    return 8 * 6144 + 4 * 4096 + (w - 12) * 6144;
}

template <int NRES, int NPRE>
__device__ __forceinline__ void wo_phase(uint32_t sb, int w, int lane, const uint32_t (*res)[4], uint32_t parity,
                                         uint32_t tag, int tile, int h) {
    FRESH(lane);
    const int er = (lane & 7) + 8 * (lane >> 4);
    const uint32_t aaddr = sb + SM_WO + wo_tile_off(w) + er * 32 + ((((lane >> 3) & 1) ^ ((er >> 2) & 1)) << 4);
    const uint32_t baddr = sb + SM_OS + lane * 16;
    float c0[4] = {0.f, 0.f, 0.f, 0.f}, c1[4] = {0.f, 0.f, 0.f, 0.f};
    uint32_t pre[NPRE > 4 ? NPRE : 4][4];
    if (NPRE >= 4) {
        #pragma unroll
        for (int i = 0; i < 4; i++) ldsm4t(pre[i], aaddr + i * 512);
        mbar_wait(sb + SM_BAR + B_O1 * 8, parity);
        uint32_t b[2][4];
        ldsm4t(b[0], baddr);
        ldsm4t(b[1], baddr + 512);
        #pragma unroll
        for (int kp = 0; kp < 2; kp++) {
            mma16(c0, pre[2 * kp][0], pre[2 * kp][1], pre[2 * kp][2], pre[2 * kp][3], b[kp][0], b[kp][1]);
            mma16(c1, pre[2 * kp + 1][0], pre[2 * kp + 1][1], pre[2 * kp + 1][2], pre[2 * kp + 1][3], b[kp][2], b[kp][3]);
        }
    } else {
        #pragma unroll
        for (int i = 0; i < 2; i++) ldsm4t(pre[i], aaddr + i * 512);
        mbar_wait(sb + SM_BAR + B_O1 * 8, parity);
        #pragma unroll
        for (int kp = 0; kp < 2; kp++) {
            uint32_t b[4];
            ldsm4t(b, baddr + kp * 512);
            if (kp == 1) { ldsm4t(pre[0], aaddr + 2 * 512); ldsm4t(pre[1], aaddr + 3 * 512); }
            mma16(c0, pre[0][0], pre[0][1], pre[0][2], pre[0][3], b[0], b[1]);
            mma16(c1, pre[1][0], pre[1][1], pre[1][2], pre[1][3], b[2], b[3]);
        }
    }
    #pragma unroll
    for (int i = 0; i < NPRE; i++) ldsm4t(pre[i], aaddr + (4 + i) * 512);
    uint32_t off0, off1;
    {
        uint32_t ch;
        asm volatile("ld.shared.u16 %0, [%1];" : "=r"(ch) : "r"(sb + SM_CH + 2 * tile) : "memory");
        const int j = h >> 4;
        const uint32_t base = (uint32_t)((tile * 4 + j) * 8192 + (h & 15) * 256 + lane * 8);
        ch >>= j;
        off0 = base + (ch & 1) * 4096;
        off1 = base + 16384 + (ch & 256) * 16;
    }
    mbar_wait(sb + SM_BAR + B_O * 8, parity);
    if (NRES == 4) {
        uint32_t b[4][4];
        #pragma unroll
        for (int i = 0; i < 4; i++) ldsm4t(b[i], baddr + (2 + i) * 512);
        #pragma unroll
        for (int i = 0; i < 2; i++) {
            mma16(c0, res[2 * i][0], res[2 * i][1], res[2 * i][2], res[2 * i][3], b[i][0], b[i][1]);
            mma16(c1, res[2 * i + 1][0], res[2 * i + 1][1], res[2 * i + 1][2], res[2 * i + 1][3], b[i][2], b[i][3]);
        }
        #pragma unroll
        for (int i = 0; i < 2; i++) {
            mma16(c0, pre[2 * i][0], pre[2 * i][1], pre[2 * i][2], pre[2 * i][3], b[2 + i][0], b[2 + i][1]);
            mma16(c1, pre[2 * i + 1][0], pre[2 * i + 1][1], pre[2 * i + 1][2], pre[2 * i + 1][3], b[2 + i][2], b[2 + i][3]);
        }
    } else if (NPRE == 4) {
        uint32_t b[2][4];
        #pragma unroll
        for (int hh = 0; hh < 2; hh++) {
            ldsm4t(b[0], baddr + (2 + 2 * hh) * 512);
            ldsm4t(b[1], baddr + (3 + 2 * hh) * 512);
            if (hh) {
                #pragma unroll
                for (int i = 0; i < 4; i++) ldsm4t(pre[i], aaddr + (8 + i) * 512);
            }
            #pragma unroll
            for (int i = 0; i < 2; i++) {
                mma16(c0, pre[2 * i][0], pre[2 * i][1], pre[2 * i][2], pre[2 * i][3], b[i][0], b[i][1]);
                mma16(c1, pre[2 * i + 1][0], pre[2 * i + 1][1], pre[2 * i + 1][2], pre[2 * i + 1][3], b[i][2], b[i][3]);
            }
        }
    }
    st_relaxed2_off(g_buf1, off0, tagw(c0[0] + c1[0], tag), tagw(c0[1] + c1[1], tag));
    st_relaxed2_off(g_buf1, off1, tagw(c0[2] + c1[2], tag), tagw(c0[3] + c1[3], tag));
}

template <int NT, bool MASK>
__device__ __forceinline__ void softmax_core(float (*sc)[2], int g, int t, uint32_t* pb) {
    const float L2E = 1.4426950408889634f;
    #pragma unroll
    for (int j = 0; j < NT; j++) score2(sc[j][0], sc[j][1]);
    if (MASK) {
        const float NEG = -999292928.0f;
        if (2 * t > g) sc[NT - 1][0] = NEG;
        if (2 * t + 1 > g) sc[NT - 1][1] = NEG;
    }
    float m[NT];
    #pragma unroll
    for (int j = 0; j < NT; j++) m[j] = fmaxf(sc[j][0], sc[j][1]);
    float mx = m[0];
    #pragma unroll
    for (int j = 1; j < NT; j++) mx = fmaxf(mx, m[j]);
    mx = fmaxf(mx, __shfl_xor_sync(0xffffffffu, mx, 1));
    mx = fmaxf(mx, __shfl_xor_sync(0xffffffffu, mx, 2));
    float s0 = 0.f, s1 = 0.f;
    #pragma unroll
    for (int j = 0; j < NT; j++) {
        sc[j][0] = ex2((sc[j][0] - mx) * L2E); sc[j][1] = ex2((sc[j][1] - mx) * L2E);
        s0 += sc[j][0]; s1 += sc[j][1];
    }
    s0 += s1;
    s0 += __shfl_xor_sync(0xffffffffu, s0, 1);
    s0 += __shfl_xor_sync(0xffffffffu, s0, 2);
    const float iv = rcpf(s0);
    #pragma unroll
    for (int j = 0; j < NT; j++) pb[j] = pack2(sc[j][0] * iv, sc[j][1] * iv);
}
template <int NT>
__device__ __forceinline__ void xsoftmax(uint32_t a, uint32_t pa, int g, int t) {
    float sc[NT][2];
    #pragma unroll
    for (int j = 0; j < NT; j++) {
        float2 v0 = lds2f(a + j * 512), v1 = lds2f(a + j * 512 + 4096), v2 = lds2f(a + j * 512 + 8192);
        sc[j][0] = v0.x + v1.x + v2.x; sc[j][1] = v0.y + v1.y + v2.y;
    }
    uint32_t pb[NT];
    softmax_core<NT, true>(sc, g, t, pb);
    #pragma unroll
    for (int j = 0; j < NT; j++) sts1(pa + j * 256, pb[j]);
}
template <int NJ>
__device__ __forceinline__ void xscores(uint32_t sb, int p, int mi, int j0, int lane) {
    FRESH(lane);
    const int r = lane & 7, cq = lane >> 3;
    const int qrow = mi * 16 + r + 8 * (cq & 1);
    uint32_t kb[NJ][8];
    float d[NJ][4];
    #pragma unroll
    for (int j = 0; j < NJ; j++) {
        ldsm4(kb[j], sb + SM_KS + ((j0 + j) * 8 + r) * 128 + ((cq ^ r) << 4));
        ldsm4(kb[j] + 4, sb + SM_KS + ((j0 + j) * 8 + r) * 128 + (((cq + 4) ^ r) << 4));
        d[j][0] = 0.f; d[j][1] = 0.f; d[j][2] = 0.f; d[j][3] = 0.f;
    }
    #pragma unroll
    for (int kt = 0; kt < 4; kt++) {
        uint32_t a[4];
        ldsm4(a, sb + SM_QX + qrow * 128 + (((2 * kt + (cq >> 1)) ^ r) << 4));
        #pragma unroll
        for (int j = 0; j < NJ; j++) mma16(d[j], a[0], a[1], a[2], a[3], kb[j][2 * kt], kb[j][2 * kt + 1]);
    }
    const uint32_t la = sb + SM_XS + p * 4096 + (mi * 3 + j0) * 512 + lane * 16;
    #pragma unroll
    for (int rk = 0; rk < 3; rk++) {
        const uint32_t ra = mapa(la, rk), rb = mapa(sb + SM_BAR + B_XS * 8, rk);
        #pragma unroll
        for (int j = 0; j < NJ; j++) st_async4(ra + j * 512, d[j], rb);
    }
}
__device__ __forceinline__ void mbar_arrive_remote(uint32_t bar) {
    asm volatile("mbarrier.arrive.relaxed.cluster.shared::cluster.b64 _, [%0];" :: "r"(bar) : "memory");
}

__global__ void __launch_bounds__(512, 1)
k_rec(const bf16* __restrict__ mem0, const bf16* __restrict__ Wq, const bf16* __restrict__ Wk,
      const bf16* __restrict__ Wv, const bf16* __restrict__ Wo) {
    extern __shared__ __align__(1024) uint8_t smem_raw[];
    constexpr uint32_t SBC = 1024;
    const uint32_t sb = smem_u32(smem_raw);
    if ((sb & 0xFFFFFFu) != SBC) __trap();
    int lane = __shfl_sync(0xffffffffu, threadIdx.x & 31, threadIdx.x & 31);
    const int warp = __shfl_sync(0xffffffffu, threadIdx.x >> 5, 0), wg = warp >> 2;
    const int tid = warp * 32 + lane;
    const int b = blockIdx.x, h = b / 3, p = b % 3;
    const int g = lane >> 2, t = lane & 3;
    const int tile0 = p == 0 ? 0 : (p == 1 ? 14 : 27);
    const int ntile = p == 0 ? 14 : 13;
    const uint32_t bar = sb + SM_BAR;

    if (tid == 0) {
        mbar_init(bar + B_MEM_FULL * 8, 4);
        mbar_init(bar + B_MEM_FREE * 8, 12);
        mbar_init(bar + B_HLO_FULL * 8, 1);
        mbar_init(bar + B_HHI_FULL * 8, 1);
        mbar_init(bar + B_HLO_FREE * 8, 12);
        mbar_init(bar + B_HHI_FREE * 8, 12);
        mbar_init(bar + B_MS * 8, 1);
        mbar_init(bar + B_O * 8, 1);
        mbar_init(bar + B_XS * 8, 1);
        mbar_init(bar + B_O1 * 8, 4);
        mbar_init(bar + B_XSFREE * 8, 12);
        asm volatile("fence.mbarrier_init.release.cluster;" ::: "memory");
        mbar_expect(bar + B_MS * 8, 3840);
        mbar_expect(bar + B_O * 8, 2048);
        mbar_expect(bar + B_XS * 8, 12288);
        mbar_expect(bar + B_HLO_FULL * 8, 12288);
        bulk_g2s(sb + SM_HB, g_ht, 12288, sb + SM_BAR + B_HLO_FULL * 8);
        mbar_expect(bar + B_HHI_FULL * 8, 28672);
        bulk_g2s(sb + SM_HB + 12288, (const char*)g_ht + 12288, 28672, sb + SM_BAR + B_HHI_FULL * 8);
    }
    cluster_sync();

    if (wg < 2) {
        asm volatile("setmaxnreg.inc.sync.aligned.u32 200;");
        const int w = warp & 3;
        uint32_t wa[40][4];
        {
            const bf16* W = (wg == 0 ? Wq : Wk) + (size_t)h * DH + p * 64 + w * 16 + t * 4;
            #pragma unroll
            for (int kt = 0; kt < 40; kt++) {
                uint2 l1 = __ldg((const uint2*)(W + (size_t)(kt * 16 + g) * HD));
                uint2 l2 = __ldg((const uint2*)(W + (size_t)(kt * 16 + 8 + g) * HD));
                wa[kt][0] = l1.x; wa[kt][1] = l1.y; wa[kt][2] = l2.x; wa[kt][3] = l2.y;
            }
            #pragma unroll
            for (int kt = 0; kt < 40; kt++) {
                #pragma unroll
                for (int i = 0; i < 4; i++) wa[kt][i] = movm(wa[kt][i]);
            }
        }

        const uint32_t dstx = sb + (wg == 0 ? SM_QX : SM_KS + 1024);

        for (int s = -1; s < NSEG; s++) {
            const uint32_t par = s & 1;
            FRESH(lane);
            const int g = lane >> 2, t = lane & 3, tid = warp * 32 + lane;
            if (s >= 0) {
                mbar_wait(bar + B_MEM_FULL * 8, par);
                TR(0);
                float c[4][4];
                #pragma unroll
                for (int i = 0; i < 4; i++) { c[i][0] = 0.f; c[i][1] = 0.f; c[i][2] = 0.f; c[i][3] = 0.f; }
                uint32_t maddr = sb + lane * 16;
                asm volatile("" : "+r"(maddr));
                #pragma unroll
                for (int kp = 0; kp < 20; kp++) {
                    uint32_t bb[4];
                    ldsm4t(bb, maddr + (SM_HB + kp * 512));
                    mma16(c[(kp & 1) * 2], wa[2 * kp][0], wa[2 * kp][1], wa[2 * kp][2], wa[2 * kp][3], bb[0], bb[1]);
                    mma16(c[(kp & 1) * 2 + 1], wa[2 * kp + 1][0], wa[2 * kp + 1][1], wa[2 * kp + 1][2], wa[2 * kp + 1][3], bb[2], bb[3]);
                }
                {
                    const int tok = lane & 7, ch = 2 * w + ((lane >> 3) & 1);
                    stsm2t(sb + (wg == 0 ? SM_QM : SM_KS) + tok * 128 + ((ch ^ tok) << 4),
                           pack2((c[0][0] + c[1][0]) + (c[2][0] + c[3][0]), (c[0][1] + c[1][1]) + (c[2][1] + c[3][1])),
                           pack2((c[0][2] + c[1][2]) + (c[2][2] + c[3][2]), (c[0][3] + c[1][3]) + (c[2][3] + c[3][3])));
                }
                __syncwarp();
                if (lane == 0) mbar_arrive(bar + B_MEM_FREE * 8);
                TR(1);
                bar_sync(1, 256);
                if (warp < 5) {
                    const int r = lane & 7, cq = lane >> 3;
                    uint32_t a[8], kb[8];
                    ldsm4(a, sb + SM_QM + r * 128 + ((cq ^ r) << 4));
                    ldsm4(kb, sb + SM_KS + (warp * 8 + r) * 128 + ((cq ^ r) << 4));
                    ldsm4(a + 4, sb + SM_QM + r * 128 + (((cq + 4) ^ r) << 4));
                    ldsm4(kb + 4, sb + SM_KS + (warp * 8 + r) * 128 + (((cq + 4) ^ r) << 4));
                    float d0[4] = {0.f, 0.f, 0.f, 0.f}, d1[4] = {0.f, 0.f, 0.f, 0.f};
                    mma16(d0, a[0], 0u, a[1], 0u, kb[0], kb[1]);
                    mma16(d1, a[2], 0u, a[3], 0u, kb[2], kb[3]);
                    mma16(d0, a[4], 0u, a[5], 0u, kb[4], kb[5]);
                    mma16(d1, a[6], 0u, a[7], 0u, kb[6], kb[7]);
                    const uint32_t la = sb + SM_MS + p * 1280 + warp * 256 + lane * 8;
                    #pragma unroll
                    for (int rk = 0; rk < 3; rk++)
                        st_async2(mapa(la, rk), d0[0] + d1[0], d0[1] + d1[1], mapa(bar + B_MS * 8, rk));
                    bar_arrive(4, 352);
                } else if (warp < 7) {
                    xscores<1>(sb, p, warp - 5, 0, lane);
                    bar_arrive(4, 352);
                }
                TR(2);
                if (wg == 1) {
                    mbar_wait(bar + B_XS * 8, par);
                    TR(8);
                    if (tid == 128) mbar_expect(bar + B_XS * 8, 12288);
                    const uint32_t a = sb + SM_XS + (w >> 1) * 1536 + lane * 16 + (w & 1) * 8;
                    const uint32_t pa = sb + SM_QX + (w >> 1) * 768 + lane * 8 + (w & 1) * 4;
                    if (w == 0) xsoftmax<2>(a, pa, g, t);
                    else if (w == 1) xsoftmax<3>(a, pa, g, t);
                    else if (w == 2) xsoftmax<4>(a, pa, g, t);
                    else xsoftmax<5>(a, pa, g, t);
                    bar_arrive(7, 256);
                    if (lane < 3) mbar_arrive_remote(mapa(bar + B_XSFREE * 8, lane));
                    TR(9);
                }
                if (s < NSEG - 1) {
                    wo_phase<0, 4>(sb, warp, lane, nullptr, par, (uint32_t)(s % 15) + 1u, tile0 + warp, h);
                    TR(4);
                    bar_sync(6, 448);
                }
            }
            if (s < NSEG - 1) {
                FRESH(lane);
                const uint32_t hp = (s + 1) & 1;
                float d[16];
                const uint64_t db0 = make_desc(SBC + SM_HB, 16, 1024, 1);
                mbar_wait(bar + B_HHI_FULL * 8, hp);
                mbar_wait(bar + B_HLO_FULL * 8, hp);
                TR(6);
                wg_fence();
                #pragma unroll
                for (int kt = 0; kt < 36; kt++) wg_rs32(d, wa[kt], db0 + (uint64_t)(((kt >> 2) * 4096 + (kt & 3) * 32) >> 4), kt > 0);
                wg_commit();
                #pragma unroll
                for (int kt = 36; kt < 39; kt++) wg_rs32(d, wa[kt], db0 + (uint64_t)(((kt >> 2) * 4096 + (kt & 3) * 32) >> 4), 1);
                wg_commit();
                wg_wait<1>();
                bar_arrive(9, 384);
                if (lane == 0) mbar_arrive(bar + B_HLO_FREE * 8);
                {
                    const int r = lane & 7, mq = lane >> 3;
                    const uint32_t ha = sb + SM_HB + 9 * 4096 + (8 * (mq >> 1) + r) * 128 + (((6 + (mq & 1)) ^ r) << 4);
                    uint32_t b0[4], b1[4];
                    ldsm4(b0, ha);
                    ldsm4(b1, ha + 2048);
                    wg_wait<0>();
                    mma16(d + 0, wa[39][0], wa[39][1], wa[39][2], wa[39][3], b0[0], b0[1]);
                    mma16(d + 4, wa[39][0], wa[39][1], wa[39][2], wa[39][3], b0[2], b0[3]);
                    mma16(d + 8, wa[39][0], wa[39][1], wa[39][2], wa[39][3], b1[0], b1[1]);
                    mma16(d + 12, wa[39][0], wa[39][1], wa[39][2], wa[39][3], b1[2], b1[3]);
                }
                __syncwarp();
                if (lane == 0) mbar_arrive(bar + B_HHI_FREE * 8);
                TR(7);
                const int mi = lane >> 3, r = lane & 7;
                #pragma unroll
                for (int jj = 0; jj < 2; jj++) {
                    const int tok = 8 * (2 * jj + (mi >> 1)) + r, ch = 2 * w + (mi & 1);
                    stsm4t(dstx + tok * 128 + ((ch ^ r) << 4),
                           pack2(d[8 * jj + 0], d[8 * jj + 1]), pack2(d[8 * jj + 2], d[8 * jj + 3]),
                           pack2(d[8 * jj + 4], d[8 * jj + 5]), pack2(d[8 * jj + 6], d[8 * jj + 7]));
                }
                bar_arrive(8, 384);
                if (s < 0) bar_sync(0, 512);
            }
        }
    } else if (wg == 2) {
        asm volatile("setmaxnreg.dec.sync.aligned.u32 64;");
        const int w = warp & 3;
        {
            const int c = tid & 7;
            const bf16* src = Wv + (size_t)h * DH + p * 64 + c * 8;
            for (int k = (tid & 127) >> 3; k < DM; k += 16)
                cpa16(sb + SM_WV + k * 128 + ((c ^ (k & 7)) << 4), src + (size_t)k * HD);
        }
        uint32_t res[4][4];
        {
            const bf16* src = Wo + ((size_t)h * DH + ((p + 1) % 3) * 64) * DM + (tile0 + warp) * 16 + 2 * t;
            #pragma unroll
            for (int kt = 0; kt < 4; kt++) {
                res[kt][0] = __ldg((const uint32_t*)(src + (size_t)(kt * 16 + g) * DM));
                res[kt][1] = __ldg((const uint32_t*)(src + (size_t)(kt * 16 + g) * DM + 8));
                res[kt][2] = __ldg((const uint32_t*)(src + (size_t)(kt * 16 + 8 + g) * DM));
                res[kt][3] = __ldg((const uint32_t*)(src + (size_t)(kt * 16 + 8 + g) * DM + 8));
            }
            #pragma unroll
            for (int kt = 0; kt < 4; kt++) {
                #pragma unroll
                for (int i = 0; i < 4; i++) res[kt][i] = movm(res[kt][i]);
            }
        }
        cpa_wait_all();
        fence_async();
        bar_sync(2, 128);
        const uint64_t da0 = make_desc(SBC + SM_WV, 16, 1024, 1);
        uint32_t vx[8];
        #pragma unroll
        for (int i = 0; i < 8; i++) vx[i] = 0;

        for (int s = -1; s < NSEG; s++) {
            FRESH(lane);
            const int g = lane >> 2, t = lane & 3, tid = warp * 32 + lane;
            if (s >= 0) {
                const uint32_t par = s & 1;
                mbar_wait(bar + B_MEM_FULL * 8, par);
                bar_sync(4, 352);
                TR(0);
                float dv[4];
                {
                    const uint64_t dbm = make_desc(SBC + SM_HB, 128, 128, 0);
                    wg_fence();
                    #pragma unroll
                    for (int kt = 0; kt < 40; kt++) {
                        wg_ss8(dv, da0 + (uint64_t)(kt * 128), dbm + (uint64_t)(kt * 16), kt > 0);
                        wg_commit();
                        if (kt < 39) wg_wait<1>();
                    }
                    wg_commit();
                }
                TR(1);
                bar_sync(5, 160);
                TR(2);
                uint32_t pb[5];
                #pragma unroll
                for (int j = 0; j < 5; j++) pb[j] = lds1(sb + SM_PM + j * 128 + lane * 4);
                float o0[4] = {0.f, 0.f, 0.f, 0.f}, o1[4] = {0.f, 0.f, 0.f, 0.f}, o2[4] = {0.f, 0.f, 0.f, 0.f};
                wg_wait<0>();
                TR(3);
                mma16(o0, vx[0], vx[1], vx[2], vx[3], pb[1], pb[2]);
                mma16(o1, vx[4], vx[5], vx[6], vx[7], pb[3], pb[4]);
                const uint32_t vm0 = pack2(dv[0], dv[1]), vm1 = pack2(dv[2], dv[3]);
                mma8(o2, vm0, vm1, pb[0]);
                if (s < NSEG - 1) {
                    const uint32_t q0 = pack2(o0[0] + o1[0] + o2[0], o0[1] + o1[1] + o2[1]), q1 = pack2(o0[2] + o1[2] + o2[2], o0[3] + o1[3] + o2[3]);
                    const uint32_t la = sb + SM_OS + (w * 16 + g) * 16 + t * 4;
                    #pragma unroll
                    for (int i = 1; i < 3; i++) {
                        const uint32_t rk = (p + i) % 3;
                        const uint32_t ra = mapa(la + (3 - i) * 1024, rk), rb = mapa(bar + B_O * 8, rk);
                        st_async1(ra, q0, rb);
                        st_async1(ra + 128, q1, rb);
                    }
                    sts1(la, q0);
                    sts1(la + 128, q1);
                    __syncwarp();
                    if (lane == 0) { mbar_arrive(bar + B_O1 * 8); mbar_arrive(bar + B_MEM_FREE * 8); }
                }
                TR(5);
                if (s < NSEG - 1) {
                    wo_phase<4, 4>(sb, warp, lane, res, par, (uint32_t)(s % 15) + 1u, tile0 + warp, h);
                    TR(4);
                    if (tid == 256) mbar_expect(bar + B_O * 8, 2048);
                }
                bar_sync(7, 256);
                TR(8);
                FRESH(lane);
                bf16* orow = g_ox + (size_t)(s * 32 + (lane >> 2)) * HD + h * DH + p * 64 + w * 16 + 2 * (lane & 3);
                {
                    uint2 pv[8];
                    #pragma unroll
                    for (int j = 0; j < 8; j++) pv[j] = lds2(sb + SM_QX + j * 256 + lane * 8);
                    float oa[4][4];
                    #pragma unroll
                    for (int i = 0; i < 4; i++) { oa[i][0] = 0.f; oa[i][1] = 0.f; oa[i][2] = 0.f; oa[i][3] = 0.f; }
                    mma8(oa[0], vm0, vm1, pv[0].x);
                    mma8(oa[1], vm0, vm1, pv[0].y);
                    mma8(oa[2], vm0, vm1, pv[3].x);
                    mma8(oa[3], vm0, vm1, pv[3].y);
                    asm volatile("" :: "r"(pv[7].y), "r"(pv[6].x), "r"(pv[5].x), "r"(pv[4].x), "r"(pv[2].y), "r"(pv[1].x) : "memory");
                    if (s < NSEG - 1) bar_arrive(6, 448);
                    mma16(oa[0], vx[0], vx[1], vx[2], vx[3], pv[1].x, 0u);
                    mma16(oa[1], vx[0], vx[1], vx[2], vx[3], pv[1].y, pv[2].y);
                    mma16(oa[2], vx[0], vx[1], vx[2], vx[3], pv[4].x, pv[5].x);
                    mma16(oa[3], vx[0], vx[1], vx[2], vx[3], pv[4].y, pv[5].y);
                    mma16(oa[2], vx[4], vx[5], vx[6], vx[7], pv[6].x, 0u);
                    mma16(oa[3], vx[4], vx[5], vx[6], vx[7], pv[6].y, pv[7].y);
                    uint32_t u[8];
                    #pragma unroll
                    for (int i = 0; i < 4; i++) { u[2 * i] = movm(pack2(oa[i][0], oa[i][1])); u[2 * i + 1] = movm(pack2(oa[i][2], oa[i][3])); }
                    #pragma unroll
                    for (int i = 0; i < 4; i++) {
                        *(uint32_t*)(orow + (size_t)(8 * i) * HD) = u[2 * i];
                        *(uint32_t*)(orow + (size_t)(8 * i) * HD + 8) = u[2 * i + 1];
                    }
                }
                TR(9);
                if (s == NSEG - 1) break;
            }
            float d[16];
            const uint32_t hp = (s + 1) & 1;
            const uint64_t db0 = make_desc(SBC + SM_HB, 16, 1024, 1);
            mbar_wait(bar + B_HHI_FULL * 8, hp);
            mbar_wait(bar + B_HLO_FULL * 8, hp);
            bar_sync(9, 384);
            TR(6);
            wg_fence();
            #pragma unroll
            for (int kt = 0; kt < 40; kt++) {
                wg_ss32(d, da0 + (uint64_t)(kt * 128), db0 + (uint64_t)(((kt >> 2) * 4096 + (kt & 3) * 32) >> 4), kt > 0);
                wg_commit();
                if (kt < 39) wg_wait<1>();
                if (kt == 12 && lane == 0) mbar_arrive(bar + B_HLO_FREE * 8);
            }
            wg_wait<0>();
            TR(7);
            if (lane == 0) mbar_arrive(bar + B_HHI_FREE * 8);
            #pragma unroll
            for (int i = 0; i < 8; i++) vx[i] = pack2(d[2 * i], d[2 * i + 1]);
            if (s >= 0) mbar_wait_cluster(bar + B_XSFREE * 8, s & 1);
            bar_sync(8, 384);
            TR(10);
            if (w < 3) xscores<2>(sb, p, w > 0, w == 2 ? 3 : 1, lane);
            TR(11);
            if (s < 0) bar_sync(0, 512);
        }
    } else {
        asm volatile("setmaxnreg.dec.sync.aligned.u32 48;");
        const int w = warp & 3, lt = tid & 127;
        {
            const bf16* src0 = Wo + (size_t)h * DH * DM + tile0 * 16;
            const int nch = 2 * ntile;
            for (int i = lt; i < DH * nch; i += 128) {
                const int e = i / nch, c = i - e * nch, tl = c >> 1, cc = c & 1;
                int es = e;
                if (tl >= 8 && tl < 12) { if (e >= 64 && e < 128) continue; if (e >= 128) es = e - 64; }
                int eg = e + p * 64; if (eg >= DH) eg -= DH;
                cpa16(sb + SM_WO + wo_tile_off(tl) + es * 32 + ((cc ^ ((e >> 2) & 1)) << 4), src0 + (size_t)eg * DM + c * 8);
            }
        }
        const uint32_t epoch = *(volatile uint32_t*)&g_epoch;
        if (b < 80) {
            #pragma unroll
            for (int i = 0; i < 2; i++) {
                const int idx = lt + i * 128, sl = idx >> 6, pg = (idx >> 5) & 1, wd = idx & 31;
                st_relaxed1(g_buf2 + (sl * 3 + (b >> 5)) * 2048 + pg * 1024 + (b & 31) * 32 + wd, 0xFFFFFFFFu);
            }
            __threadfence();
        }
        if (lane == 0) {
            for (int i = w; i < 14; i += 4) {
                int c = 0;
                if (i < 12) c = probe_blk(g_buf2 + i * 2048 + 640 + (b & 31) * 8);
                else if (b < 80) c = probe_blk(g_buf1 + (b * 2 + (i - 12)) * 2048);
                asm volatile("st.shared.u8 [%0], %1;" :: "r"(sb + SM_CH + 96 + i), "r"(c) : "memory");
            }
        }
        bar_sync(3, 128);
        uint32_t selmask = 0;
        for (int i = 0; i < 14; i++) {
            uint32_t c; asm volatile("ld.shared.u8 %0, [%1];" : "=r"(c) : "r"(sb + SM_CH + 96 + i) : "memory");
            selmask |= c << i;
        }
        if (lt == 0 && b < 80) st_release1(&g_choice[b], (epoch << 2) | (selmask >> 12));
        if (lt < 80) {
            uint32_t v, guard = 0;
            do { v = ld_acquire1(&g_choice[lt]); if (++guard > (1u << 22)) __trap(); } while ((v >> 2) != (epoch & 0x3fffffffu));
            asm volatile("st.shared.u8 [%0], %1;" :: "r"(sb + SM_CH + lt), "r"(v & 3u) : "memory");
        }
        cpa_wait_all();
        bar_sync(0, 512);
        const bool has_tile = (12 + w) < ntile;
        for (int s = 0; s < NSEG; s++) {
            const uint32_t par = s & 1;
            FRESH(lane);
            const int g = lane >> 2, t = lane & 3, lt = w * 32 + lane;
            if (s == 0) {
                mbar_wait(bar + B_HLO_FREE * 8, par);
                for (int k = lt; k < DM; k += 128) {
                    uint32_t v[4];
                    #pragma unroll
                    for (int i = 0; i < 4; i++) {
                        uint32_t lo = *(const uint16_t*)(mem0 + (2 * i) * DM + k), hi = *(const uint16_t*)(mem0 + (2 * i + 1) * DM + k);
                        v[i] = lo | (hi << 16);
                    }
                    asm volatile("st.shared.v4.u32 [%0], {%1,%2,%3,%4};" :: "r"(sb + SM_HB + k * 16), "r"(v[0]), "r"(v[1]), "r"(v[2]), "r"(v[3]) : "memory");
                }
            } else {
                const int sl = s & 3;
                const char* q = (const char*)g_buf2 + sl * 3 * 8192 + lt * 16;
                const uint32_t sm = selmask >> (sl * 3);
                const char* q0 = q + (sm & 1) * 4096;
                const char* q1 = q + 8192 + (sm & 2) * 2048;
                const char* q2 = q + 16384 + (sm & 4) * 1024;
                const uint32_t dst = sb + SM_HB + lt * 16;
                uint32_t guard = 0;
                mbar_wait(bar + B_HLO_FREE * 8, par);
                TR(10);
                while (true) {
                    const uint4 v0 = ld_relaxed4(q0), v1 = ld_relaxed4(q0 + 2048), v2 = ld_relaxed4(q1), v3 = ld_relaxed4(q1 + 2048), v4 = ld_relaxed4(q2);
                    sts4(dst, v0); sts4(dst + 2048, v1); sts4(dst + 4096, v2); sts4(dst + 6144, v3); sts4(dst + 8192, v4);
                    if (__all_sync(0xffffffffu, oks(v0) && oks(v1) && oks(v2) && oks(v3) && oks(v4))) break;
                    if (++guard > (1u << 22)) __trap();
                }
            }
            fence_async();
            __syncwarp();
            if (lane == 0) mbar_arrive(bar + B_MEM_FULL * 8);
            TR(0);
            if (w == 2) {
                mbar_wait(bar + B_MS * 8, par);
                TR(1);
                if (lane == 0) mbar_expect(bar + B_MS * 8, 3840);
                uint32_t pb[5];
                float sc[5][2];
                {
                    const uint32_t a = sb + SM_MS + lane * 8;
                    float2 u[5], v[5];
                    #pragma unroll
                    for (int j = 0; j < 5; j++) { u[j] = lds2f(a + j * 256); v[j] = lds2f(a + j * 256 + 1280); }
                    #pragma unroll
                    for (int j = 0; j < 5; j++) { sc[j][0] = u[j].x + v[j].x; sc[j][1] = u[j].y + v[j].y; }
                    #pragma unroll
                    for (int j = 0; j < 5; j++) u[j] = lds2f(a + j * 256 + 2560);
                    #pragma unroll
                    for (int j = 0; j < 5; j++) { sc[j][0] += u[j].x; sc[j][1] += u[j].y; }
                }
                softmax_core<5, false>(sc, g, t, pb);
                #pragma unroll
                for (int j = 0; j < 5; j++) sts1(sb + SM_PM + j * 128 + lane * 4, pb[j]);
                bar_arrive(5, 160);
                TR(2);
            }
            if (s < NSEG - 1) {
                if (w == 3) {
                    if (lane == 0) {
                        const char* src = (const char*)g_ht + (size_t)(s + 1) * 40960;
                        mbar_wait(bar + B_HHI_FREE * 8, par);
                        mbar_expect(bar + B_HHI_FULL * 8, 28672);
                        bulk_g2s(sb + SM_HB + 12288, src + 12288, 28672, sb + SM_BAR + B_HHI_FULL * 8);
                        mbar_wait(bar + B_MEM_FREE * 8, par);
                        mbar_expect(bar + B_HLO_FULL * 8, 12288);
                        bulk_g2s(sb + SM_HB, src, 12288, sb + SM_BAR + B_HLO_FULL * 8);
                    }
                    __syncwarp();
                }
                const uint32_t tag = (uint32_t)(s % 15) + 1u;
                if (has_tile) wo_phase<0, 4>(sb, warp, lane, nullptr, par, tag, tile0 + warp, h);
                else mbar_wait(bar + B_O * 8, par);
                if (w < 2) bar_arrive(6, 448);
                TR(4);
                if (b < 80) {
                    FRESH(lane);
                    const char* rin0 = (const char*)g_buf1 + (size_t)(b * 2) * 8192 + ((selmask >> 12) & 1) * 4096 + (lane >> 2) * 256 + w * 64 + (lane & 3) * 16;
                    const char* rin1 = (const char*)g_buf1 + (size_t)(b * 2 + 1) * 8192 + ((selmask >> 13) & 1) * 4096 + (lane >> 2) * 256 + w * 64 + (lane & 3) * 16;
                    const int col = b * 8 + 2 * w + ((lane >> 1) & 1), wd = 2 * (lane & 1) + (lane >> 4);
                    const int sl = (lane & 8) ? ((s + 3) & 3) : ((s + 1) & 3);
                    uint32_t* dst = g_buf2 + (sl * 3 + (col >> 8)) * 2048 + ((lane >> 2) & 1) * 1024 + (col & 255) * 4 + wd;
                    asm volatile("" : "+l"(dst));
                    uint4 v0, v1, v2, v3;
                    uint32_t guard = 0;
                    while (true) {
                        v0 = ld_relaxed4(rin0); v1 = ld_relaxed4(rin0 + 2048);
                        v2 = ld_relaxed4(rin1); v3 = ld_relaxed4(rin1 + 2048);
                        if (__all_sync(0xffffffffu, ok4(v0, tag) && ok4(v1, tag) && ok4(v2, tag) && ok4(v3, tag))) break;
                        if (++guard > (1u << 22)) __trap();
                    }
                    TR(11);
                    const float a0 = (uf(v0.x) + uf(v1.x)) + (uf(v2.x) + uf(v3.x)), a1 = (uf(v0.y) + uf(v1.y)) + (uf(v2.y) + uf(v3.y));
                    const float a2 = (uf(v0.z) + uf(v1.z)) + (uf(v2.z) + uf(v3.z)), a3 = (uf(v0.w) + uf(v1.w)) + (uf(v2.w) + uf(v3.w));
                    const bool u16 = lane & 16;
                    float m0 = (u16 ? a2 : a0) + __shfl_xor_sync(0xffffffffu, u16 ? a0 : a2, 16);
                    float m1 = (u16 ? a3 : a1) + __shfl_xor_sync(0xffffffffu, u16 ? a1 : a3, 16);
                    m0 += __shfl_xor_sync(0xffffffffu, m0, 8); m1 += __shfl_xor_sync(0xffffffffu, m1, 8);
                    m0 += __shfl_xor_sync(0xffffffffu, m0, 4); m1 += __shfl_xor_sync(0xffffffffu, m1, 4);
                    st_relaxed1(dst, (lane & 8) ? 0xFFFFFFFFu : pack2(m0, m1));
                    TR(12);
                }
            }
        }
    }
    cluster_sync();
}

constexpr int G_STAGES = 5;
constexpr int G_STAGE_BYTES = 32768;
constexpr int G_SMEM = G_STAGES * G_STAGE_BYTES + 1024 + 256;

__device__ __forceinline__ void tma2d(uint32_t dst, const CUtensorMap* map, int c0, int c1, uint32_t bar) {
    asm volatile("cp.async.bulk.tensor.2d.shared::cluster.global.mbarrier::complete_tx::bytes [%0], [%1, {%2, %3}], [%4];"
                 :: "r"(dst), "l"(map), "r"(c0), "r"(c1), "r"(bar) : "memory");
}
__device__ __forceinline__ void wg_ss128(float* d, uint64_t da, uint64_t db, int sc) {
    asm volatile("{\n\t.reg .pred p;\n\tsetp.ne.b32 p, %66, 0;\n\t"
        "wgmma.mma_async.sync.aligned.m64n128k16.f32.bf16.bf16 "
        "{%0,%1,%2,%3,%4,%5,%6,%7,%8,%9,%10,%11,%12,%13,%14,%15,%16,%17,%18,%19,%20,%21,%22,%23,%24,%25,%26,%27,%28,%29,%30,%31,"
        "%32,%33,%34,%35,%36,%37,%38,%39,%40,%41,%42,%43,%44,%45,%46,%47,%48,%49,%50,%51,%52,%53,%54,%55,%56,%57,%58,%59,%60,%61,%62,%63}, "
        "%64, %65, p, 1, 1, 0, 1;\n\t}"
        : "+f"(d[0]), "+f"(d[1]), "+f"(d[2]), "+f"(d[3]), "+f"(d[4]), "+f"(d[5]), "+f"(d[6]), "+f"(d[7]),
          "+f"(d[8]), "+f"(d[9]), "+f"(d[10]), "+f"(d[11]), "+f"(d[12]), "+f"(d[13]), "+f"(d[14]), "+f"(d[15]),
          "+f"(d[16]), "+f"(d[17]), "+f"(d[18]), "+f"(d[19]), "+f"(d[20]), "+f"(d[21]), "+f"(d[22]), "+f"(d[23]),
          "+f"(d[24]), "+f"(d[25]), "+f"(d[26]), "+f"(d[27]), "+f"(d[28]), "+f"(d[29]), "+f"(d[30]), "+f"(d[31]),
          "+f"(d[32]), "+f"(d[33]), "+f"(d[34]), "+f"(d[35]), "+f"(d[36]), "+f"(d[37]), "+f"(d[38]), "+f"(d[39]),
          "+f"(d[40]), "+f"(d[41]), "+f"(d[42]), "+f"(d[43]), "+f"(d[44]), "+f"(d[45]), "+f"(d[46]), "+f"(d[47]),
          "+f"(d[48]), "+f"(d[49]), "+f"(d[50]), "+f"(d[51]), "+f"(d[52]), "+f"(d[53]), "+f"(d[54]), "+f"(d[55]),
          "+f"(d[56]), "+f"(d[57]), "+f"(d[58]), "+f"(d[59]), "+f"(d[60]), "+f"(d[61]), "+f"(d[62]), "+f"(d[63])
        : "l"(da), "l"(db), "r"(sc));
}

template <int EPI>
__global__ void __launch_bounds__(384, 1)
k_gemm(const __grid_constant__ CUtensorMap mapA, const __grid_constant__ CUtensorMap mapB, int K,
       const bf16* __restrict__ xin, bf16* __restrict__ outp) {
    extern __shared__ uint8_t smem_raw[];
    const uint32_t sb = (smem_u32(smem_raw) + 1023u) & ~1023u;
    const uint32_t bars = sb + G_STAGES * G_STAGE_BYTES;
    const int tid = threadIdx.x, lane = tid & 31, wg = tid >> 7;
    const int n0 = blockIdx.x * 128, m0 = blockIdx.y * 128;
    const int nk = K / 64;
    if (tid == 0) {
        for (int i = 0; i < G_STAGES; i++) { mbar_init(bars + i * 8, 1); mbar_init(bars + 64 + i * 8, 8); }
        asm volatile("fence.mbarrier_init.release.cluster;" ::: "memory");
    }
    __syncthreads();
    if (wg == 0) {
        if (tid == 0) {
            for (int kb = 0; kb < nk; kb++) {
                const int st = kb % G_STAGES;
                if (kb >= G_STAGES) mbar_wait(bars + 64 + st * 8, ((kb / G_STAGES) - 1) & 1);
                const uint32_t a = sb + st * G_STAGE_BYTES;
                mbar_expect(bars + st * 8, G_STAGE_BYTES);
                tma2d(a, &mapA, kb * 64, m0, bars + st * 8);
                tma2d(a + 16384, &mapB, n0, kb * 64, bars + st * 8);
                tma2d(a + 16384 + 8192, &mapB, n0 + 64, kb * 64, bars + st * 8);
            }
        }
    } else {
        float d[64];
        #pragma unroll
        for (int i = 0; i < 64; i++) d[i] = 0.f;
        const int cw = wg - 1;
        for (int kb = 0; kb < nk; kb++) {
            const int st = kb % G_STAGES;
            mbar_wait(bars + st * 8, (kb / G_STAGES) & 1);
            const uint32_t a = sb + st * G_STAGE_BYTES;
            const uint64_t da = make_desc(a + cw * 8192, 16, 1024, 1);
            const uint64_t db = make_desc(a + 16384, 8192, 1024, 1);
            wg_fence();
            #pragma unroll
            for (int k = 0; k < 4; k++) wg_ss128(d, da + (uint64_t)(k * 2), db + (uint64_t)(k * 128), 1);
            wg_commit();
            if (kb > 0) {
                wg_wait<1>();
                if (lane == 0) mbar_arrive(bars + 64 + ((kb - 1) % G_STAGES) * 8);
            }
        }
        wg_wait<0>();
        const int g = lane >> 2, t = lane & 3, w = (tid >> 5) & 3;
        const int ldo = EPI == 1 ? FF : DM;
        #pragma unroll
        for (int hf = 0; hf < 2; hf++) {
            const int row = m0 + cw * 64 + w * 16 + g + 8 * hf;
            #pragma unroll
            for (int j = 0; j < 16; j++) {
                const int col = n0 + j * 8 + 2 * t;
                float a0 = bfr(d[4 * j + 2 * hf]), a1 = bfr(d[4 * j + 2 * hf + 1]);
                uint32_t o;
                if (EPI == 1) {
                    o = pack2(a0 / (1.0f + __expf(-a0)), a1 / (1.0f + __expf(-a1)));
                } else {
                    const float2 gm = *(const float2*)(g_mod + (EPI == 0 ? 2 : 5) * DM + col);
                    const uint32_t xv = *(const uint32_t*)(xin + (size_t)row * DM + col);
                    o = pack2(bflo(xv) + bfr(gm.x * a0), bfhi(xv) + bfr(gm.y * a1));
                }
                *(uint32_t*)(outp + (size_t)row * ldo + col) = o;
            }
        }
    }
}

typedef CUresult (*EncodeFn)(CUtensorMap*, CUtensorMapDataType, cuuint32_t, void*, const cuuint64_t*, const cuuint64_t*,
                             const cuuint32_t*, const cuuint32_t*, CUtensorMapInterleave, CUtensorMapSwizzle,
                             CUtensorMapL2promotion, CUtensorMapFloatOOBfill);

static void make_map(EncodeFn fn, CUtensorMap* m, const void* ptr, uint64_t inner, uint64_t outer, uint32_t bi, uint32_t bo) {
    cuuint64_t dims[2] = {inner, outer};
    cuuint64_t strides[1] = {inner * 2};
    cuuint32_t box[2] = {bi, bo};
    cuuint32_t es[2] = {1, 1};
    fn(m, CU_TENSOR_MAP_DATA_TYPE_BFLOAT16, 2, (void*)ptr, dims, strides, box, es, CU_TENSOR_MAP_INTERLEAVE_NONE,
       CU_TENSOR_MAP_SWIZZLE_128B, CU_TENSOR_MAP_L2_PROMOTION_L2_256B, CU_TENSOR_MAP_FLOAT_OOB_FILL_NONE);
}

extern "C" void kernel_launch(void* const* d_in, const int* in_sizes, int n_in, void* d_out, int out_size) {
    const bf16* x = (const bf16*)d_in[0];
    const bf16* mem0 = (const bf16*)d_in[1];
    const bf16* Wq = (const bf16*)d_in[2];
    const bf16* Wk = (const bf16*)d_in[3];
    const bf16* Wv = (const bf16*)d_in[4];
    const bf16* Wo = (const bf16*)d_in[5];
    const bf16* w1 = (const bf16*)d_in[8];
    const bf16* w2 = (const bf16*)d_in[9];
    const bf16* c = (const bf16*)d_in[10];
    const bf16* wmod = (const bf16*)d_in[11];
    bf16* out = (bf16*)d_out;

    static EncodeFn enc = nullptr;
    static void *p_ox, *p_x1, *p_h2, *p_act;
    if (!enc) {
        cudaDriverEntryPointQueryResult qr;
        void* f = nullptr;
        cudaGetDriverEntryPoint("cuTensorMapEncodeTiled", &f, cudaEnableDefault, &qr);
        enc = (EncodeFn)f;
        cudaGetSymbolAddress(&p_ox, g_ox);
        cudaGetSymbolAddress(&p_x1, g_x1);
        cudaGetSymbolAddress(&p_h2, g_h2);
        cudaGetSymbolAddress(&p_act, g_act);
        cudaFuncSetAttribute(k_rec, cudaFuncAttributeMaxDynamicSharedMemorySize, SM_TOTAL);
        cudaFuncSetAttribute(k_gemm<0>, cudaFuncAttributeMaxDynamicSharedMemorySize, G_SMEM);
        cudaFuncSetAttribute(k_gemm<1>, cudaFuncAttributeMaxDynamicSharedMemorySize, G_SMEM);
        cudaFuncSetAttribute(k_gemm<2>, cudaFuncAttributeMaxDynamicSharedMemorySize, G_SMEM);
    }
    CUtensorMap mOx, mWo, mH2, mW1, mAct, mW2;
    make_map(enc, &mOx, p_ox, HD, SEQ, 64, 128);
    make_map(enc, &mWo, Wo, DM, HD, 64, 64);
    make_map(enc, &mH2, p_h2, DM, SEQ, 64, 128);
    make_map(enc, &mW1, w1, FF, DM, 64, 64);
    make_map(enc, &mAct, p_act, FF, SEQ, 64, 128);
    make_map(enc, &mW2, w2, DM, FF, 64, 64);

    cudaStream_t st = cudaStreamPerThread;
    k_mod<<<60, 256, 0, st>>>(c, wmod);
    k_ln<0><<<SEQ / 8, 256, 0, st>>>(x);
    {
        cudaLaunchConfig_t cfg = {};
        cfg.gridDim = dim3(96); cfg.blockDim = dim3(512); cfg.dynamicSmemBytes = SM_TOTAL; cfg.stream = st;
        cudaLaunchAttribute at[1];
        at[0].id = cudaLaunchAttributeClusterDimension;
        at[0].val.clusterDim.x = 3; at[0].val.clusterDim.y = 1; at[0].val.clusterDim.z = 1;
        cfg.attrs = at; cfg.numAttrs = 1;
        cudaLaunchKernelEx(&cfg, k_rec, mem0, Wq, Wk, Wv, Wo);
    }
    k_gemm<0><<<dim3(5, 16), 384, G_SMEM, st>>>(mOx, mWo, HD, x, (bf16*)p_x1);
    k_ln<1><<<SEQ / 8, 256, 0, st>>>(nullptr);
    k_gemm<1><<<dim3(12, 16), 384, G_SMEM, st>>>(mH2, mW1, DM, nullptr, (bf16*)p_act);
    k_gemm<2><<<dim3(5, 16), 384, G_SMEM, st>>>(mAct, mW2, FF, (const bf16*)p_x1, out);
}
```

```cpp
#include <cuda_runtime.h>
#include <cuda_bf16.h>
#include <cuda.h>
#include <stdint.h>

typedef __nv_bfloat16 bf16;
#define VX_THROTTLE 1
#define H1_DELAY 0
#define H1_BACK 0
#define VM_THROTTLE 1

constexpr int SEQ = 2048, DM = 640, NH = 32, DH = 192, NSEG = 64, FF = 1536, HD = NH * DH;

__device__ float g_mod[6 * DM];
__device__ __align__(1024) bf16 g_ht[(size_t)SEQ * DM];
__device__ __align__(1024) bf16 g_ox[(size_t)SEQ * HD];
__device__ __align__(1024) bf16 g_x1[(size_t)SEQ * DM];
__device__ __align__(1024) bf16 g_h2[(size_t)SEQ * DM];
__device__ __align__(1024) bf16 g_act[(size_t)SEQ * FF];
__device__ __align__(8192) uint32_t g_buf1[80 * 2 * 2048];
__device__ __align__(8192) uint32_t g_buf2[4 * 3 * 2048];
__device__ uint32_t g_choice[128];
__device__ uint32_t g_epoch;
#define TR(k)

#define FRESH(x) asm volatile("" : "+r"(x))
__device__ __forceinline__ float bfr(float x) { return __bfloat162float(__float2bfloat16_rn(x)); }
__device__ __forceinline__ uint32_t pack2(float a, float b) {
    uint32_t r; asm("cvt.rn.bf16x2.f32 %0, %1, %2;" : "=r"(r) : "f"(b), "f"(a)); return r;
}
__device__ __forceinline__ float bflo(uint32_t v) { return __uint_as_float(v << 16); }
__device__ __forceinline__ float bfhi(uint32_t v) { return __uint_as_float(v & 0xffff0000u); }
__device__ __forceinline__ float ex2(float x) { float r; asm("ex2.approx.ftz.f32 %0, %1;" : "=f"(r) : "f"(x)); return r; }
__device__ __forceinline__ float rcpf(float x) { float r; asm("rcp.approx.ftz.f32 %0, %1;" : "=f"(r) : "f"(x)); return r; }
__device__ __forceinline__ void score2(float& a, float& b) {
    const float SCALE = 0.07216878364870322f;
    uint32_t u = pack2(a, b);
    u = pack2(bflo(u) * SCALE, bfhi(u) * SCALE);
    a = bflo(u); b = bfhi(u);
}
__device__ __forceinline__ uint32_t smem_u32(const void* p) { return (uint32_t)__cvta_generic_to_shared(p); }

__device__ __forceinline__ void mbar_init(uint32_t bar, uint32_t cnt) {
    asm volatile("mbarrier.init.shared::cta.b64 [%0], %1;" :: "r"(bar), "r"(cnt) : "memory");
}
__device__ __forceinline__ void mbar_arrive(uint32_t bar) {
    asm volatile("mbarrier.arrive.shared::cta.b64 _, [%0];" :: "r"(bar) : "memory");
}
__device__ __forceinline__ void mbar_expect(uint32_t bar, uint32_t bytes) {
    asm volatile("mbarrier.arrive.expect_tx.shared::cta.b64 _, [%0], %1;" :: "r"(bar), "r"(bytes) : "memory");
}
__device__ __forceinline__ bool mbar_try(uint32_t bar, uint32_t parity) {
    uint32_t ok;
    asm volatile("{\n\t.reg .pred p;\n\tmbarrier.try_wait.parity.shared::cta.b64 p, [%1], %2;\n\tselp.u32 %0, 1, 0, p;\n\t}"
                 : "=r"(ok) : "r"(bar), "r"(parity) : "memory");
    return ok != 0;
}
__device__ __forceinline__ bool mbar_try_cluster(uint32_t bar, uint32_t parity) {
    uint32_t ok;
    asm volatile("{\n\t.reg .pred p;\n\tmbarrier.try_wait.parity.acquire.cluster.shared::cta.b64 p, [%1], %2;\n\tselp.u32 %0, 1, 0, p;\n\t}"
                 : "=r"(ok) : "r"(bar), "r"(parity) : "memory");
    return ok != 0;
}
__device__ __forceinline__ void mbar_wait(uint32_t bar, uint32_t parity) {
    uint32_t guard = 0;
    while (!mbar_try(bar, parity)) { if (++guard > (1u << 22)) __trap(); }
}
__device__ __forceinline__ void mbar_wait_cluster(uint32_t bar, uint32_t parity) {
    uint32_t guard = 0;
    while (!mbar_try_cluster(bar, parity)) { if (++guard > (1u << 22)) __trap(); }
}
__device__ __forceinline__ void bar_sync(int id, int n) { asm volatile("bar.sync %0, %1;" :: "r"(id), "r"(n) : "memory"); }
__device__ __forceinline__ void bar_arrive(int id, int n) { asm volatile("bar.arrive %0, %1;" :: "r"(id), "r"(n) : "memory"); }
__device__ __forceinline__ void sts1(uint32_t a, uint32_t v) { asm volatile("st.shared.u32 [%0], %1;" :: "r"(a), "r"(v) : "memory"); }
__device__ __forceinline__ uint32_t lds1(uint32_t a) { uint32_t v; asm volatile("ld.shared.u32 %0, [%1];" : "=r"(v) : "r"(a) : "memory"); return v; }
__device__ __forceinline__ void fence_async() { asm volatile("fence.proxy.async.shared::cta;" ::: "memory"); }
__device__ __forceinline__ void cluster_sync() {
    asm volatile("barrier.cluster.arrive.release.aligned;\n\tbarrier.cluster.wait.acquire.aligned;" ::: "memory");
}
__device__ __forceinline__ uint32_t mapa(uint32_t a, uint32_t rank) {
    uint32_t r; asm("mapa.shared::cluster.u32 %0, %1, %2;" : "=r"(r) : "r"(a), "r"(rank)); return r;
}
__device__ __forceinline__ void st_async1(uint32_t a, uint32_t v, uint32_t bar) {
    asm volatile("st.async.weak.shared::cluster.mbarrier::complete_tx::bytes.b32 [%0], %1, [%2];" :: "r"(a), "r"(v), "r"(bar) : "memory");
}
__device__ __forceinline__ void st_async2(uint32_t a, float x, float y, uint32_t bar) {
    asm volatile("st.async.weak.shared::cluster.mbarrier::complete_tx::bytes.v2.f32 [%0], {%1,%2}, [%3];" :: "r"(a), "f"(x), "f"(y), "r"(bar) : "memory");
}
__device__ __forceinline__ void st_async4(uint32_t a, const float* c, uint32_t bar) {
    asm volatile("st.async.weak.shared::cluster.mbarrier::complete_tx::bytes.v4.f32 [%0], {%1,%2,%3,%4}, [%5];"
                 :: "r"(a), "f"(c[0]), "f"(c[1]), "f"(c[2]), "f"(c[3]), "r"(bar) : "memory");
}
__device__ __forceinline__ void bulk_g2s(uint32_t dst, const void* src, uint32_t bytes, uint32_t bar) {
    asm volatile("cp.async.bulk.shared::cluster.global.mbarrier::complete_tx::bytes [%0], [%1], %2, [%3];"
                 :: "r"(dst), "l"(src), "r"(bytes), "r"(bar) : "memory");
}
__device__ __forceinline__ void cpa16(uint32_t s, const void* g) {
    asm volatile("cp.async.cg.shared.global [%0], [%1], 16;" :: "r"(s), "l"(g) : "memory");
}
__device__ __forceinline__ void cpa_wait_all() { asm volatile("cp.async.wait_all;" ::: "memory"); }
__device__ __forceinline__ void ldsm4(uint32_t* r, uint32_t a) {
    asm volatile("ldmatrix.sync.aligned.m8n8.x4.shared.b16 {%0,%1,%2,%3}, [%4];" : "=r"(r[0]), "=r"(r[1]), "=r"(r[2]), "=r"(r[3]) : "r"(a) : "memory");
}
__device__ __forceinline__ void ldsm4t(uint32_t* r, uint32_t a) {
    asm volatile("ldmatrix.sync.aligned.m8n8.x4.trans.shared.b16 {%0,%1,%2,%3}, [%4];" : "=r"(r[0]), "=r"(r[1]), "=r"(r[2]), "=r"(r[3]) : "r"(a) : "memory");
}
__device__ __forceinline__ void stsm2t(uint32_t a, uint32_t r0, uint32_t r1) {
    asm volatile("stmatrix.sync.aligned.m8n8.x2.trans.shared.b16 [%0], {%1,%2};" :: "r"(a), "r"(r0), "r"(r1) : "memory");
}
__device__ __forceinline__ void stsm4t(uint32_t a, uint32_t r0, uint32_t r1, uint32_t r2, uint32_t r3) {
    asm volatile("stmatrix.sync.aligned.m8n8.x4.trans.shared.b16 [%0], {%1,%2,%3,%4};" :: "r"(a), "r"(r0), "r"(r1), "r"(r2), "r"(r3) : "memory");
}
__device__ __forceinline__ uint32_t movm(uint32_t v) {
    uint32_t r; asm volatile("movmatrix.sync.aligned.m8n8.trans.b16 %0, %1;" : "=r"(r) : "r"(v)); return r;
}
__device__ __forceinline__ void mma16(float* c, uint32_t a0, uint32_t a1, uint32_t a2, uint32_t a3, uint32_t b0, uint32_t b1) {
    asm volatile("mma.sync.aligned.m16n8k16.row.col.f32.bf16.bf16.f32 {%0,%1,%2,%3}, {%4,%5,%6,%7}, {%8,%9}, {%0,%1,%2,%3};"
                 : "+f"(c[0]), "+f"(c[1]), "+f"(c[2]), "+f"(c[3]) : "r"(a0), "r"(a1), "r"(a2), "r"(a3), "r"(b0), "r"(b1));
}
__device__ __forceinline__ void mma8(float* c, uint32_t a0, uint32_t a1, uint32_t b0) {
    asm volatile("mma.sync.aligned.m16n8k8.row.col.f32.bf16.bf16.f32 {%0,%1,%2,%3}, {%4,%5}, {%6}, {%0,%1,%2,%3};"
                 : "+f"(c[0]), "+f"(c[1]), "+f"(c[2]), "+f"(c[3]) : "r"(a0), "r"(a1), "r"(b0));
}
__host__ __device__ constexpr uint64_t make_desc(uint32_t saddr, uint32_t lbo, uint32_t sbo, uint32_t layout) {
    return (uint64_t)((saddr & 0x3FFFF) >> 4) | ((uint64_t)(lbo >> 4) << 16) | ((uint64_t)(sbo >> 4) << 32) | ((uint64_t)layout << 62);
}
__device__ __forceinline__ void wg_fence() { asm volatile("wgmma.fence.sync.aligned;" ::: "memory"); }
__device__ __forceinline__ void wg_commit() { asm volatile("wgmma.commit_group.sync.aligned;" ::: "memory"); }
template <int N> __device__ __forceinline__ void wg_wait() { asm volatile("wgmma.wait_group.sync.aligned %0;" :: "n"(N) : "memory"); }

#define D16(C) C(d[0]), C(d[1]), C(d[2]), C(d[3]), C(d[4]), C(d[5]), C(d[6]), C(d[7]), \
               C(d[8]), C(d[9]), C(d[10]), C(d[11]), C(d[12]), C(d[13]), C(d[14]), C(d[15])
#define DREG16 "{%0,%1,%2,%3,%4,%5,%6,%7,%8,%9,%10,%11,%12,%13,%14,%15}"
__device__ __forceinline__ void wg_rs32(float* d, const uint32_t* a, uint64_t db, bool acc) {
    if (acc)
        asm volatile("wgmma.mma_async.sync.aligned.m64n32k16.f32.bf16.bf16 " DREG16 ", {%16,%17,%18,%19}, %20, 1, 1, 1, 0;"
            : D16("+f") : "r"(a[0]), "r"(a[1]), "r"(a[2]), "r"(a[3]), "l"(db));
    else
        asm volatile("wgmma.mma_async.sync.aligned.m64n32k16.f32.bf16.bf16 " DREG16 ", {%16,%17,%18,%19}, %20, 0, 1, 1, 0;"
            : D16("=f") : "r"(a[0]), "r"(a[1]), "r"(a[2]), "r"(a[3]), "l"(db));
}
__device__ __forceinline__ void wg_ss32(float* d, uint64_t da, uint64_t db, bool acc) {
    if (acc)
        asm volatile("wgmma.mma_async.sync.aligned.m64n32k16.f32.bf16.bf16 " DREG16 ", %16, %17, 1, 1, 1, 1, 0;"
            : D16("+f") : "l"(da), "l"(db));
    else
        asm volatile("wgmma.mma_async.sync.aligned.m64n32k16.f32.bf16.bf16 " DREG16 ", %16, %17, 0, 1, 1, 1, 0;"
            : D16("=f") : "l"(da), "l"(db));
}
__device__ __forceinline__ void wg_ss8(float* d, uint64_t da, uint64_t db, bool acc) {
    if (acc)
        asm volatile("wgmma.mma_async.sync.aligned.m64n8k16.f32.bf16.bf16 {%0,%1,%2,%3}, %4, %5, 1, 1, 1, 1, 1;"
            : "+f"(d[0]), "+f"(d[1]), "+f"(d[2]), "+f"(d[3]) : "l"(da), "l"(db));
    else
        asm volatile("wgmma.mma_async.sync.aligned.m64n8k16.f32.bf16.bf16 {%0,%1,%2,%3}, %4, %5, 0, 1, 1, 1, 1;"
            : "=f"(d[0]), "=f"(d[1]), "=f"(d[2]), "=f"(d[3]) : "l"(da), "l"(db));
}
template <int OFF> __device__ __forceinline__ void ldsm4t_i(uint32_t* r, uint32_t a) {
    asm volatile("ldmatrix.sync.aligned.m8n8.x4.trans.shared.b16 {%0,%1,%2,%3}, [%4+%5];"
                 : "=r"(r[0]), "=r"(r[1]), "=r"(r[2]), "=r"(r[3]) : "r"(a), "n"(OFF) : "memory");
}

__device__ __forceinline__ uint4 ld_relaxed4(const void* p) {
    uint4 v;
    asm volatile("ld.relaxed.gpu.global.v4.u32 {%0,%1,%2,%3}, [%4];" : "=r"(v.x), "=r"(v.y), "=r"(v.z), "=r"(v.w) : "l"(p) : "memory");
    return v;
}
__device__ __forceinline__ void st_relaxed2(void* p, uint32_t a, uint32_t b) {
    asm volatile("st.relaxed.gpu.global.v2.u32 [%0], {%1,%2};" :: "l"(p), "r"(a), "r"(b) : "memory");
}
__device__ __forceinline__ void st_relaxed2_off(void* base, uint32_t off, uint32_t a, uint32_t b) {
    asm volatile("{\n\t.reg .u64 ad;\n\tcvt.u64.u32 ad, %1;\n\tadd.u64 ad, ad, %0;\n\tst.relaxed.gpu.global.v2.u32 [ad], {%2,%3};\n\t}"
                 :: "l"(base), "r"(off), "r"(a), "r"(b) : "memory");
}
__device__ __forceinline__ void st_relaxed1(void* p, uint32_t a) {
    asm volatile("st.relaxed.gpu.global.u32 [%0], %1;" :: "l"(p), "r"(a) : "memory");
}
__device__ __forceinline__ uint32_t ld_acquire1(const uint32_t* p) {
    uint32_t v; asm volatile("ld.acquire.gpu.global.u32 %0, [%1];" : "=r"(v) : "l"(p) : "memory"); return v;
}
__device__ __forceinline__ void st_release1(uint32_t* p, uint32_t a) {
    asm volatile("st.release.gpu.global.u32 [%0], %1;" :: "l"(p), "r"(a) : "memory");
}
__device__ __forceinline__ uint4 lds4(uint32_t s) {
    uint4 v; asm volatile("ld.shared.v4.u32 {%0,%1,%2,%3}, [%4];" : "=r"(v.x), "=r"(v.y), "=r"(v.z), "=r"(v.w) : "r"(s) : "memory"); return v;
}
__device__ __forceinline__ void sts4(uint32_t s, const uint4& v) {
    asm volatile("st.shared.v4.u32 [%0], {%1,%2,%3,%4};" :: "r"(s), "r"(v.x), "r"(v.y), "r"(v.z), "r"(v.w) : "memory");
}
__device__ __forceinline__ float4 lds4f(uint32_t s) {
    float4 v; asm volatile("ld.shared.v4.f32 {%0,%1,%2,%3}, [%4];" : "=f"(v.x), "=f"(v.y), "=f"(v.z), "=f"(v.w) : "r"(s) : "memory"); return v;
}
__device__ __forceinline__ uint2 lds2(uint32_t s) {
    uint2 v; asm volatile("ld.shared.v2.u32 {%0,%1}, [%2];" : "=r"(v.x), "=r"(v.y) : "r"(s) : "memory"); return v;
}
__device__ __forceinline__ float2 lds2f(uint32_t s) {
    float2 v; asm volatile("ld.shared.v2.f32 {%0,%1}, [%2];" : "=f"(v.x), "=f"(v.y) : "r"(s) : "memory"); return v;
}
__device__ __forceinline__ uint32_t clk32() { uint32_t c; asm volatile("mov.u32 %0, %%clock;" : "=r"(c) :: "memory"); return c; }
__device__ __forceinline__ uint32_t tagw(float v, uint32_t tag) { return ((__float_as_uint(v) + 8u) & ~15u) | tag; }
__device__ __forceinline__ bool ok4(const uint4& v, uint32_t tag) { return (((v.x ^ tag) | (v.y ^ tag) | (v.z ^ tag) | (v.w ^ tag)) & 15u) == 0; }
__device__ __forceinline__ bool oks(const uint4& v) { return v.x != 0xFFFFFFFFu && v.y != 0xFFFFFFFFu && v.z != 0xFFFFFFFFu && v.w != 0xFFFFFFFFu; }
__device__ __forceinline__ float uf(uint32_t x) { return __uint_as_float(x & ~15u); }

__global__ void __launch_bounds__(256) k_mod(const bf16* __restrict__ c, const bf16* __restrict__ wmod) {
    __shared__ float sc[DM];
    __shared__ float red[8][64];
    const int tid = threadIdx.x;
    for (int i = tid; i < DM; i += 256) {
        float v = __bfloat162float(c[i]);
        sc[i] = bfr(v / (1.0f + __expf(-v)));
    }
    __syncthreads();
    const int cp = tid & 31, kg = tid >> 5;
    const int col = blockIdx.x * 64 + cp * 2;
    float a0 = 0.f, a1 = 0.f;
    #pragma unroll 8
    for (int k = kg * 80; k < kg * 80 + 80; k++) {
        uint32_t w = *(const uint32_t*)(wmod + (size_t)k * (6 * DM) + col);
        a0 += sc[k] * bflo(w); a1 += sc[k] * bfhi(w);
    }
    red[kg][cp * 2] = a0; red[kg][cp * 2 + 1] = a1;
    __syncthreads();
    if (tid < 64) {
        float s = 0.f;
        #pragma unroll
        for (int i = 0; i < 8; i++) s += red[i][tid];
        g_mod[blockIdx.x * 64 + tid] = bfr(s);
    }
    if (blockIdx.x == 0 && tid == 0) g_epoch = g_epoch + 1;
}

template <int MODE>
__global__ void __launch_bounds__(256) k_ln(const bf16* __restrict__ xin) {
    const int lane = threadIdx.x & 31, row = blockIdx.x * 8 + (threadIdx.x >> 5);
    const bf16* src = (MODE == 0 ? xin : g_x1) + (size_t)row * DM;
    const float* shift = g_mod + (MODE == 0 ? 0 : 3 * DM);
    const float* scale = g_mod + (MODE == 0 ? DM : 4 * DM);
    float v[3][8];
    float s = 0.f;
    #pragma unroll
    for (int i = 0; i < 3; i++) {
        int c = lane + 32 * i;
        if (c < 80) {
            uint4 u = *(const uint4*)(src + c * 8);
            v[i][0] = bflo(u.x); v[i][1] = bfhi(u.x); v[i][2] = bflo(u.y); v[i][3] = bfhi(u.y);
            v[i][4] = bflo(u.z); v[i][5] = bfhi(u.z); v[i][6] = bflo(u.w); v[i][7] = bfhi(u.w);
        } else {
            #pragma unroll
            for (int j = 0; j < 8; j++) v[i][j] = 0.f;
        }
        #pragma unroll
        for (int j = 0; j < 8; j++) s += v[i][j];
    }
    #pragma unroll
    for (int o = 16; o > 0; o >>= 1) s += __shfl_xor_sync(0xffffffffu, s, o);
    const float mean = s * (1.0f / DM);
    float q = 0.f;
    #pragma unroll
    for (int i = 0; i < 3; i++) {
        if (lane + 32 * i < 80) {
            #pragma unroll
            for (int j = 0; j < 8; j++) { float d = v[i][j] - mean; q += d * d; }
        }
    }
    #pragma unroll
    for (int o = 16; o > 0; o >>= 1) q += __shfl_xor_sync(0xffffffffu, q, o);
    const float mb = bfr(mean);
    const float var = bfr(q * (1.0f / DM));
    const float sd = bfr(sqrtf(bfr(var + 1e-5f)));
    #pragma unroll
    for (int i = 0; i < 3; i++) {
        int c = lane + 32 * i;
        if (c < 80) {
            float o[8];
            #pragma unroll
            for (int j = 0; j < 8; j++) {
                float n = bfr(bfr(v[i][j] - mb) / sd);
                float m1 = bfr(1.0f + scale[c * 8 + j]);
                o[j] = bfr(n * m1) + shift[c * 8 + j];
            }
            uint4 u = make_uint4(pack2(o[0], o[1]), pack2(o[2], o[3]), pack2(o[4], o[5]), pack2(o[6], o[7]));
            if (MODE == 0) {
                int seg = row >> 5, r = row & 31, blk = c >> 3, cc = c & 7;
                *(uint4*)(g_ht + (size_t)seg * 20480 + blk * 2048 + r * 64 + ((cc ^ (r & 7)) << 3)) = u;
            } else {
                *(uint4*)(g_h2 + (size_t)row * DM + c * 8) = u;
            }
        }
    }
}

constexpr int SM_WV = 0;
constexpr int SM_HB = 81920;
constexpr int SM_WO = SM_HB + 40960;
constexpr int SM_QX = SM_WO + 77824;
constexpr int SM_KS = SM_QX + 4096;
constexpr int SM_QM = SM_KS + 5120;
constexpr int SM_XS = SM_QM + 1024;
constexpr int SM_MS = SM_XS + 12288;
constexpr int SM_OS = SM_MS + 3840;
constexpr int SM_PM = SM_OS + 3072;
constexpr int SM_BAR = SM_PM + 640;
constexpr int SM_CH = SM_BAR + 128;
constexpr int SM_TOTAL = SM_CH + 128;
static_assert(SM_TOTAL <= 232448, "smem");

enum { B_MEM_FULL = 0, B_MEM_FREE, B_HLO_FULL, B_HHI_FULL, B_HLO_FREE, B_HHI_FREE, B_MS, B_O, B_XS, B_O1, B_XSFREE };

__device__ __forceinline__ int probe_blk(uint32_t* blk) {
    uint32_t t0 = 0xffffffffu, t1 = 0xffffffffu, acc = 0;
    for (int rep = 0; rep < 3; rep++) {
        #pragma unroll
        for (int pg = 0; pg < 2; pg++) {
            uint32_t c0 = clk32();
            uint32_t v = atomicOr(blk + pg * 1024 + acc, 0u);
            acc = (v == 0x12345678u) ? 1u : 0u;
            asm volatile("" :: "r"(acc) : "memory");
            uint32_t c1 = clk32() + acc;
            uint32_t d = c1 - c0;
            if (rep > 0) { if (pg == 0) t0 = min(t0, d); else t1 = min(t1, d); }
        }
    }
    return t1 < t0 ? 1 : 0;
}

__device__ __forceinline__ uint32_t wo_tile_off(int w) {
    if (w < 8) return w * 6144;
    if (w < 12) return 8 * 6144 + (w - 8) * 4096;
    return 8 * 6144 + 4 * 4096 + (w - 12) * 6144;
}

template <int NRES, int NPRE>
__device__ __forceinline__ void wo_phase(uint32_t sb, int w, int lane, const uint32_t (*res)[4], uint32_t parity,
                                         uint32_t tag, int tile, int h) {
    FRESH(lane);
    const int er = (lane & 7) + 8 * (lane >> 4);
    const uint32_t aaddr = sb + SM_WO + wo_tile_off(w) + er * 32 + ((((lane >> 3) & 1) ^ ((er >> 2) & 1)) << 4);
    const uint32_t baddr = sb + SM_OS + lane * 16;
    float c0[4] = {0.f, 0.f, 0.f, 0.f}, c1[4] = {0.f, 0.f, 0.f, 0.f};
    uint32_t pre[NPRE > 4 ? NPRE : 4][4];
    if (NPRE >= 4) {
        #pragma unroll
        for (int i = 0; i < 4; i++) ldsm4t(pre[i], aaddr + i * 512);
        mbar_wait(sb + SM_BAR + B_O1 * 8, parity);
        uint32_t b[2][4];
        ldsm4t(b[0], baddr);
        ldsm4t(b[1], baddr + 512);
        #pragma unroll
        for (int kp = 0; kp < 2; kp++) {
            mma16(c0, pre[2 * kp][0], pre[2 * kp][1], pre[2 * kp][2], pre[2 * kp][3], b[kp][0], b[kp][1]);
            mma16(c1, pre[2 * kp + 1][0], pre[2 * kp + 1][1], pre[2 * kp + 1][2], pre[2 * kp + 1][3], b[kp][2], b[kp][3]);
        }
    } else {
        #pragma unroll
        for (int i = 0; i < 2; i++) ldsm4t(pre[i], aaddr + i * 512);
        mbar_wait(sb + SM_BAR + B_O1 * 8, parity);
        #pragma unroll
        for (int kp = 0; kp < 2; kp++) {
            uint32_t b[4];
            ldsm4t(b, baddr + kp * 512);
            if (kp == 1) { ldsm4t(pre[0], aaddr + 2 * 512); ldsm4t(pre[1], aaddr + 3 * 512); }
            mma16(c0, pre[0][0], pre[0][1], pre[0][2], pre[0][3], b[0], b[1]);
            mma16(c1, pre[1][0], pre[1][1], pre[1][2], pre[1][3], b[2], b[3]);
        }
    }
    #pragma unroll
    for (int i = 0; i < NPRE; i++) ldsm4t(pre[i], aaddr + (4 + i) * 512);
    uint32_t off0, off1;
    {
        uint32_t ch;
        asm volatile("ld.shared.u16 %0, [%1];" : "=r"(ch) : "r"(sb + SM_CH + 2 * tile) : "memory");
        const int j = h >> 4;
        const uint32_t base = (uint32_t)((tile * 4 + j) * 8192 + (h & 15) * 256 + lane * 8);
        ch >>= j;
        off0 = base + (ch & 1) * 4096;
        off1 = base + 16384 + (ch & 256) * 16;
    }
    mbar_wait(sb + SM_BAR + B_O * 8, parity);
    if (NRES == 4) {
        uint32_t b[4][4];
        #pragma unroll
        for (int i = 0; i < 4; i++) ldsm4t(b[i], baddr + (2 + i) * 512);
        #pragma unroll
        for (int i = 0; i < 2; i++) {
            mma16(c0, res[2 * i][0], res[2 * i][1], res[2 * i][2], res[2 * i][3], b[i][0], b[i][1]);
            mma16(c1, res[2 * i + 1][0], res[2 * i + 1][1], res[2 * i + 1][2], res[2 * i + 1][3], b[i][2], b[i][3]);
        }
        #pragma unroll
        for (int i = 0; i < 2; i++) {
            mma16(c0, pre[2 * i][0], pre[2 * i][1], pre[2 * i][2], pre[2 * i][3], b[2 + i][0], b[2 + i][1]);
            mma16(c1, pre[2 * i + 1][0], pre[2 * i + 1][1], pre[2 * i + 1][2], pre[2 * i + 1][3], b[2 + i][2], b[2 + i][3]);
        }
    } else if (NPRE == 4) {
        uint32_t b[2][4];
        #pragma unroll
        for (int hh = 0; hh < 2; hh++) {
            ldsm4t(b[0], baddr + (2 + 2 * hh) * 512);
            ldsm4t(b[1], baddr + (3 + 2 * hh) * 512);
            if (hh) {
                #pragma unroll
                for (int i = 0; i < 4; i++) ldsm4t(pre[i], aaddr + (8 + i) * 512);
            }
            #pragma unroll
            for (int i = 0; i < 2; i++) {
                mma16(c0, pre[2 * i][0], pre[2 * i][1], pre[2 * i][2], pre[2 * i][3], b[i][0], b[i][1]);
                mma16(c1, pre[2 * i + 1][0], pre[2 * i + 1][1], pre[2 * i + 1][2], pre[2 * i + 1][3], b[i][2], b[i][3]);
            }
        }
    }
    st_relaxed2_off(g_buf1, off0, tagw(c0[0] + c1[0], tag), tagw(c0[1] + c1[1], tag));
    st_relaxed2_off(g_buf1, off1, tagw(c0[2] + c1[2], tag), tagw(c0[3] + c1[3], tag));
}

template <int NT, bool MASK>
__device__ __forceinline__ void softmax_core(float (*sc)[2], int g, int t, uint32_t* pb) {
    const float L2E = 1.4426950408889634f;
    #pragma unroll
    for (int j = 0; j < NT; j++) score2(sc[j][0], sc[j][1]);
    if (MASK) {
        const float NEG = -999292928.0f;
        if (2 * t > g) sc[NT - 1][0] = NEG;
        if (2 * t + 1 > g) sc[NT - 1][1] = NEG;
    }
    float m[NT];
    #pragma unroll
    for (int j = 0; j < NT; j++) m[j] = fmaxf(sc[j][0], sc[j][1]);
    float mx = m[0];
    #pragma unroll
    for (int j = 1; j < NT; j++) mx = fmaxf(mx, m[j]);
    mx = fmaxf(mx, __shfl_xor_sync(0xffffffffu, mx, 1));
    mx = fmaxf(mx, __shfl_xor_sync(0xffffffffu, mx, 2));
    float s0 = 0.f, s1 = 0.f;
    #pragma unroll
    for (int j = 0; j < NT; j++) {
        sc[j][0] = ex2((sc[j][0] - mx) * L2E); sc[j][1] = ex2((sc[j][1] - mx) * L2E);
        s0 += sc[j][0]; s1 += sc[j][1];
    }
    s0 += s1;
    s0 += __shfl_xor_sync(0xffffffffu, s0, 1);
    s0 += __shfl_xor_sync(0xffffffffu, s0, 2);
    const float iv = rcpf(s0);
    #pragma unroll
    for (int j = 0; j < NT; j++) pb[j] = pack2(sc[j][0] * iv, sc[j][1] * iv);
}
template <int NT>
__device__ __forceinline__ void xsoftmax(uint32_t a, int g, int t) {
    float sc[NT][2];
    #pragma unroll
    for (int j = 0; j < NT; j++) {
        float2 v0 = lds2f(a + j * 512), v1 = lds2f(a + j * 512 + 4096), v2 = lds2f(a + j * 512 + 8192);
        sc[j][0] = v0.x + v1.x + v2.x; sc[j][1] = v0.y + v1.y + v2.y;
    }
    uint32_t pb[NT];
    softmax_core<NT, true>(sc, g, t, pb);
    #pragma unroll
    for (int j = 0; j < NT; j += 2) {
        if (j + 1 < NT) asm volatile("st.shared.v2.u32 [%0], {%1,%2};" :: "r"(a + j * 512), "r"(pb[j]), "r"(pb[j + 1]) : "memory");
        else sts1(a + j * 512, pb[j]);
    }
}
template <int NJ>
__device__ __forceinline__ void xscores(uint32_t sb, int p, int mi, int j0, int lane) {
    FRESH(lane);
    const int r = lane & 7, cq = lane >> 3;
    const int qrow = mi * 16 + r + 8 * (cq & 1);
    uint32_t kb[NJ][8];
    float d[NJ][4];
    #pragma unroll
    for (int j = 0; j < NJ; j++) {
        ldsm4(kb[j], sb + SM_KS + ((j0 + j) * 8 + r) * 128 + ((cq ^ r) << 4));
        ldsm4(kb[j] + 4, sb + SM_KS + ((j0 + j) * 8 + r) * 128 + (((cq + 4) ^ r) << 4));
        d[j][0] = 0.f; d[j][1] = 0.f; d[j][2] = 0.f; d[j][3] = 0.f;
    }
    #pragma unroll
    for (int kt = 0; kt < 4; kt++) {
        uint32_t a[4];
        ldsm4(a, sb + SM_QX + qrow * 128 + (((2 * kt + (cq >> 1)) ^ r) << 4));
        #pragma unroll
        for (int j = 0; j < NJ; j++) mma16(d[j], a[0], a[1], a[2], a[3], kb[j][2 * kt], kb[j][2 * kt + 1]);
    }
    const uint32_t la = sb + SM_XS + p * 4096 + (mi * 3 + j0) * 512 + lane * 16;
    #pragma unroll
    for (int rk = 0; rk < 3; rk++) {
        const uint32_t ra = mapa(la, rk), rb = mapa(sb + SM_BAR + B_XS * 8, rk);
        #pragma unroll
        for (int j = 0; j < NJ; j++) st_async4(ra + j * 512, d[j], rb);
    }
}
__device__ __forceinline__ void mbar_arrive_remote(uint32_t bar) {
    asm volatile("mbarrier.arrive.relaxed.cluster.shared::cluster.b64 _, [%0];" :: "r"(bar) : "memory");
}

__global__ void __launch_bounds__(512, 1)
k_rec(const bf16* __restrict__ mem0, const bf16* __restrict__ Wq, const bf16* __restrict__ Wk,
      const bf16* __restrict__ Wv, const bf16* __restrict__ Wo) {
    extern __shared__ __align__(1024) uint8_t smem_raw[];
    constexpr uint32_t SBC = 1024;
    const uint32_t sb = smem_u32(smem_raw);
    if ((sb & 0xFFFFFFu) != SBC) __trap();
    int lane = __shfl_sync(0xffffffffu, threadIdx.x & 31, threadIdx.x & 31);
    const int warp = __shfl_sync(0xffffffffu, threadIdx.x >> 5, 0), wg = warp >> 2;
    const int tid = warp * 32 + lane;
    const int b = blockIdx.x, h = b / 3, p = b % 3;
    const int g = lane >> 2, t = lane & 3;
    const int tile0 = p == 0 ? 0 : (p == 1 ? 14 : 27);
    const int ntile = p == 0 ? 14 : 13;
    const uint32_t bar = sb + SM_BAR;

    if (tid == 0) {
        mbar_init(bar + B_MEM_FULL * 8, 4);
        mbar_init(bar + B_MEM_FREE * 8, 12);
        mbar_init(bar + B_HLO_FULL * 8, 1);
        mbar_init(bar + B_HHI_FULL * 8, 1);
        mbar_init(bar + B_HLO_FREE * 8, 12);
        mbar_init(bar + B_HHI_FREE * 8, 12);
        mbar_init(bar + B_MS * 8, 1);
        mbar_init(bar + B_O * 8, 1);
        mbar_init(bar + B_XS * 8, 1);
        mbar_init(bar + B_O1 * 8, 4);
        mbar_init(bar + B_XSFREE * 8, 12);
        asm volatile("fence.mbarrier_init.release.cluster;" ::: "memory");
        mbar_expect(bar + B_MS * 8, 3840);
        mbar_expect(bar + B_O * 8, 2048);
        mbar_expect(bar + B_XS * 8, 12288);
        mbar_expect(bar + B_HLO_FULL * 8, 12288);
        bulk_g2s(sb + SM_HB, g_ht, 12288, sb + SM_BAR + B_HLO_FULL * 8);
        mbar_expect(bar + B_HHI_FULL * 8, 28672);
        bulk_g2s(sb + SM_HB + 12288, (const char*)g_ht + 12288, 28672, sb + SM_BAR + B_HHI_FULL * 8);
    }
    cluster_sync();

    if (wg < 2) {
        asm volatile("setmaxnreg.inc.sync.aligned.u32 200;");
        const int w = warp & 3;
        uint32_t wa[40][4];
        {
            const bf16* W = (wg == 0 ? Wq : Wk) + (size_t)h * DH + p * 64 + w * 16 + t * 4;
            #pragma unroll
            for (int kt = 0; kt < 40; kt++) {
                uint2 l1 = __ldg((const uint2*)(W + (size_t)(kt * 16 + g) * HD));
                uint2 l2 = __ldg((const uint2*)(W + (size_t)(kt * 16 + 8 + g) * HD));
                wa[kt][0] = l1.x; wa[kt][1] = l1.y; wa[kt][2] = l2.x; wa[kt][3] = l2.y;
            }
            #pragma unroll
            for (int kt = 0; kt < 40; kt++) {
                #pragma unroll
                for (int i = 0; i < 4; i++) wa[kt][i] = movm(wa[kt][i]);
            }
        }

        const uint32_t dstx = sb + (wg == 0 ? SM_QX : SM_KS + 1024);

        for (int s = -1; s < NSEG; s++) {
            const uint32_t par = s & 1;
            FRESH(lane);
            const int g = lane >> 2, t = lane & 3, tid = warp * 32 + lane;
            if (s >= 0) {
                mbar_wait(bar + B_MEM_FULL * 8, par);
                TR(0);
                float c[4][4];
                #pragma unroll
                for (int i = 0; i < 4; i++) { c[i][0] = 0.f; c[i][1] = 0.f; c[i][2] = 0.f; c[i][3] = 0.f; }
                uint32_t maddr = sb + lane * 16;
                asm volatile("" : "+r"(maddr));
                #pragma unroll
                for (int kp = 0; kp < 20; kp++) {
                    uint32_t bb[4];
                    ldsm4t(bb, maddr + (SM_HB + kp * 512));
                    mma16(c[(kp & 1) * 2], wa[2 * kp][0], wa[2 * kp][1], wa[2 * kp][2], wa[2 * kp][3], bb[0], bb[1]);
                    mma16(c[(kp & 1) * 2 + 1], wa[2 * kp + 1][0], wa[2 * kp + 1][1], wa[2 * kp + 1][2], wa[2 * kp + 1][3], bb[2], bb[3]);
                }
                {
                    const int tok = lane & 7, ch = 2 * w + ((lane >> 3) & 1);
                    stsm2t(sb + (wg == 0 ? SM_QM : SM_KS) + tok * 128 + ((ch ^ tok) << 4),
                           pack2((c[0][0] + c[1][0]) + (c[2][0] + c[3][0]), (c[0][1] + c[1][1]) + (c[2][1] + c[3][1])),
                           pack2((c[0][2] + c[1][2]) + (c[2][2] + c[3][2]), (c[0][3] + c[1][3]) + (c[2][3] + c[3][3])));
                }
                __syncwarp();
                if (lane == 0) mbar_arrive(bar + B_MEM_FREE * 8);
                TR(1);
                bar_sync(1, 256);
                if (warp < 5) {
                    const int r = lane & 7, cq = lane >> 3;
                    uint32_t a[8], kb[8];
                    ldsm4(a, sb + SM_QM + r * 128 + ((cq ^ r) << 4));
                    ldsm4(kb, sb + SM_KS + (warp * 8 + r) * 128 + ((cq ^ r) << 4));
                    ldsm4(a + 4, sb + SM_QM + r * 128 + (((cq + 4) ^ r) << 4));
                    ldsm4(kb + 4, sb + SM_KS + (warp * 8 + r) * 128 + (((cq + 4) ^ r) << 4));
                    float d0[4] = {0.f, 0.f, 0.f, 0.f}, d1[4] = {0.f, 0.f, 0.f, 0.f};
                    mma16(d0, a[0], 0u, a[1], 0u, kb[0], kb[1]);
                    mma16(d1, a[2], 0u, a[3], 0u, kb[2], kb[3]);
                    mma16(d0, a[4], 0u, a[5], 0u, kb[4], kb[5]);
                    mma16(d1, a[6], 0u, a[7], 0u, kb[6], kb[7]);
                    const uint32_t la = sb + SM_MS + p * 1280 + warp * 256 + lane * 8;
                    #pragma unroll
                    for (int rk = 0; rk < 3; rk++)
                        st_async2(mapa(la, rk), d0[0] + d1[0], d0[1] + d1[1], mapa(bar + B_MS * 8, rk));
                    bar_arrive(4, 352);
                } else if (warp < 7) {
                    xscores<1>(sb, p, warp - 5, 0, lane);
                    bar_arrive(4, 352);
                }
                TR(2);
                if (s < NSEG - 1) {
                    wo_phase<0, 4>(sb, warp, lane, nullptr, par, (uint32_t)(s % 15) + 1u, tile0 + warp, h);
                    TR(4);
                    bar_sync(6, 512);
                }
            }
            if (s < NSEG - 1) {
                FRESH(lane);
                const uint32_t hp = (s + 1) & 1;
                float d[16];
                const uint64_t db0 = make_desc(SBC + SM_HB, 16, 1024, 1);
                mbar_wait(bar + B_HHI_FULL * 8, hp);
                TR(6);
                wg_fence();
                #pragma unroll
                for (int kt = 12; kt < 39; kt++) wg_rs32(d, wa[kt], db0 + (uint64_t)(((kt >> 2) * 4096 + (kt & 3) * 32) >> 4), kt > 12);
                mbar_wait(bar + B_HLO_FULL * 8, hp);
                #pragma unroll
                for (int kt = 0; kt < 9; kt++) wg_rs32(d, wa[kt], db0 + (uint64_t)(((kt >> 2) * 4096 + (kt & 3) * 32) >> 4), 1);
                wg_commit();
                #pragma unroll
                for (int kt = 9; kt < 12; kt++) wg_rs32(d, wa[kt], db0 + (uint64_t)(((kt >> 2) * 4096 + (kt & 3) * 32) >> 4), 1);
                wg_commit();
                wg_wait<1>();
                bar_arrive(9, 384);
                {
                    const int r = lane & 7, mq = lane >> 3;
                    const uint32_t ha = sb + SM_HB + 9 * 4096 + (8 * (mq >> 1) + r) * 128 + (((6 + (mq & 1)) ^ r) << 4);
                    uint32_t b0[4], b1[4];
                    ldsm4(b0, ha);
                    ldsm4(b1, ha + 2048);
                    wg_wait<0>();
                    if (lane == 0) mbar_arrive(bar + B_HLO_FREE * 8);
                    mma16(d + 0, wa[39][0], wa[39][1], wa[39][2], wa[39][3], b0[0], b0[1]);
                    mma16(d + 4, wa[39][0], wa[39][1], wa[39][2], wa[39][3], b0[2], b0[3]);
                    mma16(d + 8, wa[39][0], wa[39][1], wa[39][2], wa[39][3], b1[0], b1[1]);
                    mma16(d + 12, wa[39][0], wa[39][1], wa[39][2], wa[39][3], b1[2], b1[3]);
                }
                __syncwarp();
                if (lane == 0) mbar_arrive(bar + B_HHI_FREE * 8);
                TR(7);
                const int mi = lane >> 3, r = lane & 7;
                #pragma unroll
                for (int jj = 0; jj < 2; jj++) {
                    const int tok = 8 * (2 * jj + (mi >> 1)) + r, ch = 2 * w + (mi & 1);
                    stsm4t(dstx + tok * 128 + ((ch ^ r) << 4),
                           pack2(d[8 * jj + 0], d[8 * jj + 1]), pack2(d[8 * jj + 2], d[8 * jj + 3]),
                           pack2(d[8 * jj + 4], d[8 * jj + 5]), pack2(d[8 * jj + 6], d[8 * jj + 7]));
                }
                bar_arrive(8, 384);
                if (s < 0) bar_sync(0, 512);
            }
        }
    } else if (wg == 2) {
        asm volatile("setmaxnreg.dec.sync.aligned.u32 64;");
        const int w = warp & 3;
        {
            const int c = tid & 7;
            const bf16* src = Wv + (size_t)h * DH + p * 64 + c * 8;
            for (int k = (tid & 127) >> 3; k < DM; k += 16)
                cpa16(sb + SM_WV + k * 128 + ((c ^ (k & 7)) << 4), src + (size_t)k * HD);
        }
        uint32_t res[4][4];
        {
            const bf16* src = Wo + ((size_t)h * DH + ((p + 1) % 3) * 64) * DM + (tile0 + warp) * 16 + 2 * t;
            #pragma unroll
            for (int kt = 0; kt < 4; kt++) {
                res[kt][0] = __ldg((const uint32_t*)(src + (size_t)(kt * 16 + g) * DM));
                res[kt][1] = __ldg((const uint32_t*)(src + (size_t)(kt * 16 + g) * DM + 8));
                res[kt][2] = __ldg((const uint32_t*)(src + (size_t)(kt * 16 + 8 + g) * DM));
                res[kt][3] = __ldg((const uint32_t*)(src + (size_t)(kt * 16 + 8 + g) * DM + 8));
            }
            #pragma unroll
            for (int kt = 0; kt < 4; kt++) {
                #pragma unroll
                for (int i = 0; i < 4; i++) res[kt][i] = movm(res[kt][i]);
            }
        }
        cpa_wait_all();
        fence_async();
        bar_sync(2, 128);
        const uint64_t da0 = make_desc(SBC + SM_WV, 16, 1024, 1);
        uint32_t vx[8];
        #pragma unroll
        for (int i = 0; i < 8; i++) vx[i] = 0;

        for (int s = -1; s < NSEG; s++) {
            FRESH(lane);
            const int g = lane >> 2, t = lane & 3, tid = warp * 32 + lane;
            if (s >= 0) {
                const uint32_t par = s & 1;
                mbar_wait(bar + B_MEM_FULL * 8, par);
                bar_sync(4, 352);
                TR(0);
                float dv[4];
                {
                    const uint64_t dbm = make_desc(SBC + SM_HB, 128, 128, 0);
                    wg_fence();
                    #pragma unroll
                    for (int kt = 0; kt < 40; kt++) {
                        wg_ss8(dv, da0 + (uint64_t)(kt * 128), dbm + (uint64_t)(kt * 16), kt > 0);
                        wg_commit();
                        if (kt < 39) wg_wait<1>();
                    }
                    wg_commit();
                }
                TR(1);
                bar_sync(5, 160);
                TR(2);
                uint32_t pb[5];
                #pragma unroll
                for (int j = 0; j < 5; j++) pb[j] = lds1(sb + SM_PM + j * 128 + lane * 4);
                float o0[4] = {0.f, 0.f, 0.f, 0.f}, o1[4] = {0.f, 0.f, 0.f, 0.f}, o2[4] = {0.f, 0.f, 0.f, 0.f};
                wg_wait<0>();
                TR(3);
                mma16(o0, vx[0], vx[1], vx[2], vx[3], pb[1], pb[2]);
                mma16(o1, vx[4], vx[5], vx[6], vx[7], pb[3], pb[4]);
                const uint32_t vm0 = pack2(dv[0], dv[1]), vm1 = pack2(dv[2], dv[3]);
                mma8(o2, vm0, vm1, pb[0]);
                if (s < NSEG - 1) {
                    const uint32_t q0 = pack2(o0[0] + o1[0] + o2[0], o0[1] + o1[1] + o2[1]), q1 = pack2(o0[2] + o1[2] + o2[2], o0[3] + o1[3] + o2[3]);
                    const uint32_t la = sb + SM_OS + (w * 16 + g) * 16 + t * 4;
                    #pragma unroll
                    for (int i = 1; i < 3; i++) {
                        const uint32_t rk = (p + i) % 3;
                        const uint32_t ra = mapa(la + (3 - i) * 1024, rk), rb = mapa(bar + B_O * 8, rk);
                        st_async1(ra, q0, rb);
                        st_async1(ra + 128, q1, rb);
                    }
                    sts1(la, q0);
                    sts1(la + 128, q1);
                    __syncwarp();
                    if (lane == 0) { mbar_arrive(bar + B_O1 * 8); mbar_arrive(bar + B_MEM_FREE * 8); }
                }
                TR(5);
                if (s < NSEG - 1) {
                    wo_phase<4, 4>(sb, warp, lane, res, par, (uint32_t)(s % 15) + 1u, tile0 + warp, h);
                    TR(4);
                    if (tid == 256) mbar_expect(bar + B_O * 8, 2048);
                }
                if (s < NSEG - 1) bar_arrive(6, 512);
                bar_sync(7, 256);
                TR(8);
                FRESH(lane);
                bf16* orow = g_ox + (size_t)(s * 32 + (lane >> 2)) * HD + h * DH + p * 64 + w * 16 + 2 * (lane & 3);
                {
                    const uint32_t pa = sb + SM_XS + lane * 16;
                    const uint4 p0 = lds4(pa), p1 = lds4(pa + 1536), p2 = lds4(pa + 2560);
                    const uint32_t p3 = lds1(pa + 1024 + 8), p4 = lds1(pa + 3584 + 8);
                    float oa[4][4];
                    #pragma unroll
                    for (int i = 0; i < 4; i++) { oa[i][0] = 0.f; oa[i][1] = 0.f; oa[i][2] = 0.f; oa[i][3] = 0.f; }
                    mma8(oa[0], vm0, vm1, p0.x);
                    mma8(oa[1], vm0, vm1, p0.z);
                    mma8(oa[2], vm0, vm1, p1.x);
                    mma8(oa[3], vm0, vm1, p1.z);
                    mma16(oa[0], vx[0], vx[1], vx[2], vx[3], p0.y, 0u);
                    mma16(oa[1], vx[0], vx[1], vx[2], vx[3], p0.w, p3);
                    mma16(oa[2], vx[0], vx[1], vx[2], vx[3], p1.y, p2.x);
                    mma16(oa[3], vx[0], vx[1], vx[2], vx[3], p1.w, p2.z);
                    mma16(oa[2], vx[4], vx[5], vx[6], vx[7], p2.y, 0u);
                    mma16(oa[3], vx[4], vx[5], vx[6], vx[7], p2.w, p4);
                    if (lane < 3) mbar_arrive_remote(mapa(bar + B_XSFREE * 8, lane));
                    uint32_t u[8];
                    #pragma unroll
                    for (int i = 0; i < 4; i++) { u[2 * i] = movm(pack2(oa[i][0], oa[i][1])); u[2 * i + 1] = movm(pack2(oa[i][2], oa[i][3])); }
                    #pragma unroll
                    for (int i = 0; i < 4; i++) {
                        *(uint32_t*)(orow + (size_t)(8 * i) * HD) = u[2 * i];
                        *(uint32_t*)(orow + (size_t)(8 * i) * HD + 8) = u[2 * i + 1];
                    }
                }
                TR(9);
                if (s == NSEG - 1) break;
            }
            float d[16];
            const uint32_t hp = (s + 1) & 1;
            const uint64_t db0 = make_desc(SBC + SM_HB, 16, 1024, 1);
            mbar_wait(bar + B_HHI_FULL * 8, hp);
            mbar_wait(bar + B_HLO_FULL * 8, hp);
            bar_sync(9, 384);
            TR(6);
            wg_fence();
            #pragma unroll
            for (int kt = 0; kt < 40; kt++) {
                wg_ss32(d, da0 + (uint64_t)(kt * 128), db0 + (uint64_t)(((kt >> 2) * 4096 + (kt & 3) * 32) >> 4), kt > 0);
                wg_commit();
                if (kt < 39) wg_wait<1>();
                if (kt == 12 && lane == 0) mbar_arrive(bar + B_HLO_FREE * 8);
            }
            wg_wait<0>();
            TR(7);
            if (lane == 0) mbar_arrive(bar + B_HHI_FREE * 8);
            #pragma unroll
            for (int i = 0; i < 8; i++) vx[i] = pack2(d[2 * i], d[2 * i + 1]);
            if (s >= 0) mbar_wait_cluster(bar + B_XSFREE * 8, s & 1);
            bar_sync(8, 384);
            TR(10);
            if (w < 3) xscores<2>(sb, p, w > 0, w == 2 ? 3 : 1, lane);
            TR(11);
            if (s < 0) bar_sync(0, 512);
        }
    } else {
        asm volatile("setmaxnreg.dec.sync.aligned.u32 48;");
        const int w = warp & 3, lt = tid & 127;
        {
            const bf16* src0 = Wo + (size_t)h * DH * DM + tile0 * 16;
            const int nch = 2 * ntile;
            for (int i = lt; i < DH * nch; i += 128) {
                const int e = i / nch, c = i - e * nch, tl = c >> 1, cc = c & 1;
                int es = e;
                if (tl >= 8 && tl < 12) { if (e >= 64 && e < 128) continue; if (e >= 128) es = e - 64; }
                int eg = e + p * 64; if (eg >= DH) eg -= DH;
                cpa16(sb + SM_WO + wo_tile_off(tl) + es * 32 + ((cc ^ ((e >> 2) & 1)) << 4), src0 + (size_t)eg * DM + c * 8);
            }
        }
        const uint32_t epoch = *(volatile uint32_t*)&g_epoch;
        if (b < 80) {
            #pragma unroll
            for (int i = 0; i < 2; i++) {
                const int idx = lt + i * 128, sl = idx >> 6, pg = (idx >> 5) & 1, wd = idx & 31;
                st_relaxed1(g_buf2 + (sl * 3 + (b >> 5)) * 2048 + pg * 1024 + (b & 31) * 32 + wd, 0xFFFFFFFFu);
            }
            __threadfence();
        }
        if (lane == 0) {
            for (int i = w; i < 14; i += 4) {
                int c = 0;
                if (i < 12) c = probe_blk(g_buf2 + i * 2048 + 640 + (b & 31) * 8);
                else if (b < 80) c = probe_blk(g_buf1 + (b * 2 + (i - 12)) * 2048);
                asm volatile("st.shared.u8 [%0], %1;" :: "r"(sb + SM_CH + 96 + i), "r"(c) : "memory");
            }
        }
        bar_sync(3, 128);
        uint32_t selmask = 0;
        for (int i = 0; i < 14; i++) {
            uint32_t c; asm volatile("ld.shared.u8 %0, [%1];" : "=r"(c) : "r"(sb + SM_CH + 96 + i) : "memory");
            selmask |= c << i;
        }
        if (lt == 0 && b < 80) st_release1(&g_choice[b], (epoch << 2) | (selmask >> 12));
        if (lt < 80) {
            uint32_t v, guard = 0;
            do { v = ld_acquire1(&g_choice[lt]); if (++guard > (1u << 22)) __trap(); } while ((v >> 2) != (epoch & 0x3fffffffu));
            asm volatile("st.shared.u8 [%0], %1;" :: "r"(sb + SM_CH + lt), "r"(v & 3u) : "memory");
        }
        cpa_wait_all();
        bar_sync(0, 512);
        const bool has_tile = (12 + w) < ntile;
        for (int s = 0; s < NSEG; s++) {
            const uint32_t par = s & 1;
            FRESH(lane);
            const int g = lane >> 2, t = lane & 3, lt = w * 32 + lane;
            if (s == 0) {
                mbar_wait(bar + B_HLO_FREE * 8, par);
                for (int k = lt; k < DM; k += 128) {
                    uint32_t v[4];
                    #pragma unroll
                    for (int i = 0; i < 4; i++) {
                        uint32_t lo = *(const uint16_t*)(mem0 + (2 * i) * DM + k), hi = *(const uint16_t*)(mem0 + (2 * i + 1) * DM + k);
                        v[i] = lo | (hi << 16);
                    }
                    asm volatile("st.shared.v4.u32 [%0], {%1,%2,%3,%4};" :: "r"(sb + SM_HB + k * 16), "r"(v[0]), "r"(v[1]), "r"(v[2]), "r"(v[3]) : "memory");
                }
            } else {
                const int sl = s & 3;
                const char* q = (const char*)g_buf2 + sl * 3 * 8192 + lt * 16;
                const uint32_t sm = selmask >> (sl * 3);
                const char* q0 = q + (sm & 1) * 4096;
                const char* q1 = q + 8192 + (sm & 2) * 2048;
                const char* q2 = q + 16384 + (sm & 4) * 1024;
                const uint32_t dst = sb + SM_HB + lt * 16;
                uint32_t guard = 0;
                mbar_wait(bar + B_HLO_FREE * 8, par);
                TR(10);
                while (true) {
                    const uint4 v0 = ld_relaxed4(q0), v1 = ld_relaxed4(q0 + 2048), v2 = ld_relaxed4(q1), v3 = ld_relaxed4(q1 + 2048), v4 = ld_relaxed4(q2);
                    sts4(dst, v0); sts4(dst + 2048, v1); sts4(dst + 4096, v2); sts4(dst + 6144, v3); sts4(dst + 8192, v4);
                    if (__all_sync(0xffffffffu, oks(v0) && oks(v1) && oks(v2) && oks(v3) && oks(v4))) break;
                    if (++guard > (1u << 22)) __trap();
                }
            }
            fence_async();
            __syncwarp();
            if (lane == 0) mbar_arrive(bar + B_MEM_FULL * 8);
            TR(0);
            if (w == 2) {
                mbar_wait(bar + B_MS * 8, par);
                TR(1);
                if (lane == 0) mbar_expect(bar + B_MS * 8, 3840);
                uint32_t pb[5];
                float sc[5][2];
                {
                    const uint32_t a = sb + SM_MS + lane * 8;
                    float2 u[5], v[5];
                    #pragma unroll
                    for (int j = 0; j < 5; j++) { u[j] = lds2f(a + j * 256); v[j] = lds2f(a + j * 256 + 1280); }
                    #pragma unroll
                    for (int j = 0; j < 5; j++) { sc[j][0] = u[j].x + v[j].x; sc[j][1] = u[j].y + v[j].y; }
                    #pragma unroll
                    for (int j = 0; j < 5; j++) u[j] = lds2f(a + j * 256 + 2560);
                    #pragma unroll
                    for (int j = 0; j < 5; j++) { sc[j][0] += u[j].x; sc[j][1] += u[j].y; }
                }
                softmax_core<5, false>(sc, g, t, pb);
                #pragma unroll
                for (int j = 0; j < 5; j++) sts1(sb + SM_PM + j * 128 + lane * 4, pb[j]);
                bar_arrive(5, 160);
                TR(2);
            }
            const uint32_t tag = (uint32_t)(s % 15) + 1u;
            if (s < NSEG - 1) {
                if (w == 3) {
                    const char* src = (const char*)g_ht + (size_t)(s + 1) * 40960;
                    mbar_wait(bar + B_HHI_FREE * 8, par);
                    if (lane == 0) {
                        mbar_expect(bar + B_HHI_FULL * 8, 28672);
                        bulk_g2s(sb + SM_HB + 12288, src + 12288, 28672, sb + SM_BAR + B_HHI_FULL * 8);
                    }
                    mbar_wait(bar + B_MEM_FREE * 8, par);
                    if (lane == 0) {
                        mbar_expect(bar + B_HLO_FULL * 8, 12288);
                        bulk_g2s(sb + SM_HB, src, 12288, sb + SM_BAR + B_HLO_FULL * 8);
                    }
                    __syncwarp();
                }
                if (has_tile) wo_phase<0, 4>(sb, warp, lane, nullptr, par, tag, tile0 + warp, h);
                TR(4);
                bar_sync(6, 512);
            }
            {
                FRESH(lane);
                mbar_wait(bar + B_XS * 8, par);
                TR(8);
                if (w == 0 && lane == 0) mbar_expect(bar + B_XS * 8, 12288);
                const uint32_t a = sb + SM_XS + (w >> 1) * 1536 + lane * 16 + (w & 1) * 8;
                if (w == 0) xsoftmax<2>(a, lane >> 2, lane & 3);
                else if (w == 1) xsoftmax<3>(a, lane >> 2, lane & 3);
                else if (w == 2) xsoftmax<4>(a, lane >> 2, lane & 3);
                else xsoftmax<5>(a, lane >> 2, lane & 3);
                bar_arrive(7, 256);
                TR(9);
            }
            if (s < NSEG - 1) {
                if (b < 80) {
                    FRESH(lane);
                    const char* rin0 = (const char*)g_buf1 + (size_t)(b * 2) * 8192 + ((selmask >> 12) & 1) * 4096 + (lane >> 2) * 256 + w * 64 + (lane & 3) * 16;
                    const char* rin1 = (const char*)g_buf1 + (size_t)(b * 2 + 1) * 8192 + ((selmask >> 13) & 1) * 4096 + (lane >> 2) * 256 + w * 64 + (lane & 3) * 16;
                    const int col = b * 8 + 2 * w + ((lane >> 1) & 1), wd = 2 * (lane & 1) + (lane >> 4);
                    const int sl = (lane & 8) ? ((s + 3) & 3) : ((s + 1) & 3);
                    uint32_t* dst = g_buf2 + (sl * 3 + (col >> 8)) * 2048 + ((lane >> 2) & 1) * 1024 + (col & 255) * 4 + wd;
                    asm volatile("" : "+l"(dst));
                    uint4 v0, v1, v2, v3;
                    uint32_t guard = 0;
                    while (true) {
                        v0 = ld_relaxed4(rin0); v1 = ld_relaxed4(rin0 + 2048);
                        v2 = ld_relaxed4(rin1); v3 = ld_relaxed4(rin1 + 2048);
                        if (__all_sync(0xffffffffu, ok4(v0, tag) && ok4(v1, tag) && ok4(v2, tag) && ok4(v3, tag))) break;
                        if (++guard > (1u << 22)) __trap();
                    }
                    TR(11);
                    const float a0 = (uf(v0.x) + uf(v1.x)) + (uf(v2.x) + uf(v3.x)), a1 = (uf(v0.y) + uf(v1.y)) + (uf(v2.y) + uf(v3.y));
                    const float a2 = (uf(v0.z) + uf(v1.z)) + (uf(v2.z) + uf(v3.z)), a3 = (uf(v0.w) + uf(v1.w)) + (uf(v2.w) + uf(v3.w));
                    const bool u16 = lane & 16;
                    float m0 = (u16 ? a2 : a0) + __shfl_xor_sync(0xffffffffu, u16 ? a0 : a2, 16);
                    float m1 = (u16 ? a3 : a1) + __shfl_xor_sync(0xffffffffu, u16 ? a1 : a3, 16);
                    m0 += __shfl_xor_sync(0xffffffffu, m0, 8); m1 += __shfl_xor_sync(0xffffffffu, m1, 8);
                    m0 += __shfl_xor_sync(0xffffffffu, m0, 4); m1 += __shfl_xor_sync(0xffffffffu, m1, 4);
                    st_relaxed1(dst, (lane & 8) ? 0xFFFFFFFFu : pack2(m0, m1));
                    TR(12);
                }
            }
        }
    }
    cluster_sync();
}

constexpr int G_STAGES = 5;
constexpr int G_STAGE_BYTES = 32768;
constexpr int G_SMEM = G_STAGES * G_STAGE_BYTES + 1024 + 256;

__device__ __forceinline__ void tma2d(uint32_t dst, const CUtensorMap* map, int c0, int c1, uint32_t bar) {
    asm volatile("cp.async.bulk.tensor.2d.shared::cluster.global.mbarrier::complete_tx::bytes [%0], [%1, {%2, %3}], [%4];"
                 :: "r"(dst), "l"(map), "r"(c0), "r"(c1), "r"(bar) : "memory");
}
__device__ __forceinline__ void wg_ss128(float* d, uint64_t da, uint64_t db, int sc) {
    asm volatile("{\n\t.reg .pred p;\n\tsetp.ne.b32 p, %66, 0;\n\t"
        "wgmma.mma_async.sync.aligned.m64n128k16.f32.bf16.bf16 "
        "{%0,%1,%2,%3,%4,%5,%6,%7,%8,%9,%10,%11,%12,%13,%14,%15,%16,%17,%18,%19,%20,%21,%22,%23,%24,%25,%26,%27,%28,%29,%30,%31,"
        "%32,%33,%34,%35,%36,%37,%38,%39,%40,%41,%42,%43,%44,%45,%46,%47,%48,%49,%50,%51,%52,%53,%54,%55,%56,%57,%58,%59,%60,%61,%62,%63}, "
        "%64, %65, p, 1, 1, 0, 1;\n\t}"
        : "+f"(d[0]), "+f"(d[1]), "+f"(d[2]), "+f"(d[3]), "+f"(d[4]), "+f"(d[5]), "+f"(d[6]), "+f"(d[7]),
          "+f"(d[8]), "+f"(d[9]), "+f"(d[10]), "+f"(d[11]), "+f"(d[12]), "+f"(d[13]), "+f"(d[14]), "+f"(d[15]),
          "+f"(d[16]), "+f"(d[17]), "+f"(d[18]), "+f"(d[19]), "+f"(d[20]), "+f"(d[21]), "+f"(d[22]), "+f"(d[23]),
          "+f"(d[24]), "+f"(d[25]), "+f"(d[26]), "+f"(d[27]), "+f"(d[28]), "+f"(d[29]), "+f"(d[30]), "+f"(d[31]),
          "+f"(d[32]), "+f"(d[33]), "+f"(d[34]), "+f"(d[35]), "+f"(d[36]), "+f"(d[37]), "+f"(d[38]), "+f"(d[39]),
          "+f"(d[40]), "+f"(d[41]), "+f"(d[42]), "+f"(d[43]), "+f"(d[44]), "+f"(d[45]), "+f"(d[46]), "+f"(d[47]),
          "+f"(d[48]), "+f"(d[49]), "+f"(d[50]), "+f"(d[51]), "+f"(d[52]), "+f"(d[53]), "+f"(d[54]), "+f"(d[55]),
          "+f"(d[56]), "+f"(d[57]), "+f"(d[58]), "+f"(d[59]), "+f"(d[60]), "+f"(d[61]), "+f"(d[62]), "+f"(d[63])
        : "l"(da), "l"(db), "r"(sc));
}

template <int EPI>
__global__ void __launch_bounds__(384, 1)
k_gemm(const __grid_constant__ CUtensorMap mapA, const __grid_constant__ CUtensorMap mapB, int K,
       const bf16* __restrict__ xin, bf16* __restrict__ outp) {
    extern __shared__ uint8_t smem_raw[];
    const uint32_t sb = (smem_u32(smem_raw) + 1023u) & ~1023u;
    const uint32_t bars = sb + G_STAGES * G_STAGE_BYTES;
    const int tid = threadIdx.x, lane = tid & 31, wg = tid >> 7;
    const int n0 = blockIdx.x * 128, m0 = blockIdx.y * 128;
    const int nk = K / 64;
    if (tid == 0) {
        for (int i = 0; i < G_STAGES; i++) { mbar_init(bars + i * 8, 1); mbar_init(bars + 64 + i * 8, 8); }
        asm volatile("fence.mbarrier_init.release.cluster;" ::: "memory");
    }
    __syncthreads();
    if (wg == 0) {
        if (tid == 0) {
            for (int kb = 0; kb < nk; kb++) {
                const int st = kb % G_STAGES;
                if (kb >= G_STAGES) mbar_wait(bars + 64 + st * 8, ((kb / G_STAGES) - 1) & 1);
                const uint32_t a = sb + st * G_STAGE_BYTES;
                mbar_expect(bars + st * 8, G_STAGE_BYTES);
                tma2d(a, &mapA, kb * 64, m0, bars + st * 8);
                tma2d(a + 16384, &mapB, n0, kb * 64, bars + st * 8);
                tma2d(a + 16384 + 8192, &mapB, n0 + 64, kb * 64, bars + st * 8);
            }
        }
    } else {
        float d[64];
        #pragma unroll
        for (int i = 0; i < 64; i++) d[i] = 0.f;
        const int cw = wg - 1;
        for (int kb = 0; kb < nk; kb++) {
            const int st = kb % G_STAGES;
            mbar_wait(bars + st * 8, (kb / G_STAGES) & 1);
            const uint32_t a = sb + st * G_STAGE_BYTES;
            const uint64_t da = make_desc(a + cw * 8192, 16, 1024, 1);
            const uint64_t db = make_desc(a + 16384, 8192, 1024, 1);
            wg_fence();
            #pragma unroll
            for (int k = 0; k < 4; k++) wg_ss128(d, da + (uint64_t)(k * 2), db + (uint64_t)(k * 128), 1);
            wg_commit();
            if (kb > 0) {
                wg_wait<1>();
                if (lane == 0) mbar_arrive(bars + 64 + ((kb - 1) % G_STAGES) * 8);
            }
        }
        wg_wait<0>();
        const int g = lane >> 2, t = lane & 3, w = (tid >> 5) & 3;
        const int ldo = EPI == 1 ? FF : DM;
        #pragma unroll
        for (int hf = 0; hf < 2; hf++) {
            const int row = m0 + cw * 64 + w * 16 + g + 8 * hf;
            #pragma unroll
            for (int j = 0; j < 16; j++) {
                const int col = n0 + j * 8 + 2 * t;
                float a0 = bfr(d[4 * j + 2 * hf]), a1 = bfr(d[4 * j + 2 * hf + 1]);
                uint32_t o;
                if (EPI == 1) {
                    o = pack2(a0 / (1.0f + __expf(-a0)), a1 / (1.0f + __expf(-a1)));
                } else {
                    const float2 gm = *(const float2*)(g_mod + (EPI == 0 ? 2 : 5) * DM + col);
                    const uint32_t xv = *(const uint32_t*)(xin + (size_t)row * DM + col);
                    o = pack2(bflo(xv) + bfr(gm.x * a0), bfhi(xv) + bfr(gm.y * a1));
                }
                *(uint32_t*)(outp + (size_t)row * ldo + col) = o;
            }
        }
    }
}

typedef CUresult (*EncodeFn)(CUtensorMap*, CUtensorMapDataType, cuuint32_t, void*, const cuuint64_t*, const cuuint64_t*,
                             const cuuint32_t*, const cuuint32_t*, CUtensorMapInterleave, CUtensorMapSwizzle,
                             CUtensorMapL2promotion, CUtensorMapFloatOOBfill);

static void make_map(EncodeFn fn, CUtensorMap* m, const void* ptr, uint64_t inner, uint64_t outer, uint32_t bi, uint32_t bo) {
    cuuint64_t dims[2] = {inner, outer};
    cuuint64_t strides[1] = {inner * 2};
    cuuint32_t box[2] = {bi, bo};
    cuuint32_t es[2] = {1, 1};
    fn(m, CU_TENSOR_MAP_DATA_TYPE_BFLOAT16, 2, (void*)ptr, dims, strides, box, es, CU_TENSOR_MAP_INTERLEAVE_NONE,
       CU_TENSOR_MAP_SWIZZLE_128B, CU_TENSOR_MAP_L2_PROMOTION_L2_256B, CU_TENSOR_MAP_FLOAT_OOB_FILL_NONE);
}

extern "C" void kernel_launch(void* const* d_in, const int* in_sizes, int n_in, void* d_out, int out_size) {
    const bf16* x = (const bf16*)d_in[0];
    const bf16* mem0 = (const bf16*)d_in[1];
    const bf16* Wq = (const bf16*)d_in[2];
    const bf16* Wk = (const bf16*)d_in[3];
    const bf16* Wv = (const bf16*)d_in[4];
    const bf16* Wo = (const bf16*)d_in[5];
    const bf16* w1 = (const bf16*)d_in[8];
    const bf16* w2 = (const bf16*)d_in[9];
    const bf16* c = (const bf16*)d_in[10];
    const bf16* wmod = (const bf16*)d_in[11];
    bf16* out = (bf16*)d_out;

    static EncodeFn enc = nullptr;
    static void *p_ox, *p_x1, *p_h2, *p_act;
    if (!enc) {
        cudaDriverEntryPointQueryResult qr;
        void* f = nullptr;
        cudaGetDriverEntryPoint("cuTensorMapEncodeTiled", &f, cudaEnableDefault, &qr);
        enc = (EncodeFn)f;
        cudaGetSymbolAddress(&p_ox, g_ox);
        cudaGetSymbolAddress(&p_x1, g_x1);
        cudaGetSymbolAddress(&p_h2, g_h2);
        cudaGetSymbolAddress(&p_act, g_act);
        cudaFuncSetAttribute(k_rec, cudaFuncAttributeMaxDynamicSharedMemorySize, SM_TOTAL);
        cudaFuncSetAttribute(k_gemm<0>, cudaFuncAttributeMaxDynamicSharedMemorySize, G_SMEM);
        cudaFuncSetAttribute(k_gemm<1>, cudaFuncAttributeMaxDynamicSharedMemorySize, G_SMEM);
        cudaFuncSetAttribute(k_gemm<2>, cudaFuncAttributeMaxDynamicSharedMemorySize, G_SMEM);
    }
    CUtensorMap mOx, mWo, mH2, mW1, mAct, mW2;
    make_map(enc, &mOx, p_ox, HD, SEQ, 64, 128);
    make_map(enc, &mWo, Wo, DM, HD, 64, 64);
    make_map(enc, &mH2, p_h2, DM, SEQ, 64, 128);
    make_map(enc, &mW1, w1, FF, DM, 64, 64);
    make_map(enc, &mAct, p_act, FF, SEQ, 64, 128);
    make_map(enc, &mW2, w2, DM, FF, 64, 64);

    cudaStream_t st = cudaStreamPerThread;
    k_mod<<<60, 256, 0, st>>>(c, wmod);
    k_ln<0><<<SEQ / 8, 256, 0, st>>>(x);
    {
        cudaLaunchConfig_t cfg = {};
        cfg.gridDim = dim3(96); cfg.blockDim = dim3(512); cfg.dynamicSmemBytes = SM_TOTAL; cfg.stream = st;
        cudaLaunchAttribute at[1];
        at[0].id = cudaLaunchAttributeClusterDimension;
        at[0].val.clusterDim.x = 3; at[0].val.clusterDim.y = 1; at[0].val.clusterDim.z = 1;
        cfg.attrs = at; cfg.numAttrs = 1;
        cudaLaunchKernelEx(&cfg, k_rec, mem0, Wq, Wk, Wv, Wo);
    }
    k_gemm<0><<<dim3(5, 16), 384, G_SMEM, st>>>(mOx, mWo, HD, x, (bf16*)p_x1);
    k_ln<1><<<SEQ / 8, 256, 0, st>>>(nullptr);
    k_gemm<1><<<dim3(12, 16), 384, G_SMEM, st>>>(mH2, mW1, DM, nullptr, (bf16*)p_act);
    k_gemm<2><<<dim3(5, 16), 384, G_SMEM, st>>>(mAct, mW2, FF, (const bf16*)p_x1, out);
}
```

```cpp
#include <cuda_runtime.h>
#include <cuda_bf16.h>
#include <cuda.h>
#include <stdint.h>

typedef __nv_bfloat16 bf16;
#define VX_THROTTLE 1
#define H1_DELAY 400
#define H1_BACK 0
#define VM_THROTTLE 1

constexpr int SEQ = 2048, DM = 640, NH = 32, DH = 192, NSEG = 64, FF = 1536, HD = NH * DH;

__device__ float g_mod[6 * DM];
__device__ __align__(1024) bf16 g_ht[(size_t)SEQ * DM];
__device__ __align__(1024) bf16 g_ox[(size_t)SEQ * HD];
__device__ __align__(1024) bf16 g_x1[(size_t)SEQ * DM];
__device__ __align__(1024) bf16 g_h2[(size_t)SEQ * DM];
__device__ __align__(1024) bf16 g_act[(size_t)SEQ * FF];
__device__ __align__(8192) uint32_t g_buf1[80 * 2 * 2048];
__device__ __align__(8192) uint32_t g_buf2[4 * 3 * 2048];
__device__ uint32_t g_choice[128];
__device__ uint32_t g_epoch;
#define TR(k)

#define FRESH(x) asm volatile("" : "+r"(x))
__device__ __forceinline__ float bfr(float x) { return __bfloat162float(__float2bfloat16_rn(x)); }
__device__ __forceinline__ uint32_t pack2(float a, float b) {
    uint32_t r; asm("cvt.rn.bf16x2.f32 %0, %1, %2;" : "=r"(r) : "f"(b), "f"(a)); return r;
}
__device__ __forceinline__ float bflo(uint32_t v) { return __uint_as_float(v << 16); }
__device__ __forceinline__ float bfhi(uint32_t v) { return __uint_as_float(v & 0xffff0000u); }
__device__ __forceinline__ float ex2(float x) { float r; asm("ex2.approx.ftz.f32 %0, %1;" : "=f"(r) : "f"(x)); return r; }
__device__ __forceinline__ float rcpf(float x) { float r; asm("rcp.approx.ftz.f32 %0, %1;" : "=f"(r) : "f"(x)); return r; }
__device__ __forceinline__ void score2(float& a, float& b) {
    const float SCALE = 0.07216878364870322f;
    uint32_t u = pack2(a, b);
    u = pack2(bflo(u) * SCALE, bfhi(u) * SCALE);
    a = bflo(u); b = bfhi(u);
}
__device__ __forceinline__ uint32_t smem_u32(const void* p) { return (uint32_t)__cvta_generic_to_shared(p); }

__device__ __forceinline__ void mbar_init(uint32_t bar, uint32_t cnt) {
    asm volatile("mbarrier.init.shared::cta.b64 [%0], %1;" :: "r"(bar), "r"(cnt) : "memory");
}
__device__ __forceinline__ void mbar_arrive(uint32_t bar) {
    asm volatile("mbarrier.arrive.shared::cta.b64 _, [%0];" :: "r"(bar) : "memory");
}
__device__ __forceinline__ void mbar_expect(uint32_t bar, uint32_t bytes) {
    asm volatile("mbarrier.arrive.expect_tx.shared::cta.b64 _, [%0], %1;" :: "r"(bar), "r"(bytes) : "memory");
}
__device__ __forceinline__ bool mbar_try(uint32_t bar, uint32_t parity) {
    uint32_t ok;
    asm volatile("{\n\t.reg .pred p;\n\tmbarrier.try_wait.parity.shared::cta.b64 p, [%1], %2;\n\tselp.u32 %0, 1, 0, p;\n\t}"
                 : "=r"(ok) : "r"(bar), "r"(parity) : "memory");
    return ok != 0;
}
__device__ __forceinline__ bool mbar_try_cluster(uint32_t bar, uint32_t parity) {
    uint32_t ok;
    asm volatile("{\n\t.reg .pred p;\n\tmbarrier.try_wait.parity.acquire.cluster.shared::cta.b64 p, [%1], %2;\n\tselp.u32 %0, 1, 0, p;\n\t}"
                 : "=r"(ok) : "r"(bar), "r"(parity) : "memory");
    return ok != 0;
}
__device__ __forceinline__ void mbar_wait(uint32_t bar, uint32_t parity) {
    uint32_t guard = 0;
    while (!mbar_try(bar, parity)) { if (++guard > (1u << 22)) __trap(); }
}
__device__ __forceinline__ void mbar_wait_cluster(uint32_t bar, uint32_t parity) {
    uint32_t guard = 0;
    while (!mbar_try_cluster(bar, parity)) { if (++guard > (1u << 22)) __trap(); }
}
__device__ __forceinline__ void bar_sync(int id, int n) { asm volatile("bar.sync %0, %1;" :: "r"(id), "r"(n) : "memory"); }
__device__ __forceinline__ void bar_arrive(int id, int n) { asm volatile("bar.arrive %0, %1;" :: "r"(id), "r"(n) : "memory"); }
__device__ __forceinline__ void sts1(uint32_t a, uint32_t v) { asm volatile("st.shared.u32 [%0], %1;" :: "r"(a), "r"(v) : "memory"); }
__device__ __forceinline__ uint32_t lds1(uint32_t a) { uint32_t v; asm volatile("ld.shared.u32 %0, [%1];" : "=r"(v) : "r"(a) : "memory"); return v; }
__device__ __forceinline__ void fence_async() { asm volatile("fence.proxy.async.shared::cta;" ::: "memory"); }
__device__ __forceinline__ void cluster_sync() {
    asm volatile("barrier.cluster.arrive.release.aligned;\n\tbarrier.cluster.wait.acquire.aligned;" ::: "memory");
}
__device__ __forceinline__ uint32_t mapa(uint32_t a, uint32_t rank) {
    uint32_t r; asm("mapa.shared::cluster.u32 %0, %1, %2;" : "=r"(r) : "r"(a), "r"(rank)); return r;
}
__device__ __forceinline__ void st_async1(uint32_t a, uint32_t v, uint32_t bar) {
    asm volatile("st.async.weak.shared::cluster.mbarrier::complete_tx::bytes.b32 [%0], %1, [%2];" :: "r"(a), "r"(v), "r"(bar) : "memory");
}
__device__ __forceinline__ void st_async2(uint32_t a, float x, float y, uint32_t bar) {
    asm volatile("st.async.weak.shared::cluster.mbarrier::complete_tx::bytes.v2.f32 [%0], {%1,%2}, [%3];" :: "r"(a), "f"(x), "f"(y), "r"(bar) : "memory");
}
__device__ __forceinline__ void st_async4(uint32_t a, const float* c, uint32_t bar) {
    asm volatile("st.async.weak.shared::cluster.mbarrier::complete_tx::bytes.v4.f32 [%0], {%1,%2,%3,%4}, [%5];"
                 :: "r"(a), "f"(c[0]), "f"(c[1]), "f"(c[2]), "f"(c[3]), "r"(bar) : "memory");
}
__device__ __forceinline__ void bulk_g2s(uint32_t dst, const void* src, uint32_t bytes, uint32_t bar) {
    asm volatile("cp.async.bulk.shared::cluster.global.mbarrier::complete_tx::bytes [%0], [%1], %2, [%3];"
                 :: "r"(dst), "l"(src), "r"(bytes), "r"(bar) : "memory");
}
__device__ __forceinline__ void cpa16(uint32_t s, const void* g) {
    asm volatile("cp.async.cg.shared.global [%0], [%1], 16;" :: "r"(s), "l"(g) : "memory");
}
__device__ __forceinline__ void cpa_wait_all() { asm volatile("cp.async.wait_all;" ::: "memory"); }
__device__ __forceinline__ void ldsm4(uint32_t* r, uint32_t a) {
    asm volatile("ldmatrix.sync.aligned.m8n8.x4.shared.b16 {%0,%1,%2,%3}, [%4];" : "=r"(r[0]), "=r"(r[1]), "=r"(r[2]), "=r"(r[3]) : "r"(a) : "memory");
}
__device__ __forceinline__ void ldsm4t(uint32_t* r, uint32_t a) {
    asm volatile("ldmatrix.sync.aligned.m8n8.x4.trans.shared.b16 {%0,%1,%2,%3}, [%4];" : "=r"(r[0]), "=r"(r[1]), "=r"(r[2]), "=r"(r[3]) : "r"(a) : "memory");
}
__device__ __forceinline__ void stsm2t(uint32_t a, uint32_t r0, uint32_t r1) {
    asm volatile("stmatrix.sync.aligned.m8n8.x2.trans.shared.b16 [%0], {%1,%2};" :: "r"(a), "r"(r0), "r"(r1) : "memory");
}
__device__ __forceinline__ void stsm4t(uint32_t a, uint32_t r0, uint32_t r1, uint32_t r2, uint32_t r3) {
    asm volatile("stmatrix.sync.aligned.m8n8.x4.trans.shared.b16 [%0], {%1,%2,%3,%4};" :: "r"(a), "r"(r0), "r"(r1), "r"(r2), "r"(r3) : "memory");
}
__device__ __forceinline__ uint32_t movm(uint32_t v) {
    uint32_t r; asm volatile("movmatrix.sync.aligned.m8n8.trans.b16 %0, %1;" : "=r"(r) : "r"(v)); return r;
}
__device__ __forceinline__ void mma16(float* c, uint32_t a0, uint32_t a1, uint32_t a2, uint32_t a3, uint32_t b0, uint32_t b1) {
    asm volatile("mma.sync.aligned.m16n8k16.row.col.f32.bf16.bf16.f32 {%0,%1,%2,%3}, {%4,%5,%6,%7}, {%8,%9}, {%0,%1,%2,%3};"
                 : "+f"(c[0]), "+f"(c[1]), "+f"(c[2]), "+f"(c[3]) : "r"(a0), "r"(a1), "r"(a2), "r"(a3), "r"(b0), "r"(b1));
}
__device__ __forceinline__ void mma8(float* c, uint32_t a0, uint32_t a1, uint32_t b0) {
    asm volatile("mma.sync.aligned.m16n8k8.row.col.f32.bf16.bf16.f32 {%0,%1,%2,%3}, {%4,%5}, {%6}, {%0,%1,%2,%3};"
                 : "+f"(c[0]), "+f"(c[1]), "+f"(c[2]), "+f"(c[3]) : "r"(a0), "r"(a1), "r"(b0));
}
__host__ __device__ constexpr uint64_t make_desc(uint32_t saddr, uint32_t lbo, uint32_t sbo, uint32_t layout) {
    return (uint64_t)((saddr & 0x3FFFF) >> 4) | ((uint64_t)(lbo >> 4) << 16) | ((uint64_t)(sbo >> 4) << 32) | ((uint64_t)layout << 62);
}
__device__ __forceinline__ void wg_fence() { asm volatile("wgmma.fence.sync.aligned;" ::: "memory"); }
__device__ __forceinline__ void wg_commit() { asm volatile("wgmma.commit_group.sync.aligned;" ::: "memory"); }
template <int N> __device__ __forceinline__ void wg_wait() { asm volatile("wgmma.wait_group.sync.aligned %0;" :: "n"(N) : "memory"); }

#define D16(C) C(d[0]), C(d[1]), C(d[2]), C(d[3]), C(d[4]), C(d[5]), C(d[6]), C(d[7]), \
               C(d[8]), C(d[9]), C(d[10]), C(d[11]), C(d[12]), C(d[13]), C(d[14]), C(d[15])
#define DREG16 "{%0,%1,%2,%3,%4,%5,%6,%7,%8,%9,%10,%11,%12,%13,%14,%15}"
__device__ __forceinline__ void wg_rs32(float* d, const uint32_t* a, uint64_t db, bool acc) {
    if (acc)
        asm volatile("wgmma.mma_async.sync.aligned.m64n32k16.f32.bf16.bf16 " DREG16 ", {%16,%17,%18,%19}, %20, 1, 1, 1, 0;"
            : D16("+f") : "r"(a[0]), "r"(a[1]), "r"(a[2]), "r"(a[3]), "l"(db));
    else
        asm volatile("wgmma.mma_async.sync.aligned.m64n32k16.f32.bf16.bf16 " DREG16 ", {%16,%17,%18,%19}, %20, 0, 1, 1, 0;"
            : D16("=f") : "r"(a[0]), "r"(a[1]), "r"(a[2]), "r"(a[3]), "l"(db));
}
__device__ __forceinline__ void wg_ss32(float* d, uint64_t da, uint64_t db, bool acc) {
    if (acc)
        asm volatile("wgmma.mma_async.sync.aligned.m64n32k16.f32.bf16.bf16 " DREG16 ", %16, %17, 1, 1, 1, 1, 0;"
            : D16("+f") : "l"(da), "l"(db));
    else
        asm volatile("wgmma.mma_async.sync.aligned.m64n32k16.f32.bf16.bf16 " DREG16 ", %16, %17, 0, 1, 1, 1, 0;"
            : D16("=f") : "l"(da), "l"(db));
}
__device__ __forceinline__ void wg_ss8(float* d, uint64_t da, uint64_t db, bool acc) {
    if (acc)
        asm volatile("wgmma.mma_async.sync.aligned.m64n8k16.f32.bf16.bf16 {%0,%1,%2,%3}, %4, %5, 1, 1, 1, 1, 1;"
            : "+f"(d[0]), "+f"(d[1]), "+f"(d[2]), "+f"(d[3]) : "l"(da), "l"(db));
    else
        asm volatile("wgmma.mma_async.sync.aligned.m64n8k16.f32.bf16.bf16 {%0,%1,%2,%3}, %4, %5, 0, 1, 1, 1, 1;"
            : "=f"(d[0]), "=f"(d[1]), "=f"(d[2]), "=f"(d[3]) : "l"(da), "l"(db));
}
template <int OFF> __device__ __forceinline__ void ldsm4t_i(uint32_t* r, uint32_t a) {
    asm volatile("ldmatrix.sync.aligned.m8n8.x4.trans.shared.b16 {%0,%1,%2,%3}, [%4+%5];"
                 : "=r"(r[0]), "=r"(r[1]), "=r"(r[2]), "=r"(r[3]) : "r"(a), "n"(OFF) : "memory");
}

__device__ __forceinline__ uint4 ld_relaxed4(const void* p) {
    uint4 v;
    asm volatile("ld.relaxed.gpu.global.v4.u32 {%0,%1,%2,%3}, [%4];" : "=r"(v.x), "=r"(v.y), "=r"(v.z), "=r"(v.w) : "l"(p) : "memory");
    return v;
}
__device__ __forceinline__ void st_relaxed2(void* p, uint32_t a, uint32_t b) {
    asm volatile("st.relaxed.gpu.global.v2.u32 [%0], {%1,%2};" :: "l"(p), "r"(a), "r"(b) : "memory");
}
__device__ __forceinline__ void st_relaxed2_off(void* base, uint32_t off, uint32_t a, uint32_t b) {
    asm volatile("{\n\t.reg .u64 ad;\n\tcvt.u64.u32 ad, %1;\n\tadd.u64 ad, ad, %0;\n\tst.relaxed.gpu.global.v2.u32 [ad], {%2,%3};\n\t}"
                 :: "l"(base), "r"(off), "r"(a), "r"(b) : "memory");
}
__device__ __forceinline__ void st_relaxed1(void* p, uint32_t a) {
    asm volatile("st.relaxed.gpu.global.u32 [%0], %1;" :: "l"(p), "r"(a) : "memory");
}
__device__ __forceinline__ uint32_t ld_acquire1(const uint32_t* p) {
    uint32_t v; asm volatile("ld.acquire.gpu.global.u32 %0, [%1];" : "=r"(v) : "l"(p) : "memory"); return v;
}
__device__ __forceinline__ void st_release1(uint32_t* p, uint32_t a) {
    asm volatile("st.release.gpu.global.u32 [%0], %1;" :: "l"(p), "r"(a) : "memory");
}
__device__ __forceinline__ uint4 lds4(uint32_t s) {
    uint4 v; asm volatile("ld.shared.v4.u32 {%0,%1,%2,%3}, [%4];" : "=r"(v.x), "=r"(v.y), "=r"(v.z), "=r"(v.w) : "r"(s) : "memory"); return v;
}
__device__ __forceinline__ void sts4(uint32_t s, const uint4& v) {
    asm volatile("st.shared.v4.u32 [%0], {%1,%2,%3,%4};" :: "r"(s), "r"(v.x), "r"(v.y), "r"(v.z), "r"(v.w) : "memory");
}
__device__ __forceinline__ float4 lds4f(uint32_t s) {
    float4 v; asm volatile("ld.shared.v4.f32 {%0,%1,%2,%3}, [%4];" : "=f"(v.x), "=f"(v.y), "=f"(v.z), "=f"(v.w) : "r"(s) : "memory"); return v;
}
__device__ __forceinline__ uint2 lds2(uint32_t s) {
    uint2 v; asm volatile("ld.shared.v2.u32 {%0,%1}, [%2];" : "=r"(v.x), "=r"(v.y) : "r"(s) : "memory"); return v;
}
__device__ __forceinline__ float2 lds2f(uint32_t s) {
    float2 v; asm volatile("ld.shared.v2.f32 {%0,%1}, [%2];" : "=f"(v.x), "=f"(v.y) : "r"(s) : "memory"); return v;
}
__device__ __forceinline__ uint32_t clk32() { uint32_t c; asm volatile("mov.u32 %0, %%clock;" : "=r"(c) :: "memory"); return c; }
__device__ __forceinline__ uint32_t tagw(float v, uint32_t tag) { return ((__float_as_uint(v) + 8u) & ~15u) | tag; }
__device__ __forceinline__ bool ok4(const uint4& v, uint32_t tag) { return (((v.x ^ tag) | (v.y ^ tag) | (v.z ^ tag) | (v.w ^ tag)) & 15u) == 0; }
__device__ __forceinline__ bool oks(const uint4& v) { return v.x != 0xFFFFFFFFu && v.y != 0xFFFFFFFFu && v.z != 0xFFFFFFFFu && v.w != 0xFFFFFFFFu; }
__device__ __forceinline__ float uf(uint32_t x) { return __uint_as_float(x & ~15u); }

__global__ void __launch_bounds__(256) k_mod(const bf16* __restrict__ c, const bf16* __restrict__ wmod) {
    __shared__ float sc[DM];
    __shared__ float red[8][64];
    const int tid = threadIdx.x;
    for (int i = tid; i < DM; i += 256) {
        float v = __bfloat162float(c[i]);
        sc[i] = bfr(v / (1.0f + __expf(-v)));
    }
    __syncthreads();
    const int cp = tid & 31, kg = tid >> 5;
    const int col = blockIdx.x * 64 + cp * 2;
    float a0 = 0.f, a1 = 0.f;
    #pragma unroll 8
    for (int k = kg * 80; k < kg * 80 + 80; k++) {
        uint32_t w = *(const uint32_t*)(wmod + (size_t)k * (6 * DM) + col);
        a0 += sc[k] * bflo(w); a1 += sc[k] * bfhi(w);
    }
    red[kg][cp * 2] = a0; red[kg][cp * 2 + 1] = a1;
    __syncthreads();
    if (tid < 64) {
        float s = 0.f;
        #pragma unroll
        for (int i = 0; i < 8; i++) s += red[i][tid];
        g_mod[blockIdx.x * 64 + tid] = bfr(s);
    }
    if (blockIdx.x == 0 && tid == 0) g_epoch = g_epoch + 1;
}

template <int MODE>
__global__ void __launch_bounds__(256) k_ln(const bf16* __restrict__ xin) {
    const int lane = threadIdx.x & 31, row = blockIdx.x * 8 + (threadIdx.x >> 5);
    const bf16* src = (MODE == 0 ? xin : g_x1) + (size_t)row * DM;
    const float* shift = g_mod + (MODE == 0 ? 0 : 3 * DM);
    const float* scale = g_mod + (MODE == 0 ? DM : 4 * DM);
    float v[3][8];
    float s = 0.f;
    #pragma unroll
    for (int i = 0; i < 3; i++) {
        int c = lane + 32 * i;
        if (c < 80) {
            uint4 u = *(const uint4*)(src + c * 8);
            v[i][0] = bflo(u.x); v[i][1] = bfhi(u.x); v[i][2] = bflo(u.y); v[i][3] = bfhi(u.y);
            v[i][4] = bflo(u.z); v[i][5] = bfhi(u.z); v[i][6] = bflo(u.w); v[i][7] = bfhi(u.w);
        } else {
            #pragma unroll
            for (int j = 0; j < 8; j++) v[i][j] = 0.f;
        }
        #pragma unroll
        for (int j = 0; j < 8; j++) s += v[i][j];
    }
    #pragma unroll
    for (int o = 16; o > 0; o >>= 1) s += __shfl_xor_sync(0xffffffffu, s, o);
    const float mean = s * (1.0f / DM);
    float q = 0.f;
    #pragma unroll
    for (int i = 0; i < 3; i++) {
        if (lane + 32 * i < 80) {
            #pragma unroll
            for (int j = 0; j < 8; j++) { float d = v[i][j] - mean; q += d * d; }
        }
    }
    #pragma unroll
    for (int o = 16; o > 0; o >>= 1) q += __shfl_xor_sync(0xffffffffu, q, o);
    const float mb = bfr(mean);
    const float var = bfr(q * (1.0f / DM));
    const float sd = bfr(sqrtf(bfr(var + 1e-5f)));
    #pragma unroll
    for (int i = 0; i < 3; i++) {
        int c = lane + 32 * i;
        if (c < 80) {
            float o[8];
            #pragma unroll
            for (int j = 0; j < 8; j++) {
                float n = bfr(bfr(v[i][j] - mb) / sd);
                float m1 = bfr(1.0f + scale[c * 8 + j]);
                o[j] = bfr(n * m1) + shift[c * 8 + j];
            }
            uint4 u = make_uint4(pack2(o[0], o[1]), pack2(o[2], o[3]), pack2(o[4], o[5]), pack2(o[6], o[7]));
            if (MODE == 0) {
                int seg = row >> 5, r = row & 31, blk = c >> 3, cc = c & 7;
                *(uint4*)(g_ht + (size_t)seg * 20480 + blk * 2048 + r * 64 + ((cc ^ (r & 7)) << 3)) = u;
            } else {
                *(uint4*)(g_h2 + (size_t)row * DM + c * 8) = u;
            }
        }
    }
}

constexpr int SM_WV = 0;
constexpr int SM_HB = 81920;
constexpr int SM_WO = SM_HB + 40960;
constexpr int SM_QX = SM_WO + 77824;
constexpr int SM_KS = SM_QX + 4096;
constexpr int SM_QM = SM_KS + 5120;
constexpr int SM_XS = SM_QM + 1024;
constexpr int SM_MS = SM_XS + 12288;
constexpr int SM_OS = SM_MS + 3840;
constexpr int SM_PM = SM_OS + 3072;
constexpr int SM_BAR = SM_PM + 640;
constexpr int SM_CH = SM_BAR + 128;
constexpr int SM_TOTAL = SM_CH + 128;
static_assert(SM_TOTAL <= 232448, "smem");

enum { B_MEM_FULL = 0, B_MEM_FREE, B_HLO_FULL, B_HHI_FULL, B_HLO_FREE, B_HHI_FREE, B_MS, B_O, B_XS, B_O1, B_XSFREE };

__device__ __forceinline__ int probe_blk(uint32_t* blk) {
    uint32_t t0 = 0xffffffffu, t1 = 0xffffffffu, acc = 0;
    for (int rep = 0; rep < 3; rep++) {
        #pragma unroll
        for (int pg = 0; pg < 2; pg++) {
            uint32_t c0 = clk32();
            uint32_t v = atomicOr(blk + pg * 1024 + acc, 0u);
            acc = (v == 0x12345678u) ? 1u : 0u;
            asm volatile("" :: "r"(acc) : "memory");
            uint32_t c1 = clk32() + acc;
            uint32_t d = c1 - c0;
            if (rep > 0) { if (pg == 0) t0 = min(t0, d); else t1 = min(t1, d); }
        }
    }
    return t1 < t0 ? 1 : 0;
}

__device__ __forceinline__ uint32_t wo_tile_off(int w) {
    if (w < 8) return w * 6144;
    if (w < 12) return 8 * 6144 + (w - 8) * 4096;
    return 8 * 6144 + 4 * 4096 + (w - 12) * 6144;
}

template <int NRES, int NPRE>
__device__ __forceinline__ void wo_phase(uint32_t sb, int w, int lane, const uint32_t (*res)[4], uint32_t parity,
                                         uint32_t tag, int tile, int h) {
    FRESH(lane);
    const int er = (lane & 7) + 8 * (lane >> 4);
    const uint32_t aaddr = sb + SM_WO + wo_tile_off(w) + er * 32 + ((((lane >> 3) & 1) ^ ((er >> 2) & 1)) << 4);
    const uint32_t baddr = sb + SM_OS + lane * 16;
    float c0[4] = {0.f, 0.f, 0.f, 0.f}, c1[4] = {0.f, 0.f, 0.f, 0.f};
    uint32_t pre[NPRE > 4 ? NPRE : 4][4];
    if (NPRE >= 4) {
        #pragma unroll
        for (int i = 0; i < 4; i++) ldsm4t(pre[i], aaddr + i * 512);
        mbar_wait(sb + SM_BAR + B_O1 * 8, parity);
        uint32_t b[2][4];
        ldsm4t(b[0], baddr);
        ldsm4t(b[1], baddr + 512);
        #pragma unroll
        for (int kp = 0; kp < 2; kp++) {
            mma16(c0, pre[2 * kp][0], pre[2 * kp][1], pre[2 * kp][2], pre[2 * kp][3], b[kp][0], b[kp][1]);
            mma16(c1, pre[2 * kp + 1][0], pre[2 * kp + 1][1], pre[2 * kp + 1][2], pre[2 * kp + 1][3], b[kp][2], b[kp][3]);
        }
    } else {
        #pragma unroll
        for (int i = 0; i < 2; i++) ldsm4t(pre[i], aaddr + i * 512);
        mbar_wait(sb + SM_BAR + B_O1 * 8, parity);
        #pragma unroll
        for (int kp = 0; kp < 2; kp++) {
            uint32_t b[4];
            ldsm4t(b, baddr + kp * 512);
            if (kp == 1) { ldsm4t(pre[0], aaddr + 2 * 512); ldsm4t(pre[1], aaddr + 3 * 512); }
            mma16(c0, pre[0][0], pre[0][1], pre[0][2], pre[0][3], b[0], b[1]);
            mma16(c1, pre[1][0], pre[1][1], pre[1][2], pre[1][3], b[2], b[3]);
        }
    }
    #pragma unroll
    for (int i = 0; i < NPRE; i++) ldsm4t(pre[i], aaddr + (4 + i) * 512);
    uint32_t off0, off1;
    {
        uint32_t ch;
        asm volatile("ld.shared.u16 %0, [%1];" : "=r"(ch) : "r"(sb + SM_CH + 2 * tile) : "memory");
        const int j = h >> 4;
        const uint32_t base = (uint32_t)((tile * 4 + j) * 8192 + (h & 15) * 256 + lane * 8);
        ch >>= j;
        off0 = base + (ch & 1) * 4096;
        off1 = base + 16384 + (ch & 256) * 16;
    }
    mbar_wait(sb + SM_BAR + B_O * 8, parity);
    if (NRES == 4) {
        uint32_t b[4][4];
        #pragma unroll
        for (int i = 0; i < 4; i++) ldsm4t(b[i], baddr + (2 + i) * 512);
        #pragma unroll
        for (int i = 0; i < 2; i++) {
            mma16(c0, res[2 * i][0], res[2 * i][1], res[2 * i][2], res[2 * i][3], b[i][0], b[i][1]);
            mma16(c1, res[2 * i + 1][0], res[2 * i + 1][1], res[2 * i + 1][2], res[2 * i + 1][3], b[i][2], b[i][3]);
        }
        #pragma unroll
        for (int i = 0; i < 2; i++) {
            mma16(c0, pre[2 * i][0], pre[2 * i][1], pre[2 * i][2], pre[2 * i][3], b[2 + i][0], b[2 + i][1]);
            mma16(c1, pre[2 * i + 1][0], pre[2 * i + 1][1], pre[2 * i + 1][2], pre[2 * i + 1][3], b[2 + i][2], b[2 + i][3]);
        }
    } else if (NPRE == 4) {
        uint32_t b[2][4];
        #pragma unroll
        for (int hh = 0; hh < 2; hh++) {
            ldsm4t(b[0], baddr + (2 + 2 * hh) * 512);
            ldsm4t(b[1], baddr + (3 + 2 * hh) * 512);
            if (hh) {
                #pragma unroll
                for (int i = 0; i < 4; i++) ldsm4t(pre[i], aaddr + (8 + i) * 512);
            }
            #pragma unroll
            for (int i = 0; i < 2; i++) {
                mma16(c0, pre[2 * i][0], pre[2 * i][1], pre[2 * i][2], pre[2 * i][3], b[i][0], b[i][1]);
                mma16(c1, pre[2 * i + 1][0], pre[2 * i + 1][1], pre[2 * i + 1][2], pre[2 * i + 1][3], b[i][2], b[i][3]);
            }
        }
    }
    st_relaxed2_off(g_buf1, off0, tagw(c0[0] + c1[0], tag), tagw(c0[1] + c1[1], tag));
    st_relaxed2_off(g_buf1, off1, tagw(c0[2] + c1[2], tag), tagw(c0[3] + c1[3], tag));
}

template <int NT, bool MASK>
__device__ __forceinline__ void softmax_core(float (*sc)[2], int g, int t, uint32_t* pb) {
    const float L2E = 1.4426950408889634f;
    #pragma unroll
    for (int j = 0; j < NT; j++) score2(sc[j][0], sc[j][1]);
    if (MASK) {
        const float NEG = -999292928.0f;
        if (2 * t > g) sc[NT - 1][0] = NEG;
        if (2 * t + 1 > g) sc[NT - 1][1] = NEG;
    }
    float m[NT];
    #pragma unroll
    for (int j = 0; j < NT; j++) m[j] = fmaxf(sc[j][0], sc[j][1]);
    float mx = m[0];
    #pragma unroll
    for (int j = 1; j < NT; j++) mx = fmaxf(mx, m[j]);
    mx = fmaxf(mx, __shfl_xor_sync(0xffffffffu, mx, 1));
    mx = fmaxf(mx, __shfl_xor_sync(0xffffffffu, mx, 2));
    float s0 = 0.f, s1 = 0.f;
    #pragma unroll
    for (int j = 0; j < NT; j++) {
        sc[j][0] = ex2((sc[j][0] - mx) * L2E); sc[j][1] = ex2((sc[j][1] - mx) * L2E);
        s0 += sc[j][0]; s1 += sc[j][1];
    }
    s0 += s1;
    s0 += __shfl_xor_sync(0xffffffffu, s0, 1);
    s0 += __shfl_xor_sync(0xffffffffu, s0, 2);
    const float iv = rcpf(s0);
    #pragma unroll
    for (int j = 0; j < NT; j++) pb[j] = pack2(sc[j][0] * iv, sc[j][1] * iv);
}
template <int NT>
__device__ __forceinline__ void xsoftmax(uint32_t a, int g, int t) {
    float sc[NT][2];
    #pragma unroll
    for (int j = 0; j < NT; j++) {
        float2 v0 = lds2f(a + j * 512), v1 = lds2f(a + j * 512 + 4096), v2 = lds2f(a + j * 512 + 8192);
        sc[j][0] = v0.x + v1.x + v2.x; sc[j][1] = v0.y + v1.y + v2.y;
    }
    uint32_t pb[NT];
    softmax_core<NT, true>(sc, g, t, pb);
    #pragma unroll
    for (int j = 0; j < NT; j += 2) {
        if (j + 1 < NT) asm volatile("st.shared.v2.u32 [%0], {%1,%2};" :: "r"(a + j * 512), "r"(pb[j]), "r"(pb[j + 1]) : "memory");
        else sts1(a + j * 512, pb[j]);
    }
}
template <int NJ>
__device__ __forceinline__ void xscores(uint32_t sb, int p, int mi, int j0, int lane) {
    FRESH(lane);
    const int r = lane & 7, cq = lane >> 3;
    const int qrow = mi * 16 + r + 8 * (cq & 1);
    uint32_t kb[NJ][8];
    float d[NJ][4];
    #pragma unroll
    for (int j = 0; j < NJ; j++) {
        ldsm4(kb[j], sb + SM_KS + ((j0 + j) * 8 + r) * 128 + ((cq ^ r) << 4));
        ldsm4(kb[j] + 4, sb + SM_KS + ((j0 + j) * 8 + r) * 128 + (((cq + 4) ^ r) << 4));
        d[j][0] = 0.f; d[j][1] = 0.f; d[j][2] = 0.f; d[j][3] = 0.f;
    }
    #pragma unroll
    for (int kt = 0; kt < 4; kt++) {
        uint32_t a[4];
        ldsm4(a, sb + SM_QX + qrow * 128 + (((2 * kt + (cq >> 1)) ^ r) << 4));
        #pragma unroll
        for (int j = 0; j < NJ; j++) mma16(d[j], a[0], a[1], a[2], a[3], kb[j][2 * kt], kb[j][2 * kt + 1]);
    }
    const uint32_t la = sb + SM_XS + p * 4096 + (mi * 3 + j0) * 512 + lane * 16;
    #pragma unroll
    for (int rk = 0; rk < 3; rk++) {
        const uint32_t ra = mapa(la, rk), rb = mapa(sb + SM_BAR + B_XS * 8, rk);
        #pragma unroll
        for (int j = 0; j < NJ; j++) st_async4(ra + j * 512, d[j], rb);
    }
}
__device__ __forceinline__ void mbar_arrive_remote(uint32_t bar) {
    asm volatile("mbarrier.arrive.relaxed.cluster.shared::cluster.b64 _, [%0];" :: "r"(bar) : "memory");
}

__global__ void __launch_bounds__(512, 1)
k_rec(const bf16* __restrict__ mem0, const bf16* __restrict__ Wq, const bf16* __restrict__ Wk,
      const bf16* __restrict__ Wv, const bf16* __restrict__ Wo) {
    extern __shared__ __align__(1024) uint8_t smem_raw[];
    constexpr uint32_t SBC = 1024;
    const uint32_t sb = smem_u32(smem_raw);
    if ((sb & 0xFFFFFFu) != SBC) __trap();
    int lane = __shfl_sync(0xffffffffu, threadIdx.x & 31, threadIdx.x & 31);
    const int warp = __shfl_sync(0xffffffffu, threadIdx.x >> 5, 0), wg = warp >> 2;
    const int tid = warp * 32 + lane;
    const int b = blockIdx.x, h = b / 3, p = b % 3;
    const int g = lane >> 2, t = lane & 3;
    const int tile0 = p == 0 ? 0 : (p == 1 ? 14 : 27);
    const int ntile = p == 0 ? 14 : 13;
    const uint32_t bar = sb + SM_BAR;

    if (tid == 0) {
        mbar_init(bar + B_MEM_FULL * 8, 4);
        mbar_init(bar + B_MEM_FREE * 8, 12);
        mbar_init(bar + B_HLO_FULL * 8, 1);
        mbar_init(bar + B_HHI_FULL * 8, 1);
        mbar_init(bar + B_HLO_FREE * 8, 12);
        mbar_init(bar + B_HHI_FREE * 8, 12);
        mbar_init(bar + B_MS * 8, 1);
        mbar_init(bar + B_O * 8, 1);
        mbar_init(bar + B_XS * 8, 1);
        mbar_init(bar + B_O1 * 8, 4);
        mbar_init(bar + B_XSFREE * 8, 12);
        asm volatile("fence.mbarrier_init.release.cluster;" ::: "memory");
        mbar_expect(bar + B_MS * 8, 3840);
        mbar_expect(bar + B_O * 8, 2048);
        mbar_expect(bar + B_XS * 8, 12288);
        mbar_expect(bar + B_HLO_FULL * 8, 12288);
        bulk_g2s(sb + SM_HB, g_ht, 12288, sb + SM_BAR + B_HLO_FULL * 8);
        mbar_expect(bar + B_HHI_FULL * 8, 28672);
        bulk_g2s(sb + SM_HB + 12288, (const char*)g_ht + 12288, 28672, sb + SM_BAR + B_HHI_FULL * 8);
    }
    cluster_sync();

    if (wg < 2) {
        asm volatile("setmaxnreg.inc.sync.aligned.u32 200;");
        const int w = warp & 3;
        uint32_t wa[40][4];
        {
            const bf16* W = (wg == 0 ? Wq : Wk) + (size_t)h * DH + p * 64 + w * 16 + t * 4;
            #pragma unroll
            for (int kt = 0; kt < 40; kt++) {
                uint2 l1 = __ldg((const uint2*)(W + (size_t)(kt * 16 + g) * HD));
                uint2 l2 = __ldg((const uint2*)(W + (size_t)(kt * 16 + 8 + g) * HD));
                wa[kt][0] = l1.x; wa[kt][1] = l1.y; wa[kt][2] = l2.x; wa[kt][3] = l2.y;
            }
            #pragma unroll
            for (int kt = 0; kt < 40; kt++) {
                #pragma unroll
                for (int i = 0; i < 4; i++) wa[kt][i] = movm(wa[kt][i]);
            }
        }

        const uint32_t dstx = sb + (wg == 0 ? SM_QX : SM_KS + 1024);

        for (int s = -1; s < NSEG; s++) {
            const uint32_t par = s & 1;
            FRESH(lane);
            const int g = lane >> 2, t = lane & 3, tid = warp * 32 + lane;
            if (s >= 0) {
                mbar_wait(bar + B_MEM_FULL * 8, par);
                TR(0);
                float c[4][4];
                #pragma unroll
                for (int i = 0; i < 4; i++) { c[i][0] = 0.f; c[i][1] = 0.f; c[i][2] = 0.f; c[i][3] = 0.f; }
                uint32_t maddr = sb + lane * 16;
                asm volatile("" : "+r"(maddr));
                #pragma unroll
                for (int kp = 0; kp < 20; kp++) {
                    uint32_t bb[4];
                    ldsm4t(bb, maddr + (SM_HB + kp * 512));
                    mma16(c[(kp & 1) * 2], wa[2 * kp][0], wa[2 * kp][1], wa[2 * kp][2], wa[2 * kp][3], bb[0], bb[1]);
                    mma16(c[(kp & 1) * 2 + 1], wa[2 * kp + 1][0], wa[2 * kp + 1][1], wa[2 * kp + 1][2], wa[2 * kp + 1][3], bb[2], bb[3]);
                }
                {
                    const int tok = lane & 7, ch = 2 * w + ((lane >> 3) & 1);
                    stsm2t(sb + (wg == 0 ? SM_QM : SM_KS) + tok * 128 + ((ch ^ tok) << 4),
                           pack2((c[0][0] + c[1][0]) + (c[2][0] + c[3][0]), (c[0][1] + c[1][1]) + (c[2][1] + c[3][1])),
                           pack2((c[0][2] + c[1][2]) + (c[2][2] + c[3][2]), (c[0][3] + c[1][3]) + (c[2][3] + c[3][3])));
                }
                __syncwarp();
                if (lane == 0) mbar_arrive(bar + B_MEM_FREE * 8);
                TR(1);
                bar_sync(1, 256);
                if (warp < 5) {
                    const int r = lane & 7, cq = lane >> 3;
                    uint32_t a[8], kb[8];
                    ldsm4(a, sb + SM_QM + r * 128 + ((cq ^ r) << 4));
                    ldsm4(kb, sb + SM_KS + (warp * 8 + r) * 128 + ((cq ^ r) << 4));
                    ldsm4(a + 4, sb + SM_QM + r * 128 + (((cq + 4) ^ r) << 4));
                    ldsm4(kb + 4, sb + SM_KS + (warp * 8 + r) * 128 + (((cq + 4) ^ r) << 4));
                    float d0[4] = {0.f, 0.f, 0.f, 0.f}, d1[4] = {0.f, 0.f, 0.f, 0.f};
                    mma16(d0, a[0], 0u, a[1], 0u, kb[0], kb[1]);
                    mma16(d1, a[2], 0u, a[3], 0u, kb[2], kb[3]);
                    mma16(d0, a[4], 0u, a[5], 0u, kb[4], kb[5]);
                    mma16(d1, a[6], 0u, a[7], 0u, kb[6], kb[7]);
                    const uint32_t la = sb + SM_MS + p * 1280 + warp * 256 + lane * 8;
                    #pragma unroll
                    for (int rk = 0; rk < 3; rk++)
                        st_async2(mapa(la, rk), d0[0] + d1[0], d0[1] + d1[1], mapa(bar + B_MS * 8, rk));
                    bar_arrive(4, 352);
                } else if (warp < 7) {
                    xscores<1>(sb, p, warp - 5, 0, lane);
                    bar_arrive(4, 352);
                }
                TR(2);
                if (s < NSEG - 1) {
                    wo_phase<0, 4>(sb, warp, lane, nullptr, par, (uint32_t)(s % 15) + 1u, tile0 + warp, h);
                    TR(4);
                }
            }
            if (s < NSEG - 1) {
                FRESH(lane);
                const uint32_t hp = (s + 1) & 1;
                float d[16];
                const uint64_t db0 = make_desc(SBC + SM_HB, 16, 1024, 1);
                mbar_wait(bar + B_HHI_FULL * 8, hp);
                {
                    const int r = lane & 7, mq = lane >> 3;
                    const uint32_t ha = sb + SM_HB + 9 * 4096 + (8 * (mq >> 1) + r) * 128 + (((6 + (mq & 1)) ^ r) << 4);
                    uint32_t b0[4], b1[4];
                    ldsm4(b0, ha);
                    ldsm4(b1, ha + 2048);
                    #pragma unroll
                    for (int i = 0; i < 16; i++) d[i] = 0.f;
                    mma16(d + 0, wa[39][0], wa[39][1], wa[39][2], wa[39][3], b0[0], b0[1]);
                    mma16(d + 4, wa[39][0], wa[39][1], wa[39][2], wa[39][3], b0[2], b0[3]);
                    mma16(d + 8, wa[39][0], wa[39][1], wa[39][2], wa[39][3], b1[0], b1[1]);
                    mma16(d + 12, wa[39][0], wa[39][1], wa[39][2], wa[39][3], b1[2], b1[3]);
                    asm volatile("" : "+f"(d[0]), "+f"(d[4]), "+f"(d[8]), "+f"(d[12]) :: "memory");
                }
                if (s >= 0) bar_sync(6, 512);
                TR(6);
                wg_fence();
                #pragma unroll
                for (int kt = 12; kt < 39; kt++) wg_rs32(d, wa[kt], db0 + (uint64_t)(((kt >> 2) * 4096 + (kt & 3) * 32) >> 4), 1);
                wg_commit();
                mbar_wait(bar + B_HLO_FULL * 8, hp);
                wg_fence();
                #pragma unroll
                for (int kt = 0; kt < 9; kt++) wg_rs32(d, wa[kt], db0 + (uint64_t)(((kt >> 2) * 4096 + (kt & 3) * 32) >> 4), 1);
                wg_commit();
                #pragma unroll
                for (int kt = 9; kt < 12; kt++) wg_rs32(d, wa[kt], db0 + (uint64_t)(((kt >> 2) * 4096 + (kt & 3) * 32) >> 4), 1);
                wg_commit();
                wg_wait<1>();
                bar_arrive(9, 384);
                wg_wait<0>();
                if (lane == 0) { mbar_arrive(bar + B_HLO_FREE * 8); mbar_arrive(bar + B_HHI_FREE * 8); }
                TR(7);
                const int mi = lane >> 3, r = lane & 7;
                #pragma unroll
                for (int jj = 0; jj < 2; jj++) {
                    const int tok = 8 * (2 * jj + (mi >> 1)) + r, ch = 2 * w + (mi & 1);
                    stsm4t(dstx + tok * 128 + ((ch ^ r) << 4),
                           pack2(d[8 * jj + 0], d[8 * jj + 1]), pack2(d[8 * jj + 2], d[8 * jj + 3]),
                           pack2(d[8 * jj + 4], d[8 * jj + 5]), pack2(d[8 * jj + 6], d[8 * jj + 7]));
                }
                bar_arrive(8, 384);
                if (s < 0) bar_sync(0, 512);
            }
            if (wg == 1 && s >= 0) {
                FRESH(lane);
                mbar_wait(bar + B_XS * 8, par);
                TR(8);
                if (w == 0 && lane == 0) mbar_expect(bar + B_XS * 8, 12288);
                const uint32_t a = sb + SM_XS + (w >> 1) * 1536 + lane * 16 + (w & 1) * 8;
                if (w == 0) xsoftmax<2>(a, lane >> 2, lane & 3);
                else if (w == 1) xsoftmax<3>(a, lane >> 2, lane & 3);
                else if (w == 2) xsoftmax<4>(a, lane >> 2, lane & 3);
                else xsoftmax<5>(a, lane >> 2, lane & 3);
                bar_arrive(7, 256);
                TR(9);
            }
        }
    } else if (wg == 2) {
        asm volatile("setmaxnreg.dec.sync.aligned.u32 64;");
        const int w = warp & 3;
        {
            const int c = tid & 7;
            const bf16* src = Wv + (size_t)h * DH + p * 64 + c * 8;
            for (int k = (tid & 127) >> 3; k < DM; k += 16)
                cpa16(sb + SM_WV + k * 128 + ((c ^ (k & 7)) << 4), src + (size_t)k * HD);
        }
        uint32_t res[4][4];
        {
            const bf16* src = Wo + ((size_t)h * DH + ((p + 1) % 3) * 64) * DM + (tile0 + warp) * 16 + 2 * t;
            #pragma unroll
            for (int kt = 0; kt < 4; kt++) {
                res[kt][0] = __ldg((const uint32_t*)(src + (size_t)(kt * 16 + g) * DM));
                res[kt][1] = __ldg((const uint32_t*)(src + (size_t)(kt * 16 + g) * DM + 8));
                res[kt][2] = __ldg((const uint32_t*)(src + (size_t)(kt * 16 + 8 + g) * DM));
                res[kt][3] = __ldg((const uint32_t*)(src + (size_t)(kt * 16 + 8 + g) * DM + 8));
            }
            #pragma unroll
            for (int kt = 0; kt < 4; kt++) {
                #pragma unroll
                for (int i = 0; i < 4; i++) res[kt][i] = movm(res[kt][i]);
            }
        }
        cpa_wait_all();
        fence_async();
        bar_sync(2, 128);
        const uint64_t da0 = make_desc(SBC + SM_WV, 16, 1024, 1);
        uint32_t vx[8], vm0 = 0, vm1 = 0;
        #pragma unroll
        for (int i = 0; i < 8; i++) vx[i] = 0;

        for (int s = -1; s < NSEG; s++) {
            FRESH(lane);
            const int g = lane >> 2, t = lane & 3, tid = warp * 32 + lane;
            if (s >= 0) {
                const uint32_t par = s & 1;
                mbar_wait(bar + B_MEM_FULL * 8, par);
                bar_sync(4, 352);
                TR(0);
                float dv[4];
                {
                    const uint64_t dbm = make_desc(SBC + SM_HB, 128, 128, 0);
                    wg_fence();
                    #pragma unroll
                    for (int kt = 0; kt < 40; kt++) {
                        wg_ss8(dv, da0 + (uint64_t)(kt * 128), dbm + (uint64_t)(kt * 16), kt > 0);
                        wg_commit();
                        if (kt < 39) wg_wait<1>();
                    }
                    wg_commit();
                }
                TR(1);
                bar_sync(5, 160);
                TR(2);
                uint32_t pb[5];
                #pragma unroll
                for (int j = 0; j < 5; j++) pb[j] = lds1(sb + SM_PM + j * 128 + lane * 4);
                float o0[4] = {0.f, 0.f, 0.f, 0.f}, o1[4] = {0.f, 0.f, 0.f, 0.f}, o2[4] = {0.f, 0.f, 0.f, 0.f};
                wg_wait<0>();
                TR(3);
                mma16(o0, vx[0], vx[1], vx[2], vx[3], pb[1], pb[2]);
                mma16(o1, vx[4], vx[5], vx[6], vx[7], pb[3], pb[4]);
                vm0 = pack2(dv[0], dv[1]); vm1 = pack2(dv[2], dv[3]);
                mma8(o2, vm0, vm1, pb[0]);
                if (s < NSEG - 1) {
                    const uint32_t q0 = pack2(o0[0] + o1[0] + o2[0], o0[1] + o1[1] + o2[1]), q1 = pack2(o0[2] + o1[2] + o2[2], o0[3] + o1[3] + o2[3]);
                    const uint32_t la = sb + SM_OS + (w * 16 + g) * 16 + t * 4;
                    #pragma unroll
                    for (int i = 1; i < 3; i++) {
                        const uint32_t rk = (p + i) % 3;
                        const uint32_t ra = mapa(la + (3 - i) * 1024, rk), rb = mapa(bar + B_O * 8, rk);
                        st_async1(ra, q0, rb);
                        st_async1(ra + 128, q1, rb);
                    }
                    sts1(la, q0);
                    sts1(la + 128, q1);
                    __syncwarp();
                    if (lane == 0) { mbar_arrive(bar + B_O1 * 8); mbar_arrive(bar + B_MEM_FREE * 8); }
                }
                TR(5);
                if (s < NSEG - 1) {
                    wo_phase<4, 4>(sb, warp, lane, res, par, (uint32_t)(s % 15) + 1u, tile0 + warp, h);
                    TR(4);
                    if (tid == 256) mbar_expect(bar + B_O * 8, 2048);
                }
                if (s < NSEG - 1) bar_arrive(6, 512);
            }
            uint32_t vn[8];
            #pragma unroll
            for (int i = 0; i < 8; i++) vn[i] = 0;
            if (s < NSEG - 1) {
            float d[16];
            const uint32_t hp = (s + 1) & 1;
            const uint64_t db0 = make_desc(SBC + SM_HB, 16, 1024, 1);
            mbar_wait(bar + B_HHI_FULL * 8, hp);
            mbar_wait(bar + B_HLO_FULL * 8, hp);
            bar_sync(9, 384);
            TR(6);
            wg_fence();
            #pragma unroll
            for (int kt = 0; kt < 40; kt++) {
                wg_ss32(d, da0 + (uint64_t)(kt * 128), db0 + (uint64_t)(((kt >> 2) * 4096 + (kt & 3) * 32) >> 4), kt > 0);
                wg_commit();
                if (kt < 39) wg_wait<1>();
                if (kt == 12 && lane == 0) mbar_arrive(bar + B_HLO_FREE * 8);
            }
            wg_wait<0>();
            TR(7);
            if (lane == 0) mbar_arrive(bar + B_HHI_FREE * 8);
            #pragma unroll
            for (int i = 0; i < 8; i++) vn[i] = pack2(d[2 * i], d[2 * i + 1]);
            }
            if (s >= 0) {
                bar_sync(7, 256);
                TR(8);
                FRESH(lane);
                bf16* orow = g_ox + (size_t)(s * 32 + (lane >> 2)) * HD + h * DH + p * 64 + w * 16 + 2 * (lane & 3);
                {
                    const uint32_t pa = sb + SM_XS + lane * 16;
                    #pragma unroll
                    for (int mi = 0; mi < 2; mi++) {
                        float oa[4] = {0.f, 0.f, 0.f, 0.f}, ob[4] = {0.f, 0.f, 0.f, 0.f};
                        if (mi == 0) {
                            const uint4 p0 = lds4(pa);
                            const uint32_t p3 = lds1(pa + 1024 + 8);
                            mma8(oa, vm0, vm1, p0.x);
                            mma8(ob, vm0, vm1, p0.z);
                            mma16(oa, vx[0], vx[1], vx[2], vx[3], p0.y, 0u);
                            mma16(ob, vx[0], vx[1], vx[2], vx[3], p0.w, p3);
                        } else {
                            const uint4 p1 = lds4(pa + 1536), p2 = lds4(pa + 2560);
                            const uint32_t p4 = lds1(pa + 3584 + 8);
                            mma8(oa, vm0, vm1, p1.x);
                            mma8(ob, vm0, vm1, p1.z);
                            mma16(oa, vx[0], vx[1], vx[2], vx[3], p1.y, p2.x);
                            mma16(ob, vx[0], vx[1], vx[2], vx[3], p1.w, p2.z);
                            mma16(oa, vx[4], vx[5], vx[6], vx[7], p2.y, 0u);
                            mma16(ob, vx[4], vx[5], vx[6], vx[7], p2.w, p4);
                            if (lane < 3) mbar_arrive_remote(mapa(bar + B_XSFREE * 8, lane));
                        }
                        const uint32_t u0 = movm(pack2(oa[0], oa[1])), u1 = movm(pack2(oa[2], oa[3]));
                        const uint32_t u2 = movm(pack2(ob[0], ob[1])), u3 = movm(pack2(ob[2], ob[3]));
                        bf16* dst = orow + (size_t)(16 * mi) * HD;
                        *(uint32_t*)dst = u0;
                        *(uint32_t*)(dst + 8) = u1;
                        *(uint32_t*)(dst + 8 * HD) = u2;
                        *(uint32_t*)(dst + 8 * HD + 8) = u3;
                    }
                }
                TR(9);
                if (s == NSEG - 1) break;
            }
            #pragma unroll
            for (int i = 0; i < 8; i++) vx[i] = vn[i];
            if (s >= 0) mbar_wait_cluster(bar + B_XSFREE * 8, s & 1);
            bar_sync(8, 384);
            TR(10);
            if (w < 3) xscores<2>(sb, p, w > 0, w == 2 ? 3 : 1, lane);
            TR(11);
            if (s < 0) bar_sync(0, 512);
        }
    } else {
        asm volatile("setmaxnreg.dec.sync.aligned.u32 48;");
        const int w = warp & 3, lt = tid & 127;
        {
            const bf16* src0 = Wo + (size_t)h * DH * DM + tile0 * 16;
            const int nch = 2 * ntile;
            for (int i = lt; i < DH * nch; i += 128) {
                const int e = i / nch, c = i - e * nch, tl = c >> 1, cc = c & 1;
                int es = e;
                if (tl >= 8 && tl < 12) { if (e >= 64 && e < 128) continue; if (e >= 128) es = e - 64; }
                int eg = e + p * 64; if (eg >= DH) eg -= DH;
                cpa16(sb + SM_WO + wo_tile_off(tl) + es * 32 + ((cc ^ ((e >> 2) & 1)) << 4), src0 + (size_t)eg * DM + c * 8);
            }
        }
        const uint32_t epoch = *(volatile uint32_t*)&g_epoch;
        if (b < 80) {
            #pragma unroll
            for (int i = 0; i < 2; i++) {
                const int idx = lt + i * 128, sl = idx >> 6, pg = (idx >> 5) & 1, wd = idx & 31;
                st_relaxed1(g_buf2 + (sl * 3 + (b >> 5)) * 2048 + pg * 1024 + (b & 31) * 32 + wd, 0xFFFFFFFFu);
            }
            __threadfence();
        }
        if (lane == 0) {
            for (int i = w; i < 14; i += 4) {
                int c = 0;
                if (i < 12) c = probe_blk(g_buf2 + i * 2048 + 640 + (b & 31) * 8);
                else if (b < 80) c = probe_blk(g_buf1 + (b * 2 + (i - 12)) * 2048);
                asm volatile("st.shared.u8 [%0], %1;" :: "r"(sb + SM_CH + 96 + i), "r"(c) : "memory");
            }
        }
        bar_sync(3, 128);
        uint32_t selmask = 0;
        for (int i = 0; i < 14; i++) {
            uint32_t c; asm volatile("ld.shared.u8 %0, [%1];" : "=r"(c) : "r"(sb + SM_CH + 96 + i) : "memory");
            selmask |= c << i;
        }
        if (lt == 0 && b < 80) st_release1(&g_choice[b], (epoch << 2) | (selmask >> 12));
        if (lt < 80) {
            uint32_t v, guard = 0;
            do { v = ld_acquire1(&g_choice[lt]); if (++guard > (1u << 22)) __trap(); } while ((v >> 2) != (epoch & 0x3fffffffu));
            asm volatile("st.shared.u8 [%0], %1;" :: "r"(sb + SM_CH + lt), "r"(v & 3u) : "memory");
        }
        cpa_wait_all();
        bar_sync(0, 512);
        const bool has_tile = (12 + w) < ntile;
        for (int s = 0; s < NSEG; s++) {
            const uint32_t par = s & 1;
            FRESH(lane);
            const int g = lane >> 2, t = lane & 3, lt = w * 32 + lane;
            if (s == 0) {
                mbar_wait(bar + B_HLO_FREE * 8, par);
                for (int k = lt; k < DM; k += 128) {
                    uint32_t v[4];
                    #pragma unroll
                    for (int i = 0; i < 4; i++) {
                        uint32_t lo = *(const uint16_t*)(mem0 + (2 * i) * DM + k), hi = *(const uint16_t*)(mem0 + (2 * i + 1) * DM + k);
                        v[i] = lo | (hi << 16);
                    }
                    asm volatile("st.shared.v4.u32 [%0], {%1,%2,%3,%4};" :: "r"(sb + SM_HB + k * 16), "r"(v[0]), "r"(v[1]), "r"(v[2]), "r"(v[3]) : "memory");
                }
            } else {
                const int sl = s & 3;
                const char* q = (const char*)g_buf2 + sl * 3 * 8192 + lt * 16;
                const uint32_t sm = selmask >> (sl * 3);
                const char* q0 = q + (sm & 1) * 4096;
                const char* q1 = q + 8192 + (sm & 2) * 2048;
                const char* q2 = q + 16384 + (sm & 4) * 1024;
                const uint32_t dst = sb + SM_HB + lt * 16;
                uint32_t guard = 0;
                mbar_wait(bar + B_HLO_FREE * 8, par);
                TR(10);
                while (true) {
                    const uint4 v0 = ld_relaxed4(q0), v1 = ld_relaxed4(q0 + 2048), v2 = ld_relaxed4(q1), v3 = ld_relaxed4(q1 + 2048), v4 = ld_relaxed4(q2);
                    sts4(dst, v0); sts4(dst + 2048, v1); sts4(dst + 4096, v2); sts4(dst + 6144, v3); sts4(dst + 8192, v4);
                    if (__all_sync(0xffffffffu, oks(v0) && oks(v1) && oks(v2) && oks(v3) && oks(v4))) break;
                    if (++guard > (1u << 22)) __trap();
                }
            }
            fence_async();
            __syncwarp();
            if (lane == 0) mbar_arrive(bar + B_MEM_FULL * 8);
            TR(0);
            if (w == 2) {
                mbar_wait(bar + B_MS * 8, par);
                TR(1);
                if (lane == 0) mbar_expect(bar + B_MS * 8, 3840);
                uint32_t pb[5];
                float sc[5][2];
                {
                    const uint32_t a = sb + SM_MS + lane * 8;
                    float2 u[5], v[5];
                    #pragma unroll
                    for (int j = 0; j < 5; j++) { u[j] = lds2f(a + j * 256); v[j] = lds2f(a + j * 256 + 1280); }
                    #pragma unroll
                    for (int j = 0; j < 5; j++) { sc[j][0] = u[j].x + v[j].x; sc[j][1] = u[j].y + v[j].y; }
                    #pragma unroll
                    for (int j = 0; j < 5; j++) u[j] = lds2f(a + j * 256 + 2560);
                    #pragma unroll
                    for (int j = 0; j < 5; j++) { sc[j][0] += u[j].x; sc[j][1] += u[j].y; }
                }
                softmax_core<5, false>(sc, g, t, pb);
                #pragma unroll
                for (int j = 0; j < 5; j++) sts1(sb + SM_PM + j * 128 + lane * 4, pb[j]);
                bar_arrive(5, 160);
                TR(2);
            }
            const uint32_t tag = (uint32_t)(s % 15) + 1u;
            if (s < NSEG - 1) {
                if (w == 3) {
                    const char* src = (const char*)g_ht + (size_t)(s + 1) * 40960;
                    mbar_wait(bar + B_HHI_FREE * 8, par);
                    if (lane == 0) {
                        mbar_expect(bar + B_HHI_FULL * 8, 28672);
                        bulk_g2s(sb + SM_HB + 12288, src + 12288, 28672, sb + SM_BAR + B_HHI_FULL * 8);
                    }
                    mbar_wait(bar + B_MEM_FREE * 8, par);
                    if (lane == 0) {
                        mbar_expect(bar + B_HLO_FULL * 8, 12288);
                        bulk_g2s(sb + SM_HB, src, 12288, sb + SM_BAR + B_HLO_FULL * 8);
                    }
                    __syncwarp();
                }
                if (has_tile) wo_phase<0, 4>(sb, warp, lane, nullptr, par, tag, tile0 + warp, h);
                TR(4);
                bar_sync(6, 512);
            }
            if (s < NSEG - 1) {
                { const uint32_t c0 = clk32(); while (clk32() - c0 < H1_DELAY); }
                if (b < 80) {
                    FRESH(lane);
                    const char* rin0 = (const char*)g_buf1 + (size_t)(b * 2) * 8192 + ((selmask >> 12) & 1) * 4096 + (lane >> 2) * 256 + w * 64 + (lane & 3) * 16;
                    const char* rin1 = (const char*)g_buf1 + (size_t)(b * 2 + 1) * 8192 + ((selmask >> 13) & 1) * 4096 + (lane >> 2) * 256 + w * 64 + (lane & 3) * 16;
                    const int col = b * 8 + 2 * w + ((lane >> 1) & 1), wd = 2 * (lane & 1) + (lane >> 4);
                    const int sl = (lane & 8) ? ((s + 3) & 3) : ((s + 1) & 3);
                    uint32_t* dst = g_buf2 + (sl * 3 + (col >> 8)) * 2048 + ((lane >> 2) & 1) * 1024 + (col & 255) * 4 + wd;
                    asm volatile("" : "+l"(dst));
                    uint4 v0, v1, v2, v3;
                    uint32_t guard = 0;
                    while (true) {
                        v0 = ld_relaxed4(rin0); v1 = ld_relaxed4(rin0 + 2048);
                        v2 = ld_relaxed4(rin1); v3 = ld_relaxed4(rin1 + 2048);
                        if (__all_sync(0xffffffffu, ok4(v0, tag) && ok4(v1, tag) && ok4(v2, tag) && ok4(v3, tag))) break;
                        if (++guard > (1u << 22)) __trap();
                    }
                    TR(11);
                    const float a0 = (uf(v0.x) + uf(v1.x)) + (uf(v2.x) + uf(v3.x)), a1 = (uf(v0.y) + uf(v1.y)) + (uf(v2.y) + uf(v3.y));
                    const float a2 = (uf(v0.z) + uf(v1.z)) + (uf(v2.z) + uf(v3.z)), a3 = (uf(v0.w) + uf(v1.w)) + (uf(v2.w) + uf(v3.w));
                    const bool u16 = lane & 16;
                    float m0 = (u16 ? a2 : a0) + __shfl_xor_sync(0xffffffffu, u16 ? a0 : a2, 16);
                    float m1 = (u16 ? a3 : a1) + __shfl_xor_sync(0xffffffffu, u16 ? a1 : a3, 16);
                    m0 += __shfl_xor_sync(0xffffffffu, m0, 8); m1 += __shfl_xor_sync(0xffffffffu, m1, 8);
                    m0 += __shfl_xor_sync(0xffffffffu, m0, 4); m1 += __shfl_xor_sync(0xffffffffu, m1, 4);
                    st_relaxed1(dst, (lane & 8) ? 0xFFFFFFFFu : pack2(m0, m1));
                    TR(12);
                }
            }
        }
    }
    cluster_sync();
}

constexpr int G_STAGES = 5;
constexpr int G_STAGE_BYTES = 32768;
constexpr int G_SMEM = G_STAGES * G_STAGE_BYTES + 1024 + 256;

__device__ __forceinline__ void tma2d(uint32_t dst, const CUtensorMap* map, int c0, int c1, uint32_t bar) {
    asm volatile("cp.async.bulk.tensor.2d.shared::cluster.global.mbarrier::complete_tx::bytes [%0], [%1, {%2, %3}], [%4];"
                 :: "r"(dst), "l"(map), "r"(c0), "r"(c1), "r"(bar) : "memory");
}
__device__ __forceinline__ void wg_ss128(float* d, uint64_t da, uint64_t db, int sc) {
    asm volatile("{\n\t.reg .pred p;\n\tsetp.ne.b32 p, %66, 0;\n\t"
        "wgmma.mma_async.sync.aligned.m64n128k16.f32.bf16.bf16 "
        "{%0,%1,%2,%3,%4,%5,%6,%7,%8,%9,%10,%11,%12,%13,%14,%15,%16,%17,%18,%19,%20,%21,%22,%23,%24,%25,%26,%27,%28,%29,%30,%31,"
        "%32,%33,%34,%35,%36,%37,%38,%39,%40,%41,%42,%43,%44,%45,%46,%47,%48,%49,%50,%51,%52,%53,%54,%55,%56,%57,%58,%59,%60,%61,%62,%63}, "
        "%64, %65, p, 1, 1, 0, 1;\n\t}"
        : "+f"(d[0]), "+f"(d[1]), "+f"(d[2]), "+f"(d[3]), "+f"(d[4]), "+f"(d[5]), "+f"(d[6]), "+f"(d[7]),
          "+f"(d[8]), "+f"(d[9]), "+f"(d[10]), "+f"(d[11]), "+f"(d[12]), "+f"(d[13]), "+f"(d[14]), "+f"(d[15]),
          "+f"(d[16]), "+f"(d[17]), "+f"(d[18]), "+f"(d[19]), "+f"(d[20]), "+f"(d[21]), "+f"(d[22]), "+f"(d[23]),
          "+f"(d[24]), "+f"(d[25]), "+f"(d[26]), "+f"(d[27]), "+f"(d[28]), "+f"(d[29]), "+f"(d[30]), "+f"(d[31]),
          "+f"(d[32]), "+f"(d[33]), "+f"(d[34]), "+f"(d[35]), "+f"(d[36]), "+f"(d[37]), "+f"(d[38]), "+f"(d[39]),
          "+f"(d[40]), "+f"(d[41]), "+f"(d[42]), "+f"(d[43]), "+f"(d[44]), "+f"(d[45]), "+f"(d[46]), "+f"(d[47]),
          "+f"(d[48]), "+f"(d[49]), "+f"(d[50]), "+f"(d[51]), "+f"(d[52]), "+f"(d[53]), "+f"(d[54]), "+f"(d[55]),
          "+f"(d[56]), "+f"(d[57]), "+f"(d[58]), "+f"(d[59]), "+f"(d[60]), "+f"(d[61]), "+f"(d[62]), "+f"(d[63])
        : "l"(da), "l"(db), "r"(sc));
}

template <int EPI>
__global__ void __launch_bounds__(384, 1)
k_gemm(const __grid_constant__ CUtensorMap mapA, const __grid_constant__ CUtensorMap mapB, int K,
       const bf16* __restrict__ xin, bf16* __restrict__ outp) {
    extern __shared__ uint8_t smem_raw[];
    const uint32_t sb = (smem_u32(smem_raw) + 1023u) & ~1023u;
    const uint32_t bars = sb + G_STAGES * G_STAGE_BYTES;
    const int tid = threadIdx.x, lane = tid & 31, wg = tid >> 7;
    const int n0 = blockIdx.x * 128, m0 = blockIdx.y * 128;
    const int nk = K / 64;
    if (tid == 0) {
        for (int i = 0; i < G_STAGES; i++) { mbar_init(bars + i * 8, 1); mbar_init(bars + 64 + i * 8, 8); }
        asm volatile("fence.mbarrier_init.release.cluster;" ::: "memory");
    }
    __syncthreads();
    if (wg == 0) {
        if (tid == 0) {
            for (int kb = 0; kb < nk; kb++) {
                const int st = kb % G_STAGES;
                if (kb >= G_STAGES) mbar_wait(bars + 64 + st * 8, ((kb / G_STAGES) - 1) & 1);
                const uint32_t a = sb + st * G_STAGE_BYTES;
                mbar_expect(bars + st * 8, G_STAGE_BYTES);
                tma2d(a, &mapA, kb * 64, m0, bars + st * 8);
                tma2d(a + 16384, &mapB, n0, kb * 64, bars + st * 8);
                tma2d(a + 16384 + 8192, &mapB, n0 + 64, kb * 64, bars + st * 8);
            }
        }
    } else {
        float d[64];
        #pragma unroll
        for (int i = 0; i < 64; i++) d[i] = 0.f;
        const int cw = wg - 1;
        for (int kb = 0; kb < nk; kb++) {
            const int st = kb % G_STAGES;
            mbar_wait(bars + st * 8, (kb / G_STAGES) & 1);
            const uint32_t a = sb + st * G_STAGE_BYTES;
            const uint64_t da = make_desc(a + cw * 8192, 16, 1024, 1);
            const uint64_t db = make_desc(a + 16384, 8192, 1024, 1);
            wg_fence();
            #pragma unroll
            for (int k = 0; k < 4; k++) wg_ss128(d, da + (uint64_t)(k * 2), db + (uint64_t)(k * 128), 1);
            wg_commit();
            if (kb > 0) {
                wg_wait<1>();
                if (lane == 0) mbar_arrive(bars + 64 + ((kb - 1) % G_STAGES) * 8);
            }
        }
        wg_wait<0>();
        const int g = lane >> 2, t = lane & 3, w = (tid >> 5) & 3;
        const int ldo = EPI == 1 ? FF : DM;
        #pragma unroll
        for (int hf = 0; hf < 2; hf++) {
            const int row = m0 + cw * 64 + w * 16 + g + 8 * hf;
            #pragma unroll
            for (int j = 0; j < 16; j++) {
                const int col = n0 + j * 8 + 2 * t;
                float a0 = bfr(d[4 * j + 2 * hf]), a1 = bfr(d[4 * j + 2 * hf + 1]);
                uint32_t o;
                if (EPI == 1) {
                    o = pack2(a0 / (1.0f + __expf(-a0)), a1 / (1.0f + __expf(-a1)));
                } else {
                    const float2 gm = *(const float2*)(g_mod + (EPI == 0 ? 2 : 5) * DM + col);
                    const uint32_t xv = *(const uint32_t*)(xin + (size_t)row * DM + col);
                    o = pack2(bflo(xv) + bfr(gm.x * a0), bfhi(xv) + bfr(gm.y * a1));
                }
                *(uint32_t*)(outp + (size_t)row * ldo + col) = o;
            }
        }
    }
}

typedef CUresult (*EncodeFn)(CUtensorMap*, CUtensorMapDataType, cuuint32_t, void*, const cuuint64_t*, const cuuint64_t*,
                             const cuuint32_t*, const cuuint32_t*, CUtensorMapInterleave, CUtensorMapSwizzle,
                             CUtensorMapL2promotion, CUtensorMapFloatOOBfill);

static void make_map(EncodeFn fn, CUtensorMap* m, const void* ptr, uint64_t inner, uint64_t outer, uint32_t bi, uint32_t bo) {
    cuuint64_t dims[2] = {inner, outer};
    cuuint64_t strides[1] = {inner * 2};
    cuuint32_t box[2] = {bi, bo};
    cuuint32_t es[2] = {1, 1};
    fn(m, CU_TENSOR_MAP_DATA_TYPE_BFLOAT16, 2, (void*)ptr, dims, strides, box, es, CU_TENSOR_MAP_INTERLEAVE_NONE,
       CU_TENSOR_MAP_SWIZZLE_128B, CU_TENSOR_MAP_L2_PROMOTION_L2_256B, CU_TENSOR_MAP_FLOAT_OOB_FILL_NONE);
}

extern "C" void kernel_launch(void* const* d_in, const int* in_sizes, int n_in, void* d_out, int out_size) {
    const bf16* x = (const bf16*)d_in[0];
    const bf16* mem0 = (const bf16*)d_in[1];
    const bf16* Wq = (const bf16*)d_in[2];
    const bf16* Wk = (const bf16*)d_in[3];
    const bf16* Wv = (const bf16*)d_in[4];
    const bf16* Wo = (const bf16*)d_in[5];
    const bf16* w1 = (const bf16*)d_in[8];
    const bf16* w2 = (const bf16*)d_in[9];
    const bf16* c = (const bf16*)d_in[10];
    const bf16* wmod = (const bf16*)d_in[11];
    bf16* out = (bf16*)d_out;

    static EncodeFn enc = nullptr;
    static void *p_ox, *p_x1, *p_h2, *p_act;
    if (!enc) {
        cudaDriverEntryPointQueryResult qr;
        void* f = nullptr;
        cudaGetDriverEntryPoint("cuTensorMapEncodeTiled", &f, cudaEnableDefault, &qr);
        enc = (EncodeFn)f;
        cudaGetSymbolAddress(&p_ox, g_ox);
        cudaGetSymbolAddress(&p_x1, g_x1);
        cudaGetSymbolAddress(&p_h2, g_h2);
        cudaGetSymbolAddress(&p_act, g_act);
        cudaFuncSetAttribute(k_rec, cudaFuncAttributeMaxDynamicSharedMemorySize, SM_TOTAL);
        cudaFuncSetAttribute(k_gemm<0>, cudaFuncAttributeMaxDynamicSharedMemorySize, G_SMEM);
        cudaFuncSetAttribute(k_gemm<1>, cudaFuncAttributeMaxDynamicSharedMemorySize, G_SMEM);
        cudaFuncSetAttribute(k_gemm<2>, cudaFuncAttributeMaxDynamicSharedMemorySize, G_SMEM);
    }
    CUtensorMap mOx, mWo, mH2, mW1, mAct, mW2;
    make_map(enc, &mOx, p_ox, HD, SEQ, 64, 128);
    make_map(enc, &mWo, Wo, DM, HD, 64, 64);
    make_map(enc, &mH2, p_h2, DM, SEQ, 64, 128);
    make_map(enc, &mW1, w1, FF, DM, 64, 64);
    make_map(enc, &mAct, p_act, FF, SEQ, 64, 128);
    make_map(enc, &mW2, w2, DM, FF, 64, 64);

    cudaStream_t st = cudaStreamPerThread;
    k_mod<<<60, 256, 0, st>>>(c, wmod);
    k_ln<0><<<SEQ / 8, 256, 0, st>>>(x);
    {
        cudaLaunchConfig_t cfg = {};
        cfg.gridDim = dim3(96); cfg.blockDim = dim3(512); cfg.dynamicSmemBytes = SM_TOTAL; cfg.stream = st;
        cudaLaunchAttribute at[1];
        at[0].id = cudaLaunchAttributeClusterDimension;
        at[0].val.clusterDim.x = 3; at[0].val.clusterDim.y = 1; at[0].val.clusterDim.z = 1;
        cfg.attrs = at; cfg.numAttrs = 1;
        cudaLaunchKernelEx(&cfg, k_rec, mem0, Wq, Wk, Wv, Wo);
    }
    k_gemm<0><<<dim3(5, 16), 384, G_SMEM, st>>>(mOx, mWo, HD, x, (bf16*)p_x1);
    k_ln<1><<<SEQ / 8, 256, 0, st>>>(nullptr);
    k_gemm<1><<<dim3(12, 16), 384, G_SMEM, st>>>(mH2, mW1, DM, nullptr, (bf16*)p_act);
    k_gemm<2><<<dim3(5, 16), 384, G_SMEM, st>>>(mAct, mW2, FF, (const bf16*)p_x1, out);
}
```

```cpp
#include <cuda_runtime.h>
#include <cuda_bf16.h>
#include <cuda.h>
#include <stdint.h>

typedef __nv_bfloat16 bf16;
#define VX_THROTTLE 1
#define H1_DELAY 400
#define H1_BACK 0
#define VM_THROTTLE 1

constexpr int SEQ = 2048, DM = 640, NH = 32, DH = 192, NSEG = 64, FF = 1536, HD = NH * DH;

__device__ float g_mod[6 * DM];
__device__ __align__(1024) bf16 g_ht[(size_t)SEQ * DM];
__device__ __align__(1024) bf16 g_ox[(size_t)SEQ * HD];
__device__ __align__(1024) bf16 g_x1[(size_t)SEQ * DM];
__device__ __align__(1024) bf16 g_h2[(size_t)SEQ * DM];
__device__ __align__(1024) bf16 g_act[(size_t)SEQ * FF];
__device__ __align__(8192) uint32_t g_buf1[80 * 2 * 2048];
__device__ __align__(8192) uint32_t g_buf2[4 * 3 * 2048];
__device__ uint32_t g_choice[128];
__device__ uint32_t g_epoch;
#define TR(k)

#define FRESH(x) asm volatile("" : "+r"(x))
__device__ __forceinline__ float bfr(float x) { return __bfloat162float(__float2bfloat16_rn(x)); }
__device__ __forceinline__ uint32_t pack2(float a, float b) {
    uint32_t r; asm("cvt.rn.bf16x2.f32 %0, %1, %2;" : "=r"(r) : "f"(b), "f"(a)); return r;
}
__device__ __forceinline__ float bflo(uint32_t v) { return __uint_as_float(v << 16); }
__device__ __forceinline__ float bfhi(uint32_t v) { return __uint_as_float(v & 0xffff0000u); }
__device__ __forceinline__ float ex2(float x) { float r; asm("ex2.approx.ftz.f32 %0, %1;" : "=f"(r) : "f"(x)); return r; }
__device__ __forceinline__ float rcpf(float x) { float r; asm("rcp.approx.ftz.f32 %0, %1;" : "=f"(r) : "f"(x)); return r; }
__device__ __forceinline__ void score2(float& a, float& b) {
    const float SCALE = 0.07216878364870322f;
    uint32_t u = pack2(a, b);
    u = pack2(bflo(u) * SCALE, bfhi(u) * SCALE);
    a = bflo(u); b = bfhi(u);
}
__device__ __forceinline__ uint32_t smem_u32(const void* p) { return (uint32_t)__cvta_generic_to_shared(p); }

__device__ __forceinline__ void mbar_init(uint32_t bar, uint32_t cnt) {
    asm volatile("mbarrier.init.shared::cta.b64 [%0], %1;" :: "r"(bar), "r"(cnt) : "memory");
}
__device__ __forceinline__ void mbar_arrive(uint32_t bar) {
    asm volatile("mbarrier.arrive.shared::cta.b64 _, [%0];" :: "r"(bar) : "memory");
}
__device__ __forceinline__ void mbar_expect(uint32_t bar, uint32_t bytes) {
    asm volatile("mbarrier.arrive.expect_tx.shared::cta.b64 _, [%0], %1;" :: "r"(bar), "r"(bytes) : "memory");
}
__device__ __forceinline__ bool mbar_try(uint32_t bar, uint32_t parity) {
    uint32_t ok;
    asm volatile("{\n\t.reg .pred p;\n\tmbarrier.try_wait.parity.shared::cta.b64 p, [%1], %2;\n\tselp.u32 %0, 1, 0, p;\n\t}"
                 : "=r"(ok) : "r"(bar), "r"(parity) : "memory");
    return ok != 0;
}
__device__ __forceinline__ bool mbar_try_cluster(uint32_t bar, uint32_t parity) {
    uint32_t ok;
    asm volatile("{\n\t.reg .pred p;\n\tmbarrier.try_wait.parity.acquire.cluster.shared::cta.b64 p, [%1], %2;\n\tselp.u32 %0, 1, 0, p;\n\t}"
                 : "=r"(ok) : "r"(bar), "r"(parity) : "memory");
    return ok != 0;
}
__device__ __forceinline__ void mbar_wait(uint32_t bar, uint32_t parity) {
    uint32_t guard = 0;
    while (!mbar_try(bar, parity)) { if (++guard > (1u << 22)) __trap(); }
}
__device__ __forceinline__ void mbar_wait_cluster(uint32_t bar, uint32_t parity) {
    uint32_t guard = 0;
    while (!mbar_try_cluster(bar, parity)) { if (++guard > (1u << 22)) __trap(); }
}
__device__ __forceinline__ void bar_sync(int id, int n) { asm volatile("bar.sync %0, %1;" :: "r"(id), "r"(n) : "memory"); }
__device__ __forceinline__ void bar_arrive(int id, int n) { asm volatile("bar.arrive %0, %1;" :: "r"(id), "r"(n) : "memory"); }
__device__ __forceinline__ void sts1(uint32_t a, uint32_t v) { asm volatile("st.shared.u32 [%0], %1;" :: "r"(a), "r"(v) : "memory"); }
__device__ __forceinline__ uint32_t lds1(uint32_t a) { uint32_t v; asm volatile("ld.shared.u32 %0, [%1];" : "=r"(v) : "r"(a) : "memory"); return v; }
__device__ __forceinline__ void fence_async() { asm volatile("fence.proxy.async.shared::cta;" ::: "memory"); }
__device__ __forceinline__ void cluster_sync() {
    asm volatile("barrier.cluster.arrive.release.aligned;\n\tbarrier.cluster.wait.acquire.aligned;" ::: "memory");
}
__device__ __forceinline__ uint32_t mapa(uint32_t a, uint32_t rank) {
    uint32_t r; asm("mapa.shared::cluster.u32 %0, %1, %2;" : "=r"(r) : "r"(a), "r"(rank)); return r;
}
__device__ __forceinline__ void st_async1(uint32_t a, uint32_t v, uint32_t bar) {
    asm volatile("st.async.weak.shared::cluster.mbarrier::complete_tx::bytes.b32 [%0], %1, [%2];" :: "r"(a), "r"(v), "r"(bar) : "memory");
}
__device__ __forceinline__ void st_async2(uint32_t a, float x, float y, uint32_t bar) {
    asm volatile("st.async.weak.shared::cluster.mbarrier::complete_tx::bytes.v2.f32 [%0], {%1,%2}, [%3];" :: "r"(a), "f"(x), "f"(y), "r"(bar) : "memory");
}
__device__ __forceinline__ void st_async4(uint32_t a, const float* c, uint32_t bar) {
    asm volatile("st.async.weak.shared::cluster.mbarrier::complete_tx::bytes.v4.f32 [%0], {%1,%2,%3,%4}, [%5];"
                 :: "r"(a), "f"(c[0]), "f"(c[1]), "f"(c[2]), "f"(c[3]), "r"(bar) : "memory");
}
__device__ __forceinline__ void bulk_g2s(uint32_t dst, const void* src, uint32_t bytes, uint32_t bar) {
    asm volatile("cp.async.bulk.shared::cluster.global.mbarrier::complete_tx::bytes [%0], [%1], %2, [%3];"
                 :: "r"(dst), "l"(src), "r"(bytes), "r"(bar) : "memory");
}
__device__ __forceinline__ void cpa16(uint32_t s, const void* g) {
    asm volatile("cp.async.cg.shared.global [%0], [%1], 16;" :: "r"(s), "l"(g) : "memory");
}
__device__ __forceinline__ void cpa_wait_all() { asm volatile("cp.async.wait_all;" ::: "memory"); }
__device__ __forceinline__ void ldsm4(uint32_t* r, uint32_t a) {
    asm volatile("ldmatrix.sync.aligned.m8n8.x4.shared.b16 {%0,%1,%2,%3}, [%4];" : "=r"(r[0]), "=r"(r[1]), "=r"(r[2]), "=r"(r[3]) : "r"(a) : "memory");
}
__device__ __forceinline__ void ldsm4t(uint32_t* r, uint32_t a) {
    asm volatile("ldmatrix.sync.aligned.m8n8.x4.trans.shared.b16 {%0,%1,%2,%3}, [%4];" : "=r"(r[0]), "=r"(r[1]), "=r"(r[2]), "=r"(r[3]) : "r"(a) : "memory");
}
__device__ __forceinline__ void stsm2t(uint32_t a, uint32_t r0, uint32_t r1) {
    asm volatile("stmatrix.sync.aligned.m8n8.x2.trans.shared.b16 [%0], {%1,%2};" :: "r"(a), "r"(r0), "r"(r1) : "memory");
}
__device__ __forceinline__ void stsm4t(uint32_t a, uint32_t r0, uint32_t r1, uint32_t r2, uint32_t r3) {
    asm volatile("stmatrix.sync.aligned.m8n8.x4.trans.shared.b16 [%0], {%1,%2,%3,%4};" :: "r"(a), "r"(r0), "r"(r1), "r"(r2), "r"(r3) : "memory");
}
__device__ __forceinline__ uint32_t movm(uint32_t v) {
    uint32_t r; asm volatile("movmatrix.sync.aligned.m8n8.trans.b16 %0, %1;" : "=r"(r) : "r"(v)); return r;
}
__device__ __forceinline__ void mma16(float* c, uint32_t a0, uint32_t a1, uint32_t a2, uint32_t a3, uint32_t b0, uint32_t b1) {
    asm volatile("mma.sync.aligned.m16n8k16.row.col.f32.bf16.bf16.f32 {%0,%1,%2,%3}, {%4,%5,%6,%7}, {%8,%9}, {%0,%1,%2,%3};"
                 : "+f"(c[0]), "+f"(c[1]), "+f"(c[2]), "+f"(c[3]) : "r"(a0), "r"(a1), "r"(a2), "r"(a3), "r"(b0), "r"(b1));
}
__device__ __forceinline__ void mma8(float* c, uint32_t a0, uint32_t a1, uint32_t b0) {
    asm volatile("mma.sync.aligned.m16n8k8.row.col.f32.bf16.bf16.f32 {%0,%1,%2,%3}, {%4,%5}, {%6}, {%0,%1,%2,%3};"
                 : "+f"(c[0]), "+f"(c[1]), "+f"(c[2]), "+f"(c[3]) : "r"(a0), "r"(a1), "r"(b0));
}
__host__ __device__ constexpr uint64_t make_desc(uint32_t saddr, uint32_t lbo, uint32_t sbo, uint32_t layout) {
    return (uint64_t)((saddr & 0x3FFFF) >> 4) | ((uint64_t)(lbo >> 4) << 16) | ((uint64_t)(sbo >> 4) << 32) | ((uint64_t)layout << 62);
}
__device__ __forceinline__ void wg_fence() { asm volatile("wgmma.fence.sync.aligned;" ::: "memory"); }
__device__ __forceinline__ void wg_commit() { asm volatile("wgmma.commit_group.sync.aligned;" ::: "memory"); }
template <int N> __device__ __forceinline__ void wg_wait() { asm volatile("wgmma.wait_group.sync.aligned %0;" :: "n"(N) : "memory"); }

#define D16(C) C(d[0]), C(d[1]), C(d[2]), C(d[3]), C(d[4]), C(d[5]), C(d[6]), C(d[7]), \
               C(d[8]), C(d[9]), C(d[10]), C(d[11]), C(d[12]), C(d[13]), C(d[14]), C(d[15])
#define DREG16 "{%0,%1,%2,%3,%4,%5,%6,%7,%8,%9,%10,%11,%12,%13,%14,%15}"
__device__ __forceinline__ void wg_rs32(float* d, const uint32_t* a, uint64_t db, bool acc) {
    if (acc)
        asm volatile("wgmma.mma_async.sync.aligned.m64n32k16.f32.bf16.bf16 " DREG16 ", {%16,%17,%18,%19}, %20, 1, 1, 1, 0;"
            : D16("+f") : "r"(a[0]), "r"(a[1]), "r"(a[2]), "r"(a[3]), "l"(db));
    else
        asm volatile("wgmma.mma_async.sync.aligned.m64n32k16.f32.bf16.bf16 " DREG16 ", {%16,%17,%18,%19}, %20, 0, 1, 1, 0;"
            : D16("=f") : "r"(a[0]), "r"(a[1]), "r"(a[2]), "r"(a[3]), "l"(db));
}
__device__ __forceinline__ void wg_ss32(float* d, uint64_t da, uint64_t db, bool acc) {
    if (acc)
        asm volatile("wgmma.mma_async.sync.aligned.m64n32k16.f32.bf16.bf16 " DREG16 ", %16, %17, 1, 1, 1, 1, 0;"
            : D16("+f") : "l"(da), "l"(db));
    else
        asm volatile("wgmma.mma_async.sync.aligned.m64n32k16.f32.bf16.bf16 " DREG16 ", %16, %17, 0, 1, 1, 1, 0;"
            : D16("=f") : "l"(da), "l"(db));
}
__device__ __forceinline__ void wg_ss8(float* d, uint64_t da, uint64_t db, bool acc) {
    if (acc)
        asm volatile("wgmma.mma_async.sync.aligned.m64n8k16.f32.bf16.bf16 {%0,%1,%2,%3}, %4, %5, 1, 1, 1, 1, 1;"
            : "+f"(d[0]), "+f"(d[1]), "+f"(d[2]), "+f"(d[3]) : "l"(da), "l"(db));
    else
        asm volatile("wgmma.mma_async.sync.aligned.m64n8k16.f32.bf16.bf16 {%0,%1,%2,%3}, %4, %5, 0, 1, 1, 1, 1;"
            : "=f"(d[0]), "=f"(d[1]), "=f"(d[2]), "=f"(d[3]) : "l"(da), "l"(db));
}
template <int OFF> __device__ __forceinline__ void ldsm4t_i(uint32_t* r, uint32_t a) {
    asm volatile("ldmatrix.sync.aligned.m8n8.x4.trans.shared.b16 {%0,%1,%2,%3}, [%4+%5];"
                 : "=r"(r[0]), "=r"(r[1]), "=r"(r[2]), "=r"(r[3]) : "r"(a), "n"(OFF) : "memory");
}

__device__ __forceinline__ uint4 ld_relaxed4(const void* p) {
    uint4 v;
    asm volatile("ld.relaxed.gpu.global.v4.u32 {%0,%1,%2,%3}, [%4];" : "=r"(v.x), "=r"(v.y), "=r"(v.z), "=r"(v.w) : "l"(p) : "memory");
    return v;
}
__device__ __forceinline__ void st_relaxed2(void* p, uint32_t a, uint32_t b) {
    asm volatile("st.relaxed.gpu.global.v2.u32 [%0], {%1,%2};" :: "l"(p), "r"(a), "r"(b) : "memory");
}
__device__ __forceinline__ void st_relaxed2_off(void* base, uint32_t off, uint32_t a, uint32_t b) {
    asm volatile("{\n\t.reg .u64 ad;\n\tcvt.u64.u32 ad, %1;\n\tadd.u64 ad, ad, %0;\n\tst.relaxed.gpu.global.v2.u32 [ad], {%2,%3};\n\t}"
                 :: "l"(base), "r"(off), "r"(a), "r"(b) : "memory");
}
__device__ __forceinline__ void st_relaxed1(void* p, uint32_t a) {
    asm volatile("st.relaxed.gpu.global.u32 [%0], %1;" :: "l"(p), "r"(a) : "memory");
}
__device__ __forceinline__ uint32_t ld_acquire1(const uint32_t* p) {
    uint32_t v; asm volatile("ld.acquire.gpu.global.u32 %0, [%1];" : "=r"(v) : "l"(p) : "memory"); return v;
}
__device__ __forceinline__ void st_release1(uint32_t* p, uint32_t a) {
    asm volatile("st.release.gpu.global.u32 [%0], %1;" :: "l"(p), "r"(a) : "memory");
}
__device__ __forceinline__ uint4 lds4(uint32_t s) {
    uint4 v; asm volatile("ld.shared.v4.u32 {%0,%1,%2,%3}, [%4];" : "=r"(v.x), "=r"(v.y), "=r"(v.z), "=r"(v.w) : "r"(s) : "memory"); return v;
}
__device__ __forceinline__ void sts4(uint32_t s, const uint4& v) {
    asm volatile("st.shared.v4.u32 [%0], {%1,%2,%3,%4};" :: "r"(s), "r"(v.x), "r"(v.y), "r"(v.z), "r"(v.w) : "memory");
}
__device__ __forceinline__ float4 lds4f(uint32_t s) {
    float4 v; asm volatile("ld.shared.v4.f32 {%0,%1,%2,%3}, [%4];" : "=f"(v.x), "=f"(v.y), "=f"(v.z), "=f"(v.w) : "r"(s) : "memory"); return v;
}
__device__ __forceinline__ uint2 lds2(uint32_t s) {
    uint2 v; asm volatile("ld.shared.v2.u32 {%0,%1}, [%2];" : "=r"(v.x), "=r"(v.y) : "r"(s) : "memory"); return v;
}
__device__ __forceinline__ float2 lds2f(uint32_t s) {
    float2 v; asm volatile("ld.shared.v2.f32 {%0,%1}, [%2];" : "=f"(v.x), "=f"(v.y) : "r"(s) : "memory"); return v;
}
__device__ __forceinline__ uint32_t clk32() { uint32_t c; asm volatile("mov.u32 %0, %%clock;" : "=r"(c) :: "memory"); return c; }
__device__ __forceinline__ uint32_t tagw(float v, uint32_t tag) { return ((__float_as_uint(v) + 8u) & ~15u) | tag; }
__device__ __forceinline__ bool ok4(const uint4& v, uint32_t tag) { return (((v.x ^ tag) | (v.y ^ tag) | (v.z ^ tag) | (v.w ^ tag)) & 15u) == 0; }
__device__ __forceinline__ bool oks(const uint4& v) { return v.x != 0xFFFFFFFFu && v.y != 0xFFFFFFFFu && v.z != 0xFFFFFFFFu && v.w != 0xFFFFFFFFu; }
__device__ __forceinline__ float uf(uint32_t x) { return __uint_as_float(x & ~15u); }

__global__ void __launch_bounds__(256) k_mod(const bf16* __restrict__ c, const bf16* __restrict__ wmod) {
    __shared__ float sc[DM];
    __shared__ float red[8][64];
    const int tid = threadIdx.x;
    for (int i = tid; i < DM; i += 256) {
        float v = __bfloat162float(c[i]);
        sc[i] = bfr(v / (1.0f + __expf(-v)));
    }
    __syncthreads();
    const int cp = tid & 31, kg = tid >> 5;
    const int col = blockIdx.x * 64 + cp * 2;
    float a0 = 0.f, a1 = 0.f;
    #pragma unroll 8
    for (int k = kg * 80; k < kg * 80 + 80; k++) {
        uint32_t w = *(const uint32_t*)(wmod + (size_t)k * (6 * DM) + col);
        a0 += sc[k] * bflo(w); a1 += sc[k] * bfhi(w);
    }
    red[kg][cp * 2] = a0; red[kg][cp * 2 + 1] = a1;
    __syncthreads();
    if (tid < 64) {
        float s = 0.f;
        #pragma unroll
        for (int i = 0; i < 8; i++) s += red[i][tid];
        g_mod[blockIdx.x * 64 + tid] = bfr(s);
    }
    if (blockIdx.x == 0 && tid == 0) g_epoch = g_epoch + 1;
}

template <int MODE>
__global__ void __launch_bounds__(256) k_ln(const bf16* __restrict__ xin) {
    const int lane = threadIdx.x & 31, row = blockIdx.x * 8 + (threadIdx.x >> 5);
    const bf16* src = (MODE == 0 ? xin : g_x1) + (size_t)row * DM;
    const float* shift = g_mod + (MODE == 0 ? 0 : 3 * DM);
    const float* scale = g_mod + (MODE == 0 ? DM : 4 * DM);
    float v[3][8];
    float s = 0.f;
    #pragma unroll
    for (int i = 0; i < 3; i++) {
        int c = lane + 32 * i;
        if (c < 80) {
            uint4 u = *(const uint4*)(src + c * 8);
            v[i][0] = bflo(u.x); v[i][1] = bfhi(u.x); v[i][2] = bflo(u.y); v[i][3] = bfhi(u.y);
            v[i][4] = bflo(u.z); v[i][5] = bfhi(u.z); v[i][6] = bflo(u.w); v[i][7] = bfhi(u.w);
        } else {
            #pragma unroll
            for (int j = 0; j < 8; j++) v[i][j] = 0.f;
        }
        #pragma unroll
        for (int j = 0; j < 8; j++) s += v[i][j];
    }
    #pragma unroll
    for (int o = 16; o > 0; o >>= 1) s += __shfl_xor_sync(0xffffffffu, s, o);
    const float mean = s * (1.0f / DM);
    float q = 0.f;
    #pragma unroll
    for (int i = 0; i < 3; i++) {
        if (lane + 32 * i < 80) {
            #pragma unroll
            for (int j = 0; j < 8; j++) { float d = v[i][j] - mean; q += d * d; }
        }
    }
    #pragma unroll
    for (int o = 16; o > 0; o >>= 1) q += __shfl_xor_sync(0xffffffffu, q, o);
    const float mb = bfr(mean);
    const float var = bfr(q * (1.0f / DM));
    const float sd = bfr(sqrtf(bfr(var + 1e-5f)));
    #pragma unroll
    for (int i = 0; i < 3; i++) {
        int c = lane + 32 * i;
        if (c < 80) {
            float o[8];
            #pragma unroll
            for (int j = 0; j < 8; j++) {
                float n = bfr(bfr(v[i][j] - mb) / sd);
                float m1 = bfr(1.0f + scale[c * 8 + j]);
                o[j] = bfr(n * m1) + shift[c * 8 + j];
            }
            uint4 u = make_uint4(pack2(o[0], o[1]), pack2(o[2], o[3]), pack2(o[4], o[5]), pack2(o[6], o[7]));
            if (MODE == 0) {
                int seg = row >> 5, r = row & 31, blk = c >> 3, cc = c & 7;
                *(uint4*)(g_ht + (size_t)seg * 20480 + blk * 2048 + r * 64 + ((cc ^ (r & 7)) << 3)) = u;
            } else {
                *(uint4*)(g_h2 + (size_t)row * DM + c * 8) = u;
            }
        }
    }
}

constexpr int SM_WV = 0;
constexpr int SM_HB = 81920;
constexpr int SM_WO = SM_HB + 40960;
constexpr int SM_QX = SM_WO + 77824;
constexpr int SM_KS = SM_QX + 4096;
constexpr int SM_QM = SM_KS + 5120;
constexpr int SM_XS = SM_QM + 1024;
constexpr int SM_MS = SM_XS + 12288;
constexpr int SM_OS = SM_MS + 3840;
constexpr int SM_PM = SM_OS + 3072;
constexpr int SM_BAR = SM_PM + 640;
constexpr int SM_CH = SM_BAR + 128;
constexpr int SM_TOTAL = SM_CH + 128;
static_assert(SM_TOTAL <= 232448, "smem");

enum { B_MEM_FULL = 0, B_MEM_FREE, B_HLO_FULL, B_HHI_FULL, B_HLO_FREE, B_HHI_FREE, B_MS, B_O, B_XS, B_O1, B_XSFREE };

__device__ __forceinline__ int probe_blk(uint32_t* blk) {
    uint32_t t0 = 0xffffffffu, t1 = 0xffffffffu, acc = 0;
    for (int rep = 0; rep < 3; rep++) {
        #pragma unroll
        for (int pg = 0; pg < 2; pg++) {
            uint32_t c0 = clk32();
            uint32_t v = atomicOr(blk + pg * 1024 + acc, 0u);
            acc = (v == 0x12345678u) ? 1u : 0u;
            asm volatile("" :: "r"(acc) : "memory");
            uint32_t c1 = clk32() + acc;
            uint32_t d = c1 - c0;
            if (rep > 0) { if (pg == 0) t0 = min(t0, d); else t1 = min(t1, d); }
        }
    }
    return t1 < t0 ? 1 : 0;
}

__device__ __forceinline__ uint32_t wo_tile_off(int w) {
    if (w < 8) return w * 6144;
    if (w < 12) return 8 * 6144 + (w - 8) * 4096;
    return 8 * 6144 + 4 * 4096 + (w - 12) * 6144;
}

template <int NRES, int NPRE>
__device__ __forceinline__ void wo_phase(uint32_t sb, int w, int lane, const uint32_t (*res)[4], uint32_t parity,
                                         uint32_t tag, int tile, int h) {
    FRESH(lane);
    const int er = (lane & 7) + 8 * (lane >> 4);
    const uint32_t aaddr = sb + SM_WO + wo_tile_off(w) + er * 32 + ((((lane >> 3) & 1) ^ ((er >> 2) & 1)) << 4);
    const uint32_t baddr = sb + SM_OS + lane * 16;
    float c0[4] = {0.f, 0.f, 0.f, 0.f}, c1[4] = {0.f, 0.f, 0.f, 0.f};
    uint32_t pre[NPRE > 4 ? NPRE : 4][4];
    if (NPRE >= 4) {
        #pragma unroll
        for (int i = 0; i < 4; i++) ldsm4t(pre[i], aaddr + i * 512);
        mbar_wait(sb + SM_BAR + B_O1 * 8, parity);
        uint32_t b[2][4];
        ldsm4t(b[0], baddr);
        ldsm4t(b[1], baddr + 512);
        #pragma unroll
        for (int kp = 0; kp < 2; kp++) {
            mma16(c0, pre[2 * kp][0], pre[2 * kp][1], pre[2 * kp][2], pre[2 * kp][3], b[kp][0], b[kp][1]);
            mma16(c1, pre[2 * kp + 1][0], pre[2 * kp + 1][1], pre[2 * kp + 1][2], pre[2 * kp + 1][3], b[kp][2], b[kp][3]);
        }
    } else {
        #pragma unroll
        for (int i = 0; i < 2; i++) ldsm4t(pre[i], aaddr + i * 512);
        mbar_wait(sb + SM_BAR + B_O1 * 8, parity);
        #pragma unroll
        for (int kp = 0; kp < 2; kp++) {
            uint32_t b[4];
            ldsm4t(b, baddr + kp * 512);
            if (kp == 1) { ldsm4t(pre[0], aaddr + 2 * 512); ldsm4t(pre[1], aaddr + 3 * 512); }
            mma16(c0, pre[0][0], pre[0][1], pre[0][2], pre[0][3], b[0], b[1]);
            mma16(c1, pre[1][0], pre[1][1], pre[1][2], pre[1][3], b[2], b[3]);
        }
    }
    #pragma unroll
    for (int i = 0; i < NPRE; i++) ldsm4t(pre[i], aaddr + (4 + i) * 512);
    uint32_t off0, off1;
    {
        uint32_t ch;
        asm volatile("ld.shared.u16 %0, [%1];" : "=r"(ch) : "r"(sb + SM_CH + 2 * tile) : "memory");
        const int j = h >> 4;
        const uint32_t base = (uint32_t)((tile * 4 + j) * 8192 + (h & 15) * 256 + lane * 8);
        ch >>= j;
        off0 = base + (ch & 1) * 4096;
        off1 = base + 16384 + (ch & 256) * 16;
    }
    mbar_wait(sb + SM_BAR + B_O * 8, parity);
    if (NRES == 4) {
        uint32_t b[4][4];
        #pragma unroll
        for (int i = 0; i < 4; i++) ldsm4t(b[i], baddr + (2 + i) * 512);
        #pragma unroll
        for (int i = 0; i < 2; i++) {
            mma16(c0, res[2 * i][0], res[2 * i][1], res[2 * i][2], res[2 * i][3], b[i][0], b[i][1]);
            mma16(c1, res[2 * i + 1][0], res[2 * i + 1][1], res[2 * i + 1][2], res[2 * i + 1][3], b[i][2], b[i][3]);
        }
        #pragma unroll
        for (int i = 0; i < 2; i++) {
            mma16(c0, pre[2 * i][0], pre[2 * i][1], pre[2 * i][2], pre[2 * i][3], b[2 + i][0], b[2 + i][1]);
            mma16(c1, pre[2 * i + 1][0], pre[2 * i + 1][1], pre[2 * i + 1][2], pre[2 * i + 1][3], b[2 + i][2], b[2 + i][3]);
        }
    } else if (NPRE == 4) {
        uint32_t b[2][4];
        #pragma unroll
        for (int hh = 0; hh < 2; hh++) {
            ldsm4t(b[0], baddr + (2 + 2 * hh) * 512);
            ldsm4t(b[1], baddr + (3 + 2 * hh) * 512);
            if (hh) {
                #pragma unroll
                for (int i = 0; i < 4; i++) ldsm4t(pre[i], aaddr + (8 + i) * 512);
            }
            #pragma unroll
            for (int i = 0; i < 2; i++) {
                mma16(c0, pre[2 * i][0], pre[2 * i][1], pre[2 * i][2], pre[2 * i][3], b[i][0], b[i][1]);
                mma16(c1, pre[2 * i + 1][0], pre[2 * i + 1][1], pre[2 * i + 1][2], pre[2 * i + 1][3], b[i][2], b[i][3]);
            }
        }
    }
    st_relaxed2_off(g_buf1, off0, tagw(c0[0] + c1[0], tag), tagw(c0[1] + c1[1], tag));
    st_relaxed2_off(g_buf1, off1, tagw(c0[2] + c1[2], tag), tagw(c0[3] + c1[3], tag));
}

template <int NT, bool MASK>
__device__ __forceinline__ void softmax_core(float (*sc)[2], int g, int t, uint32_t* pb) {
    const float L2E = 1.4426950408889634f;
    #pragma unroll
    for (int j = 0; j < NT; j++) score2(sc[j][0], sc[j][1]);
    if (MASK) {
        const float NEG = -999292928.0f;
        if (2 * t > g) sc[NT - 1][0] = NEG;
        if (2 * t + 1 > g) sc[NT - 1][1] = NEG;
    }
    float m[NT];
    #pragma unroll
    for (int j = 0; j < NT; j++) m[j] = fmaxf(sc[j][0], sc[j][1]);
    float mx = m[0];
    #pragma unroll
    for (int j = 1; j < NT; j++) mx = fmaxf(mx, m[j]);
    mx = fmaxf(mx, __shfl_xor_sync(0xffffffffu, mx, 1));
    mx = fmaxf(mx, __shfl_xor_sync(0xffffffffu, mx, 2));
    float s0 = 0.f, s1 = 0.f;
    #pragma unroll
    for (int j = 0; j < NT; j++) {
        sc[j][0] = ex2((sc[j][0] - mx) * L2E); sc[j][1] = ex2((sc[j][1] - mx) * L2E);
        s0 += sc[j][0]; s1 += sc[j][1];
    }
    s0 += s1;
    s0 += __shfl_xor_sync(0xffffffffu, s0, 1);
    s0 += __shfl_xor_sync(0xffffffffu, s0, 2);
    const float iv = rcpf(s0);
    #pragma unroll
    for (int j = 0; j < NT; j++) pb[j] = pack2(sc[j][0] * iv, sc[j][1] * iv);
}
template <int NT>
__device__ __forceinline__ void xsoftmax(uint32_t a, int g, int t) {
    float sc[NT][2];
    #pragma unroll
    for (int j = 0; j < NT; j++) {
        float2 v0 = lds2f(a + j * 512), v1 = lds2f(a + j * 512 + 4096), v2 = lds2f(a + j * 512 + 8192);
        sc[j][0] = v0.x + v1.x + v2.x; sc[j][1] = v0.y + v1.y + v2.y;
    }
    uint32_t pb[NT];
    softmax_core<NT, true>(sc, g, t, pb);
    #pragma unroll
    for (int j = 0; j < NT; j += 2) {
        if (j + 1 < NT) asm volatile("st.shared.v2.u32 [%0], {%1,%2};" :: "r"(a + j * 512), "r"(pb[j]), "r"(pb[j + 1]) : "memory");
        else sts1(a + j * 512, pb[j]);
    }
}
template <int NJ>
__device__ __forceinline__ void xscores(uint32_t sb, int p, int mi, int j0, int lane) {
    FRESH(lane);
    const int r = lane & 7, cq = lane >> 3;
    const int qrow = mi * 16 + r + 8 * (cq & 1);
    uint32_t kb[NJ][8];
    float d[NJ][4];
    #pragma unroll
    for (int j = 0; j < NJ; j++) {
        ldsm4(kb[j], sb + SM_KS + ((j0 + j) * 8 + r) * 128 + ((cq ^ r) << 4));
        ldsm4(kb[j] + 4, sb + SM_KS + ((j0 + j) * 8 + r) * 128 + (((cq + 4) ^ r) << 4));
        d[j][0] = 0.f; d[j][1] = 0.f; d[j][2] = 0.f; d[j][3] = 0.f;
    }
    #pragma unroll
    for (int kt = 0; kt < 4; kt++) {
        uint32_t a[4];
        ldsm4(a, sb + SM_QX + qrow * 128 + (((2 * kt + (cq >> 1)) ^ r) << 4));
        #pragma unroll
        for (int j = 0; j < NJ; j++) mma16(d[j], a[0], a[1], a[2], a[3], kb[j][2 * kt], kb[j][2 * kt + 1]);
    }
    const uint32_t la = sb + SM_XS + p * 4096 + (mi * 3 + j0) * 512 + lane * 16;
    #pragma unroll
    for (int rk = 0; rk < 3; rk++) {
        const uint32_t ra = mapa(la, rk), rb = mapa(sb + SM_BAR + B_XS * 8, rk);
        #pragma unroll
        for (int j = 0; j < NJ; j++) st_async4(ra + j * 512, d[j], rb);
    }
}
__device__ __forceinline__ void mbar_arrive_remote(uint32_t bar) {
    asm volatile("mbarrier.arrive.relaxed.cluster.shared::cluster.b64 _, [%0];" :: "r"(bar) : "memory");
}

__global__ void __launch_bounds__(512, 1)
k_rec(const bf16* __restrict__ mem0, const bf16* __restrict__ Wq, const bf16* __restrict__ Wk,
      const bf16* __restrict__ Wv, const bf16* __restrict__ Wo) {
    extern __shared__ __align__(1024) uint8_t smem_raw[];
    constexpr uint32_t SBC = 1024;
    const uint32_t sb = smem_u32(smem_raw);
    if ((sb & 0xFFFFFFu) != SBC) __trap();
    int lane = __shfl_sync(0xffffffffu, threadIdx.x & 31, threadIdx.x & 31);
    const int warp = __shfl_sync(0xffffffffu, threadIdx.x >> 5, 0), wg = warp >> 2;
    const int tid = warp * 32 + lane;
    const int b = blockIdx.x, h = b / 3, p = b % 3;
    const int g = lane >> 2, t = lane & 3;
    const int tile0 = p == 0 ? 0 : (p == 1 ? 14 : 27);
    const int ntile = p == 0 ? 14 : 13;
    const uint32_t bar = sb + SM_BAR;

    if (tid == 0) {
        mbar_init(bar + B_MEM_FULL * 8, 4);
        mbar_init(bar + B_MEM_FREE * 8, 12);
        mbar_init(bar + B_HLO_FULL * 8, 1);
        mbar_init(bar + B_HHI_FULL * 8, 1);
        mbar_init(bar + B_HLO_FREE * 8, 12);
        mbar_init(bar + B_HHI_FREE * 8, 12);
        mbar_init(bar + B_MS * 8, 1);
        mbar_init(bar + B_O * 8, 1);
        mbar_init(bar + B_XS * 8, 1);
        mbar_init(bar + B_O1 * 8, 4);
        mbar_init(bar + B_XSFREE * 8, 12);
        asm volatile("fence.mbarrier_init.release.cluster;" ::: "memory");
        mbar_expect(bar + B_MS * 8, 3840);
        mbar_expect(bar + B_O * 8, 2048);
        mbar_expect(bar + B_XS * 8, 12288);
        mbar_expect(bar + B_HLO_FULL * 8, 12288);
        bulk_g2s(sb + SM_HB, g_ht, 12288, sb + SM_BAR + B_HLO_FULL * 8);
        mbar_expect(bar + B_HHI_FULL * 8, 28672);
        bulk_g2s(sb + SM_HB + 12288, (const char*)g_ht + 12288, 28672, sb + SM_BAR + B_HHI_FULL * 8);
    }
    cluster_sync();

    if (wg < 2) {
        asm volatile("setmaxnreg.inc.sync.aligned.u32 200;");
        const int w = warp & 3;
        uint32_t wa[40][4];
        {
            const bf16* W = (wg == 0 ? Wq : Wk) + (size_t)h * DH + p * 64 + w * 16 + t * 4;
            #pragma unroll
            for (int kt = 0; kt < 40; kt++) {
                uint2 l1 = __ldg((const uint2*)(W + (size_t)(kt * 16 + g) * HD));
                uint2 l2 = __ldg((const uint2*)(W + (size_t)(kt * 16 + 8 + g) * HD));
                wa[kt][0] = l1.x; wa[kt][1] = l1.y; wa[kt][2] = l2.x; wa[kt][3] = l2.y;
            }
            #pragma unroll
            for (int kt = 0; kt < 40; kt++) {
                #pragma unroll
                for (int i = 0; i < 4; i++) wa[kt][i] = movm(wa[kt][i]);
            }
        }

        const uint32_t dstx = sb + (wg == 0 ? SM_QX : SM_KS + 1024);

        for (int s = -1; s < NSEG; s++) {
            const uint32_t par = s & 1;
            FRESH(lane);
            const int g = lane >> 2, t = lane & 3, tid = warp * 32 + lane;
            if (s >= 0) {
                mbar_wait(bar + B_MEM_FULL * 8, par);
                TR(0);
                float c[4][4];
                #pragma unroll
                for (int i = 0; i < 4; i++) { c[i][0] = 0.f; c[i][1] = 0.f; c[i][2] = 0.f; c[i][3] = 0.f; }
                uint32_t maddr = sb + lane * 16;
                asm volatile("" : "+r"(maddr));
                #pragma unroll
                for (int kp = 0; kp < 20; kp++) {
                    uint32_t bb[4];
                    ldsm4t(bb, maddr + (SM_HB + kp * 512));
                    mma16(c[(kp & 1) * 2], wa[2 * kp][0], wa[2 * kp][1], wa[2 * kp][2], wa[2 * kp][3], bb[0], bb[1]);
                    mma16(c[(kp & 1) * 2 + 1], wa[2 * kp + 1][0], wa[2 * kp + 1][1], wa[2 * kp + 1][2], wa[2 * kp + 1][3], bb[2], bb[3]);
                }
                {
                    const int tok = lane & 7, ch = 2 * w + ((lane >> 3) & 1);
                    stsm2t(sb + (wg == 0 ? SM_QM : SM_KS) + tok * 128 + ((ch ^ tok) << 4),
                           pack2((c[0][0] + c[1][0]) + (c[2][0] + c[3][0]), (c[0][1] + c[1][1]) + (c[2][1] + c[3][1])),
                           pack2((c[0][2] + c[1][2]) + (c[2][2] + c[3][2]), (c[0][3] + c[1][3]) + (c[2][3] + c[3][3])));
                }
                __syncwarp();
                if (lane == 0) mbar_arrive(bar + B_MEM_FREE * 8);
                TR(1);
                bar_sync(1, 256);
                if (warp < 5) {
                    const int r = lane & 7, cq = lane >> 3;
                    uint32_t a[8], kb[8];
                    ldsm4(a, sb + SM_QM + r * 128 + ((cq ^ r) << 4));
                    ldsm4(kb, sb + SM_KS + (warp * 8 + r) * 128 + ((cq ^ r) << 4));
                    ldsm4(a + 4, sb + SM_QM + r * 128 + (((cq + 4) ^ r) << 4));
                    ldsm4(kb + 4, sb + SM_KS + (warp * 8 + r) * 128 + (((cq + 4) ^ r) << 4));
                    float d0[4] = {0.f, 0.f, 0.f, 0.f}, d1[4] = {0.f, 0.f, 0.f, 0.f};
                    mma16(d0, a[0], 0u, a[1], 0u, kb[0], kb[1]);
                    mma16(d1, a[2], 0u, a[3], 0u, kb[2], kb[3]);
                    mma16(d0, a[4], 0u, a[5], 0u, kb[4], kb[5]);
                    mma16(d1, a[6], 0u, a[7], 0u, kb[6], kb[7]);
                    const uint32_t la = sb + SM_MS + p * 1280 + warp * 256 + lane * 8;
                    #pragma unroll
                    for (int rk = 0; rk < 3; rk++)
                        st_async2(mapa(la, rk), d0[0] + d1[0], d0[1] + d1[1], mapa(bar + B_MS * 8, rk));
                    bar_arrive(4, 352);
                } else if (warp < 7) {
                    xscores<1>(sb, p, warp - 5, 0, lane);
                    bar_arrive(4, 352);
                }
                TR(2);
                if (s < NSEG - 1) {
                    wo_phase<0, 4>(sb, warp, lane, nullptr, par, (uint32_t)(s % 15) + 1u, tile0 + warp, h);
                    TR(4);
                }
            }
            if (s < NSEG - 1) {
                FRESH(lane);
                const uint32_t hp = (s + 1) & 1;
                float d[16];
                const uint64_t db0 = make_desc(SBC + SM_HB, 16, 1024, 1);
                mbar_wait(bar + B_HHI_FULL * 8, hp);
                {
                    const int r = lane & 7, mq = lane >> 3;
                    const uint32_t ha = sb + SM_HB + 9 * 4096 + (8 * (mq >> 1) + r) * 128 + (((6 + (mq & 1)) ^ r) << 4);
                    uint32_t b0[4], b1[4];
                    ldsm4(b0, ha);
                    ldsm4(b1, ha + 2048);
                    #pragma unroll
                    for (int i = 0; i < 16; i++) d[i] = 0.f;
                    mma16(d + 0, wa[39][0], wa[39][1], wa[39][2], wa[39][3], b0[0], b0[1]);
                    mma16(d + 4, wa[39][0], wa[39][1], wa[39][2], wa[39][3], b0[2], b0[3]);
                    mma16(d + 8, wa[39][0], wa[39][1], wa[39][2], wa[39][3], b1[0], b1[1]);
                    mma16(d + 12, wa[39][0], wa[39][1], wa[39][2], wa[39][3], b1[2], b1[3]);
                    asm volatile("" : "+f"(d[0]), "+f"(d[4]), "+f"(d[8]), "+f"(d[12]) :: "memory");
                }
                if (s >= 0) bar_arrive(6, 512);
                mbar_wait(bar + B_HLO_FULL * 8, hp);
                bar_sync(9, 384);
                TR(6);
                wg_fence();
                #pragma unroll
                for (int kt = 0; kt < 12; kt++) wg_rs32(d, wa[kt], db0 + (uint64_t)(((kt >> 2) * 4096 + (kt & 3) * 32) >> 4), 1);
                wg_commit();
                #pragma unroll
                for (int kt = 12; kt < 39; kt++) wg_rs32(d, wa[kt], db0 + (uint64_t)(((kt >> 2) * 4096 + (kt & 3) * 32) >> 4), 1);
                wg_commit();
                wg_wait<1>();
                if (lane == 0) mbar_arrive(bar + B_HLO_FREE * 8);
                wg_wait<0>();
                if (lane == 0) mbar_arrive(bar + B_HHI_FREE * 8);
                TR(7);
                const int mi = lane >> 3, r = lane & 7;
                #pragma unroll
                for (int jj = 0; jj < 2; jj++) {
                    const int tok = 8 * (2 * jj + (mi >> 1)) + r, ch = 2 * w + (mi & 1);
                    stsm4t(dstx + tok * 128 + ((ch ^ r) << 4),
                           pack2(d[8 * jj + 0], d[8 * jj + 1]), pack2(d[8 * jj + 2], d[8 * jj + 3]),
                           pack2(d[8 * jj + 4], d[8 * jj + 5]), pack2(d[8 * jj + 6], d[8 * jj + 7]));
                }
                bar_arrive(8, 384);
                if (s < 0) bar_sync(0, 512);
            }
        }
    } else if (wg == 2) {
        asm volatile("setmaxnreg.dec.sync.aligned.u32 64;");
        const int w = warp & 3;
        {
            const int c = tid & 7;
            const bf16* src = Wv + (size_t)h * DH + p * 64 + c * 8;
            for (int k = (tid & 127) >> 3; k < DM; k += 16)
                cpa16(sb + SM_WV + k * 128 + ((c ^ (k & 7)) << 4), src + (size_t)k * HD);
        }
        uint32_t res[4][4];
        {
            const bf16* src = Wo + ((size_t)h * DH + ((p + 1) % 3) * 64) * DM + (tile0 + warp) * 16 + 2 * t;
            #pragma unroll
            for (int kt = 0; kt < 4; kt++) {
                res[kt][0] = __ldg((const uint32_t*)(src + (size_t)(kt * 16 + g) * DM));
                res[kt][1] = __ldg((const uint32_t*)(src + (size_t)(kt * 16 + g) * DM + 8));
                res[kt][2] = __ldg((const uint32_t*)(src + (size_t)(kt * 16 + 8 + g) * DM));
                res[kt][3] = __ldg((const uint32_t*)(src + (size_t)(kt * 16 + 8 + g) * DM + 8));
            }
            #pragma unroll
            for (int kt = 0; kt < 4; kt++) {
                #pragma unroll
                for (int i = 0; i < 4; i++) res[kt][i] = movm(res[kt][i]);
            }
        }
        cpa_wait_all();
        fence_async();
        bar_sync(2, 128);
        const uint64_t da0 = make_desc(SBC + SM_WV, 16, 1024, 1);
        uint32_t vx[8], vm0 = 0, vm1 = 0;
        #pragma unroll
        for (int i = 0; i < 8; i++) vx[i] = 0;

        for (int s = -1; s < NSEG; s++) {
            FRESH(lane);
            const int g = lane >> 2, t = lane & 3, tid = warp * 32 + lane;
            if (s >= 0) {
                const uint32_t par = s & 1;
                mbar_wait(bar + B_MEM_FULL * 8, par);
                bar_sync(4, 352);
                TR(0);
                float dv[4];
                {
                    const uint64_t dbm = make_desc(SBC + SM_HB, 128, 128, 0);
                    wg_fence();
                    #pragma unroll
                    for (int kt = 0; kt < 40; kt++) {
                        wg_ss8(dv, da0 + (uint64_t)(kt * 128), dbm + (uint64_t)(kt * 16), kt > 0);
                        wg_commit();
                        if (kt < 39) wg_wait<1>();
                    }
                    wg_commit();
                }
                TR(1);
                bar_sync(5, 160);
                TR(2);
                uint32_t pb[5];
                #pragma unroll
                for (int j = 0; j < 5; j++) pb[j] = lds1(sb + SM_PM + j * 128 + lane * 4);
                float o0[4] = {0.f, 0.f, 0.f, 0.f}, o1[4] = {0.f, 0.f, 0.f, 0.f}, o2[4] = {0.f, 0.f, 0.f, 0.f};
                wg_wait<0>();
                TR(3);
                mma16(o0, vx[0], vx[1], vx[2], vx[3], pb[1], pb[2]);
                mma16(o1, vx[4], vx[5], vx[6], vx[7], pb[3], pb[4]);
                vm0 = pack2(dv[0], dv[1]); vm1 = pack2(dv[2], dv[3]);
                mma8(o2, vm0, vm1, pb[0]);
                if (s < NSEG - 1) {
                    const uint32_t q0 = pack2(o0[0] + o1[0] + o2[0], o0[1] + o1[1] + o2[1]), q1 = pack2(o0[2] + o1[2] + o2[2], o0[3] + o1[3] + o2[3]);
                    const uint32_t la = sb + SM_OS + (w * 16 + g) * 16 + t * 4;
                    #pragma unroll
                    for (int i = 1; i < 3; i++) {
                        const uint32_t rk = (p + i) % 3;
                        const uint32_t ra = mapa(la + (3 - i) * 1024, rk), rb = mapa(bar + B_O * 8, rk);
                        st_async1(ra, q0, rb);
                        st_async1(ra + 128, q1, rb);
                    }
                    sts1(la, q0);
                    sts1(la + 128, q1);
                    __syncwarp();
                    if (lane == 0) { mbar_arrive(bar + B_O1 * 8); mbar_arrive(bar + B_MEM_FREE * 8); }
                }
                TR(5);
                if (s < NSEG - 1) {
                    wo_phase<4, 4>(sb, warp, lane, res, par, (uint32_t)(s % 15) + 1u, tile0 + warp, h);
                    TR(4);
                    if (tid == 256) mbar_expect(bar + B_O * 8, 2048);
                }
                if (s < NSEG - 1) bar_sync(6, 512);
            }
            uint32_t vn[8];
            #pragma unroll
            for (int i = 0; i < 8; i++) vn[i] = 0;
            if (s < NSEG - 1) {
            float d[16];
            const uint32_t hp = (s + 1) & 1;
            const uint64_t db0 = make_desc(SBC + SM_HB, 16, 1024, 1);
            mbar_wait(bar + B_HHI_FULL * 8, hp);
            TR(6);
            wg_fence();
            #pragma unroll
            for (int kt = 12; kt < 40; kt++) wg_ss32(d, da0 + (uint64_t)(kt * 128), db0 + (uint64_t)(((kt >> 2) * 4096 + (kt & 3) * 32) >> 4), kt > 12);
            wg_commit();
            mbar_wait(bar + B_HLO_FULL * 8, hp);
            wg_fence();
            #pragma unroll
            for (int kt = 0; kt < 9; kt++) wg_ss32(d, da0 + (uint64_t)(kt * 128), db0 + (uint64_t)(((kt >> 2) * 4096 + (kt & 3) * 32) >> 4), 1);
            wg_commit();
            #pragma unroll
            for (int kt = 9; kt < 12; kt++) wg_ss32(d, da0 + (uint64_t)(kt * 128), db0 + (uint64_t)(((kt >> 2) * 4096 + (kt & 3) * 32) >> 4), 1);
            wg_commit();
            wg_wait<1>();
            bar_arrive(9, 384);
            wg_wait<0>();
            if (lane == 0) mbar_arrive(bar + B_HLO_FREE * 8);
            TR(7);
            if (lane == 0) mbar_arrive(bar + B_HHI_FREE * 8);
            #pragma unroll
            for (int i = 0; i < 8; i++) vn[i] = pack2(d[2 * i], d[2 * i + 1]);
            }
            if (s >= 0) {
                {
                    FRESH(lane);
                    mbar_wait(bar + B_XS * 8, s & 1);
                    if (w == 0 && lane == 0) mbar_expect(bar + B_XS * 8, 12288);
                    const uint32_t a = sb + SM_XS + (w >> 1) * 1536 + lane * 16 + (w & 1) * 8;
                    if (w == 0) xsoftmax<2>(a, lane >> 2, lane & 3);
                    else if (w == 1) xsoftmax<3>(a, lane >> 2, lane & 3);
                    else if (w == 2) xsoftmax<4>(a, lane >> 2, lane & 3);
                    else xsoftmax<5>(a, lane >> 2, lane & 3);
                }
                TR(8);
                bar_sync(7, 128);
                FRESH(lane);
                bf16* orow = g_ox + (size_t)(s * 32 + (lane >> 2)) * HD + h * DH + p * 64 + w * 16 + 2 * (lane & 3);
                {
                    const uint32_t pa = sb + SM_XS + lane * 16;
                    #pragma unroll
                    for (int mi = 0; mi < 2; mi++) {
                        float oa[4] = {0.f, 0.f, 0.f, 0.f}, ob[4] = {0.f, 0.f, 0.f, 0.f};
                        if (mi == 0) {
                            const uint4 p0 = lds4(pa);
                            const uint32_t p3 = lds1(pa + 1024 + 8);
                            mma8(oa, vm0, vm1, p0.x);
                            mma8(ob, vm0, vm1, p0.z);
                            mma16(oa, vx[0], vx[1], vx[2], vx[3], p0.y, 0u);
                            mma16(ob, vx[0], vx[1], vx[2], vx[3], p0.w, p3);
                        } else {
                            const uint4 p1 = lds4(pa + 1536), p2 = lds4(pa + 2560);
                            const uint32_t p4 = lds1(pa + 3584 + 8);
                            mma8(oa, vm0, vm1, p1.x);
                            mma8(ob, vm0, vm1, p1.z);
                            mma16(oa, vx[0], vx[1], vx[2], vx[3], p1.y, p2.x);
                            mma16(ob, vx[0], vx[1], vx[2], vx[3], p1.w, p2.z);
                            mma16(oa, vx[4], vx[5], vx[6], vx[7], p2.y, 0u);
                            mma16(ob, vx[4], vx[5], vx[6], vx[7], p2.w, p4);
                            if (lane < 3) mbar_arrive_remote(mapa(bar + B_XSFREE * 8, lane));
                        }
                        const uint32_t u0 = movm(pack2(oa[0], oa[1])), u1 = movm(pack2(oa[2], oa[3]));
                        const uint32_t u2 = movm(pack2(ob[0], ob[1])), u3 = movm(pack2(ob[2], ob[3]));
                        bf16* dst = orow + (size_t)(16 * mi) * HD;
                        *(uint32_t*)dst = u0;
                        *(uint32_t*)(dst + 8) = u1;
                        *(uint32_t*)(dst + 8 * HD) = u2;
                        *(uint32_t*)(dst + 8 * HD + 8) = u3;
                    }
                }
                TR(9);
                if (s == NSEG - 1) break;
            }
            #pragma unroll
            for (int i = 0; i < 8; i++) vx[i] = vn[i];
            if (s >= 0) mbar_wait_cluster(bar + B_XSFREE * 8, s & 1);
            bar_sync(8, 384);
            TR(10);
            if (w < 3) xscores<2>(sb, p, w > 0, w == 2 ? 3 : 1, lane);
            TR(11);
            if (s < 0) bar_sync(0, 512);
        }
    } else {
        asm volatile("setmaxnreg.dec.sync.aligned.u32 48;");
        const int w = warp & 3, lt = tid & 127;
        {
            const bf16* src0 = Wo + (size_t)h * DH * DM + tile0 * 16;
            const int nch = 2 * ntile;
            for (int i = lt; i < DH * nch; i += 128) {
                const int e = i / nch, c = i - e * nch, tl = c >> 1, cc = c & 1;
                int es = e;
                if (tl >= 8 && tl < 12) { if (e >= 64 && e < 128) continue; if (e >= 128) es = e - 64; }
                int eg = e + p * 64; if (eg >= DH) eg -= DH;
                cpa16(sb + SM_WO + wo_tile_off(tl) + es * 32 + ((cc ^ ((e >> 2) & 1)) << 4), src0 + (size_t)eg * DM + c * 8);
            }
        }
        const uint32_t epoch = *(volatile uint32_t*)&g_epoch;
        if (b < 80) {
            #pragma unroll
            for (int i = 0; i < 2; i++) {
                const int idx = lt + i * 128, sl = idx >> 6, pg = (idx >> 5) & 1, wd = idx & 31;
                st_relaxed1(g_buf2 + (sl * 3 + (b >> 5)) * 2048 + pg * 1024 + (b & 31) * 32 + wd, 0xFFFFFFFFu);
            }
            __threadfence();
        }
        if (lane == 0) {
            for (int i = w; i < 14; i += 4) {
                int c = 0;
                if (i < 12) c = probe_blk(g_buf2 + i * 2048 + 640 + (b & 31) * 8);
                else if (b < 80) c = probe_blk(g_buf1 + (b * 2 + (i - 12)) * 2048);
                asm volatile("st.shared.u8 [%0], %1;" :: "r"(sb + SM_CH + 96 + i), "r"(c) : "memory");
            }
        }
        bar_sync(3, 128);
        uint32_t selmask = 0;
        for (int i = 0; i < 14; i++) {
            uint32_t c; asm volatile("ld.shared.u8 %0, [%1];" : "=r"(c) : "r"(sb + SM_CH + 96 + i) : "memory");
            selmask |= c << i;
        }
        if (lt == 0 && b < 80) st_release1(&g_choice[b], (epoch << 2) | (selmask >> 12));
        if (lt < 80) {
            uint32_t v, guard = 0;
            do { v = ld_acquire1(&g_choice[lt]); if (++guard > (1u << 22)) __trap(); } while ((v >> 2) != (epoch & 0x3fffffffu));
            asm volatile("st.shared.u8 [%0], %1;" :: "r"(sb + SM_CH + lt), "r"(v & 3u) : "memory");
        }
        cpa_wait_all();
        bar_sync(0, 512);
        const bool has_tile = (12 + w) < ntile;
        for (int s = 0; s < NSEG; s++) {
            const uint32_t par = s & 1;
            FRESH(lane);
            const int g = lane >> 2, t = lane & 3, lt = w * 32 + lane;
            if (s == 0) {
                mbar_wait(bar + B_HLO_FREE * 8, par);
                for (int k = lt; k < DM; k += 128) {
                    uint32_t v[4];
                    #pragma unroll
                    for (int i = 0; i < 4; i++) {
                        uint32_t lo = *(const uint16_t*)(mem0 + (2 * i) * DM + k), hi = *(const uint16_t*)(mem0 + (2 * i + 1) * DM + k);
                        v[i] = lo | (hi << 16);
                    }
                    asm volatile("st.shared.v4.u32 [%0], {%1,%2,%3,%4};" :: "r"(sb + SM_HB + k * 16), "r"(v[0]), "r"(v[1]), "r"(v[2]), "r"(v[3]) : "memory");
                }
            } else {
                const int sl = s & 3;
                const char* q = (const char*)g_buf2 + sl * 3 * 8192 + lt * 16;
                const uint32_t sm = selmask >> (sl * 3);
                const char* q0 = q + (sm & 1) * 4096;
                const char* q1 = q + 8192 + (sm & 2) * 2048;
                const char* q2 = q + 16384 + (sm & 4) * 1024;
                const uint32_t dst = sb + SM_HB + lt * 16;
                uint32_t guard = 0;
                mbar_wait(bar + B_HLO_FREE * 8, par);
                TR(10);
                while (true) {
                    const uint4 v0 = ld_relaxed4(q0), v1 = ld_relaxed4(q0 + 2048), v2 = ld_relaxed4(q1), v3 = ld_relaxed4(q1 + 2048), v4 = ld_relaxed4(q2);
                    sts4(dst, v0); sts4(dst + 2048, v1); sts4(dst + 4096, v2); sts4(dst + 6144, v3); sts4(dst + 8192, v4);
                    if (__all_sync(0xffffffffu, oks(v0) && oks(v1) && oks(v2) && oks(v3) && oks(v4))) break;
                    if (++guard > (1u << 22)) __trap();
                }
            }
            fence_async();
            __syncwarp();
            if (lane == 0) mbar_arrive(bar + B_MEM_FULL * 8);
            TR(0);
            if (w == 2) {
                mbar_wait(bar + B_MS * 8, par);
                TR(1);
                if (lane == 0) mbar_expect(bar + B_MS * 8, 3840);
                uint32_t pb[5];
                float sc[5][2];
                {
                    const uint32_t a = sb + SM_MS + lane * 8;
                    float2 u[5], v[5];
                    #pragma unroll
                    for (int j = 0; j < 5; j++) { u[j] = lds2f(a + j * 256); v[j] = lds2f(a + j * 256 + 1280); }
                    #pragma unroll
                    for (int j = 0; j < 5; j++) { sc[j][0] = u[j].x + v[j].x; sc[j][1] = u[j].y + v[j].y; }
                    #pragma unroll
                    for (int j = 0; j < 5; j++) u[j] = lds2f(a + j * 256 + 2560);
                    #pragma unroll
                    for (int j = 0; j < 5; j++) { sc[j][0] += u[j].x; sc[j][1] += u[j].y; }
                }
                softmax_core<5, false>(sc, g, t, pb);
                #pragma unroll
                for (int j = 0; j < 5; j++) sts1(sb + SM_PM + j * 128 + lane * 4, pb[j]);
                bar_arrive(5, 160);
                TR(2);
            }
            const uint32_t tag = (uint32_t)(s % 15) + 1u;
            if (s < NSEG - 1) {
                if (w == 3) {
                    const char* src = (const char*)g_ht + (size_t)(s + 1) * 40960;
                    mbar_wait(bar + B_HHI_FREE * 8, par);
                    if (lane == 0) {
                        mbar_expect(bar + B_HHI_FULL * 8, 28672);
                        bulk_g2s(sb + SM_HB + 12288, src + 12288, 28672, sb + SM_BAR + B_HHI_FULL * 8);
                    }
                    mbar_wait(bar + B_MEM_FREE * 8, par);
                    if (lane == 0) {
                        mbar_expect(bar + B_HLO_FULL * 8, 12288);
                        bulk_g2s(sb + SM_HB, src, 12288, sb + SM_BAR + B_HLO_FULL * 8);
                    }
                    __syncwarp();
                }
                if (has_tile) wo_phase<0, 4>(sb, warp, lane, nullptr, par, tag, tile0 + warp, h);
                TR(4);
                bar_sync(6, 512);
            }
            if (s < NSEG - 1) {
                { const uint32_t c0 = clk32(); while (clk32() - c0 < H1_DELAY); }
                if (b < 80) {
                    FRESH(lane);
                    const char* rin0 = (const char*)g_buf1 + (size_t)(b * 2) * 8192 + ((selmask >> 12) & 1) * 4096 + (lane >> 2) * 256 + w * 64 + (lane & 3) * 16;
                    const char* rin1 = (const char*)g_buf1 + (size_t)(b * 2 + 1) * 8192 + ((selmask >> 13) & 1) * 4096 + (lane >> 2) * 256 + w * 64 + (lane & 3) * 16;
                    const int col = b * 8 + 2 * w + ((lane >> 1) & 1), wd = 2 * (lane & 1) + (lane >> 4);
                    const int sl = (lane & 8) ? ((s + 3) & 3) : ((s + 1) & 3);
                    uint32_t* dst = g_buf2 + (sl * 3 + (col >> 8)) * 2048 + ((lane >> 2) & 1) * 1024 + (col & 255) * 4 + wd;
                    asm volatile("" : "+l"(dst));
                    uint4 v0, v1, v2, v3;
                    uint32_t guard = 0;
                    while (true) {
                        v0 = ld_relaxed4(rin0); v1 = ld_relaxed4(rin0 + 2048);
                        v2 = ld_relaxed4(rin1); v3 = ld_relaxed4(rin1 + 2048);
                        if (__all_sync(0xffffffffu, ok4(v0, tag) && ok4(v1, tag) && ok4(v2, tag) && ok4(v3, tag))) break;
                        if (++guard > (1u << 22)) __trap();
                    }
                    TR(11);
                    const float a0 = (uf(v0.x) + uf(v1.x)) + (uf(v2.x) + uf(v3.x)), a1 = (uf(v0.y) + uf(v1.y)) + (uf(v2.y) + uf(v3.y));
                    const float a2 = (uf(v0.z) + uf(v1.z)) + (uf(v2.z) + uf(v3.z)), a3 = (uf(v0.w) + uf(v1.w)) + (uf(v2.w) + uf(v3.w));
                    const bool u16 = lane & 16;
                    float m0 = (u16 ? a2 : a0) + __shfl_xor_sync(0xffffffffu, u16 ? a0 : a2, 16);
                    float m1 = (u16 ? a3 : a1) + __shfl_xor_sync(0xffffffffu, u16 ? a1 : a3, 16);
                    m0 += __shfl_xor_sync(0xffffffffu, m0, 8); m1 += __shfl_xor_sync(0xffffffffu, m1, 8);
                    m0 += __shfl_xor_sync(0xffffffffu, m0, 4); m1 += __shfl_xor_sync(0xffffffffu, m1, 4);
                    st_relaxed1(dst, (lane & 8) ? 0xFFFFFFFFu : pack2(m0, m1));
                    TR(12);
                }
            }
        }
    }
    cluster_sync();
}

constexpr int G_STAGES = 5;
constexpr int G_STAGE_BYTES = 32768;
constexpr int G_SMEM = G_STAGES * G_STAGE_BYTES + 1024 + 256;

__device__ __forceinline__ void tma2d(uint32_t dst, const CUtensorMap* map, int c0, int c1, uint32_t bar) {
    asm volatile("cp.async.bulk.tensor.2d.shared::cluster.global.mbarrier::complete_tx::bytes [%0], [%1, {%2, %3}], [%4];"
                 :: "r"(dst), "l"(map), "r"(c0), "r"(c1), "r"(bar) : "memory");
}
__device__ __forceinline__ void wg_ss128(float* d, uint64_t da, uint64_t db, int sc) {
    asm volatile("{\n\t.reg .pred p;\n\tsetp.ne.b32 p, %66, 0;\n\t"
        "wgmma.mma_async.sync.aligned.m64n128k16.f32.bf16.bf16 "
        "{%0,%1,%2,%3,%4,%5,%6,%7,%8,%9,%10,%11,%12,%13,%14,%15,%16,%17,%18,%19,%20,%21,%22,%23,%24,%25,%26,%27,%28,%29,%30,%31,"
        "%32,%33,%34,%35,%36,%37,%38,%39,%40,%41,%42,%43,%44,%45,%46,%47,%48,%49,%50,%51,%52,%53,%54,%55,%56,%57,%58,%59,%60,%61,%62,%63}, "
        "%64, %65, p, 1, 1, 0, 1;\n\t}"
        : "+f"(d[0]), "+f"(d[1]), "+f"(d[2]), "+f"(d[3]), "+f"(d[4]), "+f"(d[5]), "+f"(d[6]), "+f"(d[7]),
          "+f"(d[8]), "+f"(d[9]), "+f"(d[10]), "+f"(d[11]), "+f"(d[12]), "+f"(d[13]), "+f"(d[14]), "+f"(d[15]),
          "+f"(d[16]), "+f"(d[17]), "+f"(d[18]), "+f"(d[19]), "+f"(d[20]), "+f"(d[21]), "+f"(d[22]), "+f"(d[23]),
          "+f"(d[24]), "+f"(d[25]), "+f"(d[26]), "+f"(d[27]), "+f"(d[28]), "+f"(d[29]), "+f"(d[30]), "+f"(d[31]),
          "+f"(d[32]), "+f"(d[33]), "+f"(d[34]), "+f"(d[35]), "+f"(d[36]), "+f"(d[37]), "+f"(d[38]), "+f"(d[39]),
          "+f"(d[40]), "+f"(d[41]), "+f"(d[42]), "+f"(d[43]), "+f"(d[44]), "+f"(d[45]), "+f"(d[46]), "+f"(d[47]),
          "+f"(d[48]), "+f"(d[49]), "+f"(d[50]), "+f"(d[51]), "+f"(d[52]), "+f"(d[53]), "+f"(d[54]), "+f"(d[55]),
          "+f"(d[56]), "+f"(d[57]), "+f"(d[58]), "+f"(d[59]), "+f"(d[60]), "+f"(d[61]), "+f"(d[62]), "+f"(d[63])
        : "l"(da), "l"(db), "r"(sc));
}

template <int EPI>
__global__ void __launch_bounds__(384, 1)
k_gemm(const __grid_constant__ CUtensorMap mapA, const __grid_constant__ CUtensorMap mapB, int K,
       const bf16* __restrict__ xin, bf16* __restrict__ outp) {
    extern __shared__ uint8_t smem_raw[];
    const uint32_t sb = (smem_u32(smem_raw) + 1023u) & ~1023u;
    const uint32_t bars = sb + G_STAGES * G_STAGE_BYTES;
    const int tid = threadIdx.x, lane = tid & 31, wg = tid >> 7;
    const int n0 = blockIdx.x * 128, m0 = blockIdx.y * 128;
    const int nk = K / 64;
    if (tid == 0) {
        for (int i = 0; i < G_STAGES; i++) { mbar_init(bars + i * 8, 1); mbar_init(bars + 64 + i * 8, 8); }
        asm volatile("fence.mbarrier_init.release.cluster;" ::: "memory");
    }
    __syncthreads();
    if (wg == 0) {
        if (tid == 0) {
            for (int kb = 0; kb < nk; kb++) {
                const int st = kb % G_STAGES;
                if (kb >= G_STAGES) mbar_wait(bars + 64 + st * 8, ((kb / G_STAGES) - 1) & 1);
                const uint32_t a = sb + st * G_STAGE_BYTES;
                mbar_expect(bars + st * 8, G_STAGE_BYTES);
                tma2d(a, &mapA, kb * 64, m0, bars + st * 8);
                tma2d(a + 16384, &mapB, n0, kb * 64, bars + st * 8);
                tma2d(a + 16384 + 8192, &mapB, n0 + 64, kb * 64, bars + st * 8);
            }
        }
    } else {
        float d[64];
        #pragma unroll
        for (int i = 0; i < 64; i++) d[i] = 0.f;
        const int cw = wg - 1;
        for (int kb = 0; kb < nk; kb++) {
            const int st = kb % G_STAGES;
            mbar_wait(bars + st * 8, (kb / G_STAGES) & 1);
            const uint32_t a = sb + st * G_STAGE_BYTES;
            const uint64_t da = make_desc(a + cw * 8192, 16, 1024, 1);
            const uint64_t db = make_desc(a + 16384, 8192, 1024, 1);
            wg_fence();
            #pragma unroll
            for (int k = 0; k < 4; k++) wg_ss128(d, da + (uint64_t)(k * 2), db + (uint64_t)(k * 128), 1);
            wg_commit();
            if (kb > 0) {
                wg_wait<1>();
                if (lane == 0) mbar_arrive(bars + 64 + ((kb - 1) % G_STAGES) * 8);
            }
        }
        wg_wait<0>();
        const int g = lane >> 2, t = lane & 3, w = (tid >> 5) & 3;
        const int ldo = EPI == 1 ? FF : DM;
        #pragma unroll
        for (int hf = 0; hf < 2; hf++) {
            const int row = m0 + cw * 64 + w * 16 + g + 8 * hf;
            #pragma unroll
            for (int j = 0; j < 16; j++) {
                const int col = n0 + j * 8 + 2 * t;
                float a0 = bfr(d[4 * j + 2 * hf]), a1 = bfr(d[4 * j + 2 * hf + 1]);
                uint32_t o;
                if (EPI == 1) {
                    o = pack2(a0 / (1.0f + __expf(-a0)), a1 / (1.0f + __expf(-a1)));
                } else {
                    const float2 gm = *(const float2*)(g_mod + (EPI == 0 ? 2 : 5) * DM + col);
                    const uint32_t xv = *(const uint32_t*)(xin + (size_t)row * DM + col);
                    o = pack2(bflo(xv) + bfr(gm.x * a0), bfhi(xv) + bfr(gm.y * a1));
                }
                *(uint32_t*)(outp + (size_t)row * ldo + col) = o;
            }
        }
    }
}

typedef CUresult (*EncodeFn)(CUtensorMap*, CUtensorMapDataType, cuuint32_t, void*, const cuuint64_t*, const cuuint64_t*,
                             const cuuint32_t*, const cuuint32_t*, CUtensorMapInterleave, CUtensorMapSwizzle,
                             CUtensorMapL2promotion, CUtensorMapFloatOOBfill);

static void make_map(EncodeFn fn, CUtensorMap* m, const void* ptr, uint64_t inner, uint64_t outer, uint32_t bi, uint32_t bo) {
    cuuint64_t dims[2] = {inner, outer};
    cuuint64_t strides[1] = {inner * 2};
    cuuint32_t box[2] = {bi, bo};
    cuuint32_t es[2] = {1, 1};
    fn(m, CU_TENSOR_MAP_DATA_TYPE_BFLOAT16, 2, (void*)ptr, dims, strides, box, es, CU_TENSOR_MAP_INTERLEAVE_NONE,
       CU_TENSOR_MAP_SWIZZLE_128B, CU_TENSOR_MAP_L2_PROMOTION_L2_256B, CU_TENSOR_MAP_FLOAT_OOB_FILL_NONE);
}

extern "C" void kernel_launch(void* const* d_in, const int* in_sizes, int n_in, void* d_out, int out_size) {
    const bf16* x = (const bf16*)d_in[0];
    const bf16* mem0 = (const bf16*)d_in[1];
    const bf16* Wq = (const bf16*)d_in[2];
    const bf16* Wk = (const bf16*)d_in[3];
    const bf16* Wv = (const bf16*)d_in[4];
    const bf16* Wo = (const bf16*)d_in[5];
    const bf16* w1 = (const bf16*)d_in[8];
    const bf16* w2 = (const bf16*)d_in[9];
    const bf16* c = (const bf16*)d_in[10];
    const bf16* wmod = (const bf16*)d_in[11];
    bf16* out = (bf16*)d_out;

    static EncodeFn enc = nullptr;
    static void *p_ox, *p_x1, *p_h2, *p_act;
    if (!enc) {
        cudaDriverEntryPointQueryResult qr;
        void* f = nullptr;
        cudaGetDriverEntryPoint("cuTensorMapEncodeTiled", &f, cudaEnableDefault, &qr);
        enc = (EncodeFn)f;
        cudaGetSymbolAddress(&p_ox, g_ox);
        cudaGetSymbolAddress(&p_x1, g_x1);
        cudaGetSymbolAddress(&p_h2, g_h2);
        cudaGetSymbolAddress(&p_act, g_act);
        cudaFuncSetAttribute(k_rec, cudaFuncAttributeMaxDynamicSharedMemorySize, SM_TOTAL);
        cudaFuncSetAttribute(k_gemm<0>, cudaFuncAttributeMaxDynamicSharedMemorySize, G_SMEM);
        cudaFuncSetAttribute(k_gemm<1>, cudaFuncAttributeMaxDynamicSharedMemorySize, G_SMEM);
        cudaFuncSetAttribute(k_gemm<2>, cudaFuncAttributeMaxDynamicSharedMemorySize, G_SMEM);
    }
    CUtensorMap mOx, mWo, mH2, mW1, mAct, mW2;
    make_map(enc, &mOx, p_ox, HD, SEQ, 64, 128);
    make_map(enc, &mWo, Wo, DM, HD, 64, 64);
    make_map(enc, &mH2, p_h2, DM, SEQ, 64, 128);
    make_map(enc, &mW1, w1, FF, DM, 64, 64);
    make_map(enc, &mAct, p_act, FF, SEQ, 64, 128);
    make_map(enc, &mW2, w2, DM, FF, 64, 64);

    cudaStream_t st = cudaStreamPerThread;
    k_mod<<<60, 256, 0, st>>>(c, wmod);
    k_ln<0><<<SEQ / 8, 256, 0, st>>>(x);
    {
        cudaLaunchConfig_t cfg = {};
        cfg.gridDim = dim3(96); cfg.blockDim = dim3(512); cfg.dynamicSmemBytes = SM_TOTAL; cfg.stream = st;
        cudaLaunchAttribute at[1];
        at[0].id = cudaLaunchAttributeClusterDimension;
        at[0].val.clusterDim.x = 3; at[0].val.clusterDim.y = 1; at[0].val.clusterDim.z = 1;
        cfg.attrs = at; cfg.numAttrs = 1;
        cudaLaunchKernelEx(&cfg, k_rec, mem0, Wq, Wk, Wv, Wo);
    }
    k_gemm<0><<<dim3(5, 16), 384, G_SMEM, st>>>(mOx, mWo, HD, x, (bf16*)p_x1);
    k_ln<1><<<SEQ / 8, 256, 0, st>>>(nullptr);
    k_gemm<1><<<dim3(12, 16), 384, G_SMEM, st>>>(mH2, mW1, DM, nullptr, (bf16*)p_act);
    k_gemm<2><<<dim3(5, 16), 384, G_SMEM, st>>>(mAct, mW2, FF, (const bf16*)p_x1, out);
}
```

```cpp
#include <cuda_runtime.h>
#include <cuda_bf16.h>
#include <cuda.h>
#include <stdint.h>

typedef __nv_bfloat16 bf16;
#define VX_THROTTLE 1
#define H1_DELAY 400
#define H1_BACK 0
#define VM_THROTTLE 1
#define SIDE_CTAS 132

constexpr int SEQ = 2048, DM = 640, NH = 32, DH = 192, NSEG = 64, FF = 1536, HD = NH * DH;

__device__ __align__(128) float g_mod[6 * DM];
__device__ __align__(1024) bf16 g_ht[(size_t)SEQ * DM];
__device__ __align__(1024) bf16 g_ox[(size_t)SEQ * HD];
__device__ __align__(1024) bf16 g_x1[(size_t)SEQ * DM];
__device__ __align__(1024) bf16 g_h2[(size_t)SEQ * DM];
__device__ __align__(1024) bf16 g_act[(size_t)SEQ * FF];
__device__ __align__(8192) uint32_t g_buf1[80 * 2 * 2048];
__device__ __align__(8192) uint32_t g_buf2[4 * 3 * 2048];
__device__ uint32_t g_choice[128];
__device__ uint32_t g_epoch;
__device__ uint32_t g_pflag[32];
enum { C_Q = 0, C_MOD = 1, C_REC = 2, C_G0 = 18, C_LN = 34, C_G1 = 50, C_G2 = 66, C_FIN = 82, C_NUM = 98 };
__device__ __align__(128) uint32_t g_cnt[C_NUM * 32];
constexpr int PRING = 4;
__device__ __align__(1024) float g_p0[(size_t)PRING * 6 * 128 * DM];
__device__ __align__(1024) float g_p2[(size_t)PRING * 6 * 128 * DM];
#define TR(k)

#define FRESH(x) asm volatile("" : "+r"(x))
__device__ __forceinline__ float bfr(float x) { return __bfloat162float(__float2bfloat16_rn(x)); }
__device__ __forceinline__ uint32_t pack2(float a, float b) {
    uint32_t r; asm("cvt.rn.bf16x2.f32 %0, %1, %2;" : "=r"(r) : "f"(b), "f"(a)); return r;
}
__device__ __forceinline__ float bflo(uint32_t v) { return __uint_as_float(v << 16); }
__device__ __forceinline__ float bfhi(uint32_t v) { return __uint_as_float(v & 0xffff0000u); }
__device__ __forceinline__ float ex2(float x) { float r; asm("ex2.approx.ftz.f32 %0, %1;" : "=f"(r) : "f"(x)); return r; }
__device__ __forceinline__ float rcpf(float x) { float r; asm("rcp.approx.ftz.f32 %0, %1;" : "=f"(r) : "f"(x)); return r; }
__device__ __forceinline__ void score2(float& a, float& b) {
    const float SCALE = 0.07216878364870322f;
    uint32_t u = pack2(a, b);
    u = pack2(bflo(u) * SCALE, bfhi(u) * SCALE);
    a = bflo(u); b = bfhi(u);
}
__device__ __forceinline__ uint32_t smem_u32(const void* p) { return (uint32_t)__cvta_generic_to_shared(p); }

__device__ __forceinline__ void mbar_init(uint32_t bar, uint32_t cnt) {
    asm volatile("mbarrier.init.shared::cta.b64 [%0], %1;" :: "r"(bar), "r"(cnt) : "memory");
}
__device__ __forceinline__ void mbar_arrive(uint32_t bar) {
    asm volatile("mbarrier.arrive.shared::cta.b64 _, [%0];" :: "r"(bar) : "memory");
}
__device__ __forceinline__ void mbar_expect(uint32_t bar, uint32_t bytes) {
    asm volatile("mbarrier.arrive.expect_tx.shared::cta.b64 _, [%0], %1;" :: "r"(bar), "r"(bytes) : "memory");
}
__device__ __forceinline__ bool mbar_try(uint32_t bar, uint32_t parity) {
    uint32_t ok;
    asm volatile("{\n\t.reg .pred p;\n\tmbarrier.try_wait.parity.shared::cta.b64 p, [%1], %2;\n\tselp.u32 %0, 1, 0, p;\n\t}"
                 : "=r"(ok) : "r"(bar), "r"(parity) : "memory");
    return ok != 0;
}
__device__ __forceinline__ bool mbar_try_cluster(uint32_t bar, uint32_t parity) {
    uint32_t ok;
    asm volatile("{\n\t.reg .pred p;\n\tmbarrier.try_wait.parity.acquire.cluster.shared::cta.b64 p, [%1], %2;\n\tselp.u32 %0, 1, 0, p;\n\t}"
                 : "=r"(ok) : "r"(bar), "r"(parity) : "memory");
    return ok != 0;
}
__device__ __forceinline__ void mbar_wait(uint32_t bar, uint32_t parity) {
    uint32_t guard = 0;
    while (!mbar_try(bar, parity)) { if (++guard > (1u << 22)) __trap(); }
}
__device__ __forceinline__ void mbar_wait_cluster(uint32_t bar, uint32_t parity) {
    uint32_t guard = 0;
    while (!mbar_try_cluster(bar, parity)) { if (++guard > (1u << 22)) __trap(); }
}
__device__ __forceinline__ void bar_sync(int id, int n) { asm volatile("bar.sync %0, %1;" :: "r"(id), "r"(n) : "memory"); }
__device__ __forceinline__ void bar_arrive(int id, int n) { asm volatile("bar.arrive %0, %1;" :: "r"(id), "r"(n) : "memory"); }
__device__ __forceinline__ void sts1(uint32_t a, uint32_t v) { asm volatile("st.shared.u32 [%0], %1;" :: "r"(a), "r"(v) : "memory"); }
__device__ __forceinline__ uint32_t lds1(uint32_t a) { uint32_t v; asm volatile("ld.shared.u32 %0, [%1];" : "=r"(v) : "r"(a) : "memory"); return v; }
__device__ __forceinline__ void fence_async() { asm volatile("fence.proxy.async.shared::cta;" ::: "memory"); }
__device__ __forceinline__ void cluster_sync() {
    asm volatile("barrier.cluster.arrive.release.aligned;\n\tbarrier.cluster.wait.acquire.aligned;" ::: "memory");
}
__device__ __forceinline__ uint32_t mapa(uint32_t a, uint32_t rank) {
    uint32_t r; asm("mapa.shared::cluster.u32 %0, %1, %2;" : "=r"(r) : "r"(a), "r"(rank)); return r;
}
__device__ __forceinline__ void st_async1(uint32_t a, uint32_t v, uint32_t bar) {
    asm volatile("st.async.weak.shared::cluster.mbarrier::complete_tx::bytes.b32 [%0], %1, [%2];" :: "r"(a), "r"(v), "r"(bar) : "memory");
}
__device__ __forceinline__ void st_async2(uint32_t a, float x, float y, uint32_t bar) {
    asm volatile("st.async.weak.shared::cluster.mbarrier::complete_tx::bytes.v2.f32 [%0], {%1,%2}, [%3];" :: "r"(a), "f"(x), "f"(y), "r"(bar) : "memory");
}
__device__ __forceinline__ void st_async4(uint32_t a, const float* c, uint32_t bar) {
    asm volatile("st.async.weak.shared::cluster.mbarrier::complete_tx::bytes.v4.f32 [%0], {%1,%2,%3,%4}, [%5];"
                 :: "r"(a), "f"(c[0]), "f"(c[1]), "f"(c[2]), "f"(c[3]), "r"(bar) : "memory");
}
__device__ __forceinline__ void bulk_g2s(uint32_t dst, const void* src, uint32_t bytes, uint32_t bar) {
    asm volatile("cp.async.bulk.shared::cluster.global.mbarrier::complete_tx::bytes [%0], [%1], %2, [%3];"
                 :: "r"(dst), "l"(src), "r"(bytes), "r"(bar) : "memory");
}
__device__ __forceinline__ void cpa16(uint32_t s, const void* g) {
    asm volatile("cp.async.cg.shared.global [%0], [%1], 16;" :: "r"(s), "l"(g) : "memory");
}
__device__ __forceinline__ void cpa_wait_all() { asm volatile("cp.async.wait_all;" ::: "memory"); }
__device__ __forceinline__ void ldsm4(uint32_t* r, uint32_t a) {
    asm volatile("ldmatrix.sync.aligned.m8n8.x4.shared.b16 {%0,%1,%2,%3}, [%4];" : "=r"(r[0]), "=r"(r[1]), "=r"(r[2]), "=r"(r[3]) : "r"(a) : "memory");
}
__device__ __forceinline__ void ldsm4t(uint32_t* r, uint32_t a) {
    asm volatile("ldmatrix.sync.aligned.m8n8.x4.trans.shared.b16 {%0,%1,%2,%3}, [%4];" : "=r"(r[0]), "=r"(r[1]), "=r"(r[2]), "=r"(r[3]) : "r"(a) : "memory");
}
__device__ __forceinline__ void stsm2t(uint32_t a, uint32_t r0, uint32_t r1) {
    asm volatile("stmatrix.sync.aligned.m8n8.x2.trans.shared.b16 [%0], {%1,%2};" :: "r"(a), "r"(r0), "r"(r1) : "memory");
}
__device__ __forceinline__ void stsm4t(uint32_t a, uint32_t r0, uint32_t r1, uint32_t r2, uint32_t r3) {
    asm volatile("stmatrix.sync.aligned.m8n8.x4.trans.shared.b16 [%0], {%1,%2,%3,%4};" :: "r"(a), "r"(r0), "r"(r1), "r"(r2), "r"(r3) : "memory");
}
__device__ __forceinline__ uint32_t movm(uint32_t v) {
    uint32_t r; asm volatile("movmatrix.sync.aligned.m8n8.trans.b16 %0, %1;" : "=r"(r) : "r"(v)); return r;
}
__device__ __forceinline__ void mma16(float* c, uint32_t a0, uint32_t a1, uint32_t a2, uint32_t a3, uint32_t b0, uint32_t b1) {
    asm volatile("mma.sync.aligned.m16n8k16.row.col.f32.bf16.bf16.f32 {%0,%1,%2,%3}, {%4,%5,%6,%7}, {%8,%9}, {%0,%1,%2,%3};"
                 : "+f"(c[0]), "+f"(c[1]), "+f"(c[2]), "+f"(c[3]) : "r"(a0), "r"(a1), "r"(a2), "r"(a3), "r"(b0), "r"(b1));
}
__device__ __forceinline__ void mma8(float* c, uint32_t a0, uint32_t a1, uint32_t b0) {
    asm volatile("mma.sync.aligned.m16n8k8.row.col.f32.bf16.bf16.f32 {%0,%1,%2,%3}, {%4,%5}, {%6}, {%0,%1,%2,%3};"
                 : "+f"(c[0]), "+f"(c[1]), "+f"(c[2]), "+f"(c[3]) : "r"(a0), "r"(a1), "r"(b0));
}
__host__ __device__ constexpr uint64_t make_desc(uint32_t saddr, uint32_t lbo, uint32_t sbo, uint32_t layout) {
    return (uint64_t)((saddr & 0x3FFFF) >> 4) | ((uint64_t)(lbo >> 4) << 16) | ((uint64_t)(sbo >> 4) << 32) | ((uint64_t)layout << 62);
}
__device__ __forceinline__ void wg_fence() { asm volatile("wgmma.fence.sync.aligned;" ::: "memory"); }
__device__ __forceinline__ void wg_commit() { asm volatile("wgmma.commit_group.sync.aligned;" ::: "memory"); }
template <int N> __device__ __forceinline__ void wg_wait() { asm volatile("wgmma.wait_group.sync.aligned %0;" :: "n"(N) : "memory"); }

#define D16(C) C(d[0]), C(d[1]), C(d[2]), C(d[3]), C(d[4]), C(d[5]), C(d[6]), C(d[7]), \
               C(d[8]), C(d[9]), C(d[10]), C(d[11]), C(d[12]), C(d[13]), C(d[14]), C(d[15])
#define DREG16 "{%0,%1,%2,%3,%4,%5,%6,%7,%8,%9,%10,%11,%12,%13,%14,%15}"
__device__ __forceinline__ void wg_rs32(float* d, const uint32_t* a, uint64_t db, bool acc) {
    if (acc)
        asm volatile("wgmma.mma_async.sync.aligned.m64n32k16.f32.bf16.bf16 " DREG16 ", {%16,%17,%18,%19}, %20, 1, 1, 1, 0;"
            : D16("+f") : "r"(a[0]), "r"(a[1]), "r"(a[2]), "r"(a[3]), "l"(db));
    else
        asm volatile("wgmma.mma_async.sync.aligned.m64n32k16.f32.bf16.bf16 " DREG16 ", {%16,%17,%18,%19}, %20, 0, 1, 1, 0;"
            : D16("=f") : "r"(a[0]), "r"(a[1]), "r"(a[2]), "r"(a[3]), "l"(db));
}
__device__ __forceinline__ void wg_ss32(float* d, uint64_t da, uint64_t db, bool acc) {
    if (acc)
        asm volatile("wgmma.mma_async.sync.aligned.m64n32k16.f32.bf16.bf16 " DREG16 ", %16, %17, 1, 1, 1, 1, 0;"
            : D16("+f") : "l"(da), "l"(db));
    else
        asm volatile("wgmma.mma_async.sync.aligned.m64n32k16.f32.bf16.bf16 " DREG16 ", %16, %17, 0, 1, 1, 1, 0;"
            : D16("=f") : "l"(da), "l"(db));
}
__device__ __forceinline__ void wg_ss8(float* d, uint64_t da, uint64_t db, bool acc) {
    if (acc)
        asm volatile("wgmma.mma_async.sync.aligned.m64n8k16.f32.bf16.bf16 {%0,%1,%2,%3}, %4, %5, 1, 1, 1, 1, 1;"
            : "+f"(d[0]), "+f"(d[1]), "+f"(d[2]), "+f"(d[3]) : "l"(da), "l"(db));
    else
        asm volatile("wgmma.mma_async.sync.aligned.m64n8k16.f32.bf16.bf16 {%0,%1,%2,%3}, %4, %5, 0, 1, 1, 1, 1;"
            : "=f"(d[0]), "=f"(d[1]), "=f"(d[2]), "=f"(d[3]) : "l"(da), "l"(db));
}
template <int OFF> __device__ __forceinline__ void ldsm4t_i(uint32_t* r, uint32_t a) {
    asm volatile("ldmatrix.sync.aligned.m8n8.x4.trans.shared.b16 {%0,%1,%2,%3}, [%4+%5];"
                 : "=r"(r[0]), "=r"(r[1]), "=r"(r[2]), "=r"(r[3]) : "r"(a), "n"(OFF) : "memory");
}

__device__ __forceinline__ uint4 ld_relaxed4(const void* p) {
    uint4 v;
    asm volatile("ld.relaxed.gpu.global.v4.u32 {%0,%1,%2,%3}, [%4];" : "=r"(v.x), "=r"(v.y), "=r"(v.z), "=r"(v.w) : "l"(p) : "memory");
    return v;
}
__device__ __forceinline__ void st_relaxed2(void* p, uint32_t a, uint32_t b) {
    asm volatile("st.relaxed.gpu.global.v2.u32 [%0], {%1,%2};" :: "l"(p), "r"(a), "r"(b) : "memory");
}
__device__ __forceinline__ void st_relaxed2_off(void* base, uint32_t off, uint32_t a, uint32_t b) {
    asm volatile("{\n\t.reg .u64 ad;\n\tcvt.u64.u32 ad, %1;\n\tadd.u64 ad, ad, %0;\n\tst.relaxed.gpu.global.v2.u32 [ad], {%2,%3};\n\t}"
                 :: "l"(base), "r"(off), "r"(a), "r"(b) : "memory");
}
__device__ __forceinline__ void st_relaxed1(void* p, uint32_t a) {
    asm volatile("st.relaxed.gpu.global.u32 [%0], %1;" :: "l"(p), "r"(a) : "memory");
}
__device__ __forceinline__ uint32_t ld_acquire1(const uint32_t* p) {
    uint32_t v; asm volatile("ld.acquire.gpu.global.u32 %0, [%1];" : "=r"(v) : "l"(p) : "memory"); return v;
}
__device__ __forceinline__ void st_release1(uint32_t* p, uint32_t a) {
    asm volatile("st.release.gpu.global.u32 [%0], %1;" :: "l"(p), "r"(a) : "memory");
}
__device__ __forceinline__ uint4 lds4(uint32_t s) {
    uint4 v; asm volatile("ld.shared.v4.u32 {%0,%1,%2,%3}, [%4];" : "=r"(v.x), "=r"(v.y), "=r"(v.z), "=r"(v.w) : "r"(s) : "memory"); return v;
}
__device__ __forceinline__ void sts4(uint32_t s, const uint4& v) {
    asm volatile("st.shared.v4.u32 [%0], {%1,%2,%3,%4};" :: "r"(s), "r"(v.x), "r"(v.y), "r"(v.z), "r"(v.w) : "memory");
}
__device__ __forceinline__ float4 lds4f(uint32_t s) {
    float4 v; asm volatile("ld.shared.v4.f32 {%0,%1,%2,%3}, [%4];" : "=f"(v.x), "=f"(v.y), "=f"(v.z), "=f"(v.w) : "r"(s) : "memory"); return v;
}
__device__ __forceinline__ uint2 lds2(uint32_t s) {
    uint2 v; asm volatile("ld.shared.v2.u32 {%0,%1}, [%2];" : "=r"(v.x), "=r"(v.y) : "r"(s) : "memory"); return v;
}
__device__ __forceinline__ float2 lds2f(uint32_t s) {
    float2 v; asm volatile("ld.shared.v2.f32 {%0,%1}, [%2];" : "=f"(v.x), "=f"(v.y) : "r"(s) : "memory"); return v;
}
__device__ __forceinline__ uint32_t clk32() { uint32_t c; asm volatile("mov.u32 %0, %%clock;" : "=r"(c) :: "memory"); return c; }
__device__ __forceinline__ uint32_t tagw(float v, uint32_t tag) { return ((__float_as_uint(v) + 8u) & ~15u) | tag; }
__device__ __forceinline__ bool ok4(const uint4& v, uint32_t tag) { return (((v.x ^ tag) | (v.y ^ tag) | (v.z ^ tag) | (v.w ^ tag)) & 15u) == 0; }
__device__ __forceinline__ bool oks(const uint4& v) { return v.x != 0xFFFFFFFFu && v.y != 0xFFFFFFFFu && v.z != 0xFFFFFFFFu && v.w != 0xFFFFFFFFu; }
__device__ __forceinline__ float uf(uint32_t x) { return __uint_as_float(x & ~15u); }

template <int NT, int BAR>
__device__ __forceinline__ void mod_chunk(const bf16* __restrict__ c, const bf16* __restrict__ wmod, int col0, int tid, float* red) {
    constexpr int RG = NT / 8, NP = DM / RG;
    const int cc = tid & 7, rg = tid >> 3;
    uint4 w[NP];
    #pragma unroll
    for (int i = 0; i < NP; i++) w[i] = __ldg((const uint4*)(wmod + (size_t)(rg + i * RG) * (6 * DM) + col0 + cc * 8));
    float a[8];
    #pragma unroll
    for (int j = 0; j < 8; j++) a[j] = 0.f;
    #pragma unroll
    for (int i = 0; i < NP; i++) {
        const float v = __bfloat162float(c[rg + i * RG]);
        const float sv = bfr(v / (1.0f + __expf(-v)));
        a[0] += sv * bflo(w[i].x); a[1] += sv * bfhi(w[i].x); a[2] += sv * bflo(w[i].y); a[3] += sv * bfhi(w[i].y);
        a[4] += sv * bflo(w[i].z); a[5] += sv * bfhi(w[i].z); a[6] += sv * bflo(w[i].w); a[7] += sv * bfhi(w[i].w);
    }
    #pragma unroll
    for (int j = 0; j < 8; j++) {
        a[j] += __shfl_xor_sync(0xffffffffu, a[j], 8);
        a[j] += __shfl_xor_sync(0xffffffffu, a[j], 16);
    }
    if ((tid & 31) < 8) {
        float* d = red + (tid >> 5) * 64 + cc * 8;
        *(float4*)d = make_float4(a[0], a[1], a[2], a[3]);
        *(float4*)(d + 4) = make_float4(a[4], a[5], a[6], a[7]);
    }
    bar_sync(BAR, NT);
    if (tid < 64) {
        float s = 0.f;
        #pragma unroll
        for (int i = 0; i < NT / 32; i++) s += red[i * 64 + tid];
        g_mod[col0 + tid] = bfr(s);
    }
}

__device__ __forceinline__ void ln_stats(const float (*v)[4], float& mb, float& sd) {
    float s = 0.f;
    #pragma unroll
    for (int i = 0; i < 5; i++) s += (v[i][0] + v[i][1]) + (v[i][2] + v[i][3]);
    #pragma unroll
    for (int o = 16; o > 0; o >>= 1) s += __shfl_xor_sync(0xffffffffu, s, o);
    const float mean = s * (1.0f / DM);
    float q = 0.f;
    #pragma unroll
    for (int i = 0; i < 5; i++) {
        #pragma unroll
        for (int j = 0; j < 4; j++) { const float d = v[i][j] - mean; q += d * d; }
    }
    #pragma unroll
    for (int o = 16; o > 0; o >>= 1) q += __shfl_xor_sync(0xffffffffu, q, o);
    mb = bfr(mean);
    const float var = bfr(q * (1.0f / DM));
    sd = bfr(sqrtf(bfr(var + 1e-5f)));
}
__device__ __forceinline__ uint2 ln_apply(const float* v, float mb, float sd, const float4& sc, const float4& sh) {
    const float o0 = bfr(bfr(bfr(v[0] - mb) / sd) * bfr(1.0f + sc.x)) + sh.x;
    const float o1 = bfr(bfr(bfr(v[1] - mb) / sd) * bfr(1.0f + sc.y)) + sh.y;
    const float o2 = bfr(bfr(bfr(v[2] - mb) / sd) * bfr(1.0f + sc.z)) + sh.z;
    const float o3 = bfr(bfr(bfr(v[3] - mb) / sd) * bfr(1.0f + sc.w)) + sh.w;
    return make_uint2(pack2(o0, o1), pack2(o2, o3));
}

constexpr int PRE_CTAS = 32;
__global__ void __launch_bounds__(1024, 1) k_pre(const bf16* __restrict__ c, const bf16* __restrict__ wmod, const bf16* __restrict__ xin) {
    __shared__ __align__(16) float red[32 * 64];
    asm volatile("griddepcontrol.launch_dependents;" ::: "memory");
    const int tid = threadIdx.x, lane = tid & 31, warp = tid >> 5;
    const uint32_t tag = *(volatile uint32_t*)&g_epoch + 1u;
    constexpr int RPW = SEQ / PRE_CTAS / 32;
    uint2 xr[RPW][5];
    #pragma unroll
    for (int r = 0; r < RPW; r++) {
        const int row = (r * PRE_CTAS + blockIdx.x) * 32 + warp;
        #pragma unroll
        for (int i = 0; i < 5; i++) xr[r][i] = __ldg((const uint2*)(xin + (size_t)row * DM + (i * 32 + lane) * 4));
    }
    if (blockIdx.x < 20) {
        mod_chunk<1024, 1>(c, wmod, blockIdx.x * 64, tid, red);
        if (tid < 64) {
            bar_sync(2, 64);
            if (tid == 0) { __threadfence(); st_release1(&g_pflag[blockIdx.x], tag); }
        }
    } else if (blockIdx.x == PRE_CTAS - 1) {
        if (tid < C_NUM) g_cnt[tid * 32] = 0u;
    }
    float mb[RPW], sd[RPW];
    #pragma unroll
    for (int r = 0; r < RPW; r++) {
        float v[5][4];
        #pragma unroll
        for (int i = 0; i < 5; i++) { v[i][0] = bflo(xr[r][i].x); v[i][1] = bfhi(xr[r][i].x); v[i][2] = bflo(xr[r][i].y); v[i][3] = bfhi(xr[r][i].y); }
        ln_stats(v, mb[r], sd[r]);
    }
    if (warp == 0) {
        uint32_t guard = 0;
        while (true) {
            const uint32_t v = lane < 20 ? ld_acquire1(&g_pflag[lane]) : tag;
            if (__all_sync(0xffffffffu, v == tag)) break;
            if (++guard > (1u << 22)) __trap();
        }
    }
    __syncthreads();
    #pragma unroll
    for (int i = 0; i < 5; i++) {
        const int col = (i * 32 + lane) * 4;
        const float4 sh = __ldcg((const float4*)(g_mod + col)), sc = __ldcg((const float4*)(g_mod + DM + col));
        #pragma unroll
        for (int r = 0; r < RPW; r++) {
            const float v[4] = {bflo(xr[r][i].x), bfhi(xr[r][i].x), bflo(xr[r][i].y), bfhi(xr[r][i].y)};
            const int seg = r * PRE_CTAS + blockIdx.x, blk = col >> 6, cc = (col >> 3) & 7;
            *(uint2*)(g_ht + (size_t)seg * 20480 + blk * 2048 + warp * 64 + ((cc ^ (warp & 7)) << 3) + (col & 4)) = ln_apply(v, mb[r], sd[r], sc, sh);
        }
    }
}

constexpr int SM_WV = 0;
constexpr int SM_HB = 81920;
constexpr int SM_WO = SM_HB + 40960;
constexpr int SM_QX = SM_WO + 77824;
constexpr int SM_KS = SM_QX + 4096;
constexpr int SM_QM = SM_KS + 5120;
constexpr int SM_XS = SM_QM + 1024;
constexpr int SM_MS = SM_XS + 12288;
constexpr int SM_OS = SM_MS + 3840;
constexpr int SM_PM = SM_OS + 3072;
constexpr int SM_BAR = SM_PM + 640;
constexpr int SM_CH = SM_BAR + 128;
constexpr int SM_TOTAL = SM_CH + 128;
static_assert(SM_TOTAL <= 232448, "smem");

enum { B_MEM_FULL = 0, B_MEM_FREE, B_HLO_FULL, B_HHI_FULL, B_HLO_FREE, B_HHI_FREE, B_MS, B_O, B_XS, B_O1, B_XSFREE };

__device__ __forceinline__ int probe_blk(uint32_t* blk) {
    uint32_t t0 = 0xffffffffu, t1 = 0xffffffffu, acc = 0;
    for (int rep = 0; rep < 3; rep++) {
        #pragma unroll
        for (int pg = 0; pg < 2; pg++) {
            uint32_t c0 = clk32();
            uint32_t v = atomicOr(blk + pg * 1024 + acc, 0u);
            acc = (v == 0x12345678u) ? 1u : 0u;
            asm volatile("" :: "r"(acc) : "memory");
            uint32_t c1 = clk32() + acc;
            uint32_t d = c1 - c0;
            if (rep > 0) { if (pg == 0) t0 = min(t0, d); else t1 = min(t1, d); }
        }
    }
    return t1 < t0 ? 1 : 0;
}

__device__ __forceinline__ uint32_t wo_tile_off(int w) {
    if (w < 8) return w * 6144;
    if (w < 12) return 8 * 6144 + (w - 8) * 4096;
    return 8 * 6144 + 4 * 4096 + (w - 12) * 6144;
}

template <int NRES, int NPRE>
__device__ __forceinline__ void wo_phase(uint32_t sb, int w, int lane, const uint32_t (*res)[4], uint32_t parity,
                                         uint32_t tag, int tile, int h) {
    FRESH(lane);
    const int er = (lane & 7) + 8 * (lane >> 4);
    const uint32_t aaddr = sb + SM_WO + wo_tile_off(w) + er * 32 + ((((lane >> 3) & 1) ^ ((er >> 2) & 1)) << 4);
    const uint32_t baddr = sb + SM_OS + lane * 16;
    float c0[4] = {0.f, 0.f, 0.f, 0.f}, c1[4] = {0.f, 0.f, 0.f, 0.f};
    uint32_t pre[NPRE > 4 ? NPRE : 4][4];
    if (NPRE >= 4) {
        #pragma unroll
        for (int i = 0; i < 4; i++) ldsm4t(pre[i], aaddr + i * 512);
        mbar_wait(sb + SM_BAR + B_O1 * 8, parity);
        uint32_t b[2][4];
        ldsm4t(b[0], baddr);
        ldsm4t(b[1], baddr + 512);
        #pragma unroll
        for (int kp = 0; kp < 2; kp++) {
            mma16(c0, pre[2 * kp][0], pre[2 * kp][1], pre[2 * kp][2], pre[2 * kp][3], b[kp][0], b[kp][1]);
            mma16(c1, pre[2 * kp + 1][0], pre[2 * kp + 1][1], pre[2 * kp + 1][2], pre[2 * kp + 1][3], b[kp][2], b[kp][3]);
        }
    } else {
        #pragma unroll
        for (int i = 0; i < 2; i++) ldsm4t(pre[i], aaddr + i * 512);
        mbar_wait(sb + SM_BAR + B_O1 * 8, parity);
        #pragma unroll
        for (int kp = 0; kp < 2; kp++) {
            uint32_t b[4];
            ldsm4t(b, baddr + kp * 512);
            if (kp == 1) { ldsm4t(pre[0], aaddr + 2 * 512); ldsm4t(pre[1], aaddr + 3 * 512); }
            mma16(c0, pre[0][0], pre[0][1], pre[0][2], pre[0][3], b[0], b[1]);
            mma16(c1, pre[1][0], pre[1][1], pre[1][2], pre[1][3], b[2], b[3]);
        }
    }
    #pragma unroll
    for (int i = 0; i < NPRE; i++) ldsm4t(pre[i], aaddr + (4 + i) * 512);
    uint32_t off0, off1;
    {
        uint32_t ch;
        asm volatile("ld.shared.u16 %0, [%1];" : "=r"(ch) : "r"(sb + SM_CH + 2 * tile) : "memory");
        const int j = h >> 4;
        const uint32_t base = (uint32_t)((tile * 4 + j) * 8192 + (h & 15) * 256 + lane * 8);
        ch >>= j;
        off0 = base + (ch & 1) * 4096;
        off1 = base + 16384 + (ch & 256) * 16;
    }
    mbar_wait(sb + SM_BAR + B_O * 8, parity);
    if (NRES == 4) {
        uint32_t b[4][4];
        #pragma unroll
        for (int i = 0; i < 4; i++) ldsm4t(b[i], baddr + (2 + i) * 512);
        #pragma unroll
        for (int i = 0; i < 2; i++) {
            mma16(c0, res[2 * i][0], res[2 * i][1], res[2 * i][2], res[2 * i][3], b[i][0], b[i][1]);
            mma16(c1, res[2 * i + 1][0], res[2 * i + 1][1], res[2 * i + 1][2], res[2 * i + 1][3], b[i][2], b[i][3]);
        }
        #pragma unroll
        for (int i = 0; i < 2; i++) {
            mma16(c0, pre[2 * i][0], pre[2 * i][1], pre[2 * i][2], pre[2 * i][3], b[2 + i][0], b[2 + i][1]);
            mma16(c1, pre[2 * i + 1][0], pre[2 * i + 1][1], pre[2 * i + 1][2], pre[2 * i + 1][3], b[2 + i][2], b[2 + i][3]);
        }
    } else if (NPRE == 4) {
        uint32_t b[2][4];
        #pragma unroll
        for (int hh = 0; hh < 2; hh++) {
            ldsm4t(b[0], baddr + (2 + 2 * hh) * 512);
            ldsm4t(b[1], baddr + (3 + 2 * hh) * 512);
            if (hh) {
                #pragma unroll
                for (int i = 0; i < 4; i++) ldsm4t(pre[i], aaddr + (8 + i) * 512);
            }
            #pragma unroll
            for (int i = 0; i < 2; i++) {
                mma16(c0, pre[2 * i][0], pre[2 * i][1], pre[2 * i][2], pre[2 * i][3], b[i][0], b[i][1]);
                mma16(c1, pre[2 * i + 1][0], pre[2 * i + 1][1], pre[2 * i + 1][2], pre[2 * i + 1][3], b[i][2], b[i][3]);
            }
        }
    }
    st_relaxed2_off(g_buf1, off0, tagw(c0[0] + c1[0], tag), tagw(c0[1] + c1[1], tag));
    st_relaxed2_off(g_buf1, off1, tagw(c0[2] + c1[2], tag), tagw(c0[3] + c1[3], tag));
}

template <int NT, bool MASK>
__device__ __forceinline__ void softmax_core(float (*sc)[2], int g, int t, uint32_t* pb) {
    const float L2E = 1.4426950408889634f;
    #pragma unroll
    for (int j = 0; j < NT; j++) score2(sc[j][0], sc[j][1]);
    if (MASK) {
        const float NEG = -999292928.0f;
        if (2 * t > g) sc[NT - 1][0] = NEG;
        if (2 * t + 1 > g) sc[NT - 1][1] = NEG;
    }
    float m[NT];
    #pragma unroll
    for (int j = 0; j < NT; j++) m[j] = fmaxf(sc[j][0], sc[j][1]);
    float mx = m[0];
    #pragma unroll
    for (int j = 1; j < NT; j++) mx = fmaxf(mx, m[j]);
    mx = fmaxf(mx, __shfl_xor_sync(0xffffffffu, mx, 1));
    mx = fmaxf(mx, __shfl_xor_sync(0xffffffffu, mx, 2));
    float s0 = 0.f, s1 = 0.f;
    #pragma unroll
    for (int j = 0; j < NT; j++) {
        sc[j][0] = ex2((sc[j][0] - mx) * L2E); sc[j][1] = ex2((sc[j][1] - mx) * L2E);
        s0 += sc[j][0]; s1 += sc[j][1];
    }
    s0 += s1;
    s0 += __shfl_xor_sync(0xffffffffu, s0, 1);
    s0 += __shfl_xor_sync(0xffffffffu, s0, 2);
    const float iv = rcpf(s0);
    #pragma unroll
    for (int j = 0; j < NT; j++) pb[j] = pack2(sc[j][0] * iv, sc[j][1] * iv);
}
template <int NT>
__device__ __forceinline__ void xsoftmax(uint32_t a, int g, int t) {
    float sc[NT][2];
    #pragma unroll
    for (int j = 0; j < NT; j++) {
        float2 v0 = lds2f(a + j * 512), v1 = lds2f(a + j * 512 + 4096), v2 = lds2f(a + j * 512 + 8192);
        sc[j][0] = v0.x + v1.x + v2.x; sc[j][1] = v0.y + v1.y + v2.y;
    }
    uint32_t pb[NT];
    softmax_core<NT, true>(sc, g, t, pb);
    #pragma unroll
    for (int j = 0; j < NT; j += 2) {
        if (j + 1 < NT) asm volatile("st.shared.v2.u32 [%0], {%1,%2};" :: "r"(a + j * 512), "r"(pb[j]), "r"(pb[j + 1]) : "memory");
        else sts1(a + j * 512, pb[j]);
    }
}
template <int NJ>
__device__ __forceinline__ void xscores(uint32_t sb, int p, int mi, int j0, int lane) {
    FRESH(lane);
    const int r = lane & 7, cq = lane >> 3;
    const int qrow = mi * 16 + r + 8 * (cq & 1);
    uint32_t kb[NJ][8];
    float d[NJ][4];
    #pragma unroll
    for (int j = 0; j < NJ; j++) {
        ldsm4(kb[j], sb + SM_KS + ((j0 + j) * 8 + r) * 128 + ((cq ^ r) << 4));
        ldsm4(kb[j] + 4, sb + SM_KS + ((j0 + j) * 8 + r) * 128 + (((cq + 4) ^ r) << 4));
        d[j][0] = 0.f; d[j][1] = 0.f; d[j][2] = 0.f; d[j][3] = 0.f;
    }
    #pragma unroll
    for (int kt = 0; kt < 4; kt++) {
        uint32_t a[4];
        ldsm4(a, sb + SM_QX + qrow * 128 + (((2 * kt + (cq >> 1)) ^ r) << 4));
        #pragma unroll
        for (int j = 0; j < NJ; j++) mma16(d[j], a[0], a[1], a[2], a[3], kb[j][2 * kt], kb[j][2 * kt + 1]);
    }
    const uint32_t la = sb + SM_XS + p * 4096 + (mi * 3 + j0) * 512 + lane * 16;
    #pragma unroll
    for (int rk = 0; rk < 3; rk++) {
        const uint32_t ra = mapa(la, rk), rb = mapa(sb + SM_BAR + B_XS * 8, rk);
        #pragma unroll
        for (int j = 0; j < NJ; j++) st_async4(ra + j * 512, d[j], rb);
    }
}
__device__ __forceinline__ void mbar_arrive_remote(uint32_t bar) {
    asm volatile("mbarrier.arrive.relaxed.cluster.shared::cluster.b64 _, [%0];" :: "r"(bar) : "memory");
}

__device__ __forceinline__ void signal_cnt(int idx) {
    asm volatile("fence.proxy.async;\n\tfence.acq_rel.gpu;\n\tred.relaxed.gpu.global.add.u32 [%0], 1;" :: "l"(g_cnt + idx * 32) : "memory");
}

__global__ void __launch_bounds__(512, 1)
k_rec(const bf16* __restrict__ mem0, const bf16* __restrict__ Wq, const bf16* __restrict__ Wk,
      const bf16* __restrict__ Wv, const bf16* __restrict__ Wo) {
    extern __shared__ __align__(1024) uint8_t smem_raw[];
    constexpr uint32_t SBC = 1024;
    const uint32_t sb = smem_u32(smem_raw);
    if ((sb & 0xFFFFFFu) != SBC) __trap();
    int lane = __shfl_sync(0xffffffffu, threadIdx.x & 31, threadIdx.x & 31);
    const int warp = __shfl_sync(0xffffffffu, threadIdx.x >> 5, 0), wg = warp >> 2;
    const int tid = warp * 32 + lane;
    const int b = blockIdx.x, h = b / 3, p = b % 3;
    const int g = lane >> 2, t = lane & 3;
    const int tile0 = p == 0 ? 0 : (p == 1 ? 14 : 27);
    const int ntile = p == 0 ? 14 : 13;
    const uint32_t bar = sb + SM_BAR;

    if (tid == 0) {
        mbar_init(bar + B_MEM_FULL * 8, 4);
        mbar_init(bar + B_MEM_FREE * 8, 12);
        mbar_init(bar + B_HLO_FULL * 8, 1);
        mbar_init(bar + B_HHI_FULL * 8, 1);
        mbar_init(bar + B_HLO_FREE * 8, 12);
        mbar_init(bar + B_HHI_FREE * 8, 12);
        mbar_init(bar + B_MS * 8, 1);
        mbar_init(bar + B_O * 8, 1);
        mbar_init(bar + B_XS * 8, 1);
        mbar_init(bar + B_O1 * 8, 4);
        mbar_init(bar + B_XSFREE * 8, 12);
        asm volatile("fence.mbarrier_init.release.cluster;" ::: "memory");
        mbar_expect(bar + B_MS * 8, 3840);
        mbar_expect(bar + B_O * 8, 2048);
        mbar_expect(bar + B_XS * 8, 12288);
    }
    cluster_sync();

    if (wg < 2) {
        asm volatile("setmaxnreg.inc.sync.aligned.u32 200;");
        const int w = warp & 3;
        uint32_t wa[40][4];
        {
            const bf16* W = (wg == 0 ? Wq : Wk) + (size_t)h * DH + p * 64 + w * 16 + t * 4;
            #pragma unroll
            for (int kt = 0; kt < 40; kt++) {
                uint2 l1 = __ldg((const uint2*)(W + (size_t)(kt * 16 + g) * HD));
                uint2 l2 = __ldg((const uint2*)(W + (size_t)(kt * 16 + 8 + g) * HD));
                wa[kt][0] = l1.x; wa[kt][1] = l1.y; wa[kt][2] = l2.x; wa[kt][3] = l2.y;
            }
            #pragma unroll
            for (int kt = 0; kt < 40; kt++) {
                #pragma unroll
                for (int i = 0; i < 4; i++) wa[kt][i] = movm(wa[kt][i]);
            }
        }

        const uint32_t dstx = sb + (wg == 0 ? SM_QX : SM_KS + 1024);

        for (int s = -1; s < NSEG; s++) {
            const uint32_t par = s & 1;
            FRESH(lane);
            const int g = lane >> 2, t = lane & 3, tid = warp * 32 + lane;
            if (s >= 0) {
                mbar_wait(bar + B_MEM_FULL * 8, par);
                TR(0);
                float c[4][4];
                #pragma unroll
                for (int i = 0; i < 4; i++) { c[i][0] = 0.f; c[i][1] = 0.f; c[i][2] = 0.f; c[i][3] = 0.f; }
                uint32_t maddr = sb + lane * 16;
                asm volatile("" : "+r"(maddr));
                #pragma unroll
                for (int kp = 0; kp < 20; kp++) {
                    uint32_t bb[4];
                    ldsm4t(bb, maddr + (SM_HB + kp * 512));
                    mma16(c[(kp & 1) * 2], wa[2 * kp][0], wa[2 * kp][1], wa[2 * kp][2], wa[2 * kp][3], bb[0], bb[1]);
                    mma16(c[(kp & 1) * 2 + 1], wa[2 * kp + 1][0], wa[2 * kp + 1][1], wa[2 * kp + 1][2], wa[2 * kp + 1][3], bb[2], bb[3]);
                }
                {
                    const int tok = lane & 7, ch = 2 * w + ((lane >> 3) & 1);
                    stsm2t(sb + (wg == 0 ? SM_QM : SM_KS) + tok * 128 + ((ch ^ tok) << 4),
                           pack2((c[0][0] + c[1][0]) + (c[2][0] + c[3][0]), (c[0][1] + c[1][1]) + (c[2][1] + c[3][1])),
                           pack2((c[0][2] + c[1][2]) + (c[2][2] + c[3][2]), (c[0][3] + c[1][3]) + (c[2][3] + c[3][3])));
                }
                __syncwarp();
                if (lane == 0) mbar_arrive(bar + B_MEM_FREE * 8);
                TR(1);
                bar_sync(1, 256);
                if (warp < 5) {
                    const int r = lane & 7, cq = lane >> 3;
                    uint32_t a[8], kb[8];
                    ldsm4(a, sb + SM_QM + r * 128 + ((cq ^ r) << 4));
                    ldsm4(kb, sb + SM_KS + (warp * 8 + r) * 128 + ((cq ^ r) << 4));
                    ldsm4(a + 4, sb + SM_QM + r * 128 + (((cq + 4) ^ r) << 4));
                    ldsm4(kb + 4, sb + SM_KS + (warp * 8 + r) * 128 + (((cq + 4) ^ r) << 4));
                    float d0[4] = {0.f, 0.f, 0.f, 0.f}, d1[4] = {0.f, 0.f, 0.f, 0.f};
                    mma16(d0, a[0], 0u, a[1], 0u, kb[0], kb[1]);
                    mma16(d1, a[2], 0u, a[3], 0u, kb[2], kb[3]);
                    mma16(d0, a[4], 0u, a[5], 0u, kb[4], kb[5]);
                    mma16(d1, a[6], 0u, a[7], 0u, kb[6], kb[7]);
                    const uint32_t la = sb + SM_MS + p * 1280 + warp * 256 + lane * 8;
                    #pragma unroll
                    for (int rk = 0; rk < 3; rk++)
                        st_async2(mapa(la, rk), d0[0] + d1[0], d0[1] + d1[1], mapa(bar + B_MS * 8, rk));
                    bar_arrive(4, 352);
                } else if (warp < 7) {
                    xscores<1>(sb, p, warp - 5, 0, lane);
                    bar_arrive(4, 352);
                }
                TR(2);
                if (s < NSEG - 1) {
                    wo_phase<0, 4>(sb, warp, lane, nullptr, par, (uint32_t)(s % 15) + 1u, tile0 + warp, h);
                    TR(4);
                }
            }
            if (s < NSEG - 1) {
                FRESH(lane);
                const uint32_t hp = (s + 1) & 1;
                float d[16];
                const uint64_t db0 = make_desc(SBC + SM_HB, 16, 1024, 1);
                mbar_wait(bar + B_HHI_FULL * 8, hp);
                {
                    const int r = lane & 7, mq = lane >> 3;
                    const uint32_t ha = sb + SM_HB + 9 * 4096 + (8 * (mq >> 1) + r) * 128 + (((6 + (mq & 1)) ^ r) << 4);
                    uint32_t b0[4], b1[4];
                    ldsm4(b0, ha);
                    ldsm4(b1, ha + 2048);
                    #pragma unroll
                    for (int i = 0; i < 16; i++) d[i] = 0.f;
                    mma16(d + 0, wa[39][0], wa[39][1], wa[39][2], wa[39][3], b0[0], b0[1]);
                    mma16(d + 4, wa[39][0], wa[39][1], wa[39][2], wa[39][3], b0[2], b0[3]);
                    mma16(d + 8, wa[39][0], wa[39][1], wa[39][2], wa[39][3], b1[0], b1[1]);
                    mma16(d + 12, wa[39][0], wa[39][1], wa[39][2], wa[39][3], b1[2], b1[3]);
                    asm volatile("" : "+f"(d[0]), "+f"(d[4]), "+f"(d[8]), "+f"(d[12]) :: "memory");
                }
                if (s >= 0) bar_arrive(6, 512);
                mbar_wait(bar + B_HLO_FULL * 8, hp);
                bar_sync(9, 384);
                TR(6);
                wg_fence();
                #pragma unroll
                for (int kt = 0; kt < 12; kt++) wg_rs32(d, wa[kt], db0 + (uint64_t)(((kt >> 2) * 4096 + (kt & 3) * 32) >> 4), 1);
                wg_commit();
                #pragma unroll
                for (int kt = 12; kt < 39; kt++) wg_rs32(d, wa[kt], db0 + (uint64_t)(((kt >> 2) * 4096 + (kt & 3) * 32) >> 4), 1);
                wg_commit();
                wg_wait<1>();
                if (lane == 0) mbar_arrive(bar + B_HLO_FREE * 8);
                wg_wait<0>();
                if (lane == 0) mbar_arrive(bar + B_HHI_FREE * 8);
                TR(7);
                const int mi = lane >> 3, r = lane & 7;
                #pragma unroll
                for (int jj = 0; jj < 2; jj++) {
                    const int tok = 8 * (2 * jj + (mi >> 1)) + r, ch = 2 * w + (mi & 1);
                    stsm4t(dstx + tok * 128 + ((ch ^ r) << 4),
                           pack2(d[8 * jj + 0], d[8 * jj + 1]), pack2(d[8 * jj + 2], d[8 * jj + 3]),
                           pack2(d[8 * jj + 4], d[8 * jj + 5]), pack2(d[8 * jj + 6], d[8 * jj + 7]));
                }
                bar_arrive(8, 384);
                if (s < 0) { bar_sync(0, 512); asm volatile("griddepcontrol.launch_dependents;" ::: "memory"); }
            }
        }
    } else if (wg == 2) {
        asm volatile("setmaxnreg.dec.sync.aligned.u32 64;");
        const int w = warp & 3;
        {
            const int c = tid & 7;
            const bf16* src = Wv + (size_t)h * DH + p * 64 + c * 8;
            for (int k = (tid & 127) >> 3; k < DM; k += 16)
                cpa16(sb + SM_WV + k * 128 + ((c ^ (k & 7)) << 4), src + (size_t)k * HD);
        }
        uint32_t res[4][4];
        {
            const bf16* src = Wo + ((size_t)h * DH + ((p + 1) % 3) * 64) * DM + (tile0 + warp) * 16 + 2 * t;
            #pragma unroll
            for (int kt = 0; kt < 4; kt++) {
                res[kt][0] = __ldg((const uint32_t*)(src + (size_t)(kt * 16 + g) * DM));
                res[kt][1] = __ldg((const uint32_t*)(src + (size_t)(kt * 16 + g) * DM + 8));
                res[kt][2] = __ldg((const uint32_t*)(src + (size_t)(kt * 16 + 8 + g) * DM));
                res[kt][3] = __ldg((const uint32_t*)(src + (size_t)(kt * 16 + 8 + g) * DM + 8));
            }
            #pragma unroll
            for (int kt = 0; kt < 4; kt++) {
                #pragma unroll
                for (int i = 0; i < 4; i++) res[kt][i] = movm(res[kt][i]);
            }
        }
        cpa_wait_all();
        fence_async();
        bar_sync(2, 128);
        const uint64_t da0 = make_desc(SBC + SM_WV, 16, 1024, 1);
        uint32_t vx[8], vm0 = 0, vm1 = 0;
        #pragma unroll
        for (int i = 0; i < 8; i++) vx[i] = 0;

        for (int s = -1; s < NSEG; s++) {
            FRESH(lane);
            const int g = lane >> 2, t = lane & 3, tid = warp * 32 + lane;
            if (s >= 0) {
                const uint32_t par = s & 1;
                mbar_wait(bar + B_MEM_FULL * 8, par);
                bar_sync(4, 352);
                TR(0);
                float dv[4];
                {
                    const uint64_t dbm = make_desc(SBC + SM_HB, 128, 128, 0);
                    wg_fence();
                    #pragma unroll
                    for (int kt = 0; kt < 40; kt++) {
                        wg_ss8(dv, da0 + (uint64_t)(kt * 128), dbm + (uint64_t)(kt * 16), kt > 0);
                        wg_commit();
                        if (kt < 39) wg_wait<1>();
                    }
                    wg_commit();
                }
                TR(1);
                bar_sync(5, 160);
                TR(2);
                uint32_t pb[5];
                #pragma unroll
                for (int j = 0; j < 5; j++) pb[j] = lds1(sb + SM_PM + j * 128 + lane * 4);
                float o0[4] = {0.f, 0.f, 0.f, 0.f}, o1[4] = {0.f, 0.f, 0.f, 0.f}, o2[4] = {0.f, 0.f, 0.f, 0.f};
                wg_wait<0>();
                TR(3);
                mma16(o0, vx[0], vx[1], vx[2], vx[3], pb[1], pb[2]);
                mma16(o1, vx[4], vx[5], vx[6], vx[7], pb[3], pb[4]);
                vm0 = pack2(dv[0], dv[1]); vm1 = pack2(dv[2], dv[3]);
                mma8(o2, vm0, vm1, pb[0]);
                if (s < NSEG - 1) {
                    const uint32_t q0 = pack2(o0[0] + o1[0] + o2[0], o0[1] + o1[1] + o2[1]), q1 = pack2(o0[2] + o1[2] + o2[2], o0[3] + o1[3] + o2[3]);
                    const uint32_t la = sb + SM_OS + (w * 16 + g) * 16 + t * 4;
                    #pragma unroll
                    for (int i = 1; i < 3; i++) {
                        const uint32_t rk = (p + i) % 3;
                        const uint32_t ra = mapa(la + (3 - i) * 1024, rk), rb = mapa(bar + B_O * 8, rk);
                        st_async1(ra, q0, rb);
                        st_async1(ra + 128, q1, rb);
                    }
                    sts1(la, q0);
                    sts1(la + 128, q1);
                    __syncwarp();
                    if (lane == 0) { mbar_arrive(bar + B_O1 * 8); mbar_arrive(bar + B_MEM_FREE * 8); }
                }
                TR(5);
                if (s < NSEG - 1) {
                    wo_phase<4, 4>(sb, warp, lane, res, par, (uint32_t)(s % 15) + 1u, tile0 + warp, h);
                    TR(4);
                    if (tid == 256) mbar_expect(bar + B_O * 8, 2048);
                }
                if (s < NSEG - 1) bar_sync(6, 512);
            }
            uint32_t vn[8];
            #pragma unroll
            for (int i = 0; i < 8; i++) vn[i] = 0;
            if (s < NSEG - 1) {
            float d[16];
            const uint32_t hp = (s + 1) & 1;
            const uint64_t db0 = make_desc(SBC + SM_HB, 16, 1024, 1);
            mbar_wait(bar + B_HHI_FULL * 8, hp);
            TR(6);
            wg_fence();
            #pragma unroll
            for (int kt = 12; kt < 40; kt++) wg_ss32(d, da0 + (uint64_t)(kt * 128), db0 + (uint64_t)(((kt >> 2) * 4096 + (kt & 3) * 32) >> 4), kt > 12);
            wg_commit();
            mbar_wait(bar + B_HLO_FULL * 8, hp);
            wg_fence();
            #pragma unroll
            for (int kt = 0; kt < 9; kt++) wg_ss32(d, da0 + (uint64_t)(kt * 128), db0 + (uint64_t)(((kt >> 2) * 4096 + (kt & 3) * 32) >> 4), 1);
            wg_commit();
            #pragma unroll
            for (int kt = 9; kt < 12; kt++) wg_ss32(d, da0 + (uint64_t)(kt * 128), db0 + (uint64_t)(((kt >> 2) * 4096 + (kt & 3) * 32) >> 4), 1);
            wg_commit();
            wg_wait<1>();
            bar_arrive(9, 384);
            wg_wait<0>();
            if (lane == 0) mbar_arrive(bar + B_HLO_FREE * 8);
            TR(7);
            if (lane == 0) mbar_arrive(bar + B_HHI_FREE * 8);
            #pragma unroll
            for (int i = 0; i < 8; i++) vn[i] = pack2(d[2 * i], d[2 * i + 1]);
            }
            if (s >= 0) {
                {
                    FRESH(lane);
                    mbar_wait(bar + B_XS * 8, s & 1);
                    if (w == 0 && lane == 0) mbar_expect(bar + B_XS * 8, 12288);
                    const uint32_t a = sb + SM_XS + (w >> 1) * 1536 + lane * 16 + (w & 1) * 8;
                    if (w == 0) xsoftmax<2>(a, lane >> 2, lane & 3);
                    else if (w == 1) xsoftmax<3>(a, lane >> 2, lane & 3);
                    else if (w == 2) xsoftmax<4>(a, lane >> 2, lane & 3);
                    else xsoftmax<5>(a, lane >> 2, lane & 3);
                }
                TR(8);
                bar_sync(7, 128);
                FRESH(lane);
                bf16* orow = g_ox + (size_t)(s * 32 + (lane >> 2)) * HD + h * DH + p * 64 + w * 16 + 2 * (lane & 3);
                {
                    const uint32_t pa = sb + SM_XS + lane * 16;
                    #pragma unroll
                    for (int mi = 0; mi < 2; mi++) {
                        float oa[4] = {0.f, 0.f, 0.f, 0.f}, ob[4] = {0.f, 0.f, 0.f, 0.f};
                        if (mi == 0) {
                            const uint4 p0 = lds4(pa);
                            const uint32_t p3 = lds1(pa + 1024 + 8);
                            mma8(oa, vm0, vm1, p0.x);
                            mma8(ob, vm0, vm1, p0.z);
                            mma16(oa, vx[0], vx[1], vx[2], vx[3], p0.y, 0u);
                            mma16(ob, vx[0], vx[1], vx[2], vx[3], p0.w, p3);
                        } else {
                            const uint4 p1 = lds4(pa + 1536), p2 = lds4(pa + 2560);
                            const uint32_t p4 = lds1(pa + 3584 + 8);
                            mma8(oa, vm0, vm1, p1.x);
                            mma8(ob, vm0, vm1, p1.z);
                            mma16(oa, vx[0], vx[1], vx[2], vx[3], p1.y, p2.x);
                            mma16(ob, vx[0], vx[1], vx[2], vx[3], p1.w, p2.z);
                            mma16(oa, vx[4], vx[5], vx[6], vx[7], p2.y, 0u);
                            mma16(ob, vx[4], vx[5], vx[6], vx[7], p2.w, p4);
                            if (lane < 3) mbar_arrive_remote(mapa(bar + B_XSFREE * 8, lane));
                        }
                        const uint32_t u0 = movm(pack2(oa[0], oa[1])), u1 = movm(pack2(oa[2], oa[3]));
                        const uint32_t u2 = movm(pack2(ob[0], ob[1])), u3 = movm(pack2(ob[2], ob[3]));
                        bf16* dst = orow + (size_t)(16 * mi) * HD;
                        *(uint32_t*)dst = u0;
                        *(uint32_t*)(dst + 8) = u1;
                        *(uint32_t*)(dst + 8 * HD) = u2;
                        *(uint32_t*)(dst + 8 * HD + 8) = u3;
                    }
                }
                TR(9);
                if (s == NSEG - 1) {
                    bar_sync(7, 128);
                    if (w == 3 && lane == 0) signal_cnt(C_REC + 15);
                    break;
                }
            }
            #pragma unroll
            for (int i = 0; i < 8; i++) vx[i] = vn[i];
            if (s >= 0) mbar_wait_cluster(bar + B_XSFREE * 8, s & 1);
            bar_sync(8, 384);
            TR(10);
            if (w < 3) xscores<2>(sb, p, w > 0, w == 2 ? 3 : 1, lane);
            else if ((s & 3) == 3 && s >= 0 && lane == 0) signal_cnt(C_REC + (s >> 2));
            __syncwarp();
            TR(11);
            if (s < 0) { bar_sync(0, 512); asm volatile("griddepcontrol.launch_dependents;" ::: "memory"); }
        }
    } else {
        asm volatile("setmaxnreg.dec.sync.aligned.u32 48;");
        const int w = warp & 3, lt = tid & 127;
        {
            const bf16* src0 = Wo + (size_t)h * DH * DM + tile0 * 16;
            const int nch = 2 * ntile;
            for (int i = lt; i < DH * nch; i += 128) {
                const int e = i / nch, c = i - e * nch, tl = c >> 1, cc = c & 1;
                int es = e;
                if (tl >= 8 && tl < 12) { if (e >= 64 && e < 128) continue; if (e >= 128) es = e - 64; }
                int eg = e + p * 64; if (eg >= DH) eg -= DH;
                cpa16(sb + SM_WO + wo_tile_off(tl) + es * 32 + ((cc ^ ((e >> 2) & 1)) << 4), src0 + (size_t)eg * DM + c * 8);
            }
        }
        const uint32_t epoch = *(volatile uint32_t*)&g_epoch + 1u;
        if (b < 80) {
            #pragma unroll
            for (int i = 0; i < 2; i++) {
                const int idx = lt + i * 128, sl = idx >> 6, pg = (idx >> 5) & 1, wd = idx & 31;
                st_relaxed1(g_buf2 + (sl * 3 + (b >> 5)) * 2048 + pg * 1024 + (b & 31) * 32 + wd, 0xFFFFFFFFu);
            }
            __threadfence();
        }
        if (lane == 0) {
            for (int i = w; i < 14; i += 4) {
                int c = 0;
                if (i < 12) c = probe_blk(g_buf2 + i * 2048 + 640 + (b & 31) * 8);
                else if (b < 80) c = probe_blk(g_buf1 + (b * 2 + (i - 12)) * 2048);
                asm volatile("st.shared.u8 [%0], %1;" :: "r"(sb + SM_CH + 96 + i), "r"(c) : "memory");
            }
        }
        if (w == 3) {
            asm volatile("griddepcontrol.wait;" ::: "memory");
            if (lane == 0) {
                asm volatile("fence.proxy.async;" ::: "memory");
                mbar_expect(bar + B_HLO_FULL * 8, 12288);
                bulk_g2s(sb + SM_HB, g_ht, 12288, sb + SM_BAR + B_HLO_FULL * 8);
                mbar_expect(bar + B_HHI_FULL * 8, 28672);
                bulk_g2s(sb + SM_HB + 12288, (const char*)g_ht + 12288, 28672, sb + SM_BAR + B_HHI_FULL * 8);
            }
            __syncwarp();
        }
        bar_sync(3, 128);
        uint32_t selmask = 0;
        for (int i = 0; i < 14; i++) {
            uint32_t c; asm volatile("ld.shared.u8 %0, [%1];" : "=r"(c) : "r"(sb + SM_CH + 96 + i) : "memory");
            selmask |= c << i;
        }
        if (lt == 0 && b < 80) st_release1(&g_choice[b], (epoch << 2) | (selmask >> 12));
        if (lt < 80) {
            uint32_t v, guard = 0;
            do { v = ld_acquire1(&g_choice[lt]); if (++guard > (1u << 22)) __trap(); } while ((v >> 2) != (epoch & 0x3fffffffu));
            asm volatile("st.shared.u8 [%0], %1;" :: "r"(sb + SM_CH + lt), "r"(v & 3u) : "memory");
        }
        cpa_wait_all();
        bar_sync(0, 512);
        asm volatile("griddepcontrol.launch_dependents;" ::: "memory");
        const bool has_tile = (12 + w) < ntile;
        for (int s = 0; s < NSEG; s++) {
            const uint32_t par = s & 1;
            FRESH(lane);
            const int g = lane >> 2, t = lane & 3, lt = w * 32 + lane;
            if (s == 0) {
                mbar_wait(bar + B_HLO_FREE * 8, par);
                for (int k = lt; k < DM; k += 128) {
                    uint32_t v[4];
                    #pragma unroll
                    for (int i = 0; i < 4; i++) {
                        uint32_t lo = *(const uint16_t*)(mem0 + (2 * i) * DM + k), hi = *(const uint16_t*)(mem0 + (2 * i + 1) * DM + k);
                        v[i] = lo | (hi << 16);
                    }
                    asm volatile("st.shared.v4.u32 [%0], {%1,%2,%3,%4};" :: "r"(sb + SM_HB + k * 16), "r"(v[0]), "r"(v[1]), "r"(v[2]), "r"(v[3]) : "memory");
                }
            } else {
                const int sl = s & 3;
                const char* q = (const char*)g_buf2 + sl * 3 * 8192 + lt * 16;
                const uint32_t sm = selmask >> (sl * 3);
                const char* q0 = q + (sm & 1) * 4096;
                const char* q1 = q + 8192 + (sm & 2) * 2048;
                const char* q2 = q + 16384 + (sm & 4) * 1024;
                const uint32_t dst = sb + SM_HB + lt * 16;
                uint32_t guard = 0;
                mbar_wait(bar + B_HLO_FREE * 8, par);
                TR(10);
                while (true) {
                    const uint4 v0 = ld_relaxed4(q0), v1 = ld_relaxed4(q0 + 2048), v2 = ld_relaxed4(q1), v3 = ld_relaxed4(q1 + 2048), v4 = ld_relaxed4(q2);
                    sts4(dst, v0); sts4(dst + 2048, v1); sts4(dst + 4096, v2); sts4(dst + 6144, v3); sts4(dst + 8192, v4);
                    if (__all_sync(0xffffffffu, oks(v0) && oks(v1) && oks(v2) && oks(v3) && oks(v4))) break;
                    if (++guard > (1u << 22)) __trap();
                }
            }
            fence_async();
            __syncwarp();
            if (lane == 0) mbar_arrive(bar + B_MEM_FULL * 8);
            TR(0);
            if (w == 2) {
                mbar_wait(bar + B_MS * 8, par);
                TR(1);
                if (lane == 0) mbar_expect(bar + B_MS * 8, 3840);
                uint32_t pb[5];
                float sc[5][2];
                {
                    const uint32_t a = sb + SM_MS + lane * 8;
                    float2 u[5], v[5];
                    #pragma unroll
                    for (int j = 0; j < 5; j++) { u[j] = lds2f(a + j * 256); v[j] = lds2f(a + j * 256 + 1280); }
                    #pragma unroll
                    for (int j = 0; j < 5; j++) { sc[j][0] = u[j].x + v[j].x; sc[j][1] = u[j].y + v[j].y; }
                    #pragma unroll
                    for (int j = 0; j < 5; j++) u[j] = lds2f(a + j * 256 + 2560);
                    #pragma unroll
                    for (int j = 0; j < 5; j++) { sc[j][0] += u[j].x; sc[j][1] += u[j].y; }
                }
                softmax_core<5, false>(sc, g, t, pb);
                #pragma unroll
                for (int j = 0; j < 5; j++) sts1(sb + SM_PM + j * 128 + lane * 4, pb[j]);
                bar_arrive(5, 160);
                TR(2);
            }
            const uint32_t tag = (uint32_t)(s % 15) + 1u;
            if (s < NSEG - 1) {
                if (w == 3) {
                    const char* src = (const char*)g_ht + (size_t)(s + 1) * 40960;
                    mbar_wait(bar + B_HHI_FREE * 8, par);
                    if (lane == 0) {
                        mbar_expect(bar + B_HHI_FULL * 8, 28672);
                        bulk_g2s(sb + SM_HB + 12288, src + 12288, 28672, sb + SM_BAR + B_HHI_FULL * 8);
                    }
                    mbar_wait(bar + B_MEM_FREE * 8, par);
                    if (lane == 0) {
                        mbar_expect(bar + B_HLO_FULL * 8, 12288);
                        bulk_g2s(sb + SM_HB, src, 12288, sb + SM_BAR + B_HLO_FULL * 8);
                    }
                    __syncwarp();
                }
                if (has_tile) wo_phase<0, 4>(sb, warp, lane, nullptr, par, tag, tile0 + warp, h);
                TR(4);
                bar_sync(6, 512);
            }
            if (s < NSEG - 1) {
                { const uint32_t c0 = clk32(); while (clk32() - c0 < H1_DELAY); }
                if (b < 80) {
                    FRESH(lane);
                    const char* rin0 = (const char*)g_buf1 + (size_t)(b * 2) * 8192 + ((selmask >> 12) & 1) * 4096 + (lane >> 2) * 256 + w * 64 + (lane & 3) * 16;
                    const char* rin1 = (const char*)g_buf1 + (size_t)(b * 2 + 1) * 8192 + ((selmask >> 13) & 1) * 4096 + (lane >> 2) * 256 + w * 64 + (lane & 3) * 16;
                    const int col = b * 8 + 2 * w + ((lane >> 1) & 1), wd = 2 * (lane & 1) + (lane >> 4);
                    const int sl = (lane & 8) ? ((s + 3) & 3) : ((s + 1) & 3);
                    uint32_t* dst = g_buf2 + (sl * 3 + (col >> 8)) * 2048 + ((lane >> 2) & 1) * 1024 + (col & 255) * 4 + wd;
                    asm volatile("" : "+l"(dst));
                    uint4 v0, v1, v2, v3;
                    uint32_t guard = 0;
                    while (true) {
                        v0 = ld_relaxed4(rin0); v1 = ld_relaxed4(rin0 + 2048);
                        v2 = ld_relaxed4(rin1); v3 = ld_relaxed4(rin1 + 2048);
                        if (__all_sync(0xffffffffu, ok4(v0, tag) && ok4(v1, tag) && ok4(v2, tag) && ok4(v3, tag))) break;
                        if (++guard > (1u << 22)) __trap();
                    }
                    TR(11);
                    const float a0 = (uf(v0.x) + uf(v1.x)) + (uf(v2.x) + uf(v3.x)), a1 = (uf(v0.y) + uf(v1.y)) + (uf(v2.y) + uf(v3.y));
                    const float a2 = (uf(v0.z) + uf(v1.z)) + (uf(v2.z) + uf(v3.z)), a3 = (uf(v0.w) + uf(v1.w)) + (uf(v2.w) + uf(v3.w));
                    const bool u16 = lane & 16;
                    float m0 = (u16 ? a2 : a0) + __shfl_xor_sync(0xffffffffu, u16 ? a0 : a2, 16);
                    float m1 = (u16 ? a3 : a1) + __shfl_xor_sync(0xffffffffu, u16 ? a1 : a3, 16);
                    m0 += __shfl_xor_sync(0xffffffffu, m0, 8); m1 += __shfl_xor_sync(0xffffffffu, m1, 8);
                    m0 += __shfl_xor_sync(0xffffffffu, m0, 4); m1 += __shfl_xor_sync(0xffffffffu, m1, 4);
                    st_relaxed1(dst, (lane & 8) ? 0xFFFFFFFFu : pack2(m0, m1));
                    TR(12);
                }
            }
        }
    }
    cluster_sync();
}

constexpr int G_STAGES = 6;
constexpr int G_STAGE_BYTES = 32768;
constexpr int G_SMEM = G_STAGES * G_STAGE_BYTES + 1024 + 256 + 2048;

__device__ __forceinline__ void tma2d(uint32_t dst, const CUtensorMap* map, int c0, int c1, uint32_t bar) {
    asm volatile("cp.async.bulk.tensor.2d.shared::cluster.global.mbarrier::complete_tx::bytes [%0], [%1, {%2, %3}], [%4];"
                 :: "r"(dst), "l"(map), "r"(c0), "r"(c1), "r"(bar) : "memory");
}
__device__ __forceinline__ void wg_ss128(float* d, uint64_t da, uint64_t db, int sc) {
    asm volatile("{\n\t.reg .pred p;\n\tsetp.ne.b32 p, %66, 0;\n\t"
        "wgmma.mma_async.sync.aligned.m64n128k16.f32.bf16.bf16 "
        "{%0,%1,%2,%3,%4,%5,%6,%7,%8,%9,%10,%11,%12,%13,%14,%15,%16,%17,%18,%19,%20,%21,%22,%23,%24,%25,%26,%27,%28,%29,%30,%31,"
        "%32,%33,%34,%35,%36,%37,%38,%39,%40,%41,%42,%43,%44,%45,%46,%47,%48,%49,%50,%51,%52,%53,%54,%55,%56,%57,%58,%59,%60,%61,%62,%63}, "
        "%64, %65, p, 1, 1, 0, 1;\n\t}"
        : "+f"(d[0]), "+f"(d[1]), "+f"(d[2]), "+f"(d[3]), "+f"(d[4]), "+f"(d[5]), "+f"(d[6]), "+f"(d[7]),
          "+f"(d[8]), "+f"(d[9]), "+f"(d[10]), "+f"(d[11]), "+f"(d[12]), "+f"(d[13]), "+f"(d[14]), "+f"(d[15]),
          "+f"(d[16]), "+f"(d[17]), "+f"(d[18]), "+f"(d[19]), "+f"(d[20]), "+f"(d[21]), "+f"(d[22]), "+f"(d[23]),
          "+f"(d[24]), "+f"(d[25]), "+f"(d[26]), "+f"(d[27]), "+f"(d[28]), "+f"(d[29]), "+f"(d[30]), "+f"(d[31]),
          "+f"(d[32]), "+f"(d[33]), "+f"(d[34]), "+f"(d[35]), "+f"(d[36]), "+f"(d[37]), "+f"(d[38]), "+f"(d[39]),
          "+f"(d[40]), "+f"(d[41]), "+f"(d[42]), "+f"(d[43]), "+f"(d[44]), "+f"(d[45]), "+f"(d[46]), "+f"(d[47]),
          "+f"(d[48]), "+f"(d[49]), "+f"(d[50]), "+f"(d[51]), "+f"(d[52]), "+f"(d[53]), "+f"(d[54]), "+f"(d[55]),
          "+f"(d[56]), "+f"(d[57]), "+f"(d[58]), "+f"(d[59]), "+f"(d[60]), "+f"(d[61]), "+f"(d[62]), "+f"(d[63])
        : "l"(da), "l"(db), "r"(sc));
}

enum { J_MOD = 0, J_G0, J_LN, J_G1, J_G2, J_FIN, J_END };
__host__ __device__ constexpr int sp0(int b) { return b >= 14 ? 6 : 3; }
__host__ __device__ constexpr int sp2(int b) { return b >= 15 ? 6 : (b == 14 ? 3 : 2); }
__host__ __device__ constexpr int njr(int b) { return b >= 15 ? 16 : (b == 14 ? 8 : 4); }
struct JobTab { uint32_t n; uint32_t j[1200]; };
constexpr uint32_t mkjob(int ty, int b, int n, int k0, int nk, int ks) {
    return (uint32_t)(ty | (b << 3) | (n << 7) | (k0 << 11) | (nk << 18) | (ks << 25));
}
constexpr void add_jobs(JobTab& t, int ty, int b) {
    if (b < 0) return;
    if (ty == J_G0) { for (int ks = 0; ks < sp0(b); ks++) for (int n = 0; n < 5; n++) t.j[t.n++] = mkjob(ty, b, n, ks * (96 / sp0(b)), 96 / sp0(b), ks); }
    else if (ty == J_G2) { for (int ks = 0; ks < sp2(b); ks++) for (int n = 0; n < 5; n++) t.j[t.n++] = mkjob(ty, b, n, ks * (24 / sp2(b)), 24 / sp2(b), ks); }
    else if (ty == J_G1) { for (int n = 0; n < 12; n++) t.j[t.n++] = mkjob(ty, b, n, 0, 10, 0); }
    else { for (int n = 0; n < njr(b); n++) t.j[t.n++] = mkjob(ty, b, n, 0, 16 / njr(b), ty == J_LN ? sp0(b) : sp2(b)); }
}
constexpr JobTab make_tab() {
    JobTab t = {};
    for (int i = 20; i < 60; i++) t.j[t.n++] = mkjob(J_MOD, 0, 0, i, 0, 0);
    for (int b = 0; b < 15; b++) {
        add_jobs(t, J_G0, b); add_jobs(t, J_G2, b - 1); add_jobs(t, J_FIN, b - 1); add_jobs(t, J_LN, b); add_jobs(t, J_G1, b);
    }
    add_jobs(t, J_G2, 14); add_jobs(t, J_FIN, 14);
    add_jobs(t, J_G0, 15); add_jobs(t, J_LN, 15); add_jobs(t, J_G1, 15); add_jobs(t, J_G2, 15); add_jobs(t, J_FIN, 15);
    return t;
}
__constant__ JobTab c_jobs = make_tab();

__device__ __forceinline__ bool cnt_ge(int idx, uint32_t target) { return ld_acquire1(g_cnt + idx * 32) >= target; }
__device__ __forceinline__ void cnt_wait(int idx, uint32_t target) {
    uint32_t guard = 0;
    while (!cnt_ge(idx, target)) { __nanosleep(64); if (++guard > (1u << 22)) __trap(); }
}

struct SMaps { CUtensorMap ox, wo, h2, w1, act, w2; };

__global__ void __launch_bounds__(384, 1)
k_side(const __grid_constant__ SMaps maps, const bf16* __restrict__ xin, const bf16* __restrict__ cvec,
       const bf16* __restrict__ wmod, bf16* __restrict__ outp) {
    extern __shared__ uint8_t smem_raw[];
    const uint32_t sb = (smem_u32(smem_raw) + 1023u) & ~1023u;
    const uint32_t bars = sb + G_STAGES * G_STAGE_BYTES;
    float* red = (float*)(smem_raw + (bars + 256 - smem_u32(smem_raw)));
    const int tid = threadIdx.x, lane = tid & 31, wg = tid >> 7;
    if (tid == 0) {
        for (int i = 0; i < G_STAGES; i++) { mbar_init(bars + i * 8, 1); mbar_init(bars + 64 + i * 8, 8); }
        for (int i = 0; i < 2; i++) { mbar_init(bars + 128 + i * 8, 1); mbar_init(bars + 144 + i * 8, 8); }
        asm volatile("fence.mbarrier_init.release.cluster;" ::: "memory");
    }
    __syncthreads();
    if (wg == 0) {
        if (tid == 0) {
            uint32_t st = 0, ph = 1;
            for (uint32_t it = 0;; it++) {
                const uint32_t ji = atomicAdd(g_cnt + C_Q * 32, 1u);
                const uint32_t job = ji < c_jobs.n ? c_jobs.j[ji] : (uint32_t)J_END;
                if (ji == 0) g_epoch = g_epoch + 1u;
                const int ty = job & 7, b = (job >> 3) & 15, n = (job >> 7) & 15, k0 = (job >> 11) & 127, nk = (job >> 18) & 127;
                const uint32_t sl = it & 1;
                mbar_wait(bars + 144 + sl * 8, ((it >> 1) & 1) ^ 1);
                sts1(bars + 160 + sl * 4, job);
                if (ty == J_G0 || ty == J_G1 || ty == J_G2) {
                    if (b >= PRING && ty != J_G1) cnt_wait((ty == J_G0 ? C_LN : C_FIN) + b - PRING, njr(b - PRING));
                    mbar_arrive(bars + 128 + sl * 8);
                    const CUtensorMap* mA = ty == J_G0 ? &maps.ox : (ty == J_G1 ? &maps.h2 : &maps.act);
                    const CUtensorMap* mB = ty == J_G0 ? &maps.wo : (ty == J_G1 ? &maps.w1 : &maps.w2);
                    const int didx = ty == J_G0 ? C_REC + b : (ty == J_G1 ? C_LN + b : C_G1 + b);
                    const uint32_t dtgt = ty == J_G0 ? 96u : (ty == J_G1 ? (uint32_t)njr(b) : 12u);
                    int pre = 0;
                    if (!cnt_ge(didx, dtgt)) {
                        pre = nk < G_STAGES ? nk : G_STAGES;
                        uint32_t s2 = st, p2 = ph;
                        for (int i = 0; i < pre; i++) {
                            mbar_wait(bars + 64 + s2 * 8, p2);
                            const uint32_t a = sb + s2 * G_STAGE_BYTES;
                            mbar_expect(bars + s2 * 8, G_STAGE_BYTES);
                            tma2d(a + 16384, mB, n * 128, (k0 + i) * 64, bars + s2 * 8);
                            tma2d(a + 16384 + 8192, mB, n * 128 + 64, (k0 + i) * 64, bars + s2 * 8);
                            if (++s2 == G_STAGES) { s2 = 0; p2 ^= 1; }
                        }
                        cnt_wait(didx, dtgt);
                    }
                    asm volatile("fence.proxy.async;" ::: "memory");
                    for (int i = 0; i < nk; i++) {
                        const uint32_t a = sb + st * G_STAGE_BYTES;
                        if (i >= pre) {
                            mbar_wait(bars + 64 + st * 8, ph);
                            mbar_expect(bars + st * 8, G_STAGE_BYTES);
                        }
                        tma2d(a, mA, (k0 + i) * 64, b * 128, bars + st * 8);
                        if (i >= pre) {
                            tma2d(a + 16384, mB, n * 128, (k0 + i) * 64, bars + st * 8);
                            tma2d(a + 16384 + 8192, mB, n * 128 + 64, (k0 + i) * 64, bars + st * 8);
                        }
                        if (++st == G_STAGES) { st = 0; ph ^= 1; }
                    }
                } else {
                    if (ty == J_LN) { cnt_wait(C_MOD, 40u); cnt_wait(C_G0 + b, 5u * sp0(b)); }
                    else if (ty == J_FIN) cnt_wait(C_G2 + b, 5u * sp2(b));
                    mbar_arrive(bars + 128 + sl * 8);
                    if (ty == J_END) break;
                }
            }
        }
    } else {
        const int cw = wg - 1, ct = tid - 128, cwarp = ct >> 5;
        uint32_t st = 0, ph = 0;
        for (uint32_t it = 0;; it++) {
            const uint32_t sl = it & 1;
            mbar_wait(bars + 128 + sl * 8, (it >> 1) & 1);
            const uint32_t job = lds1(bars + 160 + sl * 4);
            __syncwarp();
            if (lane == 0) mbar_arrive(bars + 144 + sl * 8);
            const int ty = job & 7, b = (job >> 3) & 15, n = (job >> 7) & 15, k0 = (job >> 11) & 127, nk = (job >> 18) & 127, ks = (job >> 25) & 7;
            if (ty == J_END) break;
            int sig = -1;
            if (ty == J_G0 || ty == J_G1 || ty == J_G2) {
                float d[64];
                #pragma unroll
                for (int i = 0; i < 64; i++) d[i] = 0.f;
                uint32_t pst = 0;
                for (int kb = 0; kb < nk; kb++) {
                    mbar_wait(bars + st * 8, ph);
                    const uint32_t a = sb + st * G_STAGE_BYTES;
                    const uint64_t da = make_desc(a + cw * 8192, 16, 1024, 1);
                    const uint64_t db = make_desc(a + 16384, 8192, 1024, 1);
                    wg_fence();
                    #pragma unroll
                    for (int k = 0; k < 4; k++) wg_ss128(d, da + (uint64_t)(k * 2), db + (uint64_t)(k * 128), 1);
                    wg_commit();
                    if (kb > 0) {
                        wg_wait<1>();
                        if (lane == 0) mbar_arrive(bars + 64 + pst * 8);
                    }
                    pst = st;
                    if (++st == G_STAGES) { st = 0; ph ^= 1; }
                }
                wg_wait<0>();
                if (lane == 0) mbar_arrive(bars + 64 + pst * 8);
                const int g = lane >> 2, t = lane & 3;
                if (ty == J_G1) {
                    #pragma unroll
                    for (int hf = 0; hf < 2; hf++) {
                        bf16* o = g_act + (size_t)(b * 128 + cwarp * 16 + g + 8 * hf) * FF + n * 128 + 2 * t;
                        #pragma unroll
                        for (int j = 0; j < 16; j++) {
                            const float a0 = bfr(d[4 * j + 2 * hf]), a1 = bfr(d[4 * j + 2 * hf + 1]);
                            *(uint32_t*)(o + j * 8) = pack2(a0 / (1.0f + __expf(-a0)), a1 / (1.0f + __expf(-a1)));
                        }
                    }
                    sig = C_G1 + b;
                } else {
                    float* o = (ty == J_G0 ? g_p0 : g_p2) + ((size_t)((b % PRING) * 6 + ks) * 128 + cwarp * 16 + g) * DM + n * 128 + 2 * t;
                    #pragma unroll
                    for (int hf = 0; hf < 2; hf++) {
                        #pragma unroll
                        for (int j = 0; j < 16; j++)
                            *(float2*)(o + hf * 8 * DM + j * 8) = make_float2(d[4 * j + 2 * hf], d[4 * j + 2 * hf + 1]);
                    }
                    sig = (ty == J_G0 ? C_G0 : C_G2) + b;
                }
            } else if (ty == J_MOD) {
                mod_chunk<256, 2>(cvec, wmod, k0 * 64, ct, red);
                sig = C_MOD;
            } else {
                const bool ln = ty == J_LN;
                const float* gm = g_mod + (ln ? 2 : 5) * DM + lane * 4;
                for (int r = 0; r < nk; r++) {
                    const int lr = (n * nk + r) * 8 + cwarp, row = b * 128 + lr;
                    const float* pp = (ln ? g_p0 : g_p2) + ((size_t)((b % PRING) * 6) * 128 + lr) * DM + lane * 4;
                    const bf16* xs = (ln ? xin : (const bf16*)g_x1) + (size_t)row * DM + lane * 4;
                    float v[5][4];
                    uint2 xv[5];
                    #pragma unroll
                    for (int i = 0; i < 5; i++) {
                        const float4 a = __ldcg((const float4*)(pp + i * 128)), c2 = __ldcg((const float4*)(pp + 128 * DM + i * 128));
                        xv[i] = __ldcg((const uint2*)(xs + i * 128));
                        v[i][0] = a.x + c2.x; v[i][1] = a.y + c2.y; v[i][2] = a.z + c2.z; v[i][3] = a.w + c2.w;
                    }
                    if (ks == 6) {
                        #pragma unroll
                        for (int q = 2; q < 6; q++) {
                            #pragma unroll
                            for (int i = 0; i < 5; i++) {
                                const float4 a = __ldcg((const float4*)(pp + (size_t)q * 128 * DM + i * 128));
                                v[i][0] += a.x; v[i][1] += a.y; v[i][2] += a.z; v[i][3] += a.w;
                            }
                        }
                    } else if (ks == 3) {
                        #pragma unroll
                        for (int i = 0; i < 5; i++) {
                            const float4 a = __ldcg((const float4*)(pp + (size_t)2 * 128 * DM + i * 128));
                            v[i][0] += a.x; v[i][1] += a.y; v[i][2] += a.z; v[i][3] += a.w;
                        }
                    }
                    bf16* dst = (ln ? (bf16*)g_x1 : outp) + (size_t)row * DM + lane * 4;
                    #pragma unroll
                    for (int i = 0; i < 5; i++) {
                        const float4 gg = __ldcg((const float4*)(gm + i * 128));
                        const uint32_t o0 = pack2(bflo(xv[i].x) + bfr(gg.x * bfr(v[i][0])), bfhi(xv[i].x) + bfr(gg.y * bfr(v[i][1])));
                        const uint32_t o1 = pack2(bflo(xv[i].y) + bfr(gg.z * bfr(v[i][2])), bfhi(xv[i].y) + bfr(gg.w * bfr(v[i][3])));
                        *(uint2*)(dst + i * 128) = make_uint2(o0, o1);
                        v[i][0] = bflo(o0); v[i][1] = bfhi(o0); v[i][2] = bflo(o1); v[i][3] = bfhi(o1);
                    }
                    if (ln) {
                        float mb, sd;
                        ln_stats(v, mb, sd);
                        #pragma unroll
                        for (int i = 0; i < 5; i++) {
                            const float4 sh = __ldcg((const float4*)(gm + DM + i * 128)), sc = __ldcg((const float4*)(gm + 2 * DM + i * 128));
                            *(uint2*)(g_h2 + (size_t)row * DM + lane * 4 + i * 128) = ln_apply(v[i], mb, sd, sc, sh);
                        }
                    }
                }
                if (ln) sig = C_LN + b; else if (b < 16 - PRING) sig = C_FIN + b;
            }
            if (sig >= 0) {
                bar_sync(1, 256);
                if (ct == 0) signal_cnt(sig);
            }
        }
    }
}

typedef CUresult (*EncodeFn)(CUtensorMap*, CUtensorMapDataType, cuuint32_t, void*, const cuuint64_t*, const cuuint64_t*,
                             const cuuint32_t*, const cuuint32_t*, CUtensorMapInterleave, CUtensorMapSwizzle,
                             CUtensorMapL2promotion, CUtensorMapFloatOOBfill);

static void make_map(EncodeFn fn, CUtensorMap* m, const void* ptr, uint64_t inner, uint64_t outer, uint32_t bi, uint32_t bo) {
    cuuint64_t dims[2] = {inner, outer};
    cuuint64_t strides[1] = {inner * 2};
    cuuint32_t box[2] = {bi, bo};
    cuuint32_t es[2] = {1, 1};
    fn(m, CU_TENSOR_MAP_DATA_TYPE_BFLOAT16, 2, (void*)ptr, dims, strides, box, es, CU_TENSOR_MAP_INTERLEAVE_NONE,
       CU_TENSOR_MAP_SWIZZLE_128B, CU_TENSOR_MAP_L2_PROMOTION_L2_256B, CU_TENSOR_MAP_FLOAT_OOB_FILL_NONE);
}

extern "C" void kernel_launch(void* const* d_in, const int* in_sizes, int n_in, void* d_out, int out_size) {
    const bf16* x = (const bf16*)d_in[0];
    const bf16* mem0 = (const bf16*)d_in[1];
    const bf16* Wq = (const bf16*)d_in[2];
    const bf16* Wk = (const bf16*)d_in[3];
    const bf16* Wv = (const bf16*)d_in[4];
    const bf16* Wo = (const bf16*)d_in[5];
    const bf16* w1 = (const bf16*)d_in[8];
    const bf16* w2 = (const bf16*)d_in[9];
    const bf16* c = (const bf16*)d_in[10];
    const bf16* wmod = (const bf16*)d_in[11];
    bf16* out = (bf16*)d_out;

    static EncodeFn enc = nullptr;
    static void *p_ox, *p_x1, *p_h2, *p_act;
    if (!enc) {
        cudaDriverEntryPointQueryResult qr;
        void* f = nullptr;
        cudaGetDriverEntryPoint("cuTensorMapEncodeTiled", &f, cudaEnableDefault, &qr);
        enc = (EncodeFn)f;
        cudaGetSymbolAddress(&p_ox, g_ox);
        cudaGetSymbolAddress(&p_x1, g_x1);
        cudaGetSymbolAddress(&p_h2, g_h2);
        cudaGetSymbolAddress(&p_act, g_act);
        cudaFuncSetAttribute(k_rec, cudaFuncAttributeMaxDynamicSharedMemorySize, SM_TOTAL);
        cudaFuncSetAttribute(k_side, cudaFuncAttributeMaxDynamicSharedMemorySize, G_SMEM);
    }
    SMaps m;
    make_map(enc, &m.ox, p_ox, HD, SEQ, 64, 128);
    make_map(enc, &m.wo, Wo, DM, HD, 64, 64);
    make_map(enc, &m.h2, p_h2, DM, SEQ, 64, 128);
    make_map(enc, &m.w1, w1, FF, DM, 64, 64);
    make_map(enc, &m.act, p_act, FF, SEQ, 64, 128);
    make_map(enc, &m.w2, w2, DM, FF, 64, 64);

    cudaStream_t st = cudaStreamPerThread;
    k_pre<<<PRE_CTAS, 1024, 0, st>>>(c, wmod, x);
    {
        cudaLaunchConfig_t cfg = {};
        cfg.gridDim = dim3(96); cfg.blockDim = dim3(512); cfg.dynamicSmemBytes = SM_TOTAL; cfg.stream = st;
        cudaLaunchAttribute at[2];
        at[0].id = cudaLaunchAttributeClusterDimension;
        at[0].val.clusterDim.x = 3; at[0].val.clusterDim.y = 1; at[0].val.clusterDim.z = 1;
        at[1].id = cudaLaunchAttributeProgrammaticStreamSerialization;
        at[1].val.programmaticStreamSerializationAllowed = 1;
        cfg.attrs = at; cfg.numAttrs = 2;
        cudaLaunchKernelEx(&cfg, k_rec, mem0, Wq, Wk, Wv, Wo);
    }
    {
        cudaLaunchConfig_t cfg = {};
        cfg.gridDim = dim3(SIDE_CTAS); cfg.blockDim = dim3(384); cfg.dynamicSmemBytes = G_SMEM; cfg.stream = st;
        cudaLaunchAttribute at[1];
        at[0].id = cudaLaunchAttributeProgrammaticStreamSerialization;
        at[0].val.programmaticStreamSerializationAllowed = 1;
        cfg.attrs = at; cfg.numAttrs = 1;
        cudaLaunchKernelEx(&cfg, k_side, m, x, c, wmod, out);
    }
}
```

```cpp
#include <cuda_runtime.h>
#include <cuda_bf16.h>
#include <cuda.h>
#include <stdint.h>

typedef __nv_bfloat16 bf16;
#define VX_THROTTLE 1
#define H1_DELAY 400
#define H1_BACK 0
#define VM_THROTTLE 1
#define SIDE_CTAS 132

constexpr int SEQ = 2048, DM = 640, NH = 32, DH = 192, NSEG = 64, FF = 1536, HD = NH * DH;

__device__ __align__(128) float g_mod[6 * DM];
__device__ __align__(1024) bf16 g_ht[(size_t)SEQ * DM];
__device__ __align__(1024) bf16 g_ox[(size_t)SEQ * HD];
__device__ __align__(1024) bf16 g_x1[(size_t)SEQ * DM];
__device__ __align__(1024) bf16 g_h2[(size_t)SEQ * DM];
__device__ __align__(1024) bf16 g_act[(size_t)SEQ * FF];
__device__ __align__(8192) uint32_t g_buf1[80 * 2 * 2048];
__device__ __align__(8192) uint32_t g_buf2[4 * 3 * 2048];
__device__ uint32_t g_choice[128];
__device__ uint32_t g_epoch;
__device__ uint32_t g_pflag[32];
#define T2(i)
enum { C_Q = 0, C_MOD = 1, C_REC = 2, C_G0 = 18, C_LN = 34, C_G1 = 50, C_G2 = 66, C_FIN = 82, C_NUM = 98 };
__device__ __align__(128) uint32_t g_cnt[C_NUM * 32];
constexpr int PMAX = 12;
constexpr int PRING = 4;
__device__ __align__(1024) float g_p0[(size_t)PRING * PMAX * 128 * DM];
__device__ __align__(1024) float g_p2[(size_t)PRING * PMAX * 128 * DM];
#define TR(k)

#define FRESH(x) asm volatile("" : "+r"(x))
__device__ __forceinline__ float bfr(float x) { return __bfloat162float(__float2bfloat16_rn(x)); }
__device__ __forceinline__ uint32_t pack2(float a, float b) {
    uint32_t r; asm("cvt.rn.bf16x2.f32 %0, %1, %2;" : "=r"(r) : "f"(b), "f"(a)); return r;
}
__device__ __forceinline__ float bflo(uint32_t v) { return __uint_as_float(v << 16); }
__device__ __forceinline__ float bfhi(uint32_t v) { return __uint_as_float(v & 0xffff0000u); }
__device__ __forceinline__ float ex2(float x) { float r; asm("ex2.approx.ftz.f32 %0, %1;" : "=f"(r) : "f"(x)); return r; }
__device__ __forceinline__ float rcpf(float x) { float r; asm("rcp.approx.ftz.f32 %0, %1;" : "=f"(r) : "f"(x)); return r; }
__device__ __forceinline__ void score2(float& a, float& b) {
    const float SCALE = 0.07216878364870322f;
    uint32_t u = pack2(a, b);
    u = pack2(bflo(u) * SCALE, bfhi(u) * SCALE);
    a = bflo(u); b = bfhi(u);
}
__device__ __forceinline__ uint32_t smem_u32(const void* p) { return (uint32_t)__cvta_generic_to_shared(p); }

__device__ __forceinline__ void mbar_init(uint32_t bar, uint32_t cnt) {
    asm volatile("mbarrier.init.shared::cta.b64 [%0], %1;" :: "r"(bar), "r"(cnt) : "memory");
}
__device__ __forceinline__ void mbar_arrive(uint32_t bar) {
    asm volatile("mbarrier.arrive.shared::cta.b64 _, [%0];" :: "r"(bar) : "memory");
}
__device__ __forceinline__ void mbar_expect(uint32_t bar, uint32_t bytes) {
    asm volatile("mbarrier.arrive.expect_tx.shared::cta.b64 _, [%0], %1;" :: "r"(bar), "r"(bytes) : "memory");
}
__device__ __forceinline__ bool mbar_try(uint32_t bar, uint32_t parity) {
    uint32_t ok;
    asm volatile("{\n\t.reg .pred p;\n\tmbarrier.try_wait.parity.shared::cta.b64 p, [%1], %2;\n\tselp.u32 %0, 1, 0, p;\n\t}"
                 : "=r"(ok) : "r"(bar), "r"(parity) : "memory");
    return ok != 0;
}
__device__ __forceinline__ bool mbar_try_cluster(uint32_t bar, uint32_t parity) {
    uint32_t ok;
    asm volatile("{\n\t.reg .pred p;\n\tmbarrier.try_wait.parity.acquire.cluster.shared::cta.b64 p, [%1], %2;\n\tselp.u32 %0, 1, 0, p;\n\t}"
                 : "=r"(ok) : "r"(bar), "r"(parity) : "memory");
    return ok != 0;
}
__device__ __forceinline__ void mbar_wait(uint32_t bar, uint32_t parity) {
    uint32_t guard = 0;
    while (!mbar_try(bar, parity)) { if (++guard > (1u << 22)) __trap(); }
}
__device__ __forceinline__ void mbar_wait_cluster(uint32_t bar, uint32_t parity) {
    uint32_t guard = 0;
    while (!mbar_try_cluster(bar, parity)) { if (++guard > (1u << 22)) __trap(); }
}
__device__ __forceinline__ void bar_sync(int id, int n) { asm volatile("bar.sync %0, %1;" :: "r"(id), "r"(n) : "memory"); }
__device__ __forceinline__ void bar_arrive(int id, int n) { asm volatile("bar.arrive %0, %1;" :: "r"(id), "r"(n) : "memory"); }
__device__ __forceinline__ void sts1(uint32_t a, uint32_t v) { asm volatile("st.shared.u32 [%0], %1;" :: "r"(a), "r"(v) : "memory"); }
__device__ __forceinline__ uint32_t lds1(uint32_t a) { uint32_t v; asm volatile("ld.shared.u32 %0, [%1];" : "=r"(v) : "r"(a) : "memory"); return v; }
__device__ __forceinline__ void fence_async() { asm volatile("fence.proxy.async.shared::cta;" ::: "memory"); }
__device__ __forceinline__ void cluster_sync() {
    asm volatile("barrier.cluster.arrive.release.aligned;\n\tbarrier.cluster.wait.acquire.aligned;" ::: "memory");
}
__device__ __forceinline__ uint32_t mapa(uint32_t a, uint32_t rank) {
    uint32_t r; asm("mapa.shared::cluster.u32 %0, %1, %2;" : "=r"(r) : "r"(a), "r"(rank)); return r;
}
__device__ __forceinline__ void st_async1(uint32_t a, uint32_t v, uint32_t bar) {
    asm volatile("st.async.weak.shared::cluster.mbarrier::complete_tx::bytes.b32 [%0], %1, [%2];" :: "r"(a), "r"(v), "r"(bar) : "memory");
}
__device__ __forceinline__ void st_async2(uint32_t a, float x, float y, uint32_t bar) {
    asm volatile("st.async.weak.shared::cluster.mbarrier::complete_tx::bytes.v2.f32 [%0], {%1,%2}, [%3];" :: "r"(a), "f"(x), "f"(y), "r"(bar) : "memory");
}
__device__ __forceinline__ void st_async4(uint32_t a, const float* c, uint32_t bar) {
    asm volatile("st.async.weak.shared::cluster.mbarrier::complete_tx::bytes.v4.f32 [%0], {%1,%2,%3,%4}, [%5];"
                 :: "r"(a), "f"(c[0]), "f"(c[1]), "f"(c[2]), "f"(c[3]), "r"(bar) : "memory");
}
__device__ __forceinline__ void bulk_g2s(uint32_t dst, const void* src, uint32_t bytes, uint32_t bar) {
    asm volatile("cp.async.bulk.shared::cluster.global.mbarrier::complete_tx::bytes [%0], [%1], %2, [%3];"
                 :: "r"(dst), "l"(src), "r"(bytes), "r"(bar) : "memory");
}
__device__ __forceinline__ void cpa16(uint32_t s, const void* g) {
    asm volatile("cp.async.cg.shared.global [%0], [%1], 16;" :: "r"(s), "l"(g) : "memory");
}
__device__ __forceinline__ void cpa_wait_all() { asm volatile("cp.async.wait_all;" ::: "memory"); }
__device__ __forceinline__ void ldsm4(uint32_t* r, uint32_t a) {
    asm volatile("ldmatrix.sync.aligned.m8n8.x4.shared.b16 {%0,%1,%2,%3}, [%4];" : "=r"(r[0]), "=r"(r[1]), "=r"(r[2]), "=r"(r[3]) : "r"(a) : "memory");
}
__device__ __forceinline__ void ldsm4t(uint32_t* r, uint32_t a) {
    asm volatile("ldmatrix.sync.aligned.m8n8.x4.trans.shared.b16 {%0,%1,%2,%3}, [%4];" : "=r"(r[0]), "=r"(r[1]), "=r"(r[2]), "=r"(r[3]) : "r"(a) : "memory");
}
__device__ __forceinline__ void stsm2t(uint32_t a, uint32_t r0, uint32_t r1) {
    asm volatile("stmatrix.sync.aligned.m8n8.x2.trans.shared.b16 [%0], {%1,%2};" :: "r"(a), "r"(r0), "r"(r1) : "memory");
}
__device__ __forceinline__ void stsm4t(uint32_t a, uint32_t r0, uint32_t r1, uint32_t r2, uint32_t r3) {
    asm volatile("stmatrix.sync.aligned.m8n8.x4.trans.shared.b16 [%0], {%1,%2,%3,%4};" :: "r"(a), "r"(r0), "r"(r1), "r"(r2), "r"(r3) : "memory");
}
__device__ __forceinline__ uint32_t movm(uint32_t v) {
    uint32_t r; asm volatile("movmatrix.sync.aligned.m8n8.trans.b16 %0, %1;" : "=r"(r) : "r"(v)); return r;
}
__device__ __forceinline__ void mma16(float* c, uint32_t a0, uint32_t a1, uint32_t a2, uint32_t a3, uint32_t b0, uint32_t b1) {
    asm volatile("mma.sync.aligned.m16n8k16.row.col.f32.bf16.bf16.f32 {%0,%1,%2,%3}, {%4,%5,%6,%7}, {%8,%9}, {%0,%1,%2,%3};"
                 : "+f"(c[0]), "+f"(c[1]), "+f"(c[2]), "+f"(c[3]) : "r"(a0), "r"(a1), "r"(a2), "r"(a3), "r"(b0), "r"(b1));
}
__device__ __forceinline__ void mma8(float* c, uint32_t a0, uint32_t a1, uint32_t b0) {
    asm volatile("mma.sync.aligned.m16n8k8.row.col.f32.bf16.bf16.f32 {%0,%1,%2,%3}, {%4,%5}, {%6}, {%0,%1,%2,%3};"
                 : "+f"(c[0]), "+f"(c[1]), "+f"(c[2]), "+f"(c[3]) : "r"(a0), "r"(a1), "r"(b0));
}
__host__ __device__ constexpr uint64_t make_desc(uint32_t saddr, uint32_t lbo, uint32_t sbo, uint32_t layout) {
    return (uint64_t)((saddr & 0x3FFFF) >> 4) | ((uint64_t)(lbo >> 4) << 16) | ((uint64_t)(sbo >> 4) << 32) | ((uint64_t)layout << 62);
}
__device__ __forceinline__ void wg_fence() { asm volatile("wgmma.fence.sync.aligned;" ::: "memory"); }
__device__ __forceinline__ void wg_commit() { asm volatile("wgmma.commit_group.sync.aligned;" ::: "memory"); }
template <int N> __device__ __forceinline__ void wg_wait() { asm volatile("wgmma.wait_group.sync.aligned %0;" :: "n"(N) : "memory"); }

#define D16(C) C(d[0]), C(d[1]), C(d[2]), C(d[3]), C(d[4]), C(d[5]), C(d[6]), C(d[7]), \
               C(d[8]), C(d[9]), C(d[10]), C(d[11]), C(d[12]), C(d[13]), C(d[14]), C(d[15])
#define DREG16 "{%0,%1,%2,%3,%4,%5,%6,%7,%8,%9,%10,%11,%12,%13,%14,%15}"
__device__ __forceinline__ void wg_rs32(float* d, const uint32_t* a, uint64_t db, bool acc) {
    if (acc)
        asm volatile("wgmma.mma_async.sync.aligned.m64n32k16.f32.bf16.bf16 " DREG16 ", {%16,%17,%18,%19}, %20, 1, 1, 1, 0;"
            : D16("+f") : "r"(a[0]), "r"(a[1]), "r"(a[2]), "r"(a[3]), "l"(db));
    else
        asm volatile("wgmma.mma_async.sync.aligned.m64n32k16.f32.bf16.bf16 " DREG16 ", {%16,%17,%18,%19}, %20, 0, 1, 1, 0;"
            : D16("=f") : "r"(a[0]), "r"(a[1]), "r"(a[2]), "r"(a[3]), "l"(db));
}
__device__ __forceinline__ void wg_ss32(float* d, uint64_t da, uint64_t db, bool acc) {
    if (acc)
        asm volatile("wgmma.mma_async.sync.aligned.m64n32k16.f32.bf16.bf16 " DREG16 ", %16, %17, 1, 1, 1, 1, 0;"
            : D16("+f") : "l"(da), "l"(db));
    else
        asm volatile("wgmma.mma_async.sync.aligned.m64n32k16.f32.bf16.bf16 " DREG16 ", %16, %17, 0, 1, 1, 1, 0;"
            : D16("=f") : "l"(da), "l"(db));
}
__device__ __forceinline__ void wg_ss8(float* d, uint64_t da, uint64_t db, bool acc) {
    if (acc)
        asm volatile("wgmma.mma_async.sync.aligned.m64n8k16.f32.bf16.bf16 {%0,%1,%2,%3}, %4, %5, 1, 1, 1, 1, 1;"
            : "+f"(d[0]), "+f"(d[1]), "+f"(d[2]), "+f"(d[3]) : "l"(da), "l"(db));
    else
        asm volatile("wgmma.mma_async.sync.aligned.m64n8k16.f32.bf16.bf16 {%0,%1,%2,%3}, %4, %5, 0, 1, 1, 1, 1;"
            : "=f"(d[0]), "=f"(d[1]), "=f"(d[2]), "=f"(d[3]) : "l"(da), "l"(db));
}
template <int OFF> __device__ __forceinline__ void ldsm4t_i(uint32_t* r, uint32_t a) {
    asm volatile("ldmatrix.sync.aligned.m8n8.x4.trans.shared.b16 {%0,%1,%2,%3}, [%4+%5];"
                 : "=r"(r[0]), "=r"(r[1]), "=r"(r[2]), "=r"(r[3]) : "r"(a), "n"(OFF) : "memory");
}

__device__ __forceinline__ uint4 ld_relaxed4(const void* p) {
    uint4 v;
    asm volatile("ld.relaxed.gpu.global.v4.u32 {%0,%1,%2,%3}, [%4];" : "=r"(v.x), "=r"(v.y), "=r"(v.z), "=r"(v.w) : "l"(p) : "memory");
    return v;
}
__device__ __forceinline__ void st_relaxed2(void* p, uint32_t a, uint32_t b) {
    asm volatile("st.relaxed.gpu.global.v2.u32 [%0], {%1,%2};" :: "l"(p), "r"(a), "r"(b) : "memory");
}
__device__ __forceinline__ void st_relaxed2_off(void* base, uint32_t off, uint32_t a, uint32_t b) {
    asm volatile("{\n\t.reg .u64 ad;\n\tcvt.u64.u32 ad, %1;\n\tadd.u64 ad, ad, %0;\n\tst.relaxed.gpu.global.v2.u32 [ad], {%2,%3};\n\t}"
                 :: "l"(base), "r"(off), "r"(a), "r"(b) : "memory");
}
__device__ __forceinline__ void st_relaxed1(void* p, uint32_t a) {
    asm volatile("st.relaxed.gpu.global.u32 [%0], %1;" :: "l"(p), "r"(a) : "memory");
}
__device__ __forceinline__ uint32_t ld_acquire1(const uint32_t* p) {
    uint32_t v; asm volatile("ld.acquire.gpu.global.u32 %0, [%1];" : "=r"(v) : "l"(p) : "memory"); return v;
}
__device__ __forceinline__ void st_release1(uint32_t* p, uint32_t a) {
    asm volatile("st.release.gpu.global.u32 [%0], %1;" :: "l"(p), "r"(a) : "memory");
}
__device__ __forceinline__ uint4 lds4(uint32_t s) {
    uint4 v; asm volatile("ld.shared.v4.u32 {%0,%1,%2,%3}, [%4];" : "=r"(v.x), "=r"(v.y), "=r"(v.z), "=r"(v.w) : "r"(s) : "memory"); return v;
}
__device__ __forceinline__ void sts4(uint32_t s, const uint4& v) {
    asm volatile("st.shared.v4.u32 [%0], {%1,%2,%3,%4};" :: "r"(s), "r"(v.x), "r"(v.y), "r"(v.z), "r"(v.w) : "memory");
}
__device__ __forceinline__ float4 lds4f(uint32_t s) {
    float4 v; asm volatile("ld.shared.v4.f32 {%0,%1,%2,%3}, [%4];" : "=f"(v.x), "=f"(v.y), "=f"(v.z), "=f"(v.w) : "r"(s) : "memory"); return v;
}
__device__ __forceinline__ uint2 lds2(uint32_t s) {
    uint2 v; asm volatile("ld.shared.v2.u32 {%0,%1}, [%2];" : "=r"(v.x), "=r"(v.y) : "r"(s) : "memory"); return v;
}
__device__ __forceinline__ float2 lds2f(uint32_t s) {
    float2 v; asm volatile("ld.shared.v2.f32 {%0,%1}, [%2];" : "=f"(v.x), "=f"(v.y) : "r"(s) : "memory"); return v;
}
__device__ __forceinline__ uint32_t clk32() { uint32_t c; asm volatile("mov.u32 %0, %%clock;" : "=r"(c) :: "memory"); return c; }
__device__ __forceinline__ uint32_t tagw(float v, uint32_t tag) { return ((__float_as_uint(v) + 8u) & ~15u) | tag; }
__device__ __forceinline__ bool ok4(const uint4& v, uint32_t tag) { return (((v.x ^ tag) | (v.y ^ tag) | (v.z ^ tag) | (v.w ^ tag)) & 15u) == 0; }
__device__ __forceinline__ bool oks(const uint4& v) { return v.x != 0xFFFFFFFFu && v.y != 0xFFFFFFFFu && v.z != 0xFFFFFFFFu && v.w != 0xFFFFFFFFu; }
__device__ __forceinline__ float uf(uint32_t x) { return __uint_as_float(x & ~15u); }

template <int NT, int BAR>
__device__ __forceinline__ void mod_chunk(const bf16* __restrict__ c, const bf16* __restrict__ wmod, int col0, int tid, float* red) {
    constexpr int RG = NT / 8, NP = DM / RG;
    const int cc = tid & 7, rg = tid >> 3;
    uint4 w[NP];
    #pragma unroll
    for (int i = 0; i < NP; i++) w[i] = __ldg((const uint4*)(wmod + (size_t)(rg + i * RG) * (6 * DM) + col0 + cc * 8));
    float a[8];
    #pragma unroll
    for (int j = 0; j < 8; j++) a[j] = 0.f;
    #pragma unroll
    for (int i = 0; i < NP; i++) {
        const float v = __bfloat162float(c[rg + i * RG]);
        const float sv = bfr(v / (1.0f + __expf(-v)));
        a[0] += sv * bflo(w[i].x); a[1] += sv * bfhi(w[i].x); a[2] += sv * bflo(w[i].y); a[3] += sv * bfhi(w[i].y);
        a[4] += sv * bflo(w[i].z); a[5] += sv * bfhi(w[i].z); a[6] += sv * bflo(w[i].w); a[7] += sv * bfhi(w[i].w);
    }
    #pragma unroll
    for (int j = 0; j < 8; j++) {
        a[j] += __shfl_xor_sync(0xffffffffu, a[j], 8);
        a[j] += __shfl_xor_sync(0xffffffffu, a[j], 16);
    }
    if ((tid & 31) < 8) {
        float* d = red + (tid >> 5) * 64 + cc * 8;
        *(float4*)d = make_float4(a[0], a[1], a[2], a[3]);
        *(float4*)(d + 4) = make_float4(a[4], a[5], a[6], a[7]);
    }
    bar_sync(BAR, NT);
    if (tid < 64) {
        float s = 0.f;
        #pragma unroll
        for (int i = 0; i < NT / 32; i++) s += red[i * 64 + tid];
        g_mod[col0 + tid] = bfr(s);
    }
}

__device__ __forceinline__ void ln_stats(const float (*v)[4], float& mb, float& sd) {
    float s = 0.f;
    #pragma unroll
    for (int i = 0; i < 5; i++) s += (v[i][0] + v[i][1]) + (v[i][2] + v[i][3]);
    #pragma unroll
    for (int o = 16; o > 0; o >>= 1) s += __shfl_xor_sync(0xffffffffu, s, o);
    const float mean = s * (1.0f / DM);
    float q = 0.f;
    #pragma unroll
    for (int i = 0; i < 5; i++) {
        #pragma unroll
        for (int j = 0; j < 4; j++) { const float d = v[i][j] - mean; q += d * d; }
    }
    #pragma unroll
    for (int o = 16; o > 0; o >>= 1) q += __shfl_xor_sync(0xffffffffu, q, o);
    mb = bfr(mean);
    const float var = bfr(q * (1.0f / DM));
    sd = 1.0f / bfr(sqrtf(bfr(var + 1e-5f)));
}
__device__ __forceinline__ uint2 ln_apply(const float* v, float mb, float rs, const float4& sc, const float4& sh) {
    const float o0 = bfr(bfr(bfr(v[0] - mb) * rs) * bfr(1.0f + sc.x)) + sh.x;
    const float o1 = bfr(bfr(bfr(v[1] - mb) * rs) * bfr(1.0f + sc.y)) + sh.y;
    const float o2 = bfr(bfr(bfr(v[2] - mb) * rs) * bfr(1.0f + sc.z)) + sh.z;
    const float o3 = bfr(bfr(bfr(v[3] - mb) * rs) * bfr(1.0f + sc.w)) + sh.w;
    return make_uint2(pack2(o0, o1), pack2(o2, o3));
}

constexpr int PRE_CTAS = 32;
__global__ void __launch_bounds__(1024, 1) k_pre(const bf16* __restrict__ c, const bf16* __restrict__ wmod, const bf16* __restrict__ xin) {
    __shared__ __align__(16) float red[32 * 64];
    asm volatile("griddepcontrol.launch_dependents;" ::: "memory");
    const int tid = threadIdx.x, lane = tid & 31, warp = tid >> 5;
    const uint32_t tag = *(volatile uint32_t*)&g_epoch + 1u;
    if (tid == 0) T2(blockIdx.x);
    constexpr int RPW = SEQ / PRE_CTAS / 32;
    uint2 xr[RPW][5];
    #pragma unroll
    for (int r = 0; r < RPW; r++) {
        const int row = (r * PRE_CTAS + blockIdx.x) * 32 + warp;
        #pragma unroll
        for (int i = 0; i < 5; i++) xr[r][i] = __ldg((const uint2*)(xin + (size_t)row * DM + (i * 32 + lane) * 4));
    }
    if (blockIdx.x < 20) {
        mod_chunk<1024, 1>(c, wmod, blockIdx.x * 64, tid, red);
        if (tid < 64) {
            bar_sync(2, 64);
            if (tid == 0) { __threadfence(); st_release1(&g_pflag[blockIdx.x], tag); }
        }
    } else if (blockIdx.x == PRE_CTAS - 1) {
        if (tid < C_NUM) g_cnt[tid * 32] = 0u;
    }
    float mb[RPW], sd[RPW];
    #pragma unroll
    for (int r = 0; r < RPW; r++) {
        float v[5][4];
        #pragma unroll
        for (int i = 0; i < 5; i++) { v[i][0] = bflo(xr[r][i].x); v[i][1] = bfhi(xr[r][i].x); v[i][2] = bflo(xr[r][i].y); v[i][3] = bfhi(xr[r][i].y); }
        ln_stats(v, mb[r], sd[r]);
    }
    if (warp == 0) {
        uint32_t guard = 0;
        while (true) {
            const uint32_t v = lane < 20 ? ld_acquire1(&g_pflag[lane]) : tag;
            if (__all_sync(0xffffffffu, v == tag)) break;
            if (++guard > (1u << 22)) __trap();
        }
    }
    __syncthreads();
    if (tid < 320) *(float4*)(red + tid * 4) = __ldcg((const float4*)(g_mod + tid * 4));
    __syncthreads();
    #pragma unroll
    for (int i = 0; i < 5; i++) {
        const int col = (i * 32 + lane) * 4;
        const float4 sh = *(const float4*)(red + col), sc = *(const float4*)(red + DM + col);
        #pragma unroll
        for (int r = 0; r < RPW; r++) {
            const float v[4] = {bflo(xr[r][i].x), bfhi(xr[r][i].x), bflo(xr[r][i].y), bfhi(xr[r][i].y)};
            const int seg = r * PRE_CTAS + blockIdx.x, blk = col >> 6, cc = (col >> 3) & 7;
            *(uint2*)(g_ht + (size_t)seg * 20480 + blk * 2048 + warp * 64 + ((cc ^ (warp & 7)) << 3) + (col & 4)) = ln_apply(v, mb[r], sd[r], sc, sh);
        }
    }
    if (tid == 0) T2(32 + blockIdx.x);
}

constexpr int SM_WV = 0;
constexpr int SM_HB = 81920;
constexpr int SM_WO = SM_HB + 40960;
constexpr int SM_QX = SM_WO + 77824;
constexpr int SM_KS = SM_QX + 4096;
constexpr int SM_QM = SM_KS + 5120;
constexpr int SM_XS = SM_QM + 1024;
constexpr int SM_MS = SM_XS + 12288;
constexpr int SM_OS = SM_MS + 3840;
constexpr int SM_PM = SM_OS + 3072;
constexpr int SM_BAR = SM_PM + 640;
constexpr int SM_CH = SM_BAR + 128;
constexpr int SM_TOTAL = SM_CH + 128;
static_assert(SM_TOTAL <= 232448, "smem");

enum { B_MEM_FULL = 0, B_MEM_FREE, B_HLO_FULL, B_HHI_FULL, B_HLO_FREE, B_HHI_FREE, B_MS, B_O, B_XS, B_O1, B_XSFREE };

__device__ __forceinline__ int probe_blk(uint32_t* blk) {
    uint32_t t0 = 0xffffffffu, t1 = 0xffffffffu, acc = 0;
    for (int rep = 0; rep < 3; rep++) {
        #pragma unroll
        for (int pg = 0; pg < 2; pg++) {
            uint32_t c0 = clk32();
            uint32_t v = atomicOr(blk + pg * 1024 + acc, 0u);
            acc = (v == 0x12345678u) ? 1u : 0u;
            asm volatile("" :: "r"(acc) : "memory");
            uint32_t c1 = clk32() + acc;
            uint32_t d = c1 - c0;
            if (rep > 0) { if (pg == 0) t0 = min(t0, d); else t1 = min(t1, d); }
        }
    }
    return t1 < t0 ? 1 : 0;
}

__device__ __forceinline__ uint32_t wo_tile_off(int w) {
    if (w < 8) return w * 6144;
    if (w < 12) return 8 * 6144 + (w - 8) * 4096;
    return 8 * 6144 + 4 * 4096 + (w - 12) * 6144;
}

template <int NRES, int NPRE>
__device__ __forceinline__ void wo_phase(uint32_t sb, int w, int lane, const uint32_t (*res)[4], uint32_t parity,
                                         uint32_t tag, int tile, int h) {
    FRESH(lane);
    const int er = (lane & 7) + 8 * (lane >> 4);
    const uint32_t aaddr = sb + SM_WO + wo_tile_off(w) + er * 32 + ((((lane >> 3) & 1) ^ ((er >> 2) & 1)) << 4);
    const uint32_t baddr = sb + SM_OS + lane * 16;
    float c0[4] = {0.f, 0.f, 0.f, 0.f}, c1[4] = {0.f, 0.f, 0.f, 0.f};
    uint32_t pre[NPRE > 4 ? NPRE : 4][4];
    if (NPRE >= 4) {
        #pragma unroll
        for (int i = 0; i < 4; i++) ldsm4t(pre[i], aaddr + i * 512);
        mbar_wait(sb + SM_BAR + B_O1 * 8, parity);
        uint32_t b[2][4];
        ldsm4t(b[0], baddr);
        ldsm4t(b[1], baddr + 512);
        #pragma unroll
        for (int kp = 0; kp < 2; kp++) {
            mma16(c0, pre[2 * kp][0], pre[2 * kp][1], pre[2 * kp][2], pre[2 * kp][3], b[kp][0], b[kp][1]);
            mma16(c1, pre[2 * kp + 1][0], pre[2 * kp + 1][1], pre[2 * kp + 1][2], pre[2 * kp + 1][3], b[kp][2], b[kp][3]);
        }
    } else {
        #pragma unroll
        for (int i = 0; i < 2; i++) ldsm4t(pre[i], aaddr + i * 512);
        mbar_wait(sb + SM_BAR + B_O1 * 8, parity);
        #pragma unroll
        for (int kp = 0; kp < 2; kp++) {
            uint32_t b[4];
            ldsm4t(b, baddr + kp * 512);
            if (kp == 1) { ldsm4t(pre[0], aaddr + 2 * 512); ldsm4t(pre[1], aaddr + 3 * 512); }
            mma16(c0, pre[0][0], pre[0][1], pre[0][2], pre[0][3], b[0], b[1]);
            mma16(c1, pre[1][0], pre[1][1], pre[1][2], pre[1][3], b[2], b[3]);
        }
    }
    #pragma unroll
    for (int i = 0; i < NPRE; i++) ldsm4t(pre[i], aaddr + (4 + i) * 512);
    uint32_t off0, off1;
    {
        uint32_t ch;
        asm volatile("ld.shared.u16 %0, [%1];" : "=r"(ch) : "r"(sb + SM_CH + 2 * tile) : "memory");
        const int j = h >> 4;
        const uint32_t base = (uint32_t)((tile * 4 + j) * 8192 + (h & 15) * 256 + lane * 8);
        ch >>= j;
        off0 = base + (ch & 1) * 4096;
        off1 = base + 16384 + (ch & 256) * 16;
    }
    mbar_wait(sb + SM_BAR + B_O * 8, parity);
    if (NRES == 4) {
        uint32_t b[4][4];
        #pragma unroll
        for (int i = 0; i < 4; i++) ldsm4t(b[i], baddr + (2 + i) * 512);
        #pragma unroll
        for (int i = 0; i < 2; i++) {
            mma16(c0, res[2 * i][0], res[2 * i][1], res[2 * i][2], res[2 * i][3], b[i][0], b[i][1]);
            mma16(c1, res[2 * i + 1][0], res[2 * i + 1][1], res[2 * i + 1][2], res[2 * i + 1][3], b[i][2], b[i][3]);
        }
        #pragma unroll
        for (int i = 0; i < 2; i++) {
            mma16(c0, pre[2 * i][0], pre[2 * i][1], pre[2 * i][2], pre[2 * i][3], b[2 + i][0], b[2 + i][1]);
            mma16(c1, pre[2 * i + 1][0], pre[2 * i + 1][1], pre[2 * i + 1][2], pre[2 * i + 1][3], b[2 + i][2], b[2 + i][3]);
        }
    } else if (NPRE == 4) {
        uint32_t b[2][4];
        #pragma unroll
        for (int hh = 0; hh < 2; hh++) {
            ldsm4t(b[0], baddr + (2 + 2 * hh) * 512);
            ldsm4t(b[1], baddr + (3 + 2 * hh) * 512);
            if (hh) {
                #pragma unroll
                for (int i = 0; i < 4; i++) ldsm4t(pre[i], aaddr + (8 + i) * 512);
            }
            #pragma unroll
            for (int i = 0; i < 2; i++) {
                mma16(c0, pre[2 * i][0], pre[2 * i][1], pre[2 * i][2], pre[2 * i][3], b[i][0], b[i][1]);
                mma16(c1, pre[2 * i + 1][0], pre[2 * i + 1][1], pre[2 * i + 1][2], pre[2 * i + 1][3], b[i][2], b[i][3]);
            }
        }
    }
    st_relaxed2_off(g_buf1, off0, tagw(c0[0] + c1[0], tag), tagw(c0[1] + c1[1], tag));
    st_relaxed2_off(g_buf1, off1, tagw(c0[2] + c1[2], tag), tagw(c0[3] + c1[3], tag));
}

template <int NT, bool MASK>
__device__ __forceinline__ void softmax_core(float (*sc)[2], int g, int t, uint32_t* pb) {
    const float L2E = 1.4426950408889634f;
    #pragma unroll
    for (int j = 0; j < NT; j++) score2(sc[j][0], sc[j][1]);
    if (MASK) {
        const float NEG = -999292928.0f;
        if (2 * t > g) sc[NT - 1][0] = NEG;
        if (2 * t + 1 > g) sc[NT - 1][1] = NEG;
    }
    float m[NT];
    #pragma unroll
    for (int j = 0; j < NT; j++) m[j] = fmaxf(sc[j][0], sc[j][1]);
    float mx = m[0];
    #pragma unroll
    for (int j = 1; j < NT; j++) mx = fmaxf(mx, m[j]);
    mx = fmaxf(mx, __shfl_xor_sync(0xffffffffu, mx, 1));
    mx = fmaxf(mx, __shfl_xor_sync(0xffffffffu, mx, 2));
    float s0 = 0.f, s1 = 0.f;
    #pragma unroll
    for (int j = 0; j < NT; j++) {
        sc[j][0] = ex2((sc[j][0] - mx) * L2E); sc[j][1] = ex2((sc[j][1] - mx) * L2E);
        s0 += sc[j][0]; s1 += sc[j][1];
    }
    s0 += s1;
    s0 += __shfl_xor_sync(0xffffffffu, s0, 1);
    s0 += __shfl_xor_sync(0xffffffffu, s0, 2);
    const float iv = rcpf(s0);
    #pragma unroll
    for (int j = 0; j < NT; j++) pb[j] = pack2(sc[j][0] * iv, sc[j][1] * iv);
}
template <int NT>
__device__ __forceinline__ void xsoftmax(uint32_t a, int g, int t) {
    float sc[NT][2];
    #pragma unroll
    for (int j = 0; j < NT; j++) {
        float2 v0 = lds2f(a + j * 512), v1 = lds2f(a + j * 512 + 4096), v2 = lds2f(a + j * 512 + 8192);
        sc[j][0] = v0.x + v1.x + v2.x; sc[j][1] = v0.y + v1.y + v2.y;
    }
    uint32_t pb[NT];
    softmax_core<NT, true>(sc, g, t, pb);
    #pragma unroll
    for (int j = 0; j < NT; j += 2) {
        if (j + 1 < NT) asm volatile("st.shared.v2.u32 [%0], {%1,%2};" :: "r"(a + j * 512), "r"(pb[j]), "r"(pb[j + 1]) : "memory");
        else sts1(a + j * 512, pb[j]);
    }
}
template <int NJ>
__device__ __forceinline__ void xscores(uint32_t sb, int p, int mi, int j0, int lane) {
    FRESH(lane);
    const int r = lane & 7, cq = lane >> 3;
    const int qrow = mi * 16 + r + 8 * (cq & 1);
    uint32_t kb[NJ][8];
    float d[NJ][4];
    #pragma unroll
    for (int j = 0; j < NJ; j++) {
        ldsm4(kb[j], sb + SM_KS + ((j0 + j) * 8 + r) * 128 + ((cq ^ r) << 4));
        ldsm4(kb[j] + 4, sb + SM_KS + ((j0 + j) * 8 + r) * 128 + (((cq + 4) ^ r) << 4));
        d[j][0] = 0.f; d[j][1] = 0.f; d[j][2] = 0.f; d[j][3] = 0.f;
    }
    #pragma unroll
    for (int kt = 0; kt < 4; kt++) {
        uint32_t a[4];
        ldsm4(a, sb + SM_QX + qrow * 128 + (((2 * kt + (cq >> 1)) ^ r) << 4));
        #pragma unroll
        for (int j = 0; j < NJ; j++) mma16(d[j], a[0], a[1], a[2], a[3], kb[j][2 * kt], kb[j][2 * kt + 1]);
    }
    const uint32_t la = sb + SM_XS + p * 4096 + (mi * 3 + j0) * 512 + lane * 16;
    #pragma unroll
    for (int rk = 0; rk < 3; rk++) {
        const uint32_t ra = mapa(la, rk), rb = mapa(sb + SM_BAR + B_XS * 8, rk);
        #pragma unroll
        for (int j = 0; j < NJ; j++) st_async4(ra + j * 512, d[j], rb);
    }
}
__device__ __forceinline__ void mbar_arrive_remote(uint32_t bar) {
    asm volatile("mbarrier.arrive.relaxed.cluster.shared::cluster.b64 _, [%0];" :: "r"(bar) : "memory");
}

__device__ __forceinline__ void signal_cnt(int idx) {
    asm volatile("fence.proxy.async;\n\tfence.acq_rel.gpu;\n\tred.relaxed.gpu.global.add.u32 [%0], 1;" :: "l"(g_cnt + idx * 32) : "memory");
}

__global__ void __launch_bounds__(512, 1)
k_rec(const bf16* __restrict__ mem0, const bf16* __restrict__ Wq, const bf16* __restrict__ Wk,
      const bf16* __restrict__ Wv, const bf16* __restrict__ Wo) {
    extern __shared__ __align__(1024) uint8_t smem_raw[];
    constexpr uint32_t SBC = 1024;
    const uint32_t sb = smem_u32(smem_raw);
    if ((sb & 0xFFFFFFu) != SBC) __trap();
    int lane = __shfl_sync(0xffffffffu, threadIdx.x & 31, threadIdx.x & 31);
    const int warp = __shfl_sync(0xffffffffu, threadIdx.x >> 5, 0), wg = warp >> 2;
    const int tid = warp * 32 + lane;
    const int b = blockIdx.x, h = b / 3, p = b % 3;
    const int g = lane >> 2, t = lane & 3;
    const int tile0 = p == 0 ? 0 : (p == 1 ? 14 : 27);
    const int ntile = p == 0 ? 14 : 13;
    const uint32_t bar = sb + SM_BAR;

    if (tid == 0) T2(100 + b);
    if (tid == 0) {
        mbar_init(bar + B_MEM_FULL * 8, 4);
        mbar_init(bar + B_MEM_FREE * 8, 12);
        mbar_init(bar + B_HLO_FULL * 8, 1);
        mbar_init(bar + B_HHI_FULL * 8, 1);
        mbar_init(bar + B_HLO_FREE * 8, 12);
        mbar_init(bar + B_HHI_FREE * 8, 12);
        mbar_init(bar + B_MS * 8, 1);
        mbar_init(bar + B_O * 8, 1);
        mbar_init(bar + B_XS * 8, 1);
        mbar_init(bar + B_O1 * 8, 4);
        mbar_init(bar + B_XSFREE * 8, 12);
        asm volatile("fence.mbarrier_init.release.cluster;" ::: "memory");
        mbar_expect(bar + B_MS * 8, 3840);
        mbar_expect(bar + B_O * 8, 2048);
        mbar_expect(bar + B_XS * 8, 12288);
    }
    cluster_sync();

    if (wg < 2) {
        asm volatile("setmaxnreg.inc.sync.aligned.u32 200;");
        const int w = warp & 3;
        uint32_t wa[40][4];
        {
            const bf16* W = (wg == 0 ? Wq : Wk) + (size_t)h * DH + p * 64 + w * 16 + t * 4;
            #pragma unroll
            for (int kt = 0; kt < 40; kt++) {
                uint2 l1 = __ldg((const uint2*)(W + (size_t)(kt * 16 + g) * HD));
                uint2 l2 = __ldg((const uint2*)(W + (size_t)(kt * 16 + 8 + g) * HD));
                wa[kt][0] = l1.x; wa[kt][1] = l1.y; wa[kt][2] = l2.x; wa[kt][3] = l2.y;
            }
            #pragma unroll
            for (int kt = 0; kt < 40; kt++) {
                #pragma unroll
                for (int i = 0; i < 4; i++) wa[kt][i] = movm(wa[kt][i]);
            }
        }

        const uint32_t dstx = sb + (wg == 0 ? SM_QX : SM_KS + 1024);

        for (int s = -1; s < NSEG; s++) {
            const uint32_t par = s & 1;
            FRESH(lane);
            const int g = lane >> 2, t = lane & 3, tid = warp * 32 + lane;
            if (s >= 0) {
                mbar_wait(bar + B_MEM_FULL * 8, par);
                TR(0);
                float c[4][4];
                #pragma unroll
                for (int i = 0; i < 4; i++) { c[i][0] = 0.f; c[i][1] = 0.f; c[i][2] = 0.f; c[i][3] = 0.f; }
                uint32_t maddr = sb + lane * 16;
                asm volatile("" : "+r"(maddr));
                #pragma unroll
                for (int kp = 0; kp < 20; kp++) {
                    uint32_t bb[4];
                    ldsm4t(bb, maddr + (SM_HB + kp * 512));
                    mma16(c[(kp & 1) * 2], wa[2 * kp][0], wa[2 * kp][1], wa[2 * kp][2], wa[2 * kp][3], bb[0], bb[1]);
                    mma16(c[(kp & 1) * 2 + 1], wa[2 * kp + 1][0], wa[2 * kp + 1][1], wa[2 * kp + 1][2], wa[2 * kp + 1][3], bb[2], bb[3]);
                }
                {
                    const int tok = lane & 7, ch = 2 * w + ((lane >> 3) & 1);
                    stsm2t(sb + (wg == 0 ? SM_QM : SM_KS) + tok * 128 + ((ch ^ tok) << 4),
                           pack2((c[0][0] + c[1][0]) + (c[2][0] + c[3][0]), (c[0][1] + c[1][1]) + (c[2][1] + c[3][1])),
                           pack2((c[0][2] + c[1][2]) + (c[2][2] + c[3][2]), (c[0][3] + c[1][3]) + (c[2][3] + c[3][3])));
                }
                __syncwarp();
                if (lane == 0) mbar_arrive(bar + B_MEM_FREE * 8);
                TR(1);
                bar_sync(1, 256);
                if (warp < 5) {
                    const int r = lane & 7, cq = lane >> 3;
                    uint32_t a[8], kb[8];
                    ldsm4(a, sb + SM_QM + r * 128 + ((cq ^ r) << 4));
                    ldsm4(kb, sb + SM_KS + (warp * 8 + r) * 128 + ((cq ^ r) << 4));
                    ldsm4(a + 4, sb + SM_QM + r * 128 + (((cq + 4) ^ r) << 4));
                    ldsm4(kb + 4, sb + SM_KS + (warp * 8 + r) * 128 + (((cq + 4) ^ r) << 4));
                    float d0[4] = {0.f, 0.f, 0.f, 0.f}, d1[4] = {0.f, 0.f, 0.f, 0.f};
                    mma16(d0, a[0], 0u, a[1], 0u, kb[0], kb[1]);
                    mma16(d1, a[2], 0u, a[3], 0u, kb[2], kb[3]);
                    mma16(d0, a[4], 0u, a[5], 0u, kb[4], kb[5]);
                    mma16(d1, a[6], 0u, a[7], 0u, kb[6], kb[7]);
                    const uint32_t la = sb + SM_MS + p * 1280 + warp * 256 + lane * 8;
                    #pragma unroll
                    for (int rk = 0; rk < 3; rk++)
                        st_async2(mapa(la, rk), d0[0] + d1[0], d0[1] + d1[1], mapa(bar + B_MS * 8, rk));
                    bar_arrive(4, 352);
                } else if (warp < 7) {
                    xscores<1>(sb, p, warp - 5, 0, lane);
                    bar_arrive(4, 352);
                }
                TR(2);
                if (s < NSEG - 1) {
                    wo_phase<0, 4>(sb, warp, lane, nullptr, par, (uint32_t)(s % 15) + 1u, tile0 + warp, h);
                    TR(4);
                }
            }
            if (s < NSEG - 1) {
                FRESH(lane);
                const uint32_t hp = (s + 1) & 1;
                float d[16];
                const uint64_t db0 = make_desc(SBC + SM_HB, 16, 1024, 1);
                mbar_wait(bar + B_HHI_FULL * 8, hp);
                {
                    const int r = lane & 7, mq = lane >> 3;
                    const uint32_t ha = sb + SM_HB + 9 * 4096 + (8 * (mq >> 1) + r) * 128 + (((6 + (mq & 1)) ^ r) << 4);
                    uint32_t b0[4], b1[4];
                    ldsm4(b0, ha);
                    ldsm4(b1, ha + 2048);
                    #pragma unroll
                    for (int i = 0; i < 16; i++) d[i] = 0.f;
                    mma16(d + 0, wa[39][0], wa[39][1], wa[39][2], wa[39][3], b0[0], b0[1]);
                    mma16(d + 4, wa[39][0], wa[39][1], wa[39][2], wa[39][3], b0[2], b0[3]);
                    mma16(d + 8, wa[39][0], wa[39][1], wa[39][2], wa[39][3], b1[0], b1[1]);
                    mma16(d + 12, wa[39][0], wa[39][1], wa[39][2], wa[39][3], b1[2], b1[3]);
                    asm volatile("" : "+f"(d[0]), "+f"(d[4]), "+f"(d[8]), "+f"(d[12]) :: "memory");
                }
                if (s >= 0) bar_arrive(6, 512);
                mbar_wait(bar + B_HLO_FULL * 8, hp);
                bar_sync(9, 384);
                TR(6);
                wg_fence();
                #pragma unroll
                for (int kt = 0; kt < 12; kt++) wg_rs32(d, wa[kt], db0 + (uint64_t)(((kt >> 2) * 4096 + (kt & 3) * 32) >> 4), 1);
                wg_commit();
                #pragma unroll
                for (int kt = 12; kt < 39; kt++) wg_rs32(d, wa[kt], db0 + (uint64_t)(((kt >> 2) * 4096 + (kt & 3) * 32) >> 4), 1);
                wg_commit();
                wg_wait<1>();
                if (lane == 0) mbar_arrive(bar + B_HLO_FREE * 8);
                wg_wait<0>();
                if (lane == 0) mbar_arrive(bar + B_HHI_FREE * 8);
                TR(7);
                const int mi = lane >> 3, r = lane & 7;
                #pragma unroll
                for (int jj = 0; jj < 2; jj++) {
                    const int tok = 8 * (2 * jj + (mi >> 1)) + r, ch = 2 * w + (mi & 1);
                    stsm4t(dstx + tok * 128 + ((ch ^ r) << 4),
                           pack2(d[8 * jj + 0], d[8 * jj + 1]), pack2(d[8 * jj + 2], d[8 * jj + 3]),
                           pack2(d[8 * jj + 4], d[8 * jj + 5]), pack2(d[8 * jj + 6], d[8 * jj + 7]));
                }
                bar_arrive(8, 384);
                if (s < 0) { bar_sync(0, 512); asm volatile("griddepcontrol.launch_dependents;" ::: "memory"); }
            }
        }
    } else if (wg == 2) {
        asm volatile("setmaxnreg.dec.sync.aligned.u32 64;");
        const int w = warp & 3;
        {
            const int c = tid & 7;
            const bf16* src = Wv + (size_t)h * DH + p * 64 + c * 8;
            for (int k = (tid & 127) >> 3; k < DM; k += 16)
                cpa16(sb + SM_WV + k * 128 + ((c ^ (k & 7)) << 4), src + (size_t)k * HD);
        }
        uint32_t res[4][4];
        {
            const bf16* src = Wo + ((size_t)h * DH + ((p + 1) % 3) * 64) * DM + (tile0 + warp) * 16 + 2 * t;
            #pragma unroll
            for (int kt = 0; kt < 4; kt++) {
                res[kt][0] = __ldg((const uint32_t*)(src + (size_t)(kt * 16 + g) * DM));
                res[kt][1] = __ldg((const uint32_t*)(src + (size_t)(kt * 16 + g) * DM + 8));
                res[kt][2] = __ldg((const uint32_t*)(src + (size_t)(kt * 16 + 8 + g) * DM));
                res[kt][3] = __ldg((const uint32_t*)(src + (size_t)(kt * 16 + 8 + g) * DM + 8));
            }
            #pragma unroll
            for (int kt = 0; kt < 4; kt++) {
                #pragma unroll
                for (int i = 0; i < 4; i++) res[kt][i] = movm(res[kt][i]);
            }
        }
        cpa_wait_all();
        fence_async();
        bar_sync(2, 128);
        const uint64_t da0 = make_desc(SBC + SM_WV, 16, 1024, 1);
        uint32_t vx[8], vm0 = 0, vm1 = 0;
        #pragma unroll
        for (int i = 0; i < 8; i++) vx[i] = 0;

        for (int s = -1; s < NSEG; s++) {
            FRESH(lane);
            const int g = lane >> 2, t = lane & 3, tid = warp * 32 + lane;
            if (s >= 0) {
                const uint32_t par = s & 1;
                mbar_wait(bar + B_MEM_FULL * 8, par);
                bar_sync(4, 352);
                TR(0);
                float dv[4];
                {
                    const uint64_t dbm = make_desc(SBC + SM_HB, 128, 128, 0);
                    wg_fence();
                    #pragma unroll
                    for (int kt = 0; kt < 40; kt++) {
                        wg_ss8(dv, da0 + (uint64_t)(kt * 128), dbm + (uint64_t)(kt * 16), kt > 0);
                        wg_commit();
                        if (kt < 39) wg_wait<1>();
                    }
                    wg_commit();
                }
                TR(1);
                bar_sync(5, 160);
                TR(2);
                uint32_t pb[5];
                #pragma unroll
                for (int j = 0; j < 5; j++) pb[j] = lds1(sb + SM_PM + j * 128 + lane * 4);
                float o0[4] = {0.f, 0.f, 0.f, 0.f}, o1[4] = {0.f, 0.f, 0.f, 0.f}, o2[4] = {0.f, 0.f, 0.f, 0.f};
                wg_wait<0>();
                TR(3);
                mma16(o0, vx[0], vx[1], vx[2], vx[3], pb[1], pb[2]);
                mma16(o1, vx[4], vx[5], vx[6], vx[7], pb[3], pb[4]);
                vm0 = pack2(dv[0], dv[1]); vm1 = pack2(dv[2], dv[3]);
                mma8(o2, vm0, vm1, pb[0]);
                if (s < NSEG - 1) {
                    const uint32_t q0 = pack2(o0[0] + o1[0] + o2[0], o0[1] + o1[1] + o2[1]), q1 = pack2(o0[2] + o1[2] + o2[2], o0[3] + o1[3] + o2[3]);
                    const uint32_t la = sb + SM_OS + (w * 16 + g) * 16 + t * 4;
                    #pragma unroll
                    for (int i = 1; i < 3; i++) {
                        const uint32_t rk = (p + i) % 3;
                        const uint32_t ra = mapa(la + (3 - i) * 1024, rk), rb = mapa(bar + B_O * 8, rk);
                        st_async1(ra, q0, rb);
                        st_async1(ra + 128, q1, rb);
                    }
                    sts1(la, q0);
                    sts1(la + 128, q1);
                    __syncwarp();
                    if (lane == 0) { mbar_arrive(bar + B_O1 * 8); mbar_arrive(bar + B_MEM_FREE * 8); }
                }
                TR(5);
                if (s < NSEG - 1) {
                    wo_phase<4, 4>(sb, warp, lane, res, par, (uint32_t)(s % 15) + 1u, tile0 + warp, h);
                    TR(4);
                    if (tid == 256) mbar_expect(bar + B_O * 8, 2048);
                }
                if (s < NSEG - 1) bar_sync(6, 512);
            }
            uint32_t vn[8];
            #pragma unroll
            for (int i = 0; i < 8; i++) vn[i] = 0;
            if (s < NSEG - 1) {
            float d[16];
            const uint32_t hp = (s + 1) & 1;
            const uint64_t db0 = make_desc(SBC + SM_HB, 16, 1024, 1);
            mbar_wait(bar + B_HHI_FULL * 8, hp);
            TR(6);
            wg_fence();
            #pragma unroll
            for (int kt = 12; kt < 40; kt++) wg_ss32(d, da0 + (uint64_t)(kt * 128), db0 + (uint64_t)(((kt >> 2) * 4096 + (kt & 3) * 32) >> 4), kt > 12);
            wg_commit();
            mbar_wait(bar + B_HLO_FULL * 8, hp);
            wg_fence();
            #pragma unroll
            for (int kt = 0; kt < 9; kt++) wg_ss32(d, da0 + (uint64_t)(kt * 128), db0 + (uint64_t)(((kt >> 2) * 4096 + (kt & 3) * 32) >> 4), 1);
            wg_commit();
            #pragma unroll
            for (int kt = 9; kt < 12; kt++) wg_ss32(d, da0 + (uint64_t)(kt * 128), db0 + (uint64_t)(((kt >> 2) * 4096 + (kt & 3) * 32) >> 4), 1);
            wg_commit();
            wg_wait<1>();
            bar_arrive(9, 384);
            wg_wait<0>();
            if (lane == 0) mbar_arrive(bar + B_HLO_FREE * 8);
            TR(7);
            if (lane == 0) mbar_arrive(bar + B_HHI_FREE * 8);
            #pragma unroll
            for (int i = 0; i < 8; i++) vn[i] = pack2(d[2 * i], d[2 * i + 1]);
            }
            if (s >= 0) {
                {
                    FRESH(lane);
                    mbar_wait(bar + B_XS * 8, s & 1);
                    if (w == 0 && lane == 0) mbar_expect(bar + B_XS * 8, 12288);
                    const uint32_t a = sb + SM_XS + (w >> 1) * 1536 + lane * 16 + (w & 1) * 8;
                    if (w == 0) xsoftmax<2>(a, lane >> 2, lane & 3);
                    else if (w == 1) xsoftmax<3>(a, lane >> 2, lane & 3);
                    else if (w == 2) xsoftmax<4>(a, lane >> 2, lane & 3);
                    else xsoftmax<5>(a, lane >> 2, lane & 3);
                }
                TR(8);
                bar_sync(7, 128);
                FRESH(lane);
                bf16* orow = g_ox + (size_t)(s * 32 + (lane >> 2)) * HD + h * DH + p * 64 + w * 16 + 2 * (lane & 3);
                {
                    const uint32_t pa = sb + SM_XS + lane * 16;
                    #pragma unroll
                    for (int mi = 0; mi < 2; mi++) {
                        float oa[4] = {0.f, 0.f, 0.f, 0.f}, ob[4] = {0.f, 0.f, 0.f, 0.f};
                        if (mi == 0) {
                            const uint4 p0 = lds4(pa);
                            const uint32_t p3 = lds1(pa + 1024 + 8);
                            mma8(oa, vm0, vm1, p0.x);
                            mma8(ob, vm0, vm1, p0.z);
                            mma16(oa, vx[0], vx[1], vx[2], vx[3], p0.y, 0u);
                            mma16(ob, vx[0], vx[1], vx[2], vx[3], p0.w, p3);
                        } else {
                            const uint4 p1 = lds4(pa + 1536), p2 = lds4(pa + 2560);
                            const uint32_t p4 = lds1(pa + 3584 + 8);
                            mma8(oa, vm0, vm1, p1.x);
                            mma8(ob, vm0, vm1, p1.z);
                            mma16(oa, vx[0], vx[1], vx[2], vx[3], p1.y, p2.x);
                            mma16(ob, vx[0], vx[1], vx[2], vx[3], p1.w, p2.z);
                            mma16(oa, vx[4], vx[5], vx[6], vx[7], p2.y, 0u);
                            mma16(ob, vx[4], vx[5], vx[6], vx[7], p2.w, p4);
                            if (lane < 3) mbar_arrive_remote(mapa(bar + B_XSFREE * 8, lane));
                        }
                        const uint32_t u0 = movm(pack2(oa[0], oa[1])), u1 = movm(pack2(oa[2], oa[3]));
                        const uint32_t u2 = movm(pack2(ob[0], ob[1])), u3 = movm(pack2(ob[2], ob[3]));
                        bf16* dst = orow + (size_t)(16 * mi) * HD;
                        *(uint32_t*)dst = u0;
                        *(uint32_t*)(dst + 8) = u1;
                        *(uint32_t*)(dst + 8 * HD) = u2;
                        *(uint32_t*)(dst + 8 * HD + 8) = u3;
                    }
                }
                TR(9);
                if (s == NSEG - 1) {
                    bar_sync(7, 128);
                    if (w == 3 && lane == 0) { signal_cnt(C_REC + 15); T2(400 + b); }
                    break;
                }
            }
            #pragma unroll
            for (int i = 0; i < 8; i++) vx[i] = vn[i];
            if (s >= 0) mbar_wait_cluster(bar + B_XSFREE * 8, s & 1);
            bar_sync(8, 384);
            TR(10);
            if (w < 3) xscores<2>(sb, p, w > 0, w == 2 ? 3 : 1, lane);
            else if ((s & 3) == 3 && s >= 0 && lane == 0) signal_cnt(C_REC + (s >> 2));
            __syncwarp();
            TR(11);
            if (s < 0) { bar_sync(0, 512); asm volatile("griddepcontrol.launch_dependents;" ::: "memory"); }
        }
    } else {
        asm volatile("setmaxnreg.dec.sync.aligned.u32 48;");
        const int w = warp & 3, lt = tid & 127;
        {
            const bf16* src0 = Wo + (size_t)h * DH * DM + tile0 * 16;
            const int nch = 2 * ntile;
            for (int i = lt; i < DH * nch; i += 128) {
                const int e = i / nch, c = i - e * nch, tl = c >> 1, cc = c & 1;
                int es = e;
                if (tl >= 8 && tl < 12) { if (e >= 64 && e < 128) continue; if (e >= 128) es = e - 64; }
                int eg = e + p * 64; if (eg >= DH) eg -= DH;
                cpa16(sb + SM_WO + wo_tile_off(tl) + es * 32 + ((cc ^ ((e >> 2) & 1)) << 4), src0 + (size_t)eg * DM + c * 8);
            }
        }
        const uint32_t epoch = *(volatile uint32_t*)&g_epoch + 1u;
        if (b < 80) {
            #pragma unroll
            for (int i = 0; i < 2; i++) {
                const int idx = lt + i * 128, sl = idx >> 6, pg = (idx >> 5) & 1, wd = idx & 31;
                st_relaxed1(g_buf2 + (sl * 3 + (b >> 5)) * 2048 + pg * 1024 + (b & 31) * 32 + wd, 0xFFFFFFFFu);
            }
            __threadfence();
        }
        if (lane == 0 && w < 3) {
            int c = 0;
            if (w == 0) c = probe_blk(g_buf2 + 640 + (b & 31) * 8);
            else if (b < 80) c = probe_blk(g_buf1 + (b * 2 + (w - 1)) * 2048);
            else if (b < 92 && w == 1) c = probe_blk(g_buf2 + (b - 80) * 2048 + 960);
            asm volatile("st.shared.u8 [%0], %1;" :: "r"(sb + SM_CH + 96 + w), "r"(c) : "memory");
        }
        bar_sync(3, 128);
        uint32_t selmask;
        {
            const uint32_t c3 = lds1(sb + SM_CH + 96);
            const uint32_t cr = c3 & 1u, c1 = (c3 >> 8) & 1u, c2 = (c3 >> 16) & 1u;
            if (lt == 0 && b < 92) st_release1(&g_choice[b], (epoch << 2) | (b < 80 ? (c1 | (c2 << 1)) : (c1 ^ cr)));
            if (lt < 92) {
                uint32_t v, guard = 0;
                while (true) {
                    v = ld_acquire1(&g_choice[lt]);
                    if ((v >> 2) == (epoch & 0x3fffffffu)) break;
                    __nanosleep(100);
                    if (++guard > (1u << 22)) __trap();
                }
                asm volatile("st.shared.u8 [%0], %1;" :: "r"(sb + SM_CH + lt), "r"(v & 3u) : "memory");
            }
        if (w == 3) {
            asm volatile("griddepcontrol.wait;" ::: "memory");
            if (lane == 0) {
                asm volatile("fence.proxy.async;" ::: "memory");
                mbar_expect(bar + B_HLO_FULL * 8, 12288);
                bulk_g2s(sb + SM_HB, g_ht, 12288, sb + SM_BAR + B_HLO_FULL * 8);
                mbar_expect(bar + B_HHI_FULL * 8, 28672);
                bulk_g2s(sb + SM_HB + 12288, (const char*)g_ht + 12288, 28672, sb + SM_BAR + B_HHI_FULL * 8);
            }
            __syncwarp();
        }
            bar_sync(3, 128);
            selmask = (c1 << 12) | (c2 << 13);
            for (int i = 0; i < 12; i++) {
                uint32_t c; asm volatile("ld.shared.u8 %0, [%1];" : "=r"(c) : "r"(sb + SM_CH + 80 + i) : "memory");
                selmask |= ((c ^ cr) & 1u) << i;
            }
        }
        cpa_wait_all();
        bar_sync(0, 512);
        asm volatile("griddepcontrol.launch_dependents;" ::: "memory");
        const bool has_tile = (12 + w) < ntile;
        for (int s = 0; s < NSEG; s++) {
            const uint32_t par = s & 1;
            FRESH(lane);
            const int g = lane >> 2, t = lane & 3, lt = w * 32 + lane;
            if (s == 0) {
                mbar_wait(bar + B_HLO_FREE * 8, par);
                for (int k = lt; k < DM; k += 128) {
                    uint32_t v[4];
                    #pragma unroll
                    for (int i = 0; i < 4; i++) {
                        uint32_t lo = *(const uint16_t*)(mem0 + (2 * i) * DM + k), hi = *(const uint16_t*)(mem0 + (2 * i + 1) * DM + k);
                        v[i] = lo | (hi << 16);
                    }
                    asm volatile("st.shared.v4.u32 [%0], {%1,%2,%3,%4};" :: "r"(sb + SM_HB + k * 16), "r"(v[0]), "r"(v[1]), "r"(v[2]), "r"(v[3]) : "memory");
                }
            } else {
                const int sl = s & 3;
                const char* q = (const char*)g_buf2 + sl * 3 * 8192 + lt * 16;
                const uint32_t sm = selmask >> (sl * 3);
                const char* q0 = q + (sm & 1) * 4096;
                const char* q1 = q + 8192 + (sm & 2) * 2048;
                const char* q2 = q + 16384 + (sm & 4) * 1024;
                const uint32_t dst = sb + SM_HB + lt * 16;
                uint32_t guard = 0;
                mbar_wait(bar + B_HLO_FREE * 8, par);
                TR(10);
                while (true) {
                    const uint4 v0 = ld_relaxed4(q0), v1 = ld_relaxed4(q0 + 2048), v2 = ld_relaxed4(q1), v3 = ld_relaxed4(q1 + 2048), v4 = ld_relaxed4(q2);
                    sts4(dst, v0); sts4(dst + 2048, v1); sts4(dst + 4096, v2); sts4(dst + 6144, v3); sts4(dst + 8192, v4);
                    if (__all_sync(0xffffffffu, oks(v0) && oks(v1) && oks(v2) && oks(v3) && oks(v4))) break;
                    if (++guard > (1u << 22)) __trap();
                }
            }
            fence_async();
            __syncwarp();
            if (lane == 0) mbar_arrive(bar + B_MEM_FULL * 8);
            if (b == 0 && lt == 0) T2(300 + s);
            if (s == 0 && lt == 0) T2(200 + b);
            TR(0);
            if (w == 2) {
                mbar_wait(bar + B_MS * 8, par);
                TR(1);
                if (lane == 0) mbar_expect(bar + B_MS * 8, 3840);
                uint32_t pb[5];
                float sc[5][2];
                {
                    const uint32_t a = sb + SM_MS + lane * 8;
                    float2 u[5], v[5];
                    #pragma unroll
                    for (int j = 0; j < 5; j++) { u[j] = lds2f(a + j * 256); v[j] = lds2f(a + j * 256 + 1280); }
                    #pragma unroll
                    for (int j = 0; j < 5; j++) { sc[j][0] = u[j].x + v[j].x; sc[j][1] = u[j].y + v[j].y; }
                    #pragma unroll
                    for (int j = 0; j < 5; j++) u[j] = lds2f(a + j * 256 + 2560);
                    #pragma unroll
                    for (int j = 0; j < 5; j++) { sc[j][0] += u[j].x; sc[j][1] += u[j].y; }
                }
                softmax_core<5, false>(sc, g, t, pb);
                #pragma unroll
                for (int j = 0; j < 5; j++) sts1(sb + SM_PM + j * 128 + lane * 4, pb[j]);
                bar_arrive(5, 160);
                TR(2);
            }
            const uint32_t tag = (uint32_t)(s % 15) + 1u;
            if (s < NSEG - 1) {
                if (w == 3) {
                    const char* src = (const char*)g_ht + (size_t)(s + 1) * 40960;
                    mbar_wait(bar + B_HHI_FREE * 8, par);
                    if (lane == 0) {
                        mbar_expect(bar + B_HHI_FULL * 8, 28672);
                        bulk_g2s(sb + SM_HB + 12288, src + 12288, 28672, sb + SM_BAR + B_HHI_FULL * 8);
                    }
                    mbar_wait(bar + B_MEM_FREE * 8, par);
                    if (lane == 0) {
                        mbar_expect(bar + B_HLO_FULL * 8, 12288);
                        bulk_g2s(sb + SM_HB, src, 12288, sb + SM_BAR + B_HLO_FULL * 8);
                    }
                    __syncwarp();
                }
                if (has_tile) wo_phase<0, 4>(sb, warp, lane, nullptr, par, tag, tile0 + warp, h);
                TR(4);
                bar_sync(6, 512);
            }
            if (s < NSEG - 1) {
                { const uint32_t c0 = clk32(); while (clk32() - c0 < H1_DELAY); }
                if (b < 80) {
                    FRESH(lane);
                    const char* rin0 = (const char*)g_buf1 + (size_t)(b * 2) * 8192 + ((selmask >> 12) & 1) * 4096 + (lane >> 2) * 256 + w * 64 + (lane & 3) * 16;
                    const char* rin1 = (const char*)g_buf1 + (size_t)(b * 2 + 1) * 8192 + ((selmask >> 13) & 1) * 4096 + (lane >> 2) * 256 + w * 64 + (lane & 3) * 16;
                    const int col = b * 8 + 2 * w + ((lane >> 1) & 1), wd = 2 * (lane & 1) + (lane >> 4);
                    const int sl = (lane & 8) ? ((s + 3) & 3) : ((s + 1) & 3);
                    uint32_t* dst = g_buf2 + (sl * 3 + (col >> 8)) * 2048 + ((lane >> 2) & 1) * 1024 + (col & 255) * 4 + wd;
                    asm volatile("" : "+l"(dst));
                    uint4 v0, v1, v2, v3;
                    uint32_t guard = 0;
                    while (true) {
                        v0 = ld_relaxed4(rin0); v1 = ld_relaxed4(rin0 + 2048);
                        v2 = ld_relaxed4(rin1); v3 = ld_relaxed4(rin1 + 2048);
                        if (__all_sync(0xffffffffu, ok4(v0, tag) && ok4(v1, tag) && ok4(v2, tag) && ok4(v3, tag))) break;
                        if (++guard > (1u << 22)) __trap();
                    }
                    TR(11);
                    const float a0 = (uf(v0.x) + uf(v1.x)) + (uf(v2.x) + uf(v3.x)), a1 = (uf(v0.y) + uf(v1.y)) + (uf(v2.y) + uf(v3.y));
                    const float a2 = (uf(v0.z) + uf(v1.z)) + (uf(v2.z) + uf(v3.z)), a3 = (uf(v0.w) + uf(v1.w)) + (uf(v2.w) + uf(v3.w));
                    const bool u16 = lane & 16;
                    float m0 = (u16 ? a2 : a0) + __shfl_xor_sync(0xffffffffu, u16 ? a0 : a2, 16);
                    float m1 = (u16 ? a3 : a1) + __shfl_xor_sync(0xffffffffu, u16 ? a1 : a3, 16);
                    m0 += __shfl_xor_sync(0xffffffffu, m0, 8); m1 += __shfl_xor_sync(0xffffffffu, m1, 8);
                    m0 += __shfl_xor_sync(0xffffffffu, m0, 4); m1 += __shfl_xor_sync(0xffffffffu, m1, 4);
                    st_relaxed1(dst, (lane & 8) ? 0xFFFFFFFFu : pack2(m0, m1));
                    TR(12);
                }
            }
        }
    }
    cluster_sync();
}

constexpr int G_STAGES = 6;
constexpr int G_STAGE_BYTES = 32768;
constexpr int G_SMEM = G_STAGES * G_STAGE_BYTES + 1024 + 256 + 2048 + 10240;

__device__ __forceinline__ void tma2d(uint32_t dst, const CUtensorMap* map, int c0, int c1, uint32_t bar) {
    asm volatile("cp.async.bulk.tensor.2d.shared::cluster.global.mbarrier::complete_tx::bytes [%0], [%1, {%2, %3}], [%4];"
                 :: "r"(dst), "l"(map), "r"(c0), "r"(c1), "r"(bar) : "memory");
}
__device__ __forceinline__ void wg_ss128(float* d, uint64_t da, uint64_t db, int sc) {
    asm volatile("{\n\t.reg .pred p;\n\tsetp.ne.b32 p, %66, 0;\n\t"
        "wgmma.mma_async.sync.aligned.m64n128k16.f32.bf16.bf16 "
        "{%0,%1,%2,%3,%4,%5,%6,%7,%8,%9,%10,%11,%12,%13,%14,%15,%16,%17,%18,%19,%20,%21,%22,%23,%24,%25,%26,%27,%28,%29,%30,%31,"
        "%32,%33,%34,%35,%36,%37,%38,%39,%40,%41,%42,%43,%44,%45,%46,%47,%48,%49,%50,%51,%52,%53,%54,%55,%56,%57,%58,%59,%60,%61,%62,%63}, "
        "%64, %65, p, 1, 1, 0, 1;\n\t}"
        : "+f"(d[0]), "+f"(d[1]), "+f"(d[2]), "+f"(d[3]), "+f"(d[4]), "+f"(d[5]), "+f"(d[6]), "+f"(d[7]),
          "+f"(d[8]), "+f"(d[9]), "+f"(d[10]), "+f"(d[11]), "+f"(d[12]), "+f"(d[13]), "+f"(d[14]), "+f"(d[15]),
          "+f"(d[16]), "+f"(d[17]), "+f"(d[18]), "+f"(d[19]), "+f"(d[20]), "+f"(d[21]), "+f"(d[22]), "+f"(d[23]),
          "+f"(d[24]), "+f"(d[25]), "+f"(d[26]), "+f"(d[27]), "+f"(d[28]), "+f"(d[29]), "+f"(d[30]), "+f"(d[31]),
          "+f"(d[32]), "+f"(d[33]), "+f"(d[34]), "+f"(d[35]), "+f"(d[36]), "+f"(d[37]), "+f"(d[38]), "+f"(d[39]),
          "+f"(d[40]), "+f"(d[41]), "+f"(d[42]), "+f"(d[43]), "+f"(d[44]), "+f"(d[45]), "+f"(d[46]), "+f"(d[47]),
          "+f"(d[48]), "+f"(d[49]), "+f"(d[50]), "+f"(d[51]), "+f"(d[52]), "+f"(d[53]), "+f"(d[54]), "+f"(d[55]),
          "+f"(d[56]), "+f"(d[57]), "+f"(d[58]), "+f"(d[59]), "+f"(d[60]), "+f"(d[61]), "+f"(d[62]), "+f"(d[63])
        : "l"(da), "l"(db), "r"(sc));
}

#define SP0_LAST 12
#define SP2_LAST 6
enum { J_MOD = 0, J_G0, J_LN, J_G1, J_G2, J_FIN, J_END };
__host__ __device__ constexpr int sp0(int b) { return b >= 15 ? SP0_LAST : (b == 14 ? 6 : 3); }
__host__ __device__ constexpr int sp2(int b) { return b >= 15 ? SP2_LAST : 3; }
__host__ __device__ constexpr int njr(int b) { return b >= 14 ? 16 : 8; }
struct JobTab { uint32_t n; uint32_t j[1200]; };
constexpr uint32_t mkjob(int ty, int b, int n, int k0, int nk, int ks) {
    return (uint32_t)(ty | (b << 3) | (n << 7) | (k0 << 11) | (nk << 18) | (ks << 25));
}
constexpr void add_jobs(JobTab& t, int ty, int b) {
    if (b < 0) return;
    if (ty == J_G0) { for (int ks = 0; ks < sp0(b); ks++) for (int n = 0; n < 5; n++) t.j[t.n++] = mkjob(ty, b, n, ks * (96 / sp0(b)), 96 / sp0(b), ks); }
    else if (ty == J_G2) { for (int ks = 0; ks < sp2(b); ks++) for (int n = 0; n < 5; n++) t.j[t.n++] = mkjob(ty, b, n, ks * (24 / sp2(b)), 24 / sp2(b), ks); }
    else if (ty == J_G1) { for (int n = 0; n < 12; n++) t.j[t.n++] = mkjob(ty, b, n, 0, 10, 0); }
    else { for (int n = 0; n < njr(b); n++) t.j[t.n++] = mkjob(ty, b, n, 0, 16 / njr(b), ty == J_LN ? sp0(b) : sp2(b)); }
}
constexpr JobTab make_tab() {
    JobTab t = {};
    for (int i = 20; i < 60; i++) t.j[t.n++] = mkjob(J_MOD, 0, 0, i, 0, 0);
    for (int b = 0; b < 15; b++) {
        add_jobs(t, J_G0, b); add_jobs(t, J_G2, b - 1); add_jobs(t, J_FIN, b - 1); add_jobs(t, J_LN, b); add_jobs(t, J_G1, b);
    }
    add_jobs(t, J_G2, 14); add_jobs(t, J_FIN, 14);
    add_jobs(t, J_G0, 15); add_jobs(t, J_LN, 15); add_jobs(t, J_G1, 15); add_jobs(t, J_G2, 15); add_jobs(t, J_FIN, 15);
    return t;
}
__constant__ JobTab c_jobs = make_tab();

__device__ __forceinline__ bool cnt_ge(int idx, uint32_t target) { return ld_acquire1(g_cnt + idx * 32) >= target; }
__device__ __forceinline__ void cnt_wait(int idx, uint32_t target) {
    uint32_t guard = 0;
    while (!cnt_ge(idx, target)) { __nanosleep(64); if (++guard > (1u << 22)) __trap(); }
}

struct SMaps { CUtensorMap ox, wo, h2, w1, act, w2; };

__global__ void __launch_bounds__(384, 1)
k_side(const __grid_constant__ SMaps maps, const bf16* __restrict__ xin, const bf16* __restrict__ cvec,
       const bf16* __restrict__ wmod, bf16* __restrict__ outp) {
    extern __shared__ uint8_t smem_raw[];
    const uint32_t sb = (smem_u32(smem_raw) + 1023u) & ~1023u;
    const uint32_t bars = sb + G_STAGES * G_STAGE_BYTES;
    float* red = (float*)(smem_raw + (bars + 256 - smem_u32(smem_raw)));
    const int tid = threadIdx.x, lane = tid & 31, wg = tid >> 7;
    if (tid == 0) T2(500 + blockIdx.x);
    if (tid == 0) {
        for (int i = 0; i < G_STAGES; i++) { mbar_init(bars + i * 8, 1); mbar_init(bars + 64 + i * 8, 8); }
        for (int i = 0; i < 2; i++) { mbar_init(bars + 128 + i * 8, 1); mbar_init(bars + 144 + i * 8, 8); }
        asm volatile("fence.mbarrier_init.release.cluster;" ::: "memory");
    }
    __syncthreads();
    if (wg == 0) {
        if (tid == 0) {
            uint32_t st = 0, ph = 1;
            for (uint32_t it = 0;; it++) {
                const uint32_t ji = atomicAdd(g_cnt + C_Q * 32, 1u);
                const uint32_t job = ji < c_jobs.n ? c_jobs.j[ji] : (uint32_t)J_END;
                if (ji == 0) g_epoch = g_epoch + 1u;
                const int ty = job & 7, b = (job >> 3) & 15, n = (job >> 7) & 15, k0 = (job >> 11) & 127, nk = (job >> 18) & 127;
                const uint32_t sl = it & 1;
                mbar_wait(bars + 144 + sl * 8, ((it >> 1) & 1) ^ 1);
                sts1(bars + 160 + sl * 4, job);
                if (ty == J_G0 || ty == J_G1 || ty == J_G2) {
                    if (b >= PRING && ty != J_G1) cnt_wait((ty == J_G0 ? C_LN : C_FIN) + b - PRING, njr(b - PRING));
                    mbar_arrive(bars + 128 + sl * 8);
                    const CUtensorMap* mA = ty == J_G0 ? &maps.ox : (ty == J_G1 ? &maps.h2 : &maps.act);
                    const CUtensorMap* mB = ty == J_G0 ? &maps.wo : (ty == J_G1 ? &maps.w1 : &maps.w2);
                    const int didx = ty == J_G0 ? C_REC + b : (ty == J_G1 ? C_LN + b : C_G1 + b);
                    const uint32_t dtgt = ty == J_G0 ? 96u : (ty == J_G1 ? (uint32_t)njr(b) : 12u);
                    int pre = 0;
                    if (!cnt_ge(didx, dtgt)) {
                        pre = nk < G_STAGES ? nk : G_STAGES;
                        uint32_t s2 = st, p2 = ph;
                        for (int i = 0; i < pre; i++) {
                            mbar_wait(bars + 64 + s2 * 8, p2);
                            const uint32_t a = sb + s2 * G_STAGE_BYTES;
                            mbar_expect(bars + s2 * 8, G_STAGE_BYTES);
                            tma2d(a + 16384, mB, n * 128, (k0 + i) * 64, bars + s2 * 8);
                            tma2d(a + 16384 + 8192, mB, n * 128 + 64, (k0 + i) * 64, bars + s2 * 8);
                            if (++s2 == G_STAGES) { s2 = 0; p2 ^= 1; }
                        }
                        cnt_wait(didx, dtgt);
                    }
                    asm volatile("fence.proxy.async;" ::: "memory");
                    T2(1024 + ji * 4 + 1);
                    for (int i = 0; i < nk; i++) {
                        const uint32_t a = sb + st * G_STAGE_BYTES;
                        if (i >= pre) {
                            mbar_wait(bars + 64 + st * 8, ph);
                            mbar_expect(bars + st * 8, G_STAGE_BYTES);
                        }
                        tma2d(a, mA, (k0 + i) * 64, b * 128, bars + st * 8);
                        if (i >= pre) {
                            tma2d(a + 16384, mB, n * 128, (k0 + i) * 64, bars + st * 8);
                            tma2d(a + 16384 + 8192, mB, n * 128 + 64, (k0 + i) * 64, bars + st * 8);
                        }
                        if (++st == G_STAGES) { st = 0; ph ^= 1; }
                    }
                } else {
                    if (ty == J_LN) { cnt_wait(C_MOD, 40u); cnt_wait(C_G0 + b, 5u * sp0(b)); }
                    else if (ty == J_FIN) cnt_wait(C_G2 + b, 5u * sp2(b));
                    if (ji < 1200) T2(1024 + ji * 4 + 1);
                    mbar_arrive(bars + 128 + sl * 8);
                    if (ty == J_END) break;
                }
            }
        }
    } else {
        const int cw = wg - 1, ct = tid - 128, cwarp = ct >> 5;
        uint32_t st = 0, ph = 0;
        float* smod = red + 512;
        bool have_mod = false;
        auto load_mod = [&]() {
            for (int i = ct; i < DM; i += 256) *(float4*)(smod + i * 4) = __ldcg((const float4*)(g_mod + 2 * DM + i * 4));
            bar_sync(1, 256);
            have_mod = true;
        };
        {
            if (ct == 0) red[0] = cnt_ge(C_MOD, 40u) ? 1.0f : 0.0f;
            bar_sync(1, 256);
            const bool rdy = red[0] != 0.0f;
            bar_sync(1, 256);
            if (rdy) load_mod();
        }
        for (uint32_t it = 0;; it++) {
            const uint32_t sl = it & 1;
            mbar_wait(bars + 128 + sl * 8, (it >> 1) & 1);
            const uint32_t job = lds1(bars + 160 + sl * 4);
            __syncwarp();
            if (lane == 0) mbar_arrive(bars + 144 + sl * 8);
            const int ty = job & 7, b = (job >> 3) & 15, n = (job >> 7) & 15, k0 = (job >> 11) & 127, nk = (job >> 18) & 127, ks = (job >> 25) & 15;
            if (ty == J_END) break;
            int sig = -1;
            if (ty == J_G0 || ty == J_G1 || ty == J_G2) {
                float d[64];
                #pragma unroll
                for (int i = 0; i < 64; i++) d[i] = 0.f;
                uint32_t pst = 0;
                for (int kb = 0; kb < nk; kb++) {
                    mbar_wait(bars + st * 8, ph);
                    const uint32_t a = sb + st * G_STAGE_BYTES;
                    const uint64_t da = make_desc(a + cw * 8192, 16, 1024, 1);
                    const uint64_t db = make_desc(a + 16384, 8192, 1024, 1);
                    wg_fence();
                    #pragma unroll
                    for (int k = 0; k < 4; k++) wg_ss128(d, da + (uint64_t)(k * 2), db + (uint64_t)(k * 128), 1);
                    wg_commit();
                    if (kb > 0) {
                        wg_wait<1>();
                        if (lane == 0) mbar_arrive(bars + 64 + pst * 8);
                    }
                    pst = st;
                    if (++st == G_STAGES) { st = 0; ph ^= 1; }
                }
                wg_wait<0>();
                if (lane == 0) mbar_arrive(bars + 64 + pst * 8);
                const int g = lane >> 2, t = lane & 3;
                if (ty == J_G1) {
                    #pragma unroll
                    for (int hf = 0; hf < 2; hf++) {
                        bf16* o = g_act + (size_t)(b * 128 + cwarp * 16 + g + 8 * hf) * FF + n * 128 + 2 * t;
                        #pragma unroll
                        for (int j = 0; j < 16; j++) {
                            const float a0 = bfr(d[4 * j + 2 * hf]), a1 = bfr(d[4 * j + 2 * hf + 1]);
                            *(uint32_t*)(o + j * 8) = pack2(__fdividef(a0, 1.0f + __expf(-a0)), __fdividef(a1, 1.0f + __expf(-a1)));
                        }
                    }
                    sig = C_G1 + b;
                } else {
                    float* o = (ty == J_G0 ? g_p0 : g_p2) + ((size_t)((b % PRING) * PMAX + ks) * 128 + cwarp * 16 + g) * DM + n * 128 + 2 * t;
                    #pragma unroll
                    for (int hf = 0; hf < 2; hf++) {
                        #pragma unroll
                        for (int j = 0; j < 16; j++)
                            *(float2*)(o + hf * 8 * DM + j * 8) = make_float2(d[4 * j + 2 * hf], d[4 * j + 2 * hf + 1]);
                    }
                    sig = (ty == J_G0 ? C_G0 : C_G2) + b;
                }
            } else if (ty == J_MOD) {
                mod_chunk<256, 2>(cvec, wmod, k0 * 64, ct, red);
                sig = C_MOD;
            } else {
                const bool ln = ty == J_LN;
                if (!have_mod) load_mod();
                const float* gm = smod + (ln ? 0 : 3) * DM + lane * 4;
                for (int r = 0; r < nk; r++) {
                    const int lr = (n * nk + r) * 8 + cwarp, row = b * 128 + lr;
                    const float* pp = (ln ? g_p0 : g_p2) + ((size_t)((b % PRING) * PMAX) * 128 + lr) * DM + lane * 4;
                    const bf16* xs = (ln ? xin : (const bf16*)g_x1) + (size_t)row * DM + lane * 4;
                    float v[5][4];
                    uint2 xv[5];
                    #pragma unroll
                    for (int i = 0; i < 5; i++) {
                        xv[i] = __ldcg((const uint2*)(xs + i * 128));
                        v[i][0] = 0.f; v[i][1] = 0.f; v[i][2] = 0.f; v[i][3] = 0.f;
                    }
                    if (ks == 3) {
                        float4 a[3][5];
                        #pragma unroll
                        for (int q = 0; q < 3; q++) {
                            #pragma unroll
                            for (int i = 0; i < 5; i++) a[q][i] = __ldcg((const float4*)(pp + (size_t)q * 128 * DM + i * 128));
                        }
                        #pragma unroll
                        for (int q = 0; q < 3; q++) {
                            #pragma unroll
                            for (int i = 0; i < 5; i++) { v[i][0] += a[q][i].x; v[i][1] += a[q][i].y; v[i][2] += a[q][i].z; v[i][3] += a[q][i].w; }
                        }
                    } else {
                        for (int q0 = 0; q0 < ks; q0 += 6) {
                            float4 a[6][5];
                            #pragma unroll
                            for (int q = 0; q < 6; q++) {
                                #pragma unroll
                                for (int i = 0; i < 5; i++) a[q][i] = __ldcg((const float4*)(pp + (size_t)(q0 + q) * 128 * DM + i * 128));
                            }
                            #pragma unroll
                            for (int q = 0; q < 6; q++) {
                                #pragma unroll
                                for (int i = 0; i < 5; i++) { v[i][0] += a[q][i].x; v[i][1] += a[q][i].y; v[i][2] += a[q][i].z; v[i][3] += a[q][i].w; }
                            }
                        }
                    }
                    bf16* dst = (ln ? (bf16*)g_x1 : outp) + (size_t)row * DM + lane * 4;
                    #pragma unroll
                    for (int i = 0; i < 5; i++) {
                        const float4 gg = *(const float4*)(gm + i * 128);
                        const uint32_t o0 = pack2(bflo(xv[i].x) + bfr(gg.x * bfr(v[i][0])), bfhi(xv[i].x) + bfr(gg.y * bfr(v[i][1])));
                        const uint32_t o1 = pack2(bflo(xv[i].y) + bfr(gg.z * bfr(v[i][2])), bfhi(xv[i].y) + bfr(gg.w * bfr(v[i][3])));
                        *(uint2*)(dst + i * 128) = make_uint2(o0, o1);
                        v[i][0] = bflo(o0); v[i][1] = bfhi(o0); v[i][2] = bflo(o1); v[i][3] = bfhi(o1);
                    }
                    if (ln) {
                        float mb, sd;
                        ln_stats(v, mb, sd);
                        #pragma unroll
                        for (int i = 0; i < 5; i++) {
                            const float4 sh = *(const float4*)(gm + DM + i * 128), sc = *(const float4*)(gm + 2 * DM + i * 128);
                            *(uint2*)(g_h2 + (size_t)row * DM + lane * 4 + i * 128) = ln_apply(v[i], mb, sd, sc, sh);
                        }
                    }
                }
                if (ln) sig = C_LN + b; else if (b < 16 - PRING) sig = C_FIN + b;
            }
            if (sig >= 0) {
                bar_sync(1, 256);
                if (ct == 0) signal_cnt(sig);
            }
            if (ct == 0) T2(1024 + ji * 4 + 2);
        }
    }
}

typedef CUresult (*EncodeFn)(CUtensorMap*, CUtensorMapDataType, cuuint32_t, void*, const cuuint64_t*, const cuuint64_t*,
                             const cuuint32_t*, const cuuint32_t*, CUtensorMapInterleave, CUtensorMapSwizzle,
                             CUtensorMapL2promotion, CUtensorMapFloatOOBfill);

static void make_map(EncodeFn fn, CUtensorMap* m, const void* ptr, uint64_t inner, uint64_t outer, uint32_t bi, uint32_t bo) {
    cuuint64_t dims[2] = {inner, outer};
    cuuint64_t strides[1] = {inner * 2};
    cuuint32_t box[2] = {bi, bo};
    cuuint32_t es[2] = {1, 1};
    fn(m, CU_TENSOR_MAP_DATA_TYPE_BFLOAT16, 2, (void*)ptr, dims, strides, box, es, CU_TENSOR_MAP_INTERLEAVE_NONE,
       CU_TENSOR_MAP_SWIZZLE_128B, CU_TENSOR_MAP_L2_PROMOTION_L2_256B, CU_TENSOR_MAP_FLOAT_OOB_FILL_NONE);
}

extern "C" void kernel_launch(void* const* d_in, const int* in_sizes, int n_in, void* d_out, int out_size) {
    const bf16* x = (const bf16*)d_in[0];
    const bf16* mem0 = (const bf16*)d_in[1];
    const bf16* Wq = (const bf16*)d_in[2];
    const bf16* Wk = (const bf16*)d_in[3];
    const bf16* Wv = (const bf16*)d_in[4];
    const bf16* Wo = (const bf16*)d_in[5];
    const bf16* w1 = (const bf16*)d_in[8];
    const bf16* w2 = (const bf16*)d_in[9];
    const bf16* c = (const bf16*)d_in[10];
    const bf16* wmod = (const bf16*)d_in[11];
    bf16* out = (bf16*)d_out;

    static EncodeFn enc = nullptr;
    static void *p_ox, *p_x1, *p_h2, *p_act;
    if (!enc) {
        cudaDriverEntryPointQueryResult qr;
        void* f = nullptr;
        cudaGetDriverEntryPoint("cuTensorMapEncodeTiled", &f, cudaEnableDefault, &qr);
        enc = (EncodeFn)f;
        cudaGetSymbolAddress(&p_ox, g_ox);
        cudaGetSymbolAddress(&p_x1, g_x1);
        cudaGetSymbolAddress(&p_h2, g_h2);
        cudaGetSymbolAddress(&p_act, g_act);
        cudaFuncSetAttribute(k_rec, cudaFuncAttributeMaxDynamicSharedMemorySize, SM_TOTAL);
        cudaFuncSetAttribute(k_side, cudaFuncAttributeMaxDynamicSharedMemorySize, G_SMEM);
    }
    SMaps m;
    make_map(enc, &m.ox, p_ox, HD, SEQ, 64, 128);
    make_map(enc, &m.wo, Wo, DM, HD, 64, 64);
    make_map(enc, &m.h2, p_h2, DM, SEQ, 64, 128);
    make_map(enc, &m.w1, w1, FF, DM, 64, 64);
    make_map(enc, &m.act, p_act, FF, SEQ, 64, 128);
    make_map(enc, &m.w2, w2, DM, FF, 64, 64);

    cudaStream_t st = cudaStreamPerThread;
    k_pre<<<PRE_CTAS, 1024, 0, st>>>(c, wmod, x);
    {
        cudaLaunchConfig_t cfg = {};
        cfg.gridDim = dim3(96); cfg.blockDim = dim3(512); cfg.dynamicSmemBytes = SM_TOTAL; cfg.stream = st;
        cudaLaunchAttribute at[2];
        at[0].id = cudaLaunchAttributeClusterDimension;
        at[0].val.clusterDim.x = 3; at[0].val.clusterDim.y = 1; at[0].val.clusterDim.z = 1;
        at[1].id = cudaLaunchAttributeProgrammaticStreamSerialization;
        at[1].val.programmaticStreamSerializationAllowed = 1;
        cfg.attrs = at; cfg.numAttrs = 2;
        cudaLaunchKernelEx(&cfg, k_rec, mem0, Wq, Wk, Wv, Wo);
    }
    {
        cudaLaunchConfig_t cfg = {};
        cfg.gridDim = dim3(SIDE_CTAS); cfg.blockDim = dim3(384); cfg.dynamicSmemBytes = G_SMEM; cfg.stream = st;
        cudaLaunchAttribute at[1];
        at[0].id = cudaLaunchAttributeProgrammaticStreamSerialization;
        at[0].val.programmaticStreamSerializationAllowed = 1;
        cfg.attrs = at; cfg.numAttrs = 1;
        cudaLaunchKernelEx(&cfg, k_side, m, x, c, wmod, out);
    }
}
```

```cpp
#include <cuda_runtime.h>
#include <cuda_bf16.h>
#include <cuda.h>
#include <stdint.h>

typedef __nv_bfloat16 bf16;
#define VX_THROTTLE 1
#define H1_DELAY 400
#define H1_BACK 0
#define VM_THROTTLE 1
#define PRE_TRIG 0
#define SIDE_CTAS 132

constexpr int SEQ = 2048, DM = 640, NH = 32, DH = 192, NSEG = 64, FF = 1536, HD = NH * DH;

__device__ __align__(128) float g_mod[6 * DM];
__device__ __align__(1024) bf16 g_ht[(size_t)SEQ * DM];
__device__ __align__(1024) bf16 g_ox[(size_t)SEQ * HD];
__device__ __align__(1024) bf16 g_x1[(size_t)SEQ * DM];
__device__ __align__(1024) bf16 g_h2[(size_t)SEQ * DM];
__device__ __align__(1024) bf16 g_act[(size_t)SEQ * FF];
__device__ __align__(8192) uint32_t g_buf1[80 * 2 * 2048];
__device__ __align__(8192) uint32_t g_buf2[4 * 3 * 2048];
__device__ uint32_t g_choice[128];
__device__ uint32_t g_epoch;
__device__ uint32_t g_pflag[32];
#define T2(i)
enum { C_Q = 0, C_MOD = 1, C_REC = 2, C_G0 = 18, C_LN = 34, C_G1 = 50, C_G2 = 66, C_FIN = 82, C_NUM = 98 };
__device__ __align__(128) uint32_t g_cnt[C_NUM * 32];
constexpr int PMAX = 12;
constexpr int PRING = 4;
__device__ __align__(1024) float g_p0[(size_t)PRING * PMAX * 128 * DM];
__device__ __align__(1024) float g_p2[(size_t)PRING * PMAX * 128 * DM];
#define TR(k)

#define FRESH(x) asm volatile("" : "+r"(x))
__device__ __forceinline__ float bfr(float x) { return __bfloat162float(__float2bfloat16_rn(x)); }
__device__ __forceinline__ uint32_t pack2(float a, float b) {
    uint32_t r; asm("cvt.rn.bf16x2.f32 %0, %1, %2;" : "=r"(r) : "f"(b), "f"(a)); return r;
}
__device__ __forceinline__ float bflo(uint32_t v) { return __uint_as_float(v << 16); }
__device__ __forceinline__ float bfhi(uint32_t v) { return __uint_as_float(v & 0xffff0000u); }
__device__ __forceinline__ float ex2(float x) { float r; asm("ex2.approx.ftz.f32 %0, %1;" : "=f"(r) : "f"(x)); return r; }
__device__ __forceinline__ float rcpf(float x) { float r; asm("rcp.approx.ftz.f32 %0, %1;" : "=f"(r) : "f"(x)); return r; }
__device__ __forceinline__ void score2(float& a, float& b) {
    const float SCALE = 0.07216878364870322f;
    uint32_t u = pack2(a, b);
    u = pack2(bflo(u) * SCALE, bfhi(u) * SCALE);
    a = bflo(u); b = bfhi(u);
}
__device__ __forceinline__ uint32_t smem_u32(const void* p) { return (uint32_t)__cvta_generic_to_shared(p); }

__device__ __forceinline__ void mbar_init(uint32_t bar, uint32_t cnt) {
    asm volatile("mbarrier.init.shared::cta.b64 [%0], %1;" :: "r"(bar), "r"(cnt) : "memory");
}
__device__ __forceinline__ void mbar_arrive(uint32_t bar) {
    asm volatile("mbarrier.arrive.shared::cta.b64 _, [%0];" :: "r"(bar) : "memory");
}
__device__ __forceinline__ void mbar_expect(uint32_t bar, uint32_t bytes) {
    asm volatile("mbarrier.arrive.expect_tx.shared::cta.b64 _, [%0], %1;" :: "r"(bar), "r"(bytes) : "memory");
}
__device__ __forceinline__ bool mbar_try(uint32_t bar, uint32_t parity) {
    uint32_t ok;
    asm volatile("{\n\t.reg .pred p;\n\tmbarrier.try_wait.parity.shared::cta.b64 p, [%1], %2;\n\tselp.u32 %0, 1, 0, p;\n\t}"
                 : "=r"(ok) : "r"(bar), "r"(parity) : "memory");
    return ok != 0;
}
__device__ __forceinline__ bool mbar_try_cluster(uint32_t bar, uint32_t parity) {
    uint32_t ok;
    asm volatile("{\n\t.reg .pred p;\n\tmbarrier.try_wait.parity.acquire.cluster.shared::cta.b64 p, [%1], %2;\n\tselp.u32 %0, 1, 0, p;\n\t}"
                 : "=r"(ok) : "r"(bar), "r"(parity) : "memory");
    return ok != 0;
}
__device__ __forceinline__ void mbar_wait(uint32_t bar, uint32_t parity) {
    uint32_t guard = 0;
    while (!mbar_try(bar, parity)) { if (++guard > (1u << 22)) __trap(); }
}
__device__ __forceinline__ void mbar_wait_cluster(uint32_t bar, uint32_t parity) {
    uint32_t guard = 0;
    while (!mbar_try_cluster(bar, parity)) { if (++guard > (1u << 22)) __trap(); }
}
__device__ __forceinline__ void bar_sync(int id, int n) { asm volatile("bar.sync %0, %1;" :: "r"(id), "r"(n) : "memory"); }
__device__ __forceinline__ void bar_arrive(int id, int n) { asm volatile("bar.arrive %0, %1;" :: "r"(id), "r"(n) : "memory"); }
__device__ __forceinline__ void sts1(uint32_t a, uint32_t v) { asm volatile("st.shared.u32 [%0], %1;" :: "r"(a), "r"(v) : "memory"); }
__device__ __forceinline__ uint32_t lds1(uint32_t a) { uint32_t v; asm volatile("ld.shared.u32 %0, [%1];" : "=r"(v) : "r"(a) : "memory"); return v; }
__device__ __forceinline__ void fence_async() { asm volatile("fence.proxy.async.shared::cta;" ::: "memory"); }
__device__ __forceinline__ void cluster_sync() {
    asm volatile("barrier.cluster.arrive.release.aligned;\n\tbarrier.cluster.wait.acquire.aligned;" ::: "memory");
}
__device__ __forceinline__ uint32_t mapa(uint32_t a, uint32_t rank) {
    uint32_t r; asm("mapa.shared::cluster.u32 %0, %1, %2;" : "=r"(r) : "r"(a), "r"(rank)); return r;
}
__device__ __forceinline__ void st_async1(uint32_t a, uint32_t v, uint32_t bar) {
    asm volatile("st.async.weak.shared::cluster.mbarrier::complete_tx::bytes.b32 [%0], %1, [%2];" :: "r"(a), "r"(v), "r"(bar) : "memory");
}
__device__ __forceinline__ void st_async2(uint32_t a, float x, float y, uint32_t bar) {
    asm volatile("st.async.weak.shared::cluster.mbarrier::complete_tx::bytes.v2.f32 [%0], {%1,%2}, [%3];" :: "r"(a), "f"(x), "f"(y), "r"(bar) : "memory");
}
__device__ __forceinline__ void st_async4(uint32_t a, const float* c, uint32_t bar) {
    asm volatile("st.async.weak.shared::cluster.mbarrier::complete_tx::bytes.v4.f32 [%0], {%1,%2,%3,%4}, [%5];"
                 :: "r"(a), "f"(c[0]), "f"(c[1]), "f"(c[2]), "f"(c[3]), "r"(bar) : "memory");
}
__device__ __forceinline__ void bulk_g2s(uint32_t dst, const void* src, uint32_t bytes, uint32_t bar) {
    asm volatile("cp.async.bulk.shared::cluster.global.mbarrier::complete_tx::bytes [%0], [%1], %2, [%3];"
                 :: "r"(dst), "l"(src), "r"(bytes), "r"(bar) : "memory");
}
__device__ __forceinline__ void cpa16(uint32_t s, const void* g) {
    asm volatile("cp.async.cg.shared.global [%0], [%1], 16;" :: "r"(s), "l"(g) : "memory");
}
__device__ __forceinline__ void cpa_wait_all() { asm volatile("cp.async.wait_all;" ::: "memory"); }
__device__ __forceinline__ void ldsm4(uint32_t* r, uint32_t a) {
    asm volatile("ldmatrix.sync.aligned.m8n8.x4.shared.b16 {%0,%1,%2,%3}, [%4];" : "=r"(r[0]), "=r"(r[1]), "=r"(r[2]), "=r"(r[3]) : "r"(a) : "memory");
}
__device__ __forceinline__ void ldsm4t(uint32_t* r, uint32_t a) {
    asm volatile("ldmatrix.sync.aligned.m8n8.x4.trans.shared.b16 {%0,%1,%2,%3}, [%4];" : "=r"(r[0]), "=r"(r[1]), "=r"(r[2]), "=r"(r[3]) : "r"(a) : "memory");
}
__device__ __forceinline__ void stsm2t(uint32_t a, uint32_t r0, uint32_t r1) {
    asm volatile("stmatrix.sync.aligned.m8n8.x2.trans.shared.b16 [%0], {%1,%2};" :: "r"(a), "r"(r0), "r"(r1) : "memory");
}
__device__ __forceinline__ void stsm4t(uint32_t a, uint32_t r0, uint32_t r1, uint32_t r2, uint32_t r3) {
    asm volatile("stmatrix.sync.aligned.m8n8.x4.trans.shared.b16 [%0], {%1,%2,%3,%4};" :: "r"(a), "r"(r0), "r"(r1), "r"(r2), "r"(r3) : "memory");
}
__device__ __forceinline__ uint32_t movm(uint32_t v) {
    uint32_t r; asm volatile("movmatrix.sync.aligned.m8n8.trans.b16 %0, %1;" : "=r"(r) : "r"(v)); return r;
}
__device__ __forceinline__ void mma16(float* c, uint32_t a0, uint32_t a1, uint32_t a2, uint32_t a3, uint32_t b0, uint32_t b1) {
    asm volatile("mma.sync.aligned.m16n8k16.row.col.f32.bf16.bf16.f32 {%0,%1,%2,%3}, {%4,%5,%6,%7}, {%8,%9}, {%0,%1,%2,%3};"
                 : "+f"(c[0]), "+f"(c[1]), "+f"(c[2]), "+f"(c[3]) : "r"(a0), "r"(a1), "r"(a2), "r"(a3), "r"(b0), "r"(b1));
}
__device__ __forceinline__ void mma8(float* c, uint32_t a0, uint32_t a1, uint32_t b0) {
    asm volatile("mma.sync.aligned.m16n8k8.row.col.f32.bf16.bf16.f32 {%0,%1,%2,%3}, {%4,%5}, {%6}, {%0,%1,%2,%3};"
                 : "+f"(c[0]), "+f"(c[1]), "+f"(c[2]), "+f"(c[3]) : "r"(a0), "r"(a1), "r"(b0));
}
__host__ __device__ constexpr uint64_t make_desc(uint32_t saddr, uint32_t lbo, uint32_t sbo, uint32_t layout) {
    return (uint64_t)((saddr & 0x3FFFF) >> 4) | ((uint64_t)(lbo >> 4) << 16) | ((uint64_t)(sbo >> 4) << 32) | ((uint64_t)layout << 62);
}
__device__ __forceinline__ void wg_fence() { asm volatile("wgmma.fence.sync.aligned;" ::: "memory"); }
__device__ __forceinline__ void wg_commit() { asm volatile("wgmma.commit_group.sync.aligned;" ::: "memory"); }
template <int N> __device__ __forceinline__ void wg_wait() { asm volatile("wgmma.wait_group.sync.aligned %0;" :: "n"(N) : "memory"); }

#define D16(C) C(d[0]), C(d[1]), C(d[2]), C(d[3]), C(d[4]), C(d[5]), C(d[6]), C(d[7]), \
               C(d[8]), C(d[9]), C(d[10]), C(d[11]), C(d[12]), C(d[13]), C(d[14]), C(d[15])
#define DREG16 "{%0,%1,%2,%3,%4,%5,%6,%7,%8,%9,%10,%11,%12,%13,%14,%15}"
__device__ __forceinline__ void wg_rs32(float* d, const uint32_t* a, uint64_t db, bool acc) {
    if (acc)
        asm volatile("wgmma.mma_async.sync.aligned.m64n32k16.f32.bf16.bf16 " DREG16 ", {%16,%17,%18,%19}, %20, 1, 1, 1, 0;"
            : D16("+f") : "r"(a[0]), "r"(a[1]), "r"(a[2]), "r"(a[3]), "l"(db));
    else
        asm volatile("wgmma.mma_async.sync.aligned.m64n32k16.f32.bf16.bf16 " DREG16 ", {%16,%17,%18,%19}, %20, 0, 1, 1, 0;"
            : D16("=f") : "r"(a[0]), "r"(a[1]), "r"(a[2]), "r"(a[3]), "l"(db));
}
__device__ __forceinline__ void wg_ss32(float* d, uint64_t da, uint64_t db, bool acc) {
    if (acc)
        asm volatile("wgmma.mma_async.sync.aligned.m64n32k16.f32.bf16.bf16 " DREG16 ", %16, %17, 1, 1, 1, 1, 0;"
            : D16("+f") : "l"(da), "l"(db));
    else
        asm volatile("wgmma.mma_async.sync.aligned.m64n32k16.f32.bf16.bf16 " DREG16 ", %16, %17, 0, 1, 1, 1, 0;"
            : D16("=f") : "l"(da), "l"(db));
}
__device__ __forceinline__ void wg_ss8(float* d, uint64_t da, uint64_t db, bool acc) {
    if (acc)
        asm volatile("wgmma.mma_async.sync.aligned.m64n8k16.f32.bf16.bf16 {%0,%1,%2,%3}, %4, %5, 1, 1, 1, 1, 1;"
            : "+f"(d[0]), "+f"(d[1]), "+f"(d[2]), "+f"(d[3]) : "l"(da), "l"(db));
    else
        asm volatile("wgmma.mma_async.sync.aligned.m64n8k16.f32.bf16.bf16 {%0,%1,%2,%3}, %4, %5, 0, 1, 1, 1, 1;"
            : "=f"(d[0]), "=f"(d[1]), "=f"(d[2]), "=f"(d[3]) : "l"(da), "l"(db));
}
template <int OFF> __device__ __forceinline__ void ldsm4t_i(uint32_t* r, uint32_t a) {
    asm volatile("ldmatrix.sync.aligned.m8n8.x4.trans.shared.b16 {%0,%1,%2,%3}, [%4+%5];"
                 : "=r"(r[0]), "=r"(r[1]), "=r"(r[2]), "=r"(r[3]) : "r"(a), "n"(OFF) : "memory");
}

__device__ __forceinline__ uint4 ld_relaxed4(const void* p) {
    uint4 v;
    asm volatile("ld.relaxed.gpu.global.v4.u32 {%0,%1,%2,%3}, [%4];" : "=r"(v.x), "=r"(v.y), "=r"(v.z), "=r"(v.w) : "l"(p) : "memory");
    return v;
}
__device__ __forceinline__ void st_relaxed2(void* p, uint32_t a, uint32_t b) {
    asm volatile("st.relaxed.gpu.global.v2.u32 [%0], {%1,%2};" :: "l"(p), "r"(a), "r"(b) : "memory");
}
__device__ __forceinline__ void st_relaxed2_off(void* base, uint32_t off, uint32_t a, uint32_t b) {
    asm volatile("{\n\t.reg .u64 ad;\n\tcvt.u64.u32 ad, %1;\n\tadd.u64 ad, ad, %0;\n\tst.relaxed.gpu.global.v2.u32 [ad], {%2,%3};\n\t}"
                 :: "l"(base), "r"(off), "r"(a), "r"(b) : "memory");
}
__device__ __forceinline__ void st_relaxed1(void* p, uint32_t a) {
    asm volatile("st.relaxed.gpu.global.u32 [%0], %1;" :: "l"(p), "r"(a) : "memory");
}
__device__ __forceinline__ uint32_t ld_acquire1(const uint32_t* p) {
    uint32_t v; asm volatile("ld.acquire.gpu.global.u32 %0, [%1];" : "=r"(v) : "l"(p) : "memory"); return v;
}
__device__ __forceinline__ void st_release1(uint32_t* p, uint32_t a) {
    asm volatile("st.release.gpu.global.u32 [%0], %1;" :: "l"(p), "r"(a) : "memory");
}
__device__ __forceinline__ uint4 lds4(uint32_t s) {
    uint4 v; asm volatile("ld.shared.v4.u32 {%0,%1,%2,%3}, [%4];" : "=r"(v.x), "=r"(v.y), "=r"(v.z), "=r"(v.w) : "r"(s) : "memory"); return v;
}
__device__ __forceinline__ void sts4(uint32_t s, const uint4& v) {
    asm volatile("st.shared.v4.u32 [%0], {%1,%2,%3,%4};" :: "r"(s), "r"(v.x), "r"(v.y), "r"(v.z), "r"(v.w) : "memory");
}
__device__ __forceinline__ float4 lds4f(uint32_t s) {
    float4 v; asm volatile("ld.shared.v4.f32 {%0,%1,%2,%3}, [%4];" : "=f"(v.x), "=f"(v.y), "=f"(v.z), "=f"(v.w) : "r"(s) : "memory"); return v;
}
__device__ __forceinline__ uint2 lds2(uint32_t s) {
    uint2 v; asm volatile("ld.shared.v2.u32 {%0,%1}, [%2];" : "=r"(v.x), "=r"(v.y) : "r"(s) : "memory"); return v;
}
__device__ __forceinline__ float2 lds2f(uint32_t s) {
    float2 v; asm volatile("ld.shared.v2.f32 {%0,%1}, [%2];" : "=f"(v.x), "=f"(v.y) : "r"(s) : "memory"); return v;
}
__device__ __forceinline__ uint32_t clk32() { uint32_t c; asm volatile("mov.u32 %0, %%clock;" : "=r"(c) :: "memory"); return c; }
__device__ __forceinline__ uint32_t tagw(float v, uint32_t tag) { return ((__float_as_uint(v) + 8u) & ~15u) | tag; }
__device__ __forceinline__ bool ok4(const uint4& v, uint32_t tag) { return (((v.x ^ tag) | (v.y ^ tag) | (v.z ^ tag) | (v.w ^ tag)) & 15u) == 0; }
__device__ __forceinline__ bool oks(const uint4& v) { return v.x != 0xFFFFFFFFu && v.y != 0xFFFFFFFFu && v.z != 0xFFFFFFFFu && v.w != 0xFFFFFFFFu; }
__device__ __forceinline__ float uf(uint32_t x) { return __uint_as_float(x & ~15u); }

template <int NT, int BAR>
__device__ __forceinline__ void mod_chunk(const bf16* __restrict__ c, const bf16* __restrict__ wmod, int col0, int tid, float* red) {
    constexpr int RG = NT / 8, NP = DM / RG;
    const int cc = tid & 7, rg = tid >> 3;
    uint4 w[NP];
    #pragma unroll
    for (int i = 0; i < NP; i++) w[i] = __ldg((const uint4*)(wmod + (size_t)(rg + i * RG) * (6 * DM) + col0 + cc * 8));
    float a[8];
    #pragma unroll
    for (int j = 0; j < 8; j++) a[j] = 0.f;
    #pragma unroll
    for (int i = 0; i < NP; i++) {
        const float v = __bfloat162float(c[rg + i * RG]);
        const float sv = bfr(v / (1.0f + __expf(-v)));
        a[0] += sv * bflo(w[i].x); a[1] += sv * bfhi(w[i].x); a[2] += sv * bflo(w[i].y); a[3] += sv * bfhi(w[i].y);
        a[4] += sv * bflo(w[i].z); a[5] += sv * bfhi(w[i].z); a[6] += sv * bflo(w[i].w); a[7] += sv * bfhi(w[i].w);
    }
    #pragma unroll
    for (int j = 0; j < 8; j++) {
        a[j] += __shfl_xor_sync(0xffffffffu, a[j], 8);
        a[j] += __shfl_xor_sync(0xffffffffu, a[j], 16);
    }
    if ((tid & 31) < 8) {
        float* d = red + (tid >> 5) * 64 + cc * 8;
        *(float4*)d = make_float4(a[0], a[1], a[2], a[3]);
        *(float4*)(d + 4) = make_float4(a[4], a[5], a[6], a[7]);
    }
    bar_sync(BAR, NT);
    if (tid < 64) {
        float s = 0.f;
        #pragma unroll
        for (int i = 0; i < NT / 32; i++) s += red[i * 64 + tid];
        g_mod[col0 + tid] = bfr(s);
    }
}

__device__ __forceinline__ void ln_stats(const float (*v)[4], float& mb, float& sd) {
    float s = 0.f;
    #pragma unroll
    for (int i = 0; i < 5; i++) s += (v[i][0] + v[i][1]) + (v[i][2] + v[i][3]);
    #pragma unroll
    for (int o = 16; o > 0; o >>= 1) s += __shfl_xor_sync(0xffffffffu, s, o);
    const float mean = s * (1.0f / DM);
    float q = 0.f;
    #pragma unroll
    for (int i = 0; i < 5; i++) {
        #pragma unroll
        for (int j = 0; j < 4; j++) { const float d = v[i][j] - mean; q += d * d; }
    }
    #pragma unroll
    for (int o = 16; o > 0; o >>= 1) q += __shfl_xor_sync(0xffffffffu, q, o);
    mb = bfr(mean);
    const float var = bfr(q * (1.0f / DM));
    sd = 1.0f / bfr(sqrtf(bfr(var + 1e-5f)));
}
__device__ __forceinline__ uint2 ln_apply(const float* v, float mb, float rs, const float4& sc, const float4& sh) {
    const float o0 = bfr(bfr(bfr(v[0] - mb) * rs) * bfr(1.0f + sc.x)) + sh.x;
    const float o1 = bfr(bfr(bfr(v[1] - mb) * rs) * bfr(1.0f + sc.y)) + sh.y;
    const float o2 = bfr(bfr(bfr(v[2] - mb) * rs) * bfr(1.0f + sc.z)) + sh.z;
    const float o3 = bfr(bfr(bfr(v[3] - mb) * rs) * bfr(1.0f + sc.w)) + sh.w;
    return make_uint2(pack2(o0, o1), pack2(o2, o3));
}

constexpr int PRE_CTAS = 32;
__global__ void __launch_bounds__(1024, 1) k_pre(const bf16* __restrict__ c, const bf16* __restrict__ wmod, const bf16* __restrict__ xin) {
    __shared__ __align__(16) float red[32 * 64];
    asm volatile("griddepcontrol.launch_dependents;" ::: "memory");
    const int tid = threadIdx.x, lane = tid & 31, warp = tid >> 5;
    const uint32_t tag = *(volatile uint32_t*)&g_epoch + 1u;
    if (tid == 0) T2(blockIdx.x);
    constexpr int RPW = SEQ / PRE_CTAS / 32;
    uint2 xr[RPW][5];
    #pragma unroll
    for (int r = 0; r < RPW; r++) {
        const int row = (r * PRE_CTAS + blockIdx.x) * 32 + warp;
        #pragma unroll
        for (int i = 0; i < 5; i++) xr[r][i] = __ldg((const uint2*)(xin + (size_t)row * DM + (i * 32 + lane) * 4));
    }
    if (blockIdx.x < 20) {
        mod_chunk<1024, 1>(c, wmod, blockIdx.x * 64, tid, red);
        if (tid < 64) {
            bar_sync(2, 64);
            if (tid == 0) { __threadfence(); st_release1(&g_pflag[blockIdx.x], tag); }
        }
    } else if (blockIdx.x == PRE_CTAS - 1) {
        if (tid < C_NUM) g_cnt[tid * 32] = 0u;
    }
    float mb[RPW], sd[RPW];
    #pragma unroll
    for (int r = 0; r < RPW; r++) {
        float v[5][4];
        #pragma unroll
        for (int i = 0; i < 5; i++) { v[i][0] = bflo(xr[r][i].x); v[i][1] = bfhi(xr[r][i].x); v[i][2] = bflo(xr[r][i].y); v[i][3] = bfhi(xr[r][i].y); }
        ln_stats(v, mb[r], sd[r]);
    }
    if (warp == 0) {
        uint32_t guard = 0;
        while (true) {
            const uint32_t v = lane < 20 ? ld_acquire1(&g_pflag[lane]) : tag;
            if (__all_sync(0xffffffffu, v == tag)) break;
            if (++guard > (1u << 22)) __trap();
        }
    }
    __syncthreads();
    if (tid < 320) *(float4*)(red + tid * 4) = __ldcg((const float4*)(g_mod + tid * 4));
    __syncthreads();
    #pragma unroll
    for (int i = 0; i < 5; i++) {
        const int col = (i * 32 + lane) * 4;
        const float4 sh = *(const float4*)(red + col), sc = *(const float4*)(red + DM + col);
        #pragma unroll
        for (int r = 0; r < RPW; r++) {
            const float v[4] = {bflo(xr[r][i].x), bfhi(xr[r][i].x), bflo(xr[r][i].y), bfhi(xr[r][i].y)};
            const int seg = r * PRE_CTAS + blockIdx.x, blk = col >> 6, cc = (col >> 3) & 7;
            *(uint2*)(g_ht + (size_t)seg * 20480 + blk * 2048 + warp * 64 + ((cc ^ (warp & 7)) << 3) + (col & 4)) = ln_apply(v, mb[r], sd[r], sc, sh);
        }
    }
    if (tid == 0) T2(32 + blockIdx.x);
}

constexpr int SM_WV = 0;
constexpr int SM_HB = 81920;
constexpr int SM_WO = SM_HB + 40960;
constexpr int SM_QX = SM_WO + 77824;
constexpr int SM_KS = SM_QX + 4096;
constexpr int SM_QM = SM_KS + 5120;
constexpr int SM_XS = SM_QM + 1024;
constexpr int SM_MS = SM_XS + 12288;
constexpr int SM_OS = SM_MS + 3840;
constexpr int SM_PM = SM_OS + 3072;
constexpr int SM_BAR = SM_PM + 640;
constexpr int SM_CH = SM_BAR + 128;
constexpr int SM_TOTAL = SM_CH + 128;
static_assert(SM_TOTAL <= 232448, "smem");

enum { B_MEM_FULL = 0, B_MEM_FREE, B_HLO_FULL, B_HHI_FULL, B_HLO_FREE, B_HHI_FREE, B_MS, B_O, B_XS, B_O1, B_XSFREE, B_WQ, B_WK, B_WV };

__device__ __forceinline__ int probe_blk(uint32_t* blk) {
    uint32_t t0 = 0xffffffffu, t1 = 0xffffffffu, acc = 0;
    for (int rep = 0; rep < 3; rep++) {
        #pragma unroll
        for (int pg = 0; pg < 2; pg++) {
            uint32_t c0 = clk32();
            uint32_t v = atomicOr(blk + pg * 1024 + acc, 0u);
            acc = (v == 0x12345678u) ? 1u : 0u;
            asm volatile("" :: "r"(acc) : "memory");
            uint32_t c1 = clk32() + acc;
            uint32_t d = c1 - c0;
            if (rep > 0) { if (pg == 0) t0 = min(t0, d); else t1 = min(t1, d); }
        }
    }
    return t1 < t0 ? 1 : 0;
}

__device__ __forceinline__ uint32_t wo_tile_off(int w) {
    if (w < 8) return w * 6144;
    if (w < 12) return 8 * 6144 + (w - 8) * 4096;
    return 8 * 6144 + 4 * 4096 + (w - 12) * 6144;
}

template <int NRES, int NPRE>
__device__ __forceinline__ void wo_phase(uint32_t sb, int w, int lane, const uint32_t (*res)[4], uint32_t parity,
                                         uint32_t tag, int tile, int h) {
    FRESH(lane);
    const int er = (lane & 7) + 8 * (lane >> 4);
    const uint32_t aaddr = sb + SM_WO + wo_tile_off(w) + er * 32 + ((((lane >> 3) & 1) ^ ((er >> 2) & 1)) << 4);
    const uint32_t baddr = sb + SM_OS + lane * 16;
    float c0[4] = {0.f, 0.f, 0.f, 0.f}, c1[4] = {0.f, 0.f, 0.f, 0.f};
    uint32_t pre[NPRE > 4 ? NPRE : 4][4];
    if (NPRE >= 4) {
        #pragma unroll
        for (int i = 0; i < 4; i++) ldsm4t(pre[i], aaddr + i * 512);
        mbar_wait(sb + SM_BAR + B_O1 * 8, parity);
        uint32_t b[2][4];
        ldsm4t(b[0], baddr);
        ldsm4t(b[1], baddr + 512);
        #pragma unroll
        for (int kp = 0; kp < 2; kp++) {
            mma16(c0, pre[2 * kp][0], pre[2 * kp][1], pre[2 * kp][2], pre[2 * kp][3], b[kp][0], b[kp][1]);
            mma16(c1, pre[2 * kp + 1][0], pre[2 * kp + 1][1], pre[2 * kp + 1][2], pre[2 * kp + 1][3], b[kp][2], b[kp][3]);
        }
    } else {
        #pragma unroll
        for (int i = 0; i < 2; i++) ldsm4t(pre[i], aaddr + i * 512);
        mbar_wait(sb + SM_BAR + B_O1 * 8, parity);
        #pragma unroll
        for (int kp = 0; kp < 2; kp++) {
            uint32_t b[4];
            ldsm4t(b, baddr + kp * 512);
            if (kp == 1) { ldsm4t(pre[0], aaddr + 2 * 512); ldsm4t(pre[1], aaddr + 3 * 512); }
            mma16(c0, pre[0][0], pre[0][1], pre[0][2], pre[0][3], b[0], b[1]);
            mma16(c1, pre[1][0], pre[1][1], pre[1][2], pre[1][3], b[2], b[3]);
        }
    }
    #pragma unroll
    for (int i = 0; i < NPRE; i++) ldsm4t(pre[i], aaddr + (4 + i) * 512);
    uint32_t off0, off1;
    {
        uint32_t ch;
        asm volatile("ld.shared.u16 %0, [%1];" : "=r"(ch) : "r"(sb + SM_CH + 2 * tile) : "memory");
        const int j = h >> 4;
        const uint32_t base = (uint32_t)((tile * 4 + j) * 8192 + (h & 15) * 256 + lane * 8);
        ch >>= j;
        off0 = base + (ch & 1) * 4096;
        off1 = base + 16384 + (ch & 256) * 16;
    }
    mbar_wait(sb + SM_BAR + B_O * 8, parity);
    if (NRES == 4) {
        uint32_t b[4][4];
        #pragma unroll
        for (int i = 0; i < 4; i++) ldsm4t(b[i], baddr + (2 + i) * 512);
        #pragma unroll
        for (int i = 0; i < 2; i++) {
            mma16(c0, res[2 * i][0], res[2 * i][1], res[2 * i][2], res[2 * i][3], b[i][0], b[i][1]);
            mma16(c1, res[2 * i + 1][0], res[2 * i + 1][1], res[2 * i + 1][2], res[2 * i + 1][3], b[i][2], b[i][3]);
        }
        #pragma unroll
        for (int i = 0; i < 2; i++) {
            mma16(c0, pre[2 * i][0], pre[2 * i][1], pre[2 * i][2], pre[2 * i][3], b[2 + i][0], b[2 + i][1]);
            mma16(c1, pre[2 * i + 1][0], pre[2 * i + 1][1], pre[2 * i + 1][2], pre[2 * i + 1][3], b[2 + i][2], b[2 + i][3]);
        }
    } else if (NPRE == 4) {
        uint32_t b[2][4];
        #pragma unroll
        for (int hh = 0; hh < 2; hh++) {
            ldsm4t(b[0], baddr + (2 + 2 * hh) * 512);
            ldsm4t(b[1], baddr + (3 + 2 * hh) * 512);
            if (hh) {
                #pragma unroll
                for (int i = 0; i < 4; i++) ldsm4t(pre[i], aaddr + (8 + i) * 512);
            }
            #pragma unroll
            for (int i = 0; i < 2; i++) {
                mma16(c0, pre[2 * i][0], pre[2 * i][1], pre[2 * i][2], pre[2 * i][3], b[i][0], b[i][1]);
                mma16(c1, pre[2 * i + 1][0], pre[2 * i + 1][1], pre[2 * i + 1][2], pre[2 * i + 1][3], b[i][2], b[i][3]);
            }
        }
    }
    st_relaxed2_off(g_buf1, off0, tagw(c0[0] + c1[0], tag), tagw(c0[1] + c1[1], tag));
    st_relaxed2_off(g_buf1, off1, tagw(c0[2] + c1[2], tag), tagw(c0[3] + c1[3], tag));
}

template <int NT, bool MASK>
__device__ __forceinline__ void softmax_core(float (*sc)[2], int g, int t, uint32_t* pb) {
    const float L2E = 1.4426950408889634f;
    #pragma unroll
    for (int j = 0; j < NT; j++) score2(sc[j][0], sc[j][1]);
    if (MASK) {
        const float NEG = -999292928.0f;
        if (2 * t > g) sc[NT - 1][0] = NEG;
        if (2 * t + 1 > g) sc[NT - 1][1] = NEG;
    }
    float m[NT];
    #pragma unroll
    for (int j = 0; j < NT; j++) m[j] = fmaxf(sc[j][0], sc[j][1]);
    float mx = m[0];
    #pragma unroll
    for (int j = 1; j < NT; j++) mx = fmaxf(mx, m[j]);
    mx = fmaxf(mx, __shfl_xor_sync(0xffffffffu, mx, 1));
    mx = fmaxf(mx, __shfl_xor_sync(0xffffffffu, mx, 2));
    float s0 = 0.f, s1 = 0.f;
    #pragma unroll
    for (int j = 0; j < NT; j++) {
        sc[j][0] = ex2((sc[j][0] - mx) * L2E); sc[j][1] = ex2((sc[j][1] - mx) * L2E);
        s0 += sc[j][0]; s1 += sc[j][1];
    }
    s0 += s1;
    s0 += __shfl_xor_sync(0xffffffffu, s0, 1);
    s0 += __shfl_xor_sync(0xffffffffu, s0, 2);
    const float iv = rcpf(s0);
    #pragma unroll
    for (int j = 0; j < NT; j++) pb[j] = pack2(sc[j][0] * iv, sc[j][1] * iv);
}
template <int NT>
__device__ __forceinline__ void xsoftmax(uint32_t a, int g, int t) {
    float sc[NT][2];
    #pragma unroll
    for (int j = 0; j < NT; j++) {
        float2 v0 = lds2f(a + j * 512), v1 = lds2f(a + j * 512 + 4096), v2 = lds2f(a + j * 512 + 8192);
        sc[j][0] = v0.x + v1.x + v2.x; sc[j][1] = v0.y + v1.y + v2.y;
    }
    uint32_t pb[NT];
    softmax_core<NT, true>(sc, g, t, pb);
    #pragma unroll
    for (int j = 0; j < NT; j += 2) {
        if (j + 1 < NT) asm volatile("st.shared.v2.u32 [%0], {%1,%2};" :: "r"(a + j * 512), "r"(pb[j]), "r"(pb[j + 1]) : "memory");
        else sts1(a + j * 512, pb[j]);
    }
}
template <int NJ>
__device__ __forceinline__ void xscores(uint32_t sb, int p, int mi, int j0, int lane) {
    FRESH(lane);
    const int r = lane & 7, cq = lane >> 3;
    const int qrow = mi * 16 + r + 8 * (cq & 1);
    uint32_t kb[NJ][8];
    float d[NJ][4];
    #pragma unroll
    for (int j = 0; j < NJ; j++) {
        ldsm4(kb[j], sb + SM_KS + ((j0 + j) * 8 + r) * 128 + ((cq ^ r) << 4));
        ldsm4(kb[j] + 4, sb + SM_KS + ((j0 + j) * 8 + r) * 128 + (((cq + 4) ^ r) << 4));
        d[j][0] = 0.f; d[j][1] = 0.f; d[j][2] = 0.f; d[j][3] = 0.f;
    }
    #pragma unroll
    for (int kt = 0; kt < 4; kt++) {
        uint32_t a[4];
        ldsm4(a, sb + SM_QX + qrow * 128 + (((2 * kt + (cq >> 1)) ^ r) << 4));
        #pragma unroll
        for (int j = 0; j < NJ; j++) mma16(d[j], a[0], a[1], a[2], a[3], kb[j][2 * kt], kb[j][2 * kt + 1]);
    }
    const uint32_t la = sb + SM_XS + p * 4096 + (mi * 3 + j0) * 512 + lane * 16;
    #pragma unroll
    for (int rk = 0; rk < 3; rk++) {
        const uint32_t ra = mapa(la, rk), rb = mapa(sb + SM_BAR + B_XS * 8, rk);
        #pragma unroll
        for (int j = 0; j < NJ; j++) st_async4(ra + j * 512, d[j], rb);
    }
}
__device__ __forceinline__ void mbar_arrive_remote(uint32_t bar) {
    asm volatile("mbarrier.arrive.relaxed.cluster.shared::cluster.b64 _, [%0];" :: "r"(bar) : "memory");
}

__device__ __forceinline__ void tma2d(uint32_t dst, const CUtensorMap* map, int c0, int c1, uint32_t bar) {
    asm volatile("cp.async.bulk.tensor.2d.shared::cluster.global.mbarrier::complete_tx::bytes [%0], [%1, {%2, %3}], [%4];"
                 :: "r"(dst), "l"(map), "r"(c0), "r"(c1), "r"(bar) : "memory");
}
__device__ __forceinline__ void tma2d_pf(const CUtensorMap* map, int c0, int c1) {
    asm volatile("cp.async.bulk.prefetch.tensor.2d.L2.global [%0, {%1, %2}];" :: "l"(map), "r"(c0), "r"(c1) : "memory");
}
__device__ __forceinline__ void bulk_pf(const void* p, uint32_t bytes) {
    asm volatile("cp.async.bulk.prefetch.L2.global [%0], %1;" :: "l"(p), "r"(bytes) : "memory");
}
struct RMaps { CUtensorMap wq, wk, wv; };
__device__ __forceinline__ void signal_cnt(int idx) {
    asm volatile("fence.proxy.async;\n\tfence.acq_rel.gpu;\n\tred.relaxed.gpu.global.add.u32 [%0], 1;" :: "l"(g_cnt + idx * 32) : "memory");
}

__global__ void __launch_bounds__(512, 1)
k_rec(const __grid_constant__ RMaps maps, const bf16* __restrict__ mem0, const bf16* __restrict__ Wo) {
    extern __shared__ __align__(1024) uint8_t smem_raw[];
    constexpr uint32_t SBC = 1024;
    const uint32_t sb = smem_u32(smem_raw);
    if ((sb & 0xFFFFFFu) != SBC) __trap();
    int lane = __shfl_sync(0xffffffffu, threadIdx.x & 31, threadIdx.x & 31);
    const int warp = __shfl_sync(0xffffffffu, threadIdx.x >> 5, 0), wg = warp >> 2;
    const int tid = warp * 32 + lane;
    const int b = blockIdx.x, h = b / 3, p = b % 3;
    const int g = lane >> 2, t = lane & 3;
    const int tile0 = p == 0 ? 0 : (p == 1 ? 14 : 27);
    const int ntile = p == 0 ? 14 : 13;
    const uint32_t bar = sb + SM_BAR;

    if (tid == 0) T2(100 + b);
    if (tid == 0) {
        mbar_init(bar + B_MEM_FULL * 8, 4);
        mbar_init(bar + B_MEM_FREE * 8, 12);
        mbar_init(bar + B_HLO_FULL * 8, 1);
        mbar_init(bar + B_HHI_FULL * 8, 1);
        mbar_init(bar + B_HLO_FREE * 8, 12);
        mbar_init(bar + B_HHI_FREE * 8, 12);
        mbar_init(bar + B_MS * 8, 1);
        mbar_init(bar + B_O * 8, 1);
        mbar_init(bar + B_XS * 8, 1);
        mbar_init(bar + B_O1 * 8, 4);
        mbar_init(bar + B_XSFREE * 8, 12);
        mbar_init(bar + B_WQ * 8, 1);
        mbar_init(bar + B_WK * 8, 1);
        mbar_init(bar + B_WV * 8, 1);
        asm volatile("fence.mbarrier_init.release.cluster;" ::: "memory");
        mbar_expect(bar + B_WQ * 8, 81920);
        mbar_expect(bar + B_WK * 8, 81920);
        #pragma unroll
        for (int i = 0; i < 5; i++) {
            tma2d(sb + SM_WO + i * 16384, &maps.wq, h * DH + p * 64, i * 128, bar + B_WQ * 8);
            tma2d(sb + SM_WV + i * 16384, &maps.wk, h * DH + p * 64, i * 128, bar + B_WK * 8);
        }
        #pragma unroll
        for (int i = 0; i < 5; i++) tma2d_pf(&maps.wv, h * DH + p * 64, i * 128);
        mbar_expect(bar + B_MS * 8, 3840);
        mbar_expect(bar + B_O * 8, 2048);
        mbar_expect(bar + B_XS * 8, 12288);
    }
    if (tid >= 128 && tid < 128 + DH) bulk_pf(Wo + ((size_t)h * DH + (tid - 128)) * DM + tile0 * 16, ntile * 32);
    cluster_sync();

    if (wg < 2) {
        asm volatile("setmaxnreg.inc.sync.aligned.u32 200;");
        const int w = warp & 3;
        uint32_t wa[40][4];
        {
            mbar_wait(bar + (wg == 0 ? B_WQ : B_WK) * 8, 0);
            const int r = lane & 7;
            const uint32_t wsrc = sb + (wg == 0 ? SM_WO : SM_WV) + (r + ((lane >> 4) << 3)) * 128 + (((2 * w + ((lane >> 3) & 1)) ^ r) << 4);
            #pragma unroll
            for (int kt = 0; kt < 40; kt++) ldsm4t(wa[kt], wsrc + kt * 2048);
            fence_async();
            bar_arrive(10 + wg, 256);
        }

        const uint32_t dstx = sb + (wg == 0 ? SM_QX : SM_KS + 1024);

        for (int s = -1; s < NSEG; s++) {
            const uint32_t par = s & 1;
            FRESH(lane);
            const int g = lane >> 2, t = lane & 3, tid = warp * 32 + lane;
            if (s >= 0) {
                mbar_wait(bar + B_MEM_FULL * 8, par);
                TR(0);
                float c[4][4];
                #pragma unroll
                for (int i = 0; i < 4; i++) { c[i][0] = 0.f; c[i][1] = 0.f; c[i][2] = 0.f; c[i][3] = 0.f; }
                uint32_t maddr = sb + lane * 16;
                asm volatile("" : "+r"(maddr));
                #pragma unroll
                for (int kp = 0; kp < 20; kp++) {
                    uint32_t bb[4];
                    ldsm4t(bb, maddr + (SM_HB + kp * 512));
                    mma16(c[(kp & 1) * 2], wa[2 * kp][0], wa[2 * kp][1], wa[2 * kp][2], wa[2 * kp][3], bb[0], bb[1]);
                    mma16(c[(kp & 1) * 2 + 1], wa[2 * kp + 1][0], wa[2 * kp + 1][1], wa[2 * kp + 1][2], wa[2 * kp + 1][3], bb[2], bb[3]);
                }
                {
                    const int tok = lane & 7, ch = 2 * w + ((lane >> 3) & 1);
                    stsm2t(sb + (wg == 0 ? SM_QM : SM_KS) + tok * 128 + ((ch ^ tok) << 4),
                           pack2((c[0][0] + c[1][0]) + (c[2][0] + c[3][0]), (c[0][1] + c[1][1]) + (c[2][1] + c[3][1])),
                           pack2((c[0][2] + c[1][2]) + (c[2][2] + c[3][2]), (c[0][3] + c[1][3]) + (c[2][3] + c[3][3])));
                }
                __syncwarp();
                if (lane == 0) mbar_arrive(bar + B_MEM_FREE * 8);
                TR(1);
                bar_sync(1, 256);
                if (warp < 5) {
                    const int r = lane & 7, cq = lane >> 3;
                    uint32_t a[8], kb[8];
                    ldsm4(a, sb + SM_QM + r * 128 + ((cq ^ r) << 4));
                    ldsm4(kb, sb + SM_KS + (warp * 8 + r) * 128 + ((cq ^ r) << 4));
                    ldsm4(a + 4, sb + SM_QM + r * 128 + (((cq + 4) ^ r) << 4));
                    ldsm4(kb + 4, sb + SM_KS + (warp * 8 + r) * 128 + (((cq + 4) ^ r) << 4));
                    float d0[4] = {0.f, 0.f, 0.f, 0.f}, d1[4] = {0.f, 0.f, 0.f, 0.f};
                    mma16(d0, a[0], 0u, a[1], 0u, kb[0], kb[1]);
                    mma16(d1, a[2], 0u, a[3], 0u, kb[2], kb[3]);
                    mma16(d0, a[4], 0u, a[5], 0u, kb[4], kb[5]);
                    mma16(d1, a[6], 0u, a[7], 0u, kb[6], kb[7]);
                    const uint32_t la = sb + SM_MS + p * 1280 + warp * 256 + lane * 8;
                    #pragma unroll
                    for (int rk = 0; rk < 3; rk++)
                        st_async2(mapa(la, rk), d0[0] + d1[0], d0[1] + d1[1], mapa(bar + B_MS * 8, rk));
                    bar_arrive(4, 352);
                } else if (warp < 7) {
                    xscores<1>(sb, p, warp - 5, 0, lane);
                    bar_arrive(4, 352);
                }
                TR(2);
                if (s < NSEG - 1) {
                    wo_phase<0, 4>(sb, warp, lane, nullptr, par, (uint32_t)(s % 15) + 1u, tile0 + warp, h);
                    TR(4);
                }
            }
            if (s < NSEG - 1) {
                FRESH(lane);
                const uint32_t hp = (s + 1) & 1;
                float d[16];
                const uint64_t db0 = make_desc(SBC + SM_HB, 16, 1024, 1);
                mbar_wait(bar + B_HHI_FULL * 8, hp);
                {
                    const int r = lane & 7, mq = lane >> 3;
                    const uint32_t ha = sb + SM_HB + 9 * 4096 + (8 * (mq >> 1) + r) * 128 + (((6 + (mq & 1)) ^ r) << 4);
                    uint32_t b0[4], b1[4];
                    ldsm4(b0, ha);
                    ldsm4(b1, ha + 2048);
                    #pragma unroll
                    for (int i = 0; i < 16; i++) d[i] = 0.f;
                    mma16(d + 0, wa[39][0], wa[39][1], wa[39][2], wa[39][3], b0[0], b0[1]);
                    mma16(d + 4, wa[39][0], wa[39][1], wa[39][2], wa[39][3], b0[2], b0[3]);
                    mma16(d + 8, wa[39][0], wa[39][1], wa[39][2], wa[39][3], b1[0], b1[1]);
                    mma16(d + 12, wa[39][0], wa[39][1], wa[39][2], wa[39][3], b1[2], b1[3]);
                    asm volatile("" : "+f"(d[0]), "+f"(d[4]), "+f"(d[8]), "+f"(d[12]) :: "memory");
                }
                if (s >= 0) bar_arrive(6, 512);
                mbar_wait(bar + B_HLO_FULL * 8, hp);
                bar_sync(9, 384);
                TR(6);
                wg_fence();
                #pragma unroll
                for (int kt = 0; kt < 12; kt++) wg_rs32(d, wa[kt], db0 + (uint64_t)(((kt >> 2) * 4096 + (kt & 3) * 32) >> 4), 1);
                wg_commit();
                #pragma unroll
                for (int kt = 12; kt < 39; kt++) wg_rs32(d, wa[kt], db0 + (uint64_t)(((kt >> 2) * 4096 + (kt & 3) * 32) >> 4), 1);
                wg_commit();
                wg_wait<1>();
                if (lane == 0) mbar_arrive(bar + B_HLO_FREE * 8);
                wg_wait<0>();
                if (lane == 0) mbar_arrive(bar + B_HHI_FREE * 8);
                TR(7);
                const int mi = lane >> 3, r = lane & 7;
                #pragma unroll
                for (int jj = 0; jj < 2; jj++) {
                    const int tok = 8 * (2 * jj + (mi >> 1)) + r, ch = 2 * w + (mi & 1);
                    stsm4t(dstx + tok * 128 + ((ch ^ r) << 4),
                           pack2(d[8 * jj + 0], d[8 * jj + 1]), pack2(d[8 * jj + 2], d[8 * jj + 3]),
                           pack2(d[8 * jj + 4], d[8 * jj + 5]), pack2(d[8 * jj + 6], d[8 * jj + 7]));
                }
                bar_arrive(8, 384);
                if (s < 0) { bar_sync(0, 512); asm volatile("griddepcontrol.launch_dependents;" ::: "memory"); }
            }
        }
    } else if (wg == 2) {
        asm volatile("setmaxnreg.dec.sync.aligned.u32 64;");
        const int w = warp & 3;
        uint32_t res[4][4];
        {
            const bf16* src = Wo + ((size_t)h * DH + ((p + 1) % 3) * 64) * DM + (tile0 + warp) * 16 + 2 * t;
            #pragma unroll
            for (int kt = 0; kt < 4; kt++) {
                res[kt][0] = __ldg((const uint32_t*)(src + (size_t)(kt * 16 + g) * DM));
                res[kt][1] = __ldg((const uint32_t*)(src + (size_t)(kt * 16 + g) * DM + 8));
                res[kt][2] = __ldg((const uint32_t*)(src + (size_t)(kt * 16 + 8 + g) * DM));
                res[kt][3] = __ldg((const uint32_t*)(src + (size_t)(kt * 16 + 8 + g) * DM + 8));
            }
            #pragma unroll
            for (int kt = 0; kt < 4; kt++) {
                #pragma unroll
                for (int i = 0; i < 4; i++) res[kt][i] = movm(res[kt][i]);
            }
        }
        bar_sync(11, 256);
        if (tid == 256) {
            fence_async();
            mbar_expect(bar + B_WV * 8, 81920);
            #pragma unroll
            for (int i = 0; i < 5; i++) tma2d(sb + SM_WV + i * 16384, &maps.wv, h * DH + p * 64, i * 128, bar + B_WV * 8);
        }
        mbar_wait(bar + B_WV * 8, 0);
        const uint64_t da0 = make_desc(SBC + SM_WV, 16, 1024, 1);
        uint32_t vx[8], vm0 = 0, vm1 = 0;
        #pragma unroll
        for (int i = 0; i < 8; i++) vx[i] = 0;

        for (int s = -1; s < NSEG; s++) {
            FRESH(lane);
            const int g = lane >> 2, t = lane & 3, tid = warp * 32 + lane;
            if (s >= 0) {
                const uint32_t par = s & 1;
                mbar_wait(bar + B_MEM_FULL * 8, par);
                bar_sync(4, 352);
                TR(0);
                float dv[4];
                {
                    const uint64_t dbm = make_desc(SBC + SM_HB, 128, 128, 0);
                    wg_fence();
                    #pragma unroll
                    for (int kt = 0; kt < 40; kt++) {
                        wg_ss8(dv, da0 + (uint64_t)(kt * 128), dbm + (uint64_t)(kt * 16), kt > 0);
                        wg_commit();
                        if (kt < 39) wg_wait<1>();
                    }
                    wg_commit();
                }
                TR(1);
                bar_sync(5, 160);
                TR(2);
                uint32_t pb[5];
                #pragma unroll
                for (int j = 0; j < 5; j++) pb[j] = lds1(sb + SM_PM + j * 128 + lane * 4);
                float o0[4] = {0.f, 0.f, 0.f, 0.f}, o1[4] = {0.f, 0.f, 0.f, 0.f}, o2[4] = {0.f, 0.f, 0.f, 0.f};
                wg_wait<0>();
                TR(3);
                mma16(o0, vx[0], vx[1], vx[2], vx[3], pb[1], pb[2]);
                mma16(o1, vx[4], vx[5], vx[6], vx[7], pb[3], pb[4]);
                vm0 = pack2(dv[0], dv[1]); vm1 = pack2(dv[2], dv[3]);
                mma8(o2, vm0, vm1, pb[0]);
                if (s < NSEG - 1) {
                    const uint32_t q0 = pack2(o0[0] + o1[0] + o2[0], o0[1] + o1[1] + o2[1]), q1 = pack2(o0[2] + o1[2] + o2[2], o0[3] + o1[3] + o2[3]);
                    const uint32_t la = sb + SM_OS + (w * 16 + g) * 16 + t * 4;
                    #pragma unroll
                    for (int i = 1; i < 3; i++) {
                        const uint32_t rk = (p + i) % 3;
                        const uint32_t ra = mapa(la + (3 - i) * 1024, rk), rb = mapa(bar + B_O * 8, rk);
                        st_async1(ra, q0, rb);
                        st_async1(ra + 128, q1, rb);
                    }
                    sts1(la, q0);
                    sts1(la + 128, q1);
                    __syncwarp();
                    if (lane == 0) { mbar_arrive(bar + B_O1 * 8); mbar_arrive(bar + B_MEM_FREE * 8); }
                }
                TR(5);
                if (s < NSEG - 1) {
                    wo_phase<4, 4>(sb, warp, lane, res, par, (uint32_t)(s % 15) + 1u, tile0 + warp, h);
                    TR(4);
                    if (tid == 256) mbar_expect(bar + B_O * 8, 2048);
                }
                if (s < NSEG - 1) bar_sync(6, 512);
            }
            uint32_t vn[8];
            #pragma unroll
            for (int i = 0; i < 8; i++) vn[i] = 0;
            if (s < NSEG - 1) {
            float d[16];
            const uint32_t hp = (s + 1) & 1;
            const uint64_t db0 = make_desc(SBC + SM_HB, 16, 1024, 1);
            mbar_wait(bar + B_HHI_FULL * 8, hp);
            TR(6);
            wg_fence();
            #pragma unroll
            for (int kt = 12; kt < 40; kt++) wg_ss32(d, da0 + (uint64_t)(kt * 128), db0 + (uint64_t)(((kt >> 2) * 4096 + (kt & 3) * 32) >> 4), kt > 12);
            wg_commit();
            mbar_wait(bar + B_HLO_FULL * 8, hp);
            wg_fence();
            #pragma unroll
            for (int kt = 0; kt < 9; kt++) wg_ss32(d, da0 + (uint64_t)(kt * 128), db0 + (uint64_t)(((kt >> 2) * 4096 + (kt & 3) * 32) >> 4), 1);
            wg_commit();
            #pragma unroll
            for (int kt = 9; kt < 12; kt++) wg_ss32(d, da0 + (uint64_t)(kt * 128), db0 + (uint64_t)(((kt >> 2) * 4096 + (kt & 3) * 32) >> 4), 1);
            wg_commit();
            wg_wait<1>();
            bar_arrive(9, 384);
            wg_wait<0>();
            if (lane == 0) mbar_arrive(bar + B_HLO_FREE * 8);
            TR(7);
            if (lane == 0) mbar_arrive(bar + B_HHI_FREE * 8);
            #pragma unroll
            for (int i = 0; i < 8; i++) vn[i] = pack2(d[2 * i], d[2 * i + 1]);
            }
            if (s >= 0) {
                {
                    FRESH(lane);
                    mbar_wait(bar + B_XS * 8, s & 1);
                    if (w == 0 && lane == 0) mbar_expect(bar + B_XS * 8, 12288);
                    const uint32_t a = sb + SM_XS + (w >> 1) * 1536 + lane * 16 + (w & 1) * 8;
                    if (w == 0) xsoftmax<2>(a, lane >> 2, lane & 3);
                    else if (w == 1) xsoftmax<3>(a, lane >> 2, lane & 3);
                    else if (w == 2) xsoftmax<4>(a, lane >> 2, lane & 3);
                    else xsoftmax<5>(a, lane >> 2, lane & 3);
                }
                TR(8);
                bar_sync(7, 128);
                FRESH(lane);
                bf16* orow = g_ox + (size_t)(s * 32 + (lane >> 2)) * HD + h * DH + p * 64 + w * 16 + 2 * (lane & 3);
                {
                    const uint32_t pa = sb + SM_XS + lane * 16;
                    #pragma unroll
                    for (int mi = 0; mi < 2; mi++) {
                        float oa[4] = {0.f, 0.f, 0.f, 0.f}, ob[4] = {0.f, 0.f, 0.f, 0.f};
                        if (mi == 0) {
                            const uint4 p0 = lds4(pa);
                            const uint32_t p3 = lds1(pa + 1024 + 8);
                            mma8(oa, vm0, vm1, p0.x);
                            mma8(ob, vm0, vm1, p0.z);
                            mma16(oa, vx[0], vx[1], vx[2], vx[3], p0.y, 0u);
                            mma16(ob, vx[0], vx[1], vx[2], vx[3], p0.w, p3);
                        } else {
                            const uint4 p1 = lds4(pa + 1536), p2 = lds4(pa + 2560);
                            const uint32_t p4 = lds1(pa + 3584 + 8);
                            mma8(oa, vm0, vm1, p1.x);
                            mma8(ob, vm0, vm1, p1.z);
                            mma16(oa, vx[0], vx[1], vx[2], vx[3], p1.y, p2.x);
                            mma16(ob, vx[0], vx[1], vx[2], vx[3], p1.w, p2.z);
                            mma16(oa, vx[4], vx[5], vx[6], vx[7], p2.y, 0u);
                            mma16(ob, vx[4], vx[5], vx[6], vx[7], p2.w, p4);
                            if (lane < 3) mbar_arrive_remote(mapa(bar + B_XSFREE * 8, lane));
                        }
                        const uint32_t u0 = movm(pack2(oa[0], oa[1])), u1 = movm(pack2(oa[2], oa[3]));
                        const uint32_t u2 = movm(pack2(ob[0], ob[1])), u3 = movm(pack2(ob[2], ob[3]));
                        bf16* dst = orow + (size_t)(16 * mi) * HD;
                        *(uint32_t*)dst = u0;
                        *(uint32_t*)(dst + 8) = u1;
                        *(uint32_t*)(dst + 8 * HD) = u2;
                        *(uint32_t*)(dst + 8 * HD + 8) = u3;
                    }
                }
                TR(9);
                if (s == NSEG - 1) {
                    bar_sync(7, 128);
                    if (w == 3 && lane == 0) { signal_cnt(C_REC + 15); T2(400 + b); }
                    break;
                }
            }
            #pragma unroll
            for (int i = 0; i < 8; i++) vx[i] = vn[i];
            if (s >= 0) mbar_wait_cluster(bar + B_XSFREE * 8, s & 1);
            bar_sync(8, 384);
            TR(10);
            if (w < 3) xscores<2>(sb, p, w > 0, w == 2 ? 3 : 1, lane);
            else if ((s & 3) == 3 && s >= 0 && lane == 0) signal_cnt(C_REC + (s >> 2));
            __syncwarp();
            TR(11);
            if (s < 0) { bar_sync(0, 512); asm volatile("griddepcontrol.launch_dependents;" ::: "memory"); }
        }
    } else {
        asm volatile("setmaxnreg.dec.sync.aligned.u32 48;");
        const int w = warp & 3, lt = tid & 127;
        const uint32_t epoch = *(volatile uint32_t*)&g_epoch + 1u;
        if (b < 80) {
            #pragma unroll
            for (int i = 0; i < 2; i++) {
                const int idx = lt + i * 128, sl = idx >> 6, pg = (idx >> 5) & 1, wd = idx & 31;
                st_relaxed1(g_buf2 + (sl * 3 + (b >> 5)) * 2048 + pg * 1024 + (b & 31) * 32 + wd, 0xFFFFFFFFu);
            }
            __threadfence();
        }
        if (lane == 0 && w < 3) {
            int c = 0;
            if (w == 0) c = probe_blk(g_buf2 + 640 + (b & 31) * 8);
            else if (b < 80) c = probe_blk(g_buf1 + (b * 2 + (w - 1)) * 2048);
            else if (b < 92 && w == 1) c = probe_blk(g_buf2 + (b - 80) * 2048 + 960);
            asm volatile("st.shared.u8 [%0], %1;" :: "r"(sb + SM_CH + 96 + w), "r"(c) : "memory");
        }
        bar_sync(3, 128);
        uint32_t selmask;
        {
            const uint32_t c3 = lds1(sb + SM_CH + 96);
            const uint32_t cr = c3 & 1u, c1 = (c3 >> 8) & 1u, c2 = (c3 >> 16) & 1u;
            if (lt == 0 && b < 92) st_release1(&g_choice[b], (epoch << 2) | (b < 80 ? (c1 | (c2 << 1)) : (c1 ^ cr)));
            bar_sync(10, 256);
        {
            const bf16* src0 = Wo + (size_t)h * DH * DM + tile0 * 16;
            const int nch = 2 * ntile;
            for (int i = lt; i < DH * nch; i += 128) {
                const int e = i / nch, c = i - e * nch, tl = c >> 1, cc = c & 1;
                int es = e;
                if (tl >= 8 && tl < 12) { if (e >= 64 && e < 128) continue; if (e >= 128) es = e - 64; }
                int eg = e + p * 64; if (eg >= DH) eg -= DH;
                cpa16(sb + SM_WO + wo_tile_off(tl) + es * 32 + ((cc ^ ((e >> 2) & 1)) << 4), src0 + (size_t)eg * DM + c * 8);
            }
        }
            if (lt < 92) {
                uint32_t v, guard = 0;
                while (true) {
                    v = ld_acquire1(&g_choice[lt]);
                    if ((v >> 2) == (epoch & 0x3fffffffu)) break;
                    __nanosleep(100);
                    if (++guard > (1u << 22)) __trap();
                }
                asm volatile("st.shared.u8 [%0], %1;" :: "r"(sb + SM_CH + lt), "r"(v & 3u) : "memory");
            }
        if (w == 3) {
            asm volatile("griddepcontrol.wait;" ::: "memory");
            if (lane == 0) {
                asm volatile("fence.proxy.async;" ::: "memory");
                mbar_expect(bar + B_HLO_FULL * 8, 12288);
                bulk_g2s(sb + SM_HB, g_ht, 12288, sb + SM_BAR + B_HLO_FULL * 8);
                mbar_expect(bar + B_HHI_FULL * 8, 28672);
                bulk_g2s(sb + SM_HB + 12288, (const char*)g_ht + 12288, 28672, sb + SM_BAR + B_HHI_FULL * 8);
            }
            __syncwarp();
        }
            bar_sync(3, 128);
            selmask = (c1 << 12) | (c2 << 13);
            for (int i = 0; i < 12; i++) {
                uint32_t c; asm volatile("ld.shared.u8 %0, [%1];" : "=r"(c) : "r"(sb + SM_CH + 80 + i) : "memory");
                selmask |= ((c ^ cr) & 1u) << i;
            }
        }
        cpa_wait_all();
        bar_sync(0, 512);
        asm volatile("griddepcontrol.launch_dependents;" ::: "memory");
        const bool has_tile = (12 + w) < ntile;
        for (int s = 0; s < NSEG; s++) {
            const uint32_t par = s & 1;
            FRESH(lane);
            const int g = lane >> 2, t = lane & 3, lt = w * 32 + lane;
            if (s == 0) {
                mbar_wait(bar + B_HLO_FREE * 8, par);
                for (int k = lt; k < DM; k += 128) {
                    uint32_t v[4];
                    #pragma unroll
                    for (int i = 0; i < 4; i++) {
                        uint32_t lo = *(const uint16_t*)(mem0 + (2 * i) * DM + k), hi = *(const uint16_t*)(mem0 + (2 * i + 1) * DM + k);
                        v[i] = lo | (hi << 16);
                    }
                    asm volatile("st.shared.v4.u32 [%0], {%1,%2,%3,%4};" :: "r"(sb + SM_HB + k * 16), "r"(v[0]), "r"(v[1]), "r"(v[2]), "r"(v[3]) : "memory");
                }
            } else {
                const int sl = s & 3;
                const char* q = (const char*)g_buf2 + sl * 3 * 8192 + lt * 16;
                const uint32_t sm = selmask >> (sl * 3);
                const char* q0 = q + (sm & 1) * 4096;
                const char* q1 = q + 8192 + (sm & 2) * 2048;
                const char* q2 = q + 16384 + (sm & 4) * 1024;
                const uint32_t dst = sb + SM_HB + lt * 16;
                uint32_t guard = 0;
                mbar_wait(bar + B_HLO_FREE * 8, par);
                TR(10);
                while (true) {
                    const uint4 v0 = ld_relaxed4(q0), v1 = ld_relaxed4(q0 + 2048), v2 = ld_relaxed4(q1), v3 = ld_relaxed4(q1 + 2048), v4 = ld_relaxed4(q2);
                    sts4(dst, v0); sts4(dst + 2048, v1); sts4(dst + 4096, v2); sts4(dst + 6144, v3); sts4(dst + 8192, v4);
                    if (__all_sync(0xffffffffu, oks(v0) && oks(v1) && oks(v2) && oks(v3) && oks(v4))) break;
                    if (++guard > (1u << 22)) __trap();
                }
            }
            fence_async();
            __syncwarp();
            if (lane == 0) mbar_arrive(bar + B_MEM_FULL * 8);
            if (b == 0 && lt == 0) T2(300 + s);
            if (s == 0 && lt == 0) T2(200 + b);
            TR(0);
            if (w == 2) {
                mbar_wait(bar + B_MS * 8, par);
                TR(1);
                if (lane == 0) mbar_expect(bar + B_MS * 8, 3840);
                uint32_t pb[5];
                float sc[5][2];
                {
                    const uint32_t a = sb + SM_MS + lane * 8;
                    float2 u[5], v[5];
                    #pragma unroll
                    for (int j = 0; j < 5; j++) { u[j] = lds2f(a + j * 256); v[j] = lds2f(a + j * 256 + 1280); }
                    #pragma unroll
                    for (int j = 0; j < 5; j++) { sc[j][0] = u[j].x + v[j].x; sc[j][1] = u[j].y + v[j].y; }
                    #pragma unroll
                    for (int j = 0; j < 5; j++) u[j] = lds2f(a + j * 256 + 2560);
                    #pragma unroll
                    for (int j = 0; j < 5; j++) { sc[j][0] += u[j].x; sc[j][1] += u[j].y; }
                }
                softmax_core<5, false>(sc, g, t, pb);
                #pragma unroll
                for (int j = 0; j < 5; j++) sts1(sb + SM_PM + j * 128 + lane * 4, pb[j]);
                bar_arrive(5, 160);
                TR(2);
            }
            const uint32_t tag = (uint32_t)(s % 15) + 1u;
            if (s < NSEG - 1) {
                if (w == 3) {
                    const char* src = (const char*)g_ht + (size_t)(s + 1) * 40960;
                    mbar_wait(bar + B_HHI_FREE * 8, par);
                    if (lane == 0) {
                        mbar_expect(bar + B_HHI_FULL * 8, 28672);
                        bulk_g2s(sb + SM_HB + 12288, src + 12288, 28672, sb + SM_BAR + B_HHI_FULL * 8);
                    }
                    mbar_wait(bar + B_MEM_FREE * 8, par);
                    if (lane == 0) {
                        mbar_expect(bar + B_HLO_FULL * 8, 12288);
                        bulk_g2s(sb + SM_HB, src, 12288, sb + SM_BAR + B_HLO_FULL * 8);
                    }
                    __syncwarp();
                }
                if (has_tile) wo_phase<0, 4>(sb, warp, lane, nullptr, par, tag, tile0 + warp, h);
                TR(4);
                bar_sync(6, 512);
            }
            if (s < NSEG - 1) {
                { const uint32_t c0 = clk32(); while (clk32() - c0 < H1_DELAY); }
                if (b < 80) {
                    FRESH(lane);
                    const char* rin0 = (const char*)g_buf1 + (size_t)(b * 2) * 8192 + ((selmask >> 12) & 1) * 4096 + (lane >> 2) * 256 + w * 64 + (lane & 3) * 16;
                    const char* rin1 = (const char*)g_buf1 + (size_t)(b * 2 + 1) * 8192 + ((selmask >> 13) & 1) * 4096 + (lane >> 2) * 256 + w * 64 + (lane & 3) * 16;
                    const int col = b * 8 + 2 * w + ((lane >> 1) & 1), wd = 2 * (lane & 1) + (lane >> 4);
                    const int sl = (lane & 8) ? ((s + 3) & 3) : ((s + 1) & 3);
                    uint32_t* dst = g_buf2 + (sl * 3 + (col >> 8)) * 2048 + ((lane >> 2) & 1) * 1024 + (col & 255) * 4 + wd;
                    asm volatile("" : "+l"(dst));
                    uint4 v0, v1, v2, v3;
                    uint32_t guard = 0;
                    while (true) {
                        v0 = ld_relaxed4(rin0); v1 = ld_relaxed4(rin0 + 2048);
                        v2 = ld_relaxed4(rin1); v3 = ld_relaxed4(rin1 + 2048);
                        if (__all_sync(0xffffffffu, ok4(v0, tag) && ok4(v1, tag) && ok4(v2, tag) && ok4(v3, tag))) break;
                        if (++guard > (1u << 22)) __trap();
                    }
                    TR(11);
                    const float a0 = (uf(v0.x) + uf(v1.x)) + (uf(v2.x) + uf(v3.x)), a1 = (uf(v0.y) + uf(v1.y)) + (uf(v2.y) + uf(v3.y));
                    const float a2 = (uf(v0.z) + uf(v1.z)) + (uf(v2.z) + uf(v3.z)), a3 = (uf(v0.w) + uf(v1.w)) + (uf(v2.w) + uf(v3.w));
                    const bool u16 = lane & 16;
                    float m0 = (u16 ? a2 : a0) + __shfl_xor_sync(0xffffffffu, u16 ? a0 : a2, 16);
                    float m1 = (u16 ? a3 : a1) + __shfl_xor_sync(0xffffffffu, u16 ? a1 : a3, 16);
                    m0 += __shfl_xor_sync(0xffffffffu, m0, 8); m1 += __shfl_xor_sync(0xffffffffu, m1, 8);
                    m0 += __shfl_xor_sync(0xffffffffu, m0, 4); m1 += __shfl_xor_sync(0xffffffffu, m1, 4);
                    st_relaxed1(dst, (lane & 8) ? 0xFFFFFFFFu : pack2(m0, m1));
                    TR(12);
                }
            }
        }
    }
    cluster_sync();
}

constexpr int G_STAGES = 6;
constexpr int G_STAGE_BYTES = 32768;
constexpr int G_SMEM = G_STAGES * G_STAGE_BYTES + 1024 + 256 + 2048 + 10240;

__device__ __forceinline__ void wg_ss128(float* d, uint64_t da, uint64_t db, int sc) {
    asm volatile("{\n\t.reg .pred p;\n\tsetp.ne.b32 p, %66, 0;\n\t"
        "wgmma.mma_async.sync.aligned.m64n128k16.f32.bf16.bf16 "
        "{%0,%1,%2,%3,%4,%5,%6,%7,%8,%9,%10,%11,%12,%13,%14,%15,%16,%17,%18,%19,%20,%21,%22,%23,%24,%25,%26,%27,%28,%29,%30,%31,"
        "%32,%33,%34,%35,%36,%37,%38,%39,%40,%41,%42,%43,%44,%45,%46,%47,%48,%49,%50,%51,%52,%53,%54,%55,%56,%57,%58,%59,%60,%61,%62,%63}, "
        "%64, %65, p, 1, 1, 0, 1;\n\t}"
        : "+f"(d[0]), "+f"(d[1]), "+f"(d[2]), "+f"(d[3]), "+f"(d[4]), "+f"(d[5]), "+f"(d[6]), "+f"(d[7]),
          "+f"(d[8]), "+f"(d[9]), "+f"(d[10]), "+f"(d[11]), "+f"(d[12]), "+f"(d[13]), "+f"(d[14]), "+f"(d[15]),
          "+f"(d[16]), "+f"(d[17]), "+f"(d[18]), "+f"(d[19]), "+f"(d[20]), "+f"(d[21]), "+f"(d[22]), "+f"(d[23]),
          "+f"(d[24]), "+f"(d[25]), "+f"(d[26]), "+f"(d[27]), "+f"(d[28]), "+f"(d[29]), "+f"(d[30]), "+f"(d[31]),
          "+f"(d[32]), "+f"(d[33]), "+f"(d[34]), "+f"(d[35]), "+f"(d[36]), "+f"(d[37]), "+f"(d[38]), "+f"(d[39]),
          "+f"(d[40]), "+f"(d[41]), "+f"(d[42]), "+f"(d[43]), "+f"(d[44]), "+f"(d[45]), "+f"(d[46]), "+f"(d[47]),
          "+f"(d[48]), "+f"(d[49]), "+f"(d[50]), "+f"(d[51]), "+f"(d[52]), "+f"(d[53]), "+f"(d[54]), "+f"(d[55]),
          "+f"(d[56]), "+f"(d[57]), "+f"(d[58]), "+f"(d[59]), "+f"(d[60]), "+f"(d[61]), "+f"(d[62]), "+f"(d[63])
        : "l"(da), "l"(db), "r"(sc));
}

#define SP0_LAST 12
#define SP2_LAST 6
enum { J_MOD = 0, J_G0, J_LN, J_G1, J_G2, J_FIN, J_END };
__host__ __device__ constexpr int sp0(int b) { return b >= 15 ? SP0_LAST : 3; }
__host__ __device__ constexpr int sp2(int b) { return b >= 15 ? SP2_LAST : 3; }
__host__ __device__ constexpr int njr(int b) { return b >= 15 ? 16 : 8; }
struct JobTab { uint32_t n; uint32_t j[1200]; };
constexpr uint32_t mkjob(int ty, int b, int n, int k0, int nk, int ks) {
    return (uint32_t)(ty | (b << 3) | (n << 7) | (k0 << 11) | (nk << 18) | (ks << 25));
}
constexpr void add_jobs(JobTab& t, int ty, int b) {
    if (b < 0) return;
    if (ty == J_G0) { for (int ks = 0; ks < sp0(b); ks++) for (int n = 0; n < 5; n++) t.j[t.n++] = mkjob(ty, b, n, ks * (96 / sp0(b)), 96 / sp0(b), ks); }
    else if (ty == J_G2) { for (int ks = 0; ks < sp2(b); ks++) for (int n = 0; n < 5; n++) t.j[t.n++] = mkjob(ty, b, n, ks * (24 / sp2(b)), 24 / sp2(b), ks); }
    else if (ty == J_G1) { for (int n = 0; n < 12; n++) t.j[t.n++] = mkjob(ty, b, n, 0, 10, 0); }
    else { for (int n = 0; n < njr(b); n++) t.j[t.n++] = mkjob(ty, b, n, 0, 16 / njr(b), ty == J_LN ? sp0(b) : sp2(b)); }
}
constexpr JobTab make_tab() {
    JobTab t = {};
    for (int i = 20; i < 60; i++) t.j[t.n++] = mkjob(J_MOD, 0, 0, i, 0, 0);
    for (int b = 0; b < 15; b++) {
        add_jobs(t, J_G0, b); add_jobs(t, J_G1, b - 1); add_jobs(t, J_FIN, b - 2); add_jobs(t, J_G2, b - 1); add_jobs(t, J_LN, b);
    }
    add_jobs(t, J_FIN, 13); add_jobs(t, J_G1, 14);
    add_jobs(t, J_G0, 15); add_jobs(t, J_G2, 14); add_jobs(t, J_LN, 15); add_jobs(t, J_FIN, 14);
    add_jobs(t, J_G1, 15); add_jobs(t, J_G2, 15); add_jobs(t, J_FIN, 15);
    return t;
}
__constant__ JobTab c_jobs = make_tab();

__device__ __forceinline__ bool cnt_ge(int idx, uint32_t target) { return ld_acquire1(g_cnt + idx * 32) >= target; }
__device__ __forceinline__ void cnt_wait(int idx, uint32_t target) {
    uint32_t guard = 0;
    while (!cnt_ge(idx, target)) { __nanosleep(64); if (++guard > (1u << 22)) __trap(); }
}

struct SMaps { CUtensorMap ox, wo, h2, w1, act, w2; };

__global__ void __launch_bounds__(384, 1)
k_side(const __grid_constant__ SMaps maps, const bf16* __restrict__ xin, const bf16* __restrict__ cvec,
       const bf16* __restrict__ wmod, bf16* __restrict__ outp) {
    extern __shared__ uint8_t smem_raw[];
    const uint32_t sb = (smem_u32(smem_raw) + 1023u) & ~1023u;
    const uint32_t bars = sb + G_STAGES * G_STAGE_BYTES;
    float* red = (float*)(smem_raw + (bars + 256 - smem_u32(smem_raw)));
    const int tid = threadIdx.x, lane = tid & 31, wg = tid >> 7;
    if (tid == 0) T2(500 + blockIdx.x);
    if (tid == 0) {
        for (int i = 0; i < G_STAGES; i++) { mbar_init(bars + i * 8, 1); mbar_init(bars + 64 + i * 8, 8); }
        for (int i = 0; i < 2; i++) { mbar_init(bars + 128 + i * 8, 1); mbar_init(bars + 144 + i * 8, 8); }
        asm volatile("fence.mbarrier_init.release.cluster;" ::: "memory");
    }
    __syncthreads();
    if (wg == 0) {
        if (tid == 0) {
            uint32_t st = 0, ph = 1;
            for (uint32_t it = 0;; it++) {
                const uint32_t ji = atomicAdd(g_cnt + C_Q * 32, 1u);
                const uint32_t job = ji < c_jobs.n ? c_jobs.j[ji] : (uint32_t)J_END;
                if (ji == 0) g_epoch = g_epoch + 1u;
                const int ty = job & 7, b = (job >> 3) & 15, n = (job >> 7) & 15, k0 = (job >> 11) & 127, nk = (job >> 18) & 127;
                const uint32_t sl = it & 1;
                mbar_wait(bars + 144 + sl * 8, ((it >> 1) & 1) ^ 1);
                sts1(bars + 160 + sl * 4, job);
                if (ty == J_G0 || ty == J_G1 || ty == J_G2) {
                    if (b >= PRING && ty != J_G1) cnt_wait((ty == J_G0 ? C_LN : C_FIN) + b - PRING, njr(b - PRING));
                    mbar_arrive(bars + 128 + sl * 8);
                    const CUtensorMap* mA = ty == J_G0 ? &maps.ox : (ty == J_G1 ? &maps.h2 : &maps.act);
                    const CUtensorMap* mB = ty == J_G0 ? &maps.wo : (ty == J_G1 ? &maps.w1 : &maps.w2);
                    const int didx = ty == J_G0 ? C_REC + b : (ty == J_G1 ? C_LN + b : C_G1 + b);
                    const uint32_t dtgt = ty == J_G0 ? 96u : (ty == J_G1 ? (uint32_t)njr(b) : 12u);
                    int pre = 0;
                    if (!cnt_ge(didx, dtgt)) {
                        pre = nk < G_STAGES ? nk : G_STAGES;
                        uint32_t s2 = st, p2 = ph;
                        for (int i = 0; i < pre; i++) {
                            mbar_wait(bars + 64 + s2 * 8, p2);
                            const uint32_t a = sb + s2 * G_STAGE_BYTES;
                            mbar_expect(bars + s2 * 8, G_STAGE_BYTES);
                            tma2d(a + 16384, mB, n * 128, (k0 + i) * 64, bars + s2 * 8);
                            tma2d(a + 16384 + 8192, mB, n * 128 + 64, (k0 + i) * 64, bars + s2 * 8);
                            if (++s2 == G_STAGES) { s2 = 0; p2 ^= 1; }
                        }
                        cnt_wait(didx, dtgt);
                    }
                    asm volatile("fence.proxy.async;" ::: "memory");
                    T2(1024 + ji * 4 + 1);
                    for (int i = 0; i < nk; i++) {
                        const uint32_t a = sb + st * G_STAGE_BYTES;
                        if (i >= pre) {
                            mbar_wait(bars + 64 + st * 8, ph);
                            mbar_expect(bars + st * 8, G_STAGE_BYTES);
                        }
                        tma2d(a, mA, (k0 + i) * 64, b * 128, bars + st * 8);
                        if (i >= pre) {
                            tma2d(a + 16384, mB, n * 128, (k0 + i) * 64, bars + st * 8);
                            tma2d(a + 16384 + 8192, mB, n * 128 + 64, (k0 + i) * 64, bars + st * 8);
                        }
                        if (++st == G_STAGES) { st = 0; ph ^= 1; }
                    }
                } else {
                    if (ty == J_LN) { bulk_pf(xin + (size_t)(b * 128 + n * nk * 8) * DM, nk * 8 * DM * 2); cnt_wait(C_MOD, 40u); cnt_wait(C_G0 + b, 5u * sp0(b)); }
                    else if (ty == J_FIN) cnt_wait(C_G2 + b, 5u * sp2(b));
                    if (ji < 1200) T2(1024 + ji * 4 + 1);
                    mbar_arrive(bars + 128 + sl * 8);
                    if (ty == J_END) break;
                }
            }
        }
    } else {
        const int cw = wg - 1, ct = tid - 128, cwarp = ct >> 5;
        uint32_t st = 0, ph = 0;
        float* smod = red + 512;
        bool have_mod = false;
        auto load_mod = [&]() {
            for (int i = ct; i < DM; i += 256) *(float4*)(smod + i * 4) = __ldcg((const float4*)(g_mod + 2 * DM + i * 4));
            bar_sync(1, 256);
            have_mod = true;
        };
        {
            if (ct == 0) red[0] = cnt_ge(C_MOD, 40u) ? 1.0f : 0.0f;
            bar_sync(1, 256);
            const bool rdy = red[0] != 0.0f;
            bar_sync(1, 256);
            if (rdy) load_mod();
        }
        for (uint32_t it = 0;; it++) {
            const uint32_t sl = it & 1;
            mbar_wait(bars + 128 + sl * 8, (it >> 1) & 1);
            const uint32_t job = lds1(bars + 160 + sl * 4);
            __syncwarp();
            if (lane == 0) mbar_arrive(bars + 144 + sl * 8);
            const int ty = job & 7, b = (job >> 3) & 15, n = (job >> 7) & 15, k0 = (job >> 11) & 127, nk = (job >> 18) & 127, ks = (job >> 25) & 15;
            if (ty == J_END) break;
            int sig = -1;
            if (ty == J_G0 || ty == J_G1 || ty == J_G2) {
                float d[64];
                #pragma unroll
                for (int i = 0; i < 64; i++) d[i] = 0.f;
                uint32_t pst = 0;
                for (int kb = 0; kb < nk; kb++) {
                    mbar_wait(bars + st * 8, ph);
                    const uint32_t a = sb + st * G_STAGE_BYTES;
                    const uint64_t da = make_desc(a + cw * 8192, 16, 1024, 1);
                    const uint64_t db = make_desc(a + 16384, 8192, 1024, 1);
                    wg_fence();
                    #pragma unroll
                    for (int k = 0; k < 4; k++) wg_ss128(d, da + (uint64_t)(k * 2), db + (uint64_t)(k * 128), 1);
                    wg_commit();
                    if (kb > 0) {
                        wg_wait<1>();
                        if (lane == 0) mbar_arrive(bars + 64 + pst * 8);
                    }
                    pst = st;
                    if (++st == G_STAGES) { st = 0; ph ^= 1; }
                }
                wg_wait<0>();
                if (lane == 0) mbar_arrive(bars + 64 + pst * 8);
                const int g = lane >> 2, t = lane & 3;
                if (ty == J_G1) {
                    #pragma unroll
                    for (int hf = 0; hf < 2; hf++) {
                        bf16* o = g_act + (size_t)(b * 128 + cwarp * 16 + g + 8 * hf) * FF + n * 128 + 8 * t;
                        #pragma unroll
                        for (int q = 0; q < 4; q++) {
                            uint32_t u[4];
                            #pragma unroll
                            for (int i = 0; i < 4; i++) {
                                const float a0 = bfr(d[4 * (4 * q + i) + 2 * hf]), a1 = bfr(d[4 * (4 * q + i) + 2 * hf + 1]);
                                u[i] = pack2(__fdividef(a0, 1.0f + __expf(-a0)), __fdividef(a1, 1.0f + __expf(-a1)));
                            }
                            const bool o1 = t & 1, o2 = t & 2;
                            uint32_t x0 = __shfl_xor_sync(0xffffffffu, o1 ? u[0] : u[1], 1), x1 = __shfl_xor_sync(0xffffffffu, o1 ? u[2] : u[3], 1);
                            if (o1) { u[0] = x0; u[2] = x1; } else { u[1] = x0; u[3] = x1; }
                            x0 = __shfl_xor_sync(0xffffffffu, o2 ? u[0] : u[2], 2); x1 = __shfl_xor_sync(0xffffffffu, o2 ? u[1] : u[3], 2);
                            if (o2) { u[0] = x0; u[1] = x1; } else { u[2] = x0; u[3] = x1; }
                            *(uint4*)(o + q * 32) = make_uint4(u[0], u[1], u[2], u[3]);
                        }
                    }
                    sig = C_G1 + b;
                } else {
                    float* o = (ty == J_G0 ? g_p0 : g_p2) + ((size_t)((b % PRING) * PMAX + ks) * 128 + cwarp * 16 + g) * DM + n * 128 + 2 * t;
                    #pragma unroll
                    for (int hf = 0; hf < 2; hf++) {
                        #pragma unroll
                        for (int j = 0; j < 16; j++)
                            *(float2*)(o + hf * 8 * DM + j * 8) = make_float2(d[4 * j + 2 * hf], d[4 * j + 2 * hf + 1]);
                    }
                    sig = (ty == J_G0 ? C_G0 : C_G2) + b;
                }
            } else if (ty == J_MOD) {
                mod_chunk<256, 2>(cvec, wmod, k0 * 64, ct, red);
                sig = C_MOD;
            } else {
                const bool ln = ty == J_LN;
                if (!have_mod) load_mod();
                const float* gm = smod + (ln ? 0 : 3) * DM + lane * 4;
                for (int r = 0; r < nk; r++) {
                    const int lr = (n * nk + r) * 8 + cwarp, row = b * 128 + lr;
                    const float* pp = (ln ? g_p0 : g_p2) + ((size_t)((b % PRING) * PMAX) * 128 + lr) * DM + lane * 4;
                    const bf16* xs = (ln ? xin : (const bf16*)g_x1) + (size_t)row * DM + lane * 4;
                    float v[5][4];
                    uint2 xv[5];
                    #pragma unroll
                    for (int i = 0; i < 5; i++) {
                        xv[i] = __ldcg((const uint2*)(xs + i * 128));
                        v[i][0] = 0.f; v[i][1] = 0.f; v[i][2] = 0.f; v[i][3] = 0.f;
                    }
                    if (ks == 3) {
                        float4 a[3][5];
                        #pragma unroll
                        for (int q = 0; q < 3; q++) {
                            #pragma unroll
                            for (int i = 0; i < 5; i++) a[q][i] = __ldcg((const float4*)(pp + (size_t)q * 128 * DM + i * 128));
                        }
                        #pragma unroll
                        for (int q = 0; q < 3; q++) {
                            #pragma unroll
                            for (int i = 0; i < 5; i++) { v[i][0] += a[q][i].x; v[i][1] += a[q][i].y; v[i][2] += a[q][i].z; v[i][3] += a[q][i].w; }
                        }
                    } else {
                        for (int q0 = 0; q0 < ks; q0 += 6) {
                            float4 a[6][5];
                            #pragma unroll
                            for (int q = 0; q < 6; q++) {
                                #pragma unroll
                                for (int i = 0; i < 5; i++) a[q][i] = __ldcg((const float4*)(pp + (size_t)(q0 + q) * 128 * DM + i * 128));
                            }
                            #pragma unroll
                            for (int q = 0; q < 6; q++) {
                                #pragma unroll
                                for (int i = 0; i < 5; i++) { v[i][0] += a[q][i].x; v[i][1] += a[q][i].y; v[i][2] += a[q][i].z; v[i][3] += a[q][i].w; }
                            }
                        }
                    }
                    bf16* dst = (ln ? (bf16*)g_x1 : outp) + (size_t)row * DM + lane * 4;
                    #pragma unroll
                    for (int i = 0; i < 5; i++) {
                        const float4 gg = *(const float4*)(gm + i * 128);
                        const uint32_t o0 = pack2(bflo(xv[i].x) + bfr(gg.x * bfr(v[i][0])), bfhi(xv[i].x) + bfr(gg.y * bfr(v[i][1])));
                        const uint32_t o1 = pack2(bflo(xv[i].y) + bfr(gg.z * bfr(v[i][2])), bfhi(xv[i].y) + bfr(gg.w * bfr(v[i][3])));
                        *(uint2*)(dst + i * 128) = make_uint2(o0, o1);
                        v[i][0] = bflo(o0); v[i][1] = bfhi(o0); v[i][2] = bflo(o1); v[i][3] = bfhi(o1);
                    }
                    if (ln) {
                        float mb, sd;
                        ln_stats(v, mb, sd);
                        #pragma unroll
                        for (int i = 0; i < 5; i++) {
                            const float4 sh = *(const float4*)(gm + DM + i * 128), sc = *(const float4*)(gm + 2 * DM + i * 128);
                            *(uint2*)(g_h2 + (size_t)row * DM + lane * 4 + i * 128) = ln_apply(v[i], mb, sd, sc, sh);
                        }
                    }
                }
                if (ln) sig = C_LN + b; else if (b < 16 - PRING) sig = C_FIN + b;
            }
            if (sig >= 0) {
                bar_sync(1, 256);
                if (ct == 0) signal_cnt(sig);
            }
            if (ct == 0) T2(1024 + ji * 4 + 2);
        }
    }
}

typedef CUresult (*EncodeFn)(CUtensorMap*, CUtensorMapDataType, cuuint32_t, void*, const cuuint64_t*, const cuuint64_t*,
                             const cuuint32_t*, const cuuint32_t*, CUtensorMapInterleave, CUtensorMapSwizzle,
                             CUtensorMapL2promotion, CUtensorMapFloatOOBfill);

static void make_map(EncodeFn fn, CUtensorMap* m, const void* ptr, uint64_t inner, uint64_t outer, uint32_t bi, uint32_t bo) {
    cuuint64_t dims[2] = {inner, outer};
    cuuint64_t strides[1] = {inner * 2};
    cuuint32_t box[2] = {bi, bo};
    cuuint32_t es[2] = {1, 1};
    fn(m, CU_TENSOR_MAP_DATA_TYPE_BFLOAT16, 2, (void*)ptr, dims, strides, box, es, CU_TENSOR_MAP_INTERLEAVE_NONE,
       CU_TENSOR_MAP_SWIZZLE_128B, CU_TENSOR_MAP_L2_PROMOTION_L2_256B, CU_TENSOR_MAP_FLOAT_OOB_FILL_NONE);
}

extern "C" void kernel_launch(void* const* d_in, const int* in_sizes, int n_in, void* d_out, int out_size) {
    const bf16* x = (const bf16*)d_in[0];
    const bf16* mem0 = (const bf16*)d_in[1];
    const bf16* Wq = (const bf16*)d_in[2];
    const bf16* Wk = (const bf16*)d_in[3];
    const bf16* Wv = (const bf16*)d_in[4];
    const bf16* Wo = (const bf16*)d_in[5];
    const bf16* w1 = (const bf16*)d_in[8];
    const bf16* w2 = (const bf16*)d_in[9];
    const bf16* c = (const bf16*)d_in[10];
    const bf16* wmod = (const bf16*)d_in[11];
    bf16* out = (bf16*)d_out;

    static EncodeFn enc = nullptr;
    static void *p_ox, *p_x1, *p_h2, *p_act;
    if (!enc) {
        cudaDriverEntryPointQueryResult qr;
        void* f = nullptr;
        cudaGetDriverEntryPoint("cuTensorMapEncodeTiled", &f, cudaEnableDefault, &qr);
        enc = (EncodeFn)f;
        cudaGetSymbolAddress(&p_ox, g_ox);
        cudaGetSymbolAddress(&p_x1, g_x1);
        cudaGetSymbolAddress(&p_h2, g_h2);
        cudaGetSymbolAddress(&p_act, g_act);
        cudaFuncSetAttribute(k_rec, cudaFuncAttributeMaxDynamicSharedMemorySize, SM_TOTAL);
        cudaFuncSetAttribute(k_side, cudaFuncAttributeMaxDynamicSharedMemorySize, G_SMEM);
    }
    RMaps rm;
    make_map(enc, &rm.wq, Wq, HD, DM, 64, 128);
    make_map(enc, &rm.wk, Wk, HD, DM, 64, 128);
    make_map(enc, &rm.wv, Wv, HD, DM, 64, 128);
    SMaps m;
    make_map(enc, &m.ox, p_ox, HD, SEQ, 64, 128);
    make_map(enc, &m.wo, Wo, DM, HD, 64, 64);
    make_map(enc, &m.h2, p_h2, DM, SEQ, 64, 128);
    make_map(enc, &m.w1, w1, FF, DM, 64, 64);
    make_map(enc, &m.act, p_act, FF, SEQ, 64, 128);
    make_map(enc, &m.w2, w2, DM, FF, 64, 64);

    cudaStream_t st = cudaStreamPerThread;
    k_pre<<<PRE_CTAS, 1024, 0, st>>>(c, wmod, x);
    {
        cudaLaunchConfig_t cfg = {};
        cfg.gridDim = dim3(96); cfg.blockDim = dim3(512); cfg.dynamicSmemBytes = SM_TOTAL; cfg.stream = st;
        cudaLaunchAttribute at[2];
        at[0].id = cudaLaunchAttributeClusterDimension;
        at[0].val.clusterDim.x = 3; at[0].val.clusterDim.y = 1; at[0].val.clusterDim.z = 1;
        at[1].id = cudaLaunchAttributeProgrammaticStreamSerialization;
        at[1].val.programmaticStreamSerializationAllowed = 1;
        cfg.attrs = at; cfg.numAttrs = 2;
        cudaLaunchKernelEx(&cfg, k_rec, rm, mem0, Wo);
    }
    {
        cudaLaunchConfig_t cfg = {};
        cfg.gridDim = dim3(SIDE_CTAS); cfg.blockDim = dim3(384); cfg.dynamicSmemBytes = G_SMEM; cfg.stream = st;
        cudaLaunchAttribute at[1];
        at[0].id = cudaLaunchAttributeProgrammaticStreamSerialization;
        at[0].val.programmaticStreamSerializationAllowed = 1;
        cfg.attrs = at; cfg.numAttrs = 1;
        cudaLaunchKernelEx(&cfg, k_side, m, x, c, wmod, out);
    }
}
```

```cpp
#include <cuda_runtime.h>
#include <cuda_bf16.h>
#include <cuda.h>
#include <stdint.h>

typedef __nv_bfloat16 bf16;
#define VX_THROTTLE 1
#define H1_DELAY 400
#define H1_BACK 0
#define VM_THROTTLE 1
#define PRE_TRIG 0
#define SIDE_CTAS 132

constexpr int SEQ = 2048, DM = 640, NH = 32, DH = 192, NSEG = 64, FF = 1536, HD = NH * DH;

__device__ __align__(128) float g_mod[6 * DM];
__device__ __align__(1024) bf16 g_ht[(size_t)SEQ * DM];
__device__ __align__(1024) bf16 g_ox[(size_t)SEQ * HD];
__device__ __align__(1024) bf16 g_x1[(size_t)SEQ * DM];
__device__ __align__(1024) bf16 g_h2[(size_t)SEQ * DM];
__device__ __align__(1024) bf16 g_act[(size_t)SEQ * FF];
__device__ __align__(8192) uint32_t g_buf1[80 * 2 * 2048];
__device__ __align__(8192) uint32_t g_buf2[4 * 3 * 2048];
__device__ uint32_t g_choice[128];
__device__ uint32_t g_epoch;
__device__ uint32_t g_hflag[64];
__device__ __align__(128) uint32_t g_modx[2 * DM];
#define T2(i)
#define T3(i)
enum { C_Q = 0, C_MOD = 1, C_REC = 2, C_G0 = 18, C_LN = 34, C_G1 = 50, C_G2 = 66, C_FIN = 82, C_NUM = 98 };
__device__ __align__(128) uint32_t g_cnt[C_NUM * 32];
constexpr int PMAX = 12;
constexpr int PRING = 4;
__device__ __align__(1024) float g_p0[(size_t)PRING * PMAX * 128 * DM];
__device__ __align__(1024) float g_p2[(size_t)PRING * PMAX * 128 * DM];
#define TR(k)

#define FRESH(x) asm volatile("" : "+r"(x))
__device__ __forceinline__ float bfr(float x) { return __bfloat162float(__float2bfloat16_rn(x)); }
__device__ __forceinline__ uint32_t pack2(float a, float b) {
    uint32_t r; asm("cvt.rn.bf16x2.f32 %0, %1, %2;" : "=r"(r) : "f"(b), "f"(a)); return r;
}
__device__ __forceinline__ float bflo(uint32_t v) { return __uint_as_float(v << 16); }
__device__ __forceinline__ float bfhi(uint32_t v) { return __uint_as_float(v & 0xffff0000u); }
__device__ __forceinline__ float ex2(float x) { float r; asm("ex2.approx.ftz.f32 %0, %1;" : "=f"(r) : "f"(x)); return r; }
__device__ __forceinline__ float rcpf(float x) { float r; asm("rcp.approx.ftz.f32 %0, %1;" : "=f"(r) : "f"(x)); return r; }
__device__ __forceinline__ void score2(float& a, float& b) {
    const float SCALE = 0.07216878364870322f;
    uint32_t u = pack2(a, b);
    u = pack2(bflo(u) * SCALE, bfhi(u) * SCALE);
    a = bflo(u); b = bfhi(u);
}
__device__ __forceinline__ uint32_t smem_u32(const void* p) { return (uint32_t)__cvta_generic_to_shared(p); }

__device__ __forceinline__ void mbar_init(uint32_t bar, uint32_t cnt) {
    asm volatile("mbarrier.init.shared::cta.b64 [%0], %1;" :: "r"(bar), "r"(cnt) : "memory");
}
__device__ __forceinline__ void mbar_arrive(uint32_t bar) {
    asm volatile("mbarrier.arrive.shared::cta.b64 _, [%0];" :: "r"(bar) : "memory");
}
__device__ __forceinline__ void mbar_expect(uint32_t bar, uint32_t bytes) {
    asm volatile("mbarrier.arrive.expect_tx.shared::cta.b64 _, [%0], %1;" :: "r"(bar), "r"(bytes) : "memory");
}
__device__ __forceinline__ bool mbar_try(uint32_t bar, uint32_t parity) {
    uint32_t ok;
    asm volatile("{\n\t.reg .pred p;\n\tmbarrier.try_wait.parity.shared::cta.b64 p, [%1], %2;\n\tselp.u32 %0, 1, 0, p;\n\t}"
                 : "=r"(ok) : "r"(bar), "r"(parity) : "memory");
    return ok != 0;
}
__device__ __forceinline__ bool mbar_try_cluster(uint32_t bar, uint32_t parity) {
    uint32_t ok;
    asm volatile("{\n\t.reg .pred p;\n\tmbarrier.try_wait.parity.acquire.cluster.shared::cta.b64 p, [%1], %2;\n\tselp.u32 %0, 1, 0, p;\n\t}"
                 : "=r"(ok) : "r"(bar), "r"(parity) : "memory");
    return ok != 0;
}
__device__ __forceinline__ void mbar_wait(uint32_t bar, uint32_t parity) {
    uint32_t guard = 0;
    while (!mbar_try(bar, parity)) { if (++guard > (1u << 22)) __trap(); }
}
__device__ __forceinline__ void mbar_wait_cluster(uint32_t bar, uint32_t parity) {
    uint32_t guard = 0;
    while (!mbar_try_cluster(bar, parity)) { if (++guard > (1u << 22)) __trap(); }
}
__device__ __forceinline__ void bar_sync(int id, int n) { asm volatile("bar.sync %0, %1;" :: "r"(id), "r"(n) : "memory"); }
__device__ __forceinline__ void bar_arrive(int id, int n) { asm volatile("bar.arrive %0, %1;" :: "r"(id), "r"(n) : "memory"); }
__device__ __forceinline__ void sts1(uint32_t a, uint32_t v) { asm volatile("st.shared.u32 [%0], %1;" :: "r"(a), "r"(v) : "memory"); }
__device__ __forceinline__ uint32_t lds1(uint32_t a) { uint32_t v; asm volatile("ld.shared.u32 %0, [%1];" : "=r"(v) : "r"(a) : "memory"); return v; }
__device__ __forceinline__ void fence_async() { asm volatile("fence.proxy.async.shared::cta;" ::: "memory"); }
__device__ __forceinline__ void cluster_sync() {
    asm volatile("barrier.cluster.arrive.release.aligned;\n\tbarrier.cluster.wait.acquire.aligned;" ::: "memory");
}
__device__ __forceinline__ uint32_t mapa(uint32_t a, uint32_t rank) {
    uint32_t r; asm("mapa.shared::cluster.u32 %0, %1, %2;" : "=r"(r) : "r"(a), "r"(rank)); return r;
}
__device__ __forceinline__ void st_async1(uint32_t a, uint32_t v, uint32_t bar) {
    asm volatile("st.async.weak.shared::cluster.mbarrier::complete_tx::bytes.b32 [%0], %1, [%2];" :: "r"(a), "r"(v), "r"(bar) : "memory");
}
__device__ __forceinline__ void st_async2(uint32_t a, float x, float y, uint32_t bar) {
    asm volatile("st.async.weak.shared::cluster.mbarrier::complete_tx::bytes.v2.f32 [%0], {%1,%2}, [%3];" :: "r"(a), "f"(x), "f"(y), "r"(bar) : "memory");
}
__device__ __forceinline__ void st_async4(uint32_t a, const float* c, uint32_t bar) {
    asm volatile("st.async.weak.shared::cluster.mbarrier::complete_tx::bytes.v4.f32 [%0], {%1,%2,%3,%4}, [%5];"
                 :: "r"(a), "f"(c[0]), "f"(c[1]), "f"(c[2]), "f"(c[3]), "r"(bar) : "memory");
}
__device__ __forceinline__ void bulk_g2s(uint32_t dst, const void* src, uint32_t bytes, uint32_t bar) {
    asm volatile("cp.async.bulk.shared::cluster.global.mbarrier::complete_tx::bytes [%0], [%1], %2, [%3];"
                 :: "r"(dst), "l"(src), "r"(bytes), "r"(bar) : "memory");
}
__device__ __forceinline__ void cpa16(uint32_t s, const void* g) {
    asm volatile("cp.async.cg.shared.global [%0], [%1], 16;" :: "r"(s), "l"(g) : "memory");
}
__device__ __forceinline__ void cpa_wait_all() { asm volatile("cp.async.wait_all;" ::: "memory"); }
__device__ __forceinline__ void ldsm4(uint32_t* r, uint32_t a) {
    asm volatile("ldmatrix.sync.aligned.m8n8.x4.shared.b16 {%0,%1,%2,%3}, [%4];" : "=r"(r[0]), "=r"(r[1]), "=r"(r[2]), "=r"(r[3]) : "r"(a) : "memory");
}
__device__ __forceinline__ void ldsm4t(uint32_t* r, uint32_t a) {
    asm volatile("ldmatrix.sync.aligned.m8n8.x4.trans.shared.b16 {%0,%1,%2,%3}, [%4];" : "=r"(r[0]), "=r"(r[1]), "=r"(r[2]), "=r"(r[3]) : "r"(a) : "memory");
}
__device__ __forceinline__ void stsm2t(uint32_t a, uint32_t r0, uint32_t r1) {
    asm volatile("stmatrix.sync.aligned.m8n8.x2.trans.shared.b16 [%0], {%1,%2};" :: "r"(a), "r"(r0), "r"(r1) : "memory");
}
__device__ __forceinline__ void stsm4t(uint32_t a, uint32_t r0, uint32_t r1, uint32_t r2, uint32_t r3) {
    asm volatile("stmatrix.sync.aligned.m8n8.x4.trans.shared.b16 [%0], {%1,%2,%3,%4};" :: "r"(a), "r"(r0), "r"(r1), "r"(r2), "r"(r3) : "memory");
}
__device__ __forceinline__ uint32_t movm(uint32_t v) {
    uint32_t r; asm volatile("movmatrix.sync.aligned.m8n8.trans.b16 %0, %1;" : "=r"(r) : "r"(v)); return r;
}
__device__ __forceinline__ void mma16(float* c, uint32_t a0, uint32_t a1, uint32_t a2, uint32_t a3, uint32_t b0, uint32_t b1) {
    asm volatile("mma.sync.aligned.m16n8k16.row.col.f32.bf16.bf16.f32 {%0,%1,%2,%3}, {%4,%5,%6,%7}, {%8,%9}, {%0,%1,%2,%3};"
                 : "+f"(c[0]), "+f"(c[1]), "+f"(c[2]), "+f"(c[3]) : "r"(a0), "r"(a1), "r"(a2), "r"(a3), "r"(b0), "r"(b1));
}
__device__ __forceinline__ void mma8(float* c, uint32_t a0, uint32_t a1, uint32_t b0) {
    asm volatile("mma.sync.aligned.m16n8k8.row.col.f32.bf16.bf16.f32 {%0,%1,%2,%3}, {%4,%5}, {%6}, {%0,%1,%2,%3};"
                 : "+f"(c[0]), "+f"(c[1]), "+f"(c[2]), "+f"(c[3]) : "r"(a0), "r"(a1), "r"(b0));
}
__host__ __device__ constexpr uint64_t make_desc(uint32_t saddr, uint32_t lbo, uint32_t sbo, uint32_t layout) {
    return (uint64_t)((saddr & 0x3FFFF) >> 4) | ((uint64_t)(lbo >> 4) << 16) | ((uint64_t)(sbo >> 4) << 32) | ((uint64_t)layout << 62);
}
__device__ __forceinline__ void wg_fence() { asm volatile("wgmma.fence.sync.aligned;" ::: "memory"); }
__device__ __forceinline__ void wg_commit() { asm volatile("wgmma.commit_group.sync.aligned;" ::: "memory"); }
template <int N> __device__ __forceinline__ void wg_wait() { asm volatile("wgmma.wait_group.sync.aligned %0;" :: "n"(N) : "memory"); }

#define D16(C) C(d[0]), C(d[1]), C(d[2]), C(d[3]), C(d[4]), C(d[5]), C(d[6]), C(d[7]), \
               C(d[8]), C(d[9]), C(d[10]), C(d[11]), C(d[12]), C(d[13]), C(d[14]), C(d[15])
#define DREG16 "{%0,%1,%2,%3,%4,%5,%6,%7,%8,%9,%10,%11,%12,%13,%14,%15}"
__device__ __forceinline__ void wg_rs32(float* d, const uint32_t* a, uint64_t db, bool acc) {
    if (acc)
        asm volatile("wgmma.mma_async.sync.aligned.m64n32k16.f32.bf16.bf16 " DREG16 ", {%16,%17,%18,%19}, %20, 1, 1, 1, 0;"
            : D16("+f") : "r"(a[0]), "r"(a[1]), "r"(a[2]), "r"(a[3]), "l"(db));
    else
        asm volatile("wgmma.mma_async.sync.aligned.m64n32k16.f32.bf16.bf16 " DREG16 ", {%16,%17,%18,%19}, %20, 0, 1, 1, 0;"
            : D16("=f") : "r"(a[0]), "r"(a[1]), "r"(a[2]), "r"(a[3]), "l"(db));
}
__device__ __forceinline__ void wg_ss32(float* d, uint64_t da, uint64_t db, bool acc) {
    if (acc)
        asm volatile("wgmma.mma_async.sync.aligned.m64n32k16.f32.bf16.bf16 " DREG16 ", %16, %17, 1, 1, 1, 1, 0;"
            : D16("+f") : "l"(da), "l"(db));
    else
        asm volatile("wgmma.mma_async.sync.aligned.m64n32k16.f32.bf16.bf16 " DREG16 ", %16, %17, 0, 1, 1, 1, 0;"
            : D16("=f") : "l"(da), "l"(db));
}
__device__ __forceinline__ void wg_ss8(float* d, uint64_t da, uint64_t db, bool acc) {
    if (acc)
        asm volatile("wgmma.mma_async.sync.aligned.m64n8k16.f32.bf16.bf16 {%0,%1,%2,%3}, %4, %5, 1, 1, 1, 1, 1;"
            : "+f"(d[0]), "+f"(d[1]), "+f"(d[2]), "+f"(d[3]) : "l"(da), "l"(db));
    else
        asm volatile("wgmma.mma_async.sync.aligned.m64n8k16.f32.bf16.bf16 {%0,%1,%2,%3}, %4, %5, 0, 1, 1, 1, 1;"
            : "=f"(d[0]), "=f"(d[1]), "=f"(d[2]), "=f"(d[3]) : "l"(da), "l"(db));
}
template <int OFF> __device__ __forceinline__ void ldsm4t_i(uint32_t* r, uint32_t a) {
    asm volatile("ldmatrix.sync.aligned.m8n8.x4.trans.shared.b16 {%0,%1,%2,%3}, [%4+%5];"
                 : "=r"(r[0]), "=r"(r[1]), "=r"(r[2]), "=r"(r[3]) : "r"(a), "n"(OFF) : "memory");
}

__device__ __forceinline__ uint4 ld_relaxed4(const void* p) {
    uint4 v;
    asm volatile("ld.relaxed.gpu.global.v4.u32 {%0,%1,%2,%3}, [%4];" : "=r"(v.x), "=r"(v.y), "=r"(v.z), "=r"(v.w) : "l"(p) : "memory");
    return v;
}
__device__ __forceinline__ void st_relaxed2(void* p, uint32_t a, uint32_t b) {
    asm volatile("st.relaxed.gpu.global.v2.u32 [%0], {%1,%2};" :: "l"(p), "r"(a), "r"(b) : "memory");
}
__device__ __forceinline__ void st_relaxed2_off(void* base, uint32_t off, uint32_t a, uint32_t b) {
    asm volatile("{\n\t.reg .u64 ad;\n\tcvt.u64.u32 ad, %1;\n\tadd.u64 ad, ad, %0;\n\tst.relaxed.gpu.global.v2.u32 [ad], {%2,%3};\n\t}"
                 :: "l"(base), "r"(off), "r"(a), "r"(b) : "memory");
}
__device__ __forceinline__ void st_relaxed1(void* p, uint32_t a) {
    asm volatile("st.relaxed.gpu.global.u32 [%0], %1;" :: "l"(p), "r"(a) : "memory");
}
__device__ __forceinline__ uint32_t ld_acquire1(const uint32_t* p) {
    uint32_t v; asm volatile("ld.acquire.gpu.global.u32 %0, [%1];" : "=r"(v) : "l"(p) : "memory"); return v;
}
__device__ __forceinline__ void st_release1(uint32_t* p, uint32_t a) {
    asm volatile("st.release.gpu.global.u32 [%0], %1;" :: "l"(p), "r"(a) : "memory");
}
__device__ __forceinline__ uint4 lds4(uint32_t s) {
    uint4 v; asm volatile("ld.shared.v4.u32 {%0,%1,%2,%3}, [%4];" : "=r"(v.x), "=r"(v.y), "=r"(v.z), "=r"(v.w) : "r"(s) : "memory"); return v;
}
__device__ __forceinline__ void sts4(uint32_t s, const uint4& v) {
    asm volatile("st.shared.v4.u32 [%0], {%1,%2,%3,%4};" :: "r"(s), "r"(v.x), "r"(v.y), "r"(v.z), "r"(v.w) : "memory");
}
__device__ __forceinline__ float4 lds4f(uint32_t s) {
    float4 v; asm volatile("ld.shared.v4.f32 {%0,%1,%2,%3}, [%4];" : "=f"(v.x), "=f"(v.y), "=f"(v.z), "=f"(v.w) : "r"(s) : "memory"); return v;
}
__device__ __forceinline__ uint2 lds2(uint32_t s) {
    uint2 v; asm volatile("ld.shared.v2.u32 {%0,%1}, [%2];" : "=r"(v.x), "=r"(v.y) : "r"(s) : "memory"); return v;
}
__device__ __forceinline__ float2 lds2f(uint32_t s) {
    float2 v; asm volatile("ld.shared.v2.f32 {%0,%1}, [%2];" : "=f"(v.x), "=f"(v.y) : "r"(s) : "memory"); return v;
}
__device__ __forceinline__ uint32_t clk32() { uint32_t c; asm volatile("mov.u32 %0, %%clock;" : "=r"(c) :: "memory"); return c; }
__device__ __forceinline__ uint32_t tagw(float v, uint32_t tag) { return ((__float_as_uint(v) + 8u) & ~15u) | tag; }
__device__ __forceinline__ bool ok4(const uint4& v, uint32_t tag) { return (((v.x ^ tag) | (v.y ^ tag) | (v.z ^ tag) | (v.w ^ tag)) & 15u) == 0; }
__device__ __forceinline__ bool oks(const uint4& v) { return v.x != 0xFFFFFFFFu && v.y != 0xFFFFFFFFu && v.z != 0xFFFFFFFFu && v.w != 0xFFFFFFFFu; }
__device__ __forceinline__ float uf(uint32_t x) { return __uint_as_float(x & ~15u); }

template <int NT, int BAR>
__device__ __forceinline__ void mod_chunk(const bf16* __restrict__ c, const bf16* __restrict__ wmod, int col0, int tid, float* red) {
    constexpr int RG = NT / 8, NP = DM / RG;
    const int cc = tid & 7, rg = tid >> 3;
    uint4 w[NP];
    #pragma unroll
    for (int i = 0; i < NP; i++) w[i] = __ldg((const uint4*)(wmod + (size_t)(rg + i * RG) * (6 * DM) + col0 + cc * 8));
    float a[8];
    #pragma unroll
    for (int j = 0; j < 8; j++) a[j] = 0.f;
    #pragma unroll
    for (int i = 0; i < NP; i++) {
        const float v = __bfloat162float(c[rg + i * RG]);
        const float sv = bfr(v / (1.0f + __expf(-v)));
        a[0] += sv * bflo(w[i].x); a[1] += sv * bfhi(w[i].x); a[2] += sv * bflo(w[i].y); a[3] += sv * bfhi(w[i].y);
        a[4] += sv * bflo(w[i].z); a[5] += sv * bfhi(w[i].z); a[6] += sv * bflo(w[i].w); a[7] += sv * bfhi(w[i].w);
    }
    #pragma unroll
    for (int j = 0; j < 8; j++) {
        a[j] += __shfl_xor_sync(0xffffffffu, a[j], 8);
        a[j] += __shfl_xor_sync(0xffffffffu, a[j], 16);
    }
    if ((tid & 31) < 8) {
        float* d = red + (tid >> 5) * 64 + cc * 8;
        *(float4*)d = make_float4(a[0], a[1], a[2], a[3]);
        *(float4*)(d + 4) = make_float4(a[4], a[5], a[6], a[7]);
    }
    bar_sync(BAR, NT);
    if (tid < 64) {
        float s = 0.f;
        #pragma unroll
        for (int i = 0; i < NT / 32; i++) s += red[i * 64 + tid];
        g_mod[col0 + tid] = bfr(s);
    }
}

__device__ __forceinline__ void ln_stats(const float (*v)[4], float& mb, float& sd) {
    float s = 0.f;
    #pragma unroll
    for (int i = 0; i < 5; i++) s += (v[i][0] + v[i][1]) + (v[i][2] + v[i][3]);
    #pragma unroll
    for (int o = 16; o > 0; o >>= 1) s += __shfl_xor_sync(0xffffffffu, s, o);
    const float mean = s * (1.0f / DM);
    float q = 0.f;
    #pragma unroll
    for (int i = 0; i < 5; i++) {
        #pragma unroll
        for (int j = 0; j < 4; j++) { const float d = v[i][j] - mean; q += d * d; }
    }
    #pragma unroll
    for (int o = 16; o > 0; o >>= 1) q += __shfl_xor_sync(0xffffffffu, q, o);
    mb = bfr(mean);
    const float var = bfr(q * (1.0f / DM));
    sd = 1.0f / bfr(sqrtf(bfr(var + 1e-5f)));
}
__device__ __forceinline__ uint2 ln_apply(const float* v, float mb, float rs, const float4& sc, const float4& sh) {
    const float o0 = bfr(bfr(bfr(v[0] - mb) * rs) * bfr(1.0f + sc.x)) + sh.x;
    const float o1 = bfr(bfr(bfr(v[1] - mb) * rs) * bfr(1.0f + sc.y)) + sh.y;
    const float o2 = bfr(bfr(bfr(v[2] - mb) * rs) * bfr(1.0f + sc.z)) + sh.z;
    const float o3 = bfr(bfr(bfr(v[3] - mb) * rs) * bfr(1.0f + sc.w)) + sh.w;
    return make_uint2(pack2(o0, o1), pack2(o2, o3));
}

constexpr int SM_WV = 0;
constexpr int SM_HB = 81920;
constexpr int SM_WO = SM_HB + 40960;
constexpr int SM_QX = SM_WO + 77824;
constexpr int SM_KS = SM_QX + 4096;
constexpr int SM_QM = SM_KS + 5120;
constexpr int SM_XS = SM_QM + 1024;
constexpr int SM_MS = SM_XS + 12288;
constexpr int SM_OS = SM_MS + 3840;
constexpr int SM_PM = SM_OS + 3072;
constexpr int SM_BAR = SM_PM + 640;
constexpr int SM_CH = SM_BAR + 128;
constexpr int SM_TOTAL = SM_CH + 128;
static_assert(SM_TOTAL <= 232448, "smem");

enum { B_MEM_FULL = 0, B_MEM_FREE, B_HLO_FULL, B_HHI_FULL, B_HLO_FREE, B_HHI_FREE, B_MS, B_O, B_XS, B_O1, B_XSFREE, B_WQ, B_WK, B_WV, B_WO };

__device__ __forceinline__ int probe_blk(uint32_t* blk) {
    uint32_t t0 = 0xffffffffu, t1 = 0xffffffffu, acc = 0;
    for (int rep = 0; rep < 3; rep++) {
        #pragma unroll
        for (int pg = 0; pg < 2; pg++) {
            uint32_t c0 = clk32();
            uint32_t v = atomicOr(blk + pg * 1024 + acc, 0u);
            acc = (v == 0x12345678u) ? 1u : 0u;
            asm volatile("" :: "r"(acc) : "memory");
            uint32_t c1 = clk32() + acc;
            uint32_t d = c1 - c0;
            if (rep > 0) { if (pg == 0) t0 = min(t0, d); else t1 = min(t1, d); }
        }
    }
    return t1 < t0 ? 1 : 0;
}

__device__ __forceinline__ uint32_t wo_tile_off(int w) {
    if (w < 8) return w * 6144;
    if (w < 12) return 8 * 6144 + (w - 8) * 4096;
    return 8 * 6144 + 4 * 4096 + (w - 12) * 6144;
}

template <int NRES, int NPRE>
__device__ __forceinline__ void wo_phase(uint32_t sb, int w, int lane, const uint32_t (*res)[4], uint32_t parity,
                                         uint32_t tag, int tile, int h) {
    FRESH(lane);
    const int er = (lane & 7) + 8 * (lane >> 4);
    const uint32_t aaddr = sb + SM_WO + wo_tile_off(w) + er * 32 + ((((lane >> 3) & 1) ^ ((er >> 2) & 1)) << 4);
    const uint32_t baddr = sb + SM_OS + lane * 16;
    float c0[4] = {0.f, 0.f, 0.f, 0.f}, c1[4] = {0.f, 0.f, 0.f, 0.f};
    uint32_t pre[NPRE > 4 ? NPRE : 4][4];
    if (NPRE >= 4) {
        #pragma unroll
        for (int i = 0; i < 4; i++) ldsm4t(pre[i], aaddr + i * 512);
        mbar_wait(sb + SM_BAR + B_O1 * 8, parity);
        uint32_t b[2][4];
        ldsm4t(b[0], baddr);
        ldsm4t(b[1], baddr + 512);
        #pragma unroll
        for (int kp = 0; kp < 2; kp++) {
            mma16(c0, pre[2 * kp][0], pre[2 * kp][1], pre[2 * kp][2], pre[2 * kp][3], b[kp][0], b[kp][1]);
            mma16(c1, pre[2 * kp + 1][0], pre[2 * kp + 1][1], pre[2 * kp + 1][2], pre[2 * kp + 1][3], b[kp][2], b[kp][3]);
        }
    } else {
        #pragma unroll
        for (int i = 0; i < 2; i++) ldsm4t(pre[i], aaddr + i * 512);
        mbar_wait(sb + SM_BAR + B_O1 * 8, parity);
        #pragma unroll
        for (int kp = 0; kp < 2; kp++) {
            uint32_t b[4];
            ldsm4t(b, baddr + kp * 512);
            if (kp == 1) { ldsm4t(pre[0], aaddr + 2 * 512); ldsm4t(pre[1], aaddr + 3 * 512); }
            mma16(c0, pre[0][0], pre[0][1], pre[0][2], pre[0][3], b[0], b[1]);
            mma16(c1, pre[1][0], pre[1][1], pre[1][2], pre[1][3], b[2], b[3]);
        }
    }
    #pragma unroll
    for (int i = 0; i < NPRE; i++) ldsm4t(pre[i], aaddr + (4 + i) * 512);
    uint32_t off0, off1;
    {
        uint32_t ch;
        asm volatile("ld.shared.u16 %0, [%1];" : "=r"(ch) : "r"(sb + SM_CH + 2 * tile) : "memory");
        const int j = h >> 4;
        const uint32_t base = (uint32_t)((tile * 4 + j) * 8192 + (h & 15) * 256 + lane * 8);
        ch >>= j;
        off0 = base + (ch & 1) * 4096;
        off1 = base + 16384 + (ch & 256) * 16;
    }
    mbar_wait(sb + SM_BAR + B_O * 8, parity);
    if (NRES == 4) {
        uint32_t b[4][4];
        #pragma unroll
        for (int i = 0; i < 4; i++) ldsm4t(b[i], baddr + (2 + i) * 512);
        #pragma unroll
        for (int i = 0; i < 2; i++) {
            mma16(c0, res[2 * i][0], res[2 * i][1], res[2 * i][2], res[2 * i][3], b[i][0], b[i][1]);
            mma16(c1, res[2 * i + 1][0], res[2 * i + 1][1], res[2 * i + 1][2], res[2 * i + 1][3], b[i][2], b[i][3]);
        }
        #pragma unroll
        for (int i = 0; i < 2; i++) {
            mma16(c0, pre[2 * i][0], pre[2 * i][1], pre[2 * i][2], pre[2 * i][3], b[2 + i][0], b[2 + i][1]);
            mma16(c1, pre[2 * i + 1][0], pre[2 * i + 1][1], pre[2 * i + 1][2], pre[2 * i + 1][3], b[2 + i][2], b[2 + i][3]);
        }
    } else if (NPRE == 4) {
        uint32_t b[2][4];
        #pragma unroll
        for (int hh = 0; hh < 2; hh++) {
            ldsm4t(b[0], baddr + (2 + 2 * hh) * 512);
            ldsm4t(b[1], baddr + (3 + 2 * hh) * 512);
            if (hh) {
                #pragma unroll
                for (int i = 0; i < 4; i++) ldsm4t(pre[i], aaddr + (8 + i) * 512);
            }
            #pragma unroll
            for (int i = 0; i < 2; i++) {
                mma16(c0, pre[2 * i][0], pre[2 * i][1], pre[2 * i][2], pre[2 * i][3], b[i][0], b[i][1]);
                mma16(c1, pre[2 * i + 1][0], pre[2 * i + 1][1], pre[2 * i + 1][2], pre[2 * i + 1][3], b[i][2], b[i][3]);
            }
        }
    }
    st_relaxed2_off(g_buf1, off0, tagw(c0[0] + c1[0], tag), tagw(c0[1] + c1[1], tag));
    st_relaxed2_off(g_buf1, off1, tagw(c0[2] + c1[2], tag), tagw(c0[3] + c1[3], tag));
}

template <int NT, bool MASK>
__device__ __forceinline__ void softmax_core(float (*sc)[2], int g, int t, uint32_t* pb) {
    const float L2E = 1.4426950408889634f;
    #pragma unroll
    for (int j = 0; j < NT; j++) score2(sc[j][0], sc[j][1]);
    if (MASK) {
        const float NEG = -999292928.0f;
        if (2 * t > g) sc[NT - 1][0] = NEG;
        if (2 * t + 1 > g) sc[NT - 1][1] = NEG;
    }
    float m[NT];
    #pragma unroll
    for (int j = 0; j < NT; j++) m[j] = fmaxf(sc[j][0], sc[j][1]);
    float mx = m[0];
    #pragma unroll
    for (int j = 1; j < NT; j++) mx = fmaxf(mx, m[j]);
    mx = fmaxf(mx, __shfl_xor_sync(0xffffffffu, mx, 1));
    mx = fmaxf(mx, __shfl_xor_sync(0xffffffffu, mx, 2));
    float s0 = 0.f, s1 = 0.f;
    #pragma unroll
    for (int j = 0; j < NT; j++) {
        sc[j][0] = ex2((sc[j][0] - mx) * L2E); sc[j][1] = ex2((sc[j][1] - mx) * L2E);
        s0 += sc[j][0]; s1 += sc[j][1];
    }
    s0 += s1;
    s0 += __shfl_xor_sync(0xffffffffu, s0, 1);
    s0 += __shfl_xor_sync(0xffffffffu, s0, 2);
    const float iv = rcpf(s0);
    #pragma unroll
    for (int j = 0; j < NT; j++) pb[j] = pack2(sc[j][0] * iv, sc[j][1] * iv);
}
template <int NT>
__device__ __forceinline__ void xsoftmax(uint32_t a, int g, int t) {
    float sc[NT][2];
    #pragma unroll
    for (int j = 0; j < NT; j++) {
        float2 v0 = lds2f(a + j * 512), v1 = lds2f(a + j * 512 + 4096), v2 = lds2f(a + j * 512 + 8192);
        sc[j][0] = v0.x + v1.x + v2.x; sc[j][1] = v0.y + v1.y + v2.y;
    }
    uint32_t pb[NT];
    softmax_core<NT, true>(sc, g, t, pb);
    #pragma unroll
    for (int j = 0; j < NT; j += 2) {
        if (j + 1 < NT) asm volatile("st.shared.v2.u32 [%0], {%1,%2};" :: "r"(a + j * 512), "r"(pb[j]), "r"(pb[j + 1]) : "memory");
        else sts1(a + j * 512, pb[j]);
    }
}
template <int NJ>
__device__ __forceinline__ void xscores(uint32_t sb, int p, int mi, int j0, int lane) {
    FRESH(lane);
    const int r = lane & 7, cq = lane >> 3;
    const int qrow = mi * 16 + r + 8 * (cq & 1);
    uint32_t kb[NJ][8];
    float d[NJ][4];
    #pragma unroll
    for (int j = 0; j < NJ; j++) {
        ldsm4(kb[j], sb + SM_KS + ((j0 + j) * 8 + r) * 128 + ((cq ^ r) << 4));
        ldsm4(kb[j] + 4, sb + SM_KS + ((j0 + j) * 8 + r) * 128 + (((cq + 4) ^ r) << 4));
        d[j][0] = 0.f; d[j][1] = 0.f; d[j][2] = 0.f; d[j][3] = 0.f;
    }
    #pragma unroll
    for (int kt = 0; kt < 4; kt++) {
        uint32_t a[4];
        ldsm4(a, sb + SM_QX + qrow * 128 + (((2 * kt + (cq >> 1)) ^ r) << 4));
        #pragma unroll
        for (int j = 0; j < NJ; j++) mma16(d[j], a[0], a[1], a[2], a[3], kb[j][2 * kt], kb[j][2 * kt + 1]);
    }
    const uint32_t la = sb + SM_XS + p * 4096 + (mi * 3 + j0) * 512 + lane * 16;
    #pragma unroll
    for (int rk = 0; rk < 3; rk++) {
        const uint32_t ra = mapa(la, rk), rb = mapa(sb + SM_BAR + B_XS * 8, rk);
        #pragma unroll
        for (int j = 0; j < NJ; j++) st_async4(ra + j * 512, d[j], rb);
    }
}
__device__ __forceinline__ void mbar_arrive_remote(uint32_t bar) {
    asm volatile("mbarrier.arrive.relaxed.cluster.shared::cluster.b64 _, [%0];" :: "r"(bar) : "memory");
}

__device__ __forceinline__ void tma2d(uint32_t dst, const CUtensorMap* map, int c0, int c1, uint32_t bar) {
    asm volatile("cp.async.bulk.tensor.2d.shared::cluster.global.mbarrier::complete_tx::bytes [%0], [%1, {%2, %3}], [%4];"
                 :: "r"(dst), "l"(map), "r"(c0), "r"(c1), "r"(bar) : "memory");
}
__device__ __forceinline__ void tma2d_pf(const CUtensorMap* map, int c0, int c1) {
    asm volatile("cp.async.bulk.prefetch.tensor.2d.L2.global [%0, {%1, %2}];" :: "l"(map), "r"(c0), "r"(c1) : "memory");
}
__device__ __forceinline__ void bulk_pf(const void* p, uint32_t bytes) {
    asm volatile("cp.async.bulk.prefetch.L2.global [%0], %1;" :: "l"(p), "r"(bytes) : "memory");
}
struct RMaps { CUtensorMap wq, wk, wv, wo; };
__device__ __forceinline__ void signal_cnt(int idx) {
    asm volatile("fence.proxy.async;\n\tfence.acq_rel.gpu;\n\tred.relaxed.gpu.global.add.u32 [%0], 1;" :: "l"(g_cnt + idx * 32) : "memory");
}

__global__ void __launch_bounds__(512, 1)
k_rec(const __grid_constant__ RMaps maps, const bf16* __restrict__ mem0, const bf16* __restrict__ Wo,
      const bf16* __restrict__ xin, const bf16* __restrict__ cvec, const bf16* __restrict__ wmod) {
    extern __shared__ __align__(1024) uint8_t smem_raw[];
    constexpr uint32_t SBC = 1024;
    const uint32_t sb = smem_u32(smem_raw);
    if ((sb & 0xFFFFFFu) != SBC) __trap();
    int lane = __shfl_sync(0xffffffffu, threadIdx.x & 31, threadIdx.x & 31);
    const int warp = __shfl_sync(0xffffffffu, threadIdx.x >> 5, 0), wg = warp >> 2;
    const int tid = warp * 32 + lane;
    const int b = blockIdx.x, h = b / 3, p = b % 3;
    const int g = lane >> 2, t = lane & 3;
    const int tile0 = p == 0 ? 0 : (p == 1 ? 14 : 27);
    const int ntile = p == 0 ? 14 : 13;
    const uint32_t bar = sb + SM_BAR;

    if (tid == 0) T2(100 + b);
    if (tid == 0) {
        mbar_init(bar + B_MEM_FULL * 8, 4);
        mbar_init(bar + B_MEM_FREE * 8, 12);
        mbar_init(bar + B_HLO_FULL * 8, 1);
        mbar_init(bar + B_HHI_FULL * 8, 1);
        mbar_init(bar + B_HLO_FREE * 8, 12);
        mbar_init(bar + B_HHI_FREE * 8, 12);
        mbar_init(bar + B_MS * 8, 1);
        mbar_init(bar + B_O * 8, 1);
        mbar_init(bar + B_XS * 8, 1);
        mbar_init(bar + B_O1 * 8, 4);
        mbar_init(bar + B_XSFREE * 8, 12);
        mbar_init(bar + B_WQ * 8, 1);
        mbar_init(bar + B_WK * 8, 1);
        mbar_init(bar + B_WV * 8, 1);
        mbar_init(bar + B_WO * 8, 1);
        asm volatile("fence.mbarrier_init.release.cluster;" ::: "memory");
        mbar_expect(bar + B_WQ * 8, 81920);
        mbar_expect(bar + B_WK * 8, 81920);
        #pragma unroll
        for (int i = 0; i < 5; i++) {
            tma2d(sb + SM_WO + i * 16384, &maps.wq, h * DH + p * 64, i * 128, bar + B_WQ * 8);
            tma2d(sb + SM_WV + i * 16384, &maps.wk, h * DH + p * 64, i * 128, bar + B_WK * 8);
        }
        mbar_expect(bar + B_MS * 8, 3840);
        mbar_expect(bar + B_O * 8, 2048);
        mbar_expect(bar + B_XS * 8, 12288);
    }
    __syncwarp();
    asm volatile("barrier.cluster.arrive.relaxed.aligned;\n\tbarrier.cluster.wait.acquire.aligned;" ::: "memory");
    if (warp == 0) T3(0);

    if (wg < 2) {
        asm volatile("setmaxnreg.inc.sync.aligned.u32 200;");
        const int w = warp & 3;
        {
            const uint32_t tag = *(volatile uint32_t*)&g_epoch + 1u;
            uint4 wm[5];
            float cv[5];
            if (b < 80) {
                #pragma unroll
                for (int i = 0; i < 5; i++) {
                    wm[i] = __ldg((const uint4*)(wmod + (size_t)((tid >> 1) + 128 * i) * (6 * DM) + b * 16 + (tid & 1) * 8));
                    cv[i] = __bfloat162float(cvec[(tid >> 1) + 128 * i]);
                }
            }
            uint2 xr[8][5];
            const int seg1 = b < NSEG - 1 ? b + 1 : 0;
            #pragma unroll
            for (int r = 0; r < 8; r++) {
                const bf16* src = xin + (size_t)((r < 4 ? 0 : seg1) * 32 + warp * 4 + (r & 3)) * DM + lane * 4;
                #pragma unroll
                for (int i = 0; i < 5; i++) xr[r][i] = __ldg((const uint2*)(src + i * 128));
            }
            if (b < 80) {
                float a[8];
                #pragma unroll
                for (int j = 0; j < 8; j++) a[j] = 0.f;
                #pragma unroll
                for (int i = 0; i < 5; i++) {
                    const float sv = bfr(cv[i] / (1.0f + __expf(-cv[i])));
                    a[0] += sv * bflo(wm[i].x); a[1] += sv * bfhi(wm[i].x); a[2] += sv * bflo(wm[i].y); a[3] += sv * bfhi(wm[i].y);
                    a[4] += sv * bflo(wm[i].z); a[5] += sv * bfhi(wm[i].z); a[6] += sv * bflo(wm[i].w); a[7] += sv * bfhi(wm[i].w);
                }
                #pragma unroll
                for (int j = 0; j < 8; j++) {
                    #pragma unroll
                    for (int o = 2; o < 32; o <<= 1) a[j] += __shfl_xor_sync(0xffffffffu, a[j], o);
                }
                if (lane < 2) {
                    const uint32_t d = sb + SM_QM + warp * 64 + lane * 32;
                    sts4(d, make_uint4(__float_as_uint(a[0]), __float_as_uint(a[1]), __float_as_uint(a[2]), __float_as_uint(a[3])));
                    sts4(d + 16, make_uint4(__float_as_uint(a[4]), __float_as_uint(a[5]), __float_as_uint(a[6]), __float_as_uint(a[7])));
                }
                bar_sync(1, 256);
                if (tid < 8) {
                    float s0 = 0.f, s1 = 0.f;
                    #pragma unroll
                    for (int i = 0; i < 8; i++) { const float2 v = lds2f(sb + SM_QM + i * 64 + tid * 8); s0 += v.x; s1 += v.y; }
                    st_relaxed2(g_modx + (b * 8 + tid) * 2, pack2(s0, s1), tag);
                }
            }
            if (tid == 32) {
                #pragma unroll
                for (int i = 0; i < 5; i++) tma2d_pf(&maps.wv, h * DH + p * 64, i * 128);
            }
            if (tid >= 64) bulk_pf(Wo + ((size_t)h * DH + (tid - 64)) * DM + tile0 * 16, ntile * 32);
            float mb[8], rs[8];
            #pragma unroll
            for (int r = 0; r < 8; r++) {
                float v[5][4];
                #pragma unroll
                for (int i = 0; i < 5; i++) { v[i][0] = bflo(xr[r][i].x); v[i][1] = bfhi(xr[r][i].x); v[i][2] = bflo(xr[r][i].y); v[i][3] = bfhi(xr[r][i].y); }
                ln_stats(v, mb[r], rs[r]);
            }
            T3(12);
            #pragma unroll
            for (int u = 0; u < 2; u++) {
                const int idx = tid + u * 256;
                if (idx < 320) {
                    uint4 v; uint32_t guard = 0;
                    while (true) {
                        v = ld_relaxed4(g_modx + idx * 4);
                        if (v.y == tag && v.w == tag) break;
                        __nanosleep(50);
                        if (++guard > (1u << 22)) __trap();
                    }
                    asm volatile("st.shared.v2.u32 [%0], {%1,%2};" :: "r"(sb + SM_KS + idx * 8), "r"(v.x), "r"(v.z) : "memory");
                }
            }
            bar_sync(1, 256);
            T3(13);
            #pragma unroll
            for (int i = 0; i < 5; i++) {
                const int col = (i * 32 + lane) * 4;
                const uint2 u0 = lds2(sb + SM_KS + col * 2), u1 = lds2(sb + SM_KS + 1280 + col * 2);
                const float4 sh = make_float4(bflo(u0.x), bfhi(u0.x), bflo(u0.y), bfhi(u0.y));
                const float4 sc = make_float4(bflo(u1.x), bfhi(u1.x), bflo(u1.y), bfhi(u1.y));
                #pragma unroll
                for (int r = 0; r < 8; r++) {
                    const float v[4] = {bflo(xr[r][i].x), bfhi(xr[r][i].x), bflo(xr[r][i].y), bfhi(xr[r][i].y)};
                    const int row = warp * 4 + (r & 3);
                    const uint32_t off = (col >> 6) * 4096 + row * 128 + ((((col >> 3) & 7) ^ (row & 7)) << 4) + (col & 4) * 2;
                    const uint2 o = ln_apply(v, mb[r], rs[r], sc, sh);
                    if (r < 4) asm volatile("st.shared.v2.u32 [%0], {%1,%2};" :: "r"(sb + SM_HB + off), "r"(o.x), "r"(o.y) : "memory");
                    else if (b < NSEG - 1) *(uint2*)((char*)g_ht + (size_t)seg1 * 40960 + off) = o;
                }
            }
            fence_async();
            bar_sync(1, 256);
            if (tid == 0) { mbar_arrive(bar + B_HLO_FULL * 8); mbar_arrive(bar + B_HHI_FULL * 8); }
            if (tid == 224 && b < NSEG - 1) {
                asm volatile("fence.proxy.async;\n\tfence.acq_rel.gpu;" ::: "memory");
                st_relaxed1(&g_hflag[seg1], tag);
            }
            __syncwarp();
        }
        uint32_t wa[40][4];
        {
            mbar_wait(bar + (wg == 0 ? B_WQ : B_WK) * 8, 0);
            if (w == 0) T3(1 + wg);
            const int r = lane & 7;
            const uint32_t wsrc = sb + (wg == 0 ? SM_WO : SM_WV) + (r + ((lane >> 4) << 3)) * 128 + (((2 * w + ((lane >> 3) & 1)) ^ r) << 4);
            #pragma unroll
            for (int kt = 0; kt < 40; kt++) ldsm4t(wa[kt], wsrc + kt * 2048);
            fence_async();
            bar_arrive(10 + wg, 256);
        }

        const uint32_t dstx = sb + (wg == 0 ? SM_QX : SM_KS + 1024);

        for (int s = -1; s < NSEG; s++) {
            const uint32_t par = s & 1;
            FRESH(lane);
            const int g = lane >> 2, t = lane & 3, tid = warp * 32 + lane;
            if (s >= 0) {
                mbar_wait(bar + B_MEM_FULL * 8, par);
                TR(0);
                float c[4][4];
                #pragma unroll
                for (int i = 0; i < 4; i++) { c[i][0] = 0.f; c[i][1] = 0.f; c[i][2] = 0.f; c[i][3] = 0.f; }
                uint32_t maddr = sb + lane * 16;
                asm volatile("" : "+r"(maddr));
                #pragma unroll
                for (int kp = 0; kp < 20; kp++) {
                    uint32_t bb[4];
                    ldsm4t(bb, maddr + (SM_HB + kp * 512));
                    mma16(c[(kp & 1) * 2], wa[2 * kp][0], wa[2 * kp][1], wa[2 * kp][2], wa[2 * kp][3], bb[0], bb[1]);
                    mma16(c[(kp & 1) * 2 + 1], wa[2 * kp + 1][0], wa[2 * kp + 1][1], wa[2 * kp + 1][2], wa[2 * kp + 1][3], bb[2], bb[3]);
                }
                {
                    const int tok = lane & 7, ch = 2 * w + ((lane >> 3) & 1);
                    stsm2t(sb + (wg == 0 ? SM_QM : SM_KS) + tok * 128 + ((ch ^ tok) << 4),
                           pack2((c[0][0] + c[1][0]) + (c[2][0] + c[3][0]), (c[0][1] + c[1][1]) + (c[2][1] + c[3][1])),
                           pack2((c[0][2] + c[1][2]) + (c[2][2] + c[3][2]), (c[0][3] + c[1][3]) + (c[2][3] + c[3][3])));
                }
                __syncwarp();
                if (lane == 0) mbar_arrive(bar + B_MEM_FREE * 8);
                TR(1);
                bar_sync(1, 256);
                if (warp < 5) {
                    const int r = lane & 7, cq = lane >> 3;
                    uint32_t a[8], kb[8];
                    ldsm4(a, sb + SM_QM + r * 128 + ((cq ^ r) << 4));
                    ldsm4(kb, sb + SM_KS + (warp * 8 + r) * 128 + ((cq ^ r) << 4));
                    ldsm4(a + 4, sb + SM_QM + r * 128 + (((cq + 4) ^ r) << 4));
                    ldsm4(kb + 4, sb + SM_KS + (warp * 8 + r) * 128 + (((cq + 4) ^ r) << 4));
                    float d0[4] = {0.f, 0.f, 0.f, 0.f}, d1[4] = {0.f, 0.f, 0.f, 0.f};
                    mma16(d0, a[0], 0u, a[1], 0u, kb[0], kb[1]);
                    mma16(d1, a[2], 0u, a[3], 0u, kb[2], kb[3]);
                    mma16(d0, a[4], 0u, a[5], 0u, kb[4], kb[5]);
                    mma16(d1, a[6], 0u, a[7], 0u, kb[6], kb[7]);
                    const uint32_t la = sb + SM_MS + p * 1280 + warp * 256 + lane * 8;
                    #pragma unroll
                    for (int rk = 0; rk < 3; rk++)
                        st_async2(mapa(la, rk), d0[0] + d1[0], d0[1] + d1[1], mapa(bar + B_MS * 8, rk));
                    bar_arrive(4, 352);
                } else if (warp < 7) {
                    xscores<1>(sb, p, warp - 5, 0, lane);
                    bar_arrive(4, 352);
                }
                TR(2);
                if (s < NSEG - 1) {
                    wo_phase<0, 4>(sb, warp, lane, nullptr, par, (uint32_t)(s % 15) + 1u, tile0 + warp, h);
                    TR(4);
                }
            }
            if (s < NSEG - 1) {
                FRESH(lane);
                const uint32_t hp = (s + 1) & 1;
                float d[16];
                const uint64_t db0 = make_desc(SBC + SM_HB, 16, 1024, 1);
                mbar_wait(bar + B_HHI_FULL * 8, hp);
                if (s < 0 && warp == 0) T3(10);
                {
                    const int r = lane & 7, mq = lane >> 3;
                    const uint32_t ha = sb + SM_HB + 9 * 4096 + (8 * (mq >> 1) + r) * 128 + (((6 + (mq & 1)) ^ r) << 4);
                    uint32_t b0[4], b1[4];
                    ldsm4(b0, ha);
                    ldsm4(b1, ha + 2048);
                    #pragma unroll
                    for (int i = 0; i < 16; i++) d[i] = 0.f;
                    mma16(d + 0, wa[39][0], wa[39][1], wa[39][2], wa[39][3], b0[0], b0[1]);
                    mma16(d + 4, wa[39][0], wa[39][1], wa[39][2], wa[39][3], b0[2], b0[3]);
                    mma16(d + 8, wa[39][0], wa[39][1], wa[39][2], wa[39][3], b1[0], b1[1]);
                    mma16(d + 12, wa[39][0], wa[39][1], wa[39][2], wa[39][3], b1[2], b1[3]);
                    asm volatile("" : "+f"(d[0]), "+f"(d[4]), "+f"(d[8]), "+f"(d[12]) :: "memory");
                }
                if (s >= 0) bar_arrive(6, 512);
                mbar_wait(bar + B_HLO_FULL * 8, hp);
                bar_sync(9, 384);
                TR(6);
                wg_fence();
                #pragma unroll
                for (int kt = 0; kt < 12; kt++) wg_rs32(d, wa[kt], db0 + (uint64_t)(((kt >> 2) * 4096 + (kt & 3) * 32) >> 4), 1);
                wg_commit();
                #pragma unroll
                for (int kt = 12; kt < 39; kt++) wg_rs32(d, wa[kt], db0 + (uint64_t)(((kt >> 2) * 4096 + (kt & 3) * 32) >> 4), 1);
                wg_commit();
                wg_wait<1>();
                if (lane == 0) mbar_arrive(bar + B_HLO_FREE * 8);
                wg_wait<0>();
                if (lane == 0) mbar_arrive(bar + B_HHI_FREE * 8);
                TR(7);
                const int mi = lane >> 3, r = lane & 7;
                #pragma unroll
                for (int jj = 0; jj < 2; jj++) {
                    const int tok = 8 * (2 * jj + (mi >> 1)) + r, ch = 2 * w + (mi & 1);
                    stsm4t(dstx + tok * 128 + ((ch ^ r) << 4),
                           pack2(d[8 * jj + 0], d[8 * jj + 1]), pack2(d[8 * jj + 2], d[8 * jj + 3]),
                           pack2(d[8 * jj + 4], d[8 * jj + 5]), pack2(d[8 * jj + 6], d[8 * jj + 7]));
                }
                bar_arrive(8, 384);
                if (s < 0 && warp == 0) T3(11);
                if (s < 0) { bar_sync(0, 512); asm volatile("griddepcontrol.launch_dependents;" ::: "memory"); }
            }
        }
    } else if (wg == 2) {
        asm volatile("setmaxnreg.dec.sync.aligned.u32 64;");
        const int w = warp & 3;
        uint32_t res[4][4];
        {
            const bf16* src = Wo + ((size_t)h * DH + ((p + 1) % 3) * 64) * DM + (tile0 + warp) * 16 + 2 * t;
            #pragma unroll
            for (int kt = 0; kt < 4; kt++) {
                res[kt][0] = __ldg((const uint32_t*)(src + (size_t)(kt * 16 + g) * DM));
                res[kt][1] = __ldg((const uint32_t*)(src + (size_t)(kt * 16 + g) * DM + 8));
                res[kt][2] = __ldg((const uint32_t*)(src + (size_t)(kt * 16 + 8 + g) * DM));
                res[kt][3] = __ldg((const uint32_t*)(src + (size_t)(kt * 16 + 8 + g) * DM + 8));
            }
            #pragma unroll
            for (int kt = 0; kt < 4; kt++) {
                #pragma unroll
                for (int i = 0; i < 4; i++) res[kt][i] = movm(res[kt][i]);
            }
        }
        bar_sync(11, 256);
        if (tid == 256) {
            fence_async();
            mbar_expect(bar + B_WV * 8, 81920);
            #pragma unroll
            for (int i = 0; i < 5; i++) tma2d(sb + SM_WV + i * 16384, &maps.wv, h * DH + p * 64, i * 128, bar + B_WV * 8);
        }
        mbar_wait(bar + B_WV * 8, 0);
        if (w == 0) T3(3);
        const uint64_t da0 = make_desc(SBC + SM_WV, 16, 1024, 1);
        uint32_t vx[8], vm0 = 0, vm1 = 0;
        #pragma unroll
        for (int i = 0; i < 8; i++) vx[i] = 0;

        for (int s = -1; s < NSEG; s++) {
            FRESH(lane);
            const int g = lane >> 2, t = lane & 3, tid = warp * 32 + lane;
            if (s >= 0) {
                const uint32_t par = s & 1;
                mbar_wait(bar + B_MEM_FULL * 8, par);
                bar_sync(4, 352);
                TR(0);
                float dv[4];
                {
                    const uint64_t dbm = make_desc(SBC + SM_HB, 128, 128, 0);
                    wg_fence();
                    #pragma unroll
                    for (int kt = 0; kt < 40; kt++) {
                        wg_ss8(dv, da0 + (uint64_t)(kt * 128), dbm + (uint64_t)(kt * 16), kt > 0);
                        wg_commit();
                        if (kt < 39) wg_wait<1>();
                    }
                    wg_commit();
                }
                TR(1);
                bar_sync(5, 160);
                TR(2);
                uint32_t pb[5];
                #pragma unroll
                for (int j = 0; j < 5; j++) pb[j] = lds1(sb + SM_PM + j * 128 + lane * 4);
                float o0[4] = {0.f, 0.f, 0.f, 0.f}, o1[4] = {0.f, 0.f, 0.f, 0.f}, o2[4] = {0.f, 0.f, 0.f, 0.f};
                wg_wait<0>();
                TR(3);
                mma16(o0, vx[0], vx[1], vx[2], vx[3], pb[1], pb[2]);
                mma16(o1, vx[4], vx[5], vx[6], vx[7], pb[3], pb[4]);
                vm0 = pack2(dv[0], dv[1]); vm1 = pack2(dv[2], dv[3]);
                mma8(o2, vm0, vm1, pb[0]);
                if (s < NSEG - 1) {
                    const uint32_t q0 = pack2(o0[0] + o1[0] + o2[0], o0[1] + o1[1] + o2[1]), q1 = pack2(o0[2] + o1[2] + o2[2], o0[3] + o1[3] + o2[3]);
                    const uint32_t la = sb + SM_OS + (w * 16 + g) * 16 + t * 4;
                    #pragma unroll
                    for (int i = 1; i < 3; i++) {
                        const uint32_t rk = (p + i) % 3;
                        const uint32_t ra = mapa(la + (3 - i) * 1024, rk), rb = mapa(bar + B_O * 8, rk);
                        st_async1(ra, q0, rb);
                        st_async1(ra + 128, q1, rb);
                    }
                    sts1(la, q0);
                    sts1(la + 128, q1);
                    __syncwarp();
                    if (lane == 0) { mbar_arrive(bar + B_O1 * 8); mbar_arrive(bar + B_MEM_FREE * 8); }
                }
                TR(5);
                if (s < NSEG - 1) {
                    wo_phase<4, 4>(sb, warp, lane, res, par, (uint32_t)(s % 15) + 1u, tile0 + warp, h);
                    TR(4);
                    if (tid == 256) mbar_expect(bar + B_O * 8, 2048);
                }
                if (s < NSEG - 1) bar_sync(6, 512);
            }
            uint32_t vn[8];
            #pragma unroll
            for (int i = 0; i < 8; i++) vn[i] = 0;
            if (s < NSEG - 1) {
            float d[16];
            const uint32_t hp = (s + 1) & 1;
            const uint64_t db0 = make_desc(SBC + SM_HB, 16, 1024, 1);
            mbar_wait(bar + B_HHI_FULL * 8, hp);
            TR(6);
            wg_fence();
            #pragma unroll
            for (int kt = 12; kt < 40; kt++) wg_ss32(d, da0 + (uint64_t)(kt * 128), db0 + (uint64_t)(((kt >> 2) * 4096 + (kt & 3) * 32) >> 4), kt > 12);
            wg_commit();
            mbar_wait(bar + B_HLO_FULL * 8, hp);
            wg_fence();
            #pragma unroll
            for (int kt = 0; kt < 9; kt++) wg_ss32(d, da0 + (uint64_t)(kt * 128), db0 + (uint64_t)(((kt >> 2) * 4096 + (kt & 3) * 32) >> 4), 1);
            wg_commit();
            #pragma unroll
            for (int kt = 9; kt < 12; kt++) wg_ss32(d, da0 + (uint64_t)(kt * 128), db0 + (uint64_t)(((kt >> 2) * 4096 + (kt & 3) * 32) >> 4), 1);
            wg_commit();
            wg_wait<1>();
            bar_arrive(9, 384);
            wg_wait<0>();
            if (lane == 0) mbar_arrive(bar + B_HLO_FREE * 8);
            TR(7);
            if (lane == 0) mbar_arrive(bar + B_HHI_FREE * 8);
            #pragma unroll
            for (int i = 0; i < 8; i++) vn[i] = pack2(d[2 * i], d[2 * i + 1]);
            }
            if (s >= 0) {
                {
                    FRESH(lane);
                    mbar_wait(bar + B_XS * 8, s & 1);
                    if (w == 0 && lane == 0) mbar_expect(bar + B_XS * 8, 12288);
                    const uint32_t a = sb + SM_XS + (w >> 1) * 1536 + lane * 16 + (w & 1) * 8;
                    if (w == 0) xsoftmax<2>(a, lane >> 2, lane & 3);
                    else if (w == 1) xsoftmax<3>(a, lane >> 2, lane & 3);
                    else if (w == 2) xsoftmax<4>(a, lane >> 2, lane & 3);
                    else xsoftmax<5>(a, lane >> 2, lane & 3);
                }
                TR(8);
                bar_sync(7, 128);
                FRESH(lane);
                bf16* orow = g_ox + (size_t)(s * 32 + (lane >> 2)) * HD + h * DH + p * 64 + w * 16 + 2 * (lane & 3);
                {
                    const uint32_t pa = sb + SM_XS + lane * 16;
                    #pragma unroll
                    for (int mi = 0; mi < 2; mi++) {
                        float oa[4] = {0.f, 0.f, 0.f, 0.f}, ob[4] = {0.f, 0.f, 0.f, 0.f};
                        if (mi == 0) {
                            const uint4 p0 = lds4(pa);
                            const uint32_t p3 = lds1(pa + 1024 + 8);
                            mma8(oa, vm0, vm1, p0.x);
                            mma8(ob, vm0, vm1, p0.z);
                            mma16(oa, vx[0], vx[1], vx[2], vx[3], p0.y, 0u);
                            mma16(ob, vx[0], vx[1], vx[2], vx[3], p0.w, p3);
                        } else {
                            const uint4 p1 = lds4(pa + 1536), p2 = lds4(pa + 2560);
                            const uint32_t p4 = lds1(pa + 3584 + 8);
                            mma8(oa, vm0, vm1, p1.x);
                            mma8(ob, vm0, vm1, p1.z);
                            mma16(oa, vx[0], vx[1], vx[2], vx[3], p1.y, p2.x);
                            mma16(ob, vx[0], vx[1], vx[2], vx[3], p1.w, p2.z);
                            mma16(oa, vx[4], vx[5], vx[6], vx[7], p2.y, 0u);
                            mma16(ob, vx[4], vx[5], vx[6], vx[7], p2.w, p4);
                            if (lane < 3) mbar_arrive_remote(mapa(bar + B_XSFREE * 8, lane));
                        }
                        const uint32_t u0 = movm(pack2(oa[0], oa[1])), u1 = movm(pack2(oa[2], oa[3]));
                        const uint32_t u2 = movm(pack2(ob[0], ob[1])), u3 = movm(pack2(ob[2], ob[3]));
                        bf16* dst = orow + (size_t)(16 * mi) * HD;
                        *(uint32_t*)dst = u0;
                        *(uint32_t*)(dst + 8) = u1;
                        *(uint32_t*)(dst + 8 * HD) = u2;
                        *(uint32_t*)(dst + 8 * HD + 8) = u3;
                    }
                }
                TR(9);
                if (s == NSEG - 1) {
                    bar_sync(7, 128);
                    if (w == 3 && lane == 0) { signal_cnt(C_REC + 15); T2(400 + b); }
                    break;
                }
            }
            #pragma unroll
            for (int i = 0; i < 8; i++) vx[i] = vn[i];
            if (s >= 0) mbar_wait_cluster(bar + B_XSFREE * 8, s & 1);
            bar_sync(8, 384);
            TR(10);
            if (w < 3) xscores<2>(sb, p, w > 0, w == 2 ? 3 : 1, lane);
            else if ((s & 3) == 3 && s >= 0 && lane == 0) signal_cnt(C_REC + (s >> 2));
            __syncwarp();
            TR(11);
            if (s < 0) { bar_sync(0, 512); asm volatile("griddepcontrol.launch_dependents;" ::: "memory"); }
        }
    } else {
        asm volatile("setmaxnreg.dec.sync.aligned.u32 48;");
        const int w = warp & 3, lt = tid & 127;
        const uint32_t epoch = *(volatile uint32_t*)&g_epoch + 1u;
        if (b == 91) { if (lt < C_NUM) g_cnt[lt * 32] = 0u; __threadfence(); }
        if (b < 80) {
            #pragma unroll
            for (int i = 0; i < 2; i++) {
                const int idx = lt + i * 128, sl = idx >> 6, pg = (idx >> 5) & 1, wd = idx & 31;
                st_relaxed1(g_buf2 + (sl * 3 + (b >> 5)) * 2048 + pg * 1024 + (b & 31) * 32 + wd, 0xFFFFFFFFu);
            }
            __threadfence();
        }
        if (lane == 0 && w < 3) {
            int c = 0;
            if (w == 0) c = probe_blk(g_buf2 + 640 + (b & 31) * 8);
            else if (b < 80) c = probe_blk(g_buf1 + (b * 2 + (w - 1)) * 2048);
            else if (b < 92 && w == 1) c = probe_blk(g_buf2 + (b - 80) * 2048 + 960);
            asm volatile("st.shared.u8 [%0], %1;" :: "r"(sb + SM_CH + 96 + w), "r"(c) : "memory");
        }
        if (w == 0) T3(4);
        bar_sync(3, 128);
        uint32_t selmask;
        {
            const uint32_t c3 = lds1(sb + SM_CH + 96);
            const uint32_t cr = c3 & 1u, c1 = (c3 >> 8) & 1u, c2 = (c3 >> 16) & 1u;
            if (lt == 0 && b < 92) st_release1(&g_choice[b], (epoch << 2) | (b < 80 ? (c1 | (c2 << 1)) : (c1 ^ cr)));
            bar_sync(10, 256);
            if (w == 3) {
                if (lane == 0) { fence_async(); mbar_expect(bar + B_WO * 8, ntile * 6144 - 8192); }
                __syncwarp();
                if (lane < ntile) {
                    #pragma unroll
                    for (int e3 = 0; e3 < 3; e3++) {
                        const bool part = lane >= 8 && lane < 12;
                        if (part && e3 == 1) continue;
                        tma2d(sb + SM_WO + wo_tile_off(lane) + ((part && e3 == 2) ? 1 : e3) * 2048, &maps.wo,
                              (tile0 + lane) * 16, h * DH + ((e3 + p) % 3) * 64, bar + B_WO * 8);
                    }
                }
                __syncwarp();
            }
            if (w == 0) T3(5);
            if (lt < 92) {
                uint32_t v, guard = 0;
                while (true) {
                    v = ld_acquire1(&g_choice[lt]);
                    if ((v >> 2) == (epoch & 0x3fffffffu)) break;
                    __nanosleep(100);
                    if (++guard > (1u << 22)) __trap();
                }
                asm volatile("st.shared.u8 [%0], %1;" :: "r"(sb + SM_CH + lt), "r"(v & 3u) : "memory");
            }
            if (w == 0) T3(6);
            bar_sync(3, 128);
            selmask = (c1 << 12) | (c2 << 13);
            for (int i = 0; i < 12; i++) {
                uint32_t c; asm volatile("ld.shared.u8 %0, [%1];" : "=r"(c) : "r"(sb + SM_CH + 80 + i) : "memory");
                selmask |= ((c ^ cr) & 1u) << i;
            }
        }
        mbar_wait(bar + B_WO * 8, 0);
        if (w == 0) T3(8);
        bar_sync(0, 512);
        if (w == 0) T3(9);
        asm volatile("griddepcontrol.launch_dependents;" ::: "memory");
        const bool has_tile = (12 + w) < ntile;
        for (int s = 0; s < NSEG; s++) {
            const uint32_t par = s & 1;
            FRESH(lane);
            const int g = lane >> 2, t = lane & 3, lt = w * 32 + lane;
            if (s == 0) {
                mbar_wait(bar + B_HLO_FREE * 8, par);
                for (int k = lt; k < DM; k += 128) {
                    uint32_t v[4];
                    #pragma unroll
                    for (int i = 0; i < 4; i++) {
                        uint32_t lo = *(const uint16_t*)(mem0 + (2 * i) * DM + k), hi = *(const uint16_t*)(mem0 + (2 * i + 1) * DM + k);
                        v[i] = lo | (hi << 16);
                    }
                    asm volatile("st.shared.v4.u32 [%0], {%1,%2,%3,%4};" :: "r"(sb + SM_HB + k * 16), "r"(v[0]), "r"(v[1]), "r"(v[2]), "r"(v[3]) : "memory");
                }
            } else {
                const int sl = s & 3;
                const char* q = (const char*)g_buf2 + sl * 3 * 8192 + lt * 16;
                const uint32_t sm = selmask >> (sl * 3);
                const char* q0 = q + (sm & 1) * 4096;
                const char* q1 = q + 8192 + (sm & 2) * 2048;
                const char* q2 = q + 16384 + (sm & 4) * 1024;
                const uint32_t dst = sb + SM_HB + lt * 16;
                uint32_t guard = 0;
                mbar_wait(bar + B_HLO_FREE * 8, par);
                TR(10);
                while (true) {
                    const uint4 v0 = ld_relaxed4(q0), v1 = ld_relaxed4(q0 + 2048), v2 = ld_relaxed4(q1), v3 = ld_relaxed4(q1 + 2048), v4 = ld_relaxed4(q2);
                    sts4(dst, v0); sts4(dst + 2048, v1); sts4(dst + 4096, v2); sts4(dst + 6144, v3); sts4(dst + 8192, v4);
                    if (__all_sync(0xffffffffu, oks(v0) && oks(v1) && oks(v2) && oks(v3) && oks(v4))) break;
                    if (++guard > (1u << 22)) __trap();
                }
            }
            fence_async();
            __syncwarp();
            if (lane == 0) mbar_arrive(bar + B_MEM_FULL * 8);
            if (b == 0 && lt == 0) T2(300 + s);
            if (s == 0 && lt == 0) T2(200 + b);
            TR(0);
            if (w == 2) {
                mbar_wait(bar + B_MS * 8, par);
                TR(1);
                if (lane == 0) mbar_expect(bar + B_MS * 8, 3840);
                uint32_t pb[5];
                float sc[5][2];
                {
                    const uint32_t a = sb + SM_MS + lane * 8;
                    float2 u[5], v[5];
                    #pragma unroll
                    for (int j = 0; j < 5; j++) { u[j] = lds2f(a + j * 256); v[j] = lds2f(a + j * 256 + 1280); }
                    #pragma unroll
                    for (int j = 0; j < 5; j++) { sc[j][0] = u[j].x + v[j].x; sc[j][1] = u[j].y + v[j].y; }
                    #pragma unroll
                    for (int j = 0; j < 5; j++) u[j] = lds2f(a + j * 256 + 2560);
                    #pragma unroll
                    for (int j = 0; j < 5; j++) { sc[j][0] += u[j].x; sc[j][1] += u[j].y; }
                }
                softmax_core<5, false>(sc, g, t, pb);
                #pragma unroll
                for (int j = 0; j < 5; j++) sts1(sb + SM_PM + j * 128 + lane * 4, pb[j]);
                bar_arrive(5, 160);
                TR(2);
            }
            const uint32_t tag = (uint32_t)(s % 15) + 1u;
            if (s < NSEG - 1) {
                if (w == 3) {
                    const char* src = (const char*)g_ht + (size_t)(s + 1) * 40960;
                    if (s == 0) {
                        uint32_t guard = 0;
                        while (true) {
                            const uint32_t f0 = lane > 0 ? ld_acquire1(&g_hflag[lane]) : epoch, f1 = ld_acquire1(&g_hflag[32 + lane]);
                            if (__all_sync(0xffffffffu, f0 == epoch && f1 == epoch)) break;
                            if (++guard > (1u << 22)) __trap();
                        }
                        asm volatile("fence.proxy.async;" ::: "memory");
                    }
                    mbar_wait(bar + B_HHI_FREE * 8, par);
                    if (lane == 0) {
                        mbar_expect(bar + B_HHI_FULL * 8, 28672);
                        bulk_g2s(sb + SM_HB + 12288, src + 12288, 28672, sb + SM_BAR + B_HHI_FULL * 8);
                    }
                    mbar_wait(bar + B_MEM_FREE * 8, par);
                    if (lane == 0) {
                        mbar_expect(bar + B_HLO_FULL * 8, 12288);
                        bulk_g2s(sb + SM_HB, src, 12288, sb + SM_BAR + B_HLO_FULL * 8);
                    }
                    __syncwarp();
                }
                if (has_tile) wo_phase<0, 4>(sb, warp, lane, nullptr, par, tag, tile0 + warp, h);
                TR(4);
                bar_sync(6, 512);
            }
            if (s < NSEG - 1) {
                { const uint32_t c0 = clk32(); while (clk32() - c0 < H1_DELAY); }
                if (b < 80) {
                    FRESH(lane);
                    const char* rin0 = (const char*)g_buf1 + (size_t)(b * 2) * 8192 + ((selmask >> 12) & 1) * 4096 + (lane >> 2) * 256 + w * 64 + (lane & 3) * 16;
                    const char* rin1 = (const char*)g_buf1 + (size_t)(b * 2 + 1) * 8192 + ((selmask >> 13) & 1) * 4096 + (lane >> 2) * 256 + w * 64 + (lane & 3) * 16;
                    const int col = b * 8 + 2 * w + ((lane >> 1) & 1), wd = 2 * (lane & 1) + (lane >> 4);
                    const int sl = (lane & 8) ? ((s + 3) & 3) : ((s + 1) & 3);
                    uint32_t* dst = g_buf2 + (sl * 3 + (col >> 8)) * 2048 + ((lane >> 2) & 1) * 1024 + (col & 255) * 4 + wd;
                    asm volatile("" : "+l"(dst));
                    uint4 v0, v1, v2, v3;
                    uint32_t guard = 0;
                    while (true) {
                        v0 = ld_relaxed4(rin0); v1 = ld_relaxed4(rin0 + 2048);
                        v2 = ld_relaxed4(rin1); v3 = ld_relaxed4(rin1 + 2048);
                        if (__all_sync(0xffffffffu, ok4(v0, tag) && ok4(v1, tag) && ok4(v2, tag) && ok4(v3, tag))) break;
                        if (++guard > (1u << 22)) __trap();
                    }
                    TR(11);
                    const float a0 = (uf(v0.x) + uf(v1.x)) + (uf(v2.x) + uf(v3.x)), a1 = (uf(v0.y) + uf(v1.y)) + (uf(v2.y) + uf(v3.y));
                    const float a2 = (uf(v0.z) + uf(v1.z)) + (uf(v2.z) + uf(v3.z)), a3 = (uf(v0.w) + uf(v1.w)) + (uf(v2.w) + uf(v3.w));
                    const bool u16 = lane & 16;
                    float m0 = (u16 ? a2 : a0) + __shfl_xor_sync(0xffffffffu, u16 ? a0 : a2, 16);
                    float m1 = (u16 ? a3 : a1) + __shfl_xor_sync(0xffffffffu, u16 ? a1 : a3, 16);
                    m0 += __shfl_xor_sync(0xffffffffu, m0, 8); m1 += __shfl_xor_sync(0xffffffffu, m1, 8);
                    m0 += __shfl_xor_sync(0xffffffffu, m0, 4); m1 += __shfl_xor_sync(0xffffffffu, m1, 4);
                    st_relaxed1(dst, (lane & 8) ? 0xFFFFFFFFu : pack2(m0, m1));
                    TR(12);
                }
            }
        }
    }
    cluster_sync();
}

constexpr int G_STAGES = 6;
constexpr int G_STAGE_BYTES = 32768;
constexpr int G_SMEM = G_STAGES * G_STAGE_BYTES + 1024 + 256 + 2048 + 10240;

__device__ __forceinline__ void wg_ss128(float* d, uint64_t da, uint64_t db, int sc) {
    asm volatile("{\n\t.reg .pred p;\n\tsetp.ne.b32 p, %66, 0;\n\t"
        "wgmma.mma_async.sync.aligned.m64n128k16.f32.bf16.bf16 "
        "{%0,%1,%2,%3,%4,%5,%6,%7,%8,%9,%10,%11,%12,%13,%14,%15,%16,%17,%18,%19,%20,%21,%22,%23,%24,%25,%26,%27,%28,%29,%30,%31,"
        "%32,%33,%34,%35,%36,%37,%38,%39,%40,%41,%42,%43,%44,%45,%46,%47,%48,%49,%50,%51,%52,%53,%54,%55,%56,%57,%58,%59,%60,%61,%62,%63}, "
        "%64, %65, p, 1, 1, 0, 1;\n\t}"
        : "+f"(d[0]), "+f"(d[1]), "+f"(d[2]), "+f"(d[3]), "+f"(d[4]), "+f"(d[5]), "+f"(d[6]), "+f"(d[7]),
          "+f"(d[8]), "+f"(d[9]), "+f"(d[10]), "+f"(d[11]), "+f"(d[12]), "+f"(d[13]), "+f"(d[14]), "+f"(d[15]),
          "+f"(d[16]), "+f"(d[17]), "+f"(d[18]), "+f"(d[19]), "+f"(d[20]), "+f"(d[21]), "+f"(d[22]), "+f"(d[23]),
          "+f"(d[24]), "+f"(d[25]), "+f"(d[26]), "+f"(d[27]), "+f"(d[28]), "+f"(d[29]), "+f"(d[30]), "+f"(d[31]),
          "+f"(d[32]), "+f"(d[33]), "+f"(d[34]), "+f"(d[35]), "+f"(d[36]), "+f"(d[37]), "+f"(d[38]), "+f"(d[39]),
          "+f"(d[40]), "+f"(d[41]), "+f"(d[42]), "+f"(d[43]), "+f"(d[44]), "+f"(d[45]), "+f"(d[46]), "+f"(d[47]),
          "+f"(d[48]), "+f"(d[49]), "+f"(d[50]), "+f"(d[51]), "+f"(d[52]), "+f"(d[53]), "+f"(d[54]), "+f"(d[55]),
          "+f"(d[56]), "+f"(d[57]), "+f"(d[58]), "+f"(d[59]), "+f"(d[60]), "+f"(d[61]), "+f"(d[62]), "+f"(d[63])
        : "l"(da), "l"(db), "r"(sc));
}

#define SP0_LAST 12
#define SP2_LAST 6
enum { J_MOD = 0, J_G0, J_LN, J_G1, J_G2, J_FIN, J_END };
__host__ __device__ constexpr int sp0(int b) { return b >= 15 ? SP0_LAST : 3; }
__host__ __device__ constexpr int sp2(int b) { return b >= 15 ? SP2_LAST : 3; }
__host__ __device__ constexpr int njr(int b) { return b >= 15 ? 16 : 8; }
struct JobTab { uint32_t n; uint32_t j[1200]; };
constexpr uint32_t mkjob(int ty, int b, int n, int k0, int nk, int ks) {
    return (uint32_t)(ty | (b << 3) | (n << 7) | (k0 << 11) | (nk << 18) | (ks << 25));
}
constexpr void add_jobs(JobTab& t, int ty, int b) {
    if (b < 0) return;
    if (ty == J_G0) { for (int ks = 0; ks < sp0(b); ks++) for (int n = 0; n < 5; n++) t.j[t.n++] = mkjob(ty, b, n, ks * (96 / sp0(b)), 96 / sp0(b), ks); }
    else if (ty == J_G2) { for (int ks = 0; ks < sp2(b); ks++) for (int n = 0; n < 5; n++) t.j[t.n++] = mkjob(ty, b, n, ks * (24 / sp2(b)), 24 / sp2(b), ks); }
    else if (ty == J_G1) { for (int n = 0; n < 12; n++) t.j[t.n++] = mkjob(ty, b, n, 0, 10, 0); }
    else { for (int n = 0; n < njr(b); n++) t.j[t.n++] = mkjob(ty, b, n, 0, 16 / njr(b), ty == J_LN ? sp0(b) : sp2(b)); }
}
constexpr JobTab make_tab() {
    JobTab t = {};
    for (int i = 20; i < 60; i++) t.j[t.n++] = mkjob(J_MOD, 0, 0, i, 0, 0);
    for (int b = 0; b < 15; b++) {
        add_jobs(t, J_G0, b); add_jobs(t, J_G1, b - 1); add_jobs(t, J_FIN, b - 2); add_jobs(t, J_G2, b - 1); add_jobs(t, J_LN, b);
    }
    add_jobs(t, J_FIN, 13); add_jobs(t, J_G1, 14);
    add_jobs(t, J_G0, 15); add_jobs(t, J_G2, 14); add_jobs(t, J_LN, 15); add_jobs(t, J_FIN, 14);
    add_jobs(t, J_G1, 15); add_jobs(t, J_G2, 15); add_jobs(t, J_FIN, 15);
    return t;
}
__constant__ JobTab c_jobs = make_tab();

__device__ __forceinline__ bool cnt_ge(int idx, uint32_t target) { return ld_acquire1(g_cnt + idx * 32) >= target; }
__device__ __forceinline__ void cnt_wait(int idx, uint32_t target) {
    uint32_t guard = 0;
    while (!cnt_ge(idx, target)) { __nanosleep(64); if (++guard > (1u << 22)) __trap(); }
}

struct SMaps { CUtensorMap ox, wo, h2, w1, act, w2; };

__global__ void __launch_bounds__(384, 1)
k_side(const __grid_constant__ SMaps maps, const bf16* __restrict__ xin, const bf16* __restrict__ cvec,
       const bf16* __restrict__ wmod, bf16* __restrict__ outp) {
    extern __shared__ uint8_t smem_raw[];
    const uint32_t sb = (smem_u32(smem_raw) + 1023u) & ~1023u;
    const uint32_t bars = sb + G_STAGES * G_STAGE_BYTES;
    float* red = (float*)(smem_raw + (bars + 256 - smem_u32(smem_raw)));
    const int tid = threadIdx.x, lane = tid & 31, wg = tid >> 7;
    if (tid == 0) T2(500 + blockIdx.x);
    if (tid == 0) {
        for (int i = 0; i < G_STAGES; i++) { mbar_init(bars + i * 8, 1); mbar_init(bars + 64 + i * 8, 8); }
        for (int i = 0; i < 2; i++) { mbar_init(bars + 128 + i * 8, 1); mbar_init(bars + 144 + i * 8, 8); }
        asm volatile("fence.mbarrier_init.release.cluster;" ::: "memory");
    }
    __syncthreads();
    if (wg == 0) {
        if (tid == 0) {
            uint32_t st = 0, ph = 1;
            for (uint32_t it = 0;; it++) {
                const uint32_t ji = atomicAdd(g_cnt + C_Q * 32, 1u);
                const uint32_t job = ji < c_jobs.n ? c_jobs.j[ji] : (uint32_t)J_END;
                if (ji == 0) g_epoch = g_epoch + 1u;
                const int ty = job & 7, b = (job >> 3) & 15, n = (job >> 7) & 15, k0 = (job >> 11) & 127, nk = (job >> 18) & 127;
                const uint32_t sl = it & 1;
                mbar_wait(bars + 144 + sl * 8, ((it >> 1) & 1) ^ 1);
                sts1(bars + 160 + sl * 4, job);
                if (ty == J_G0 || ty == J_G1 || ty == J_G2) {
                    if (b >= PRING && ty != J_G1) cnt_wait((ty == J_G0 ? C_LN : C_FIN) + b - PRING, njr(b - PRING));
                    mbar_arrive(bars + 128 + sl * 8);
                    const CUtensorMap* mA = ty == J_G0 ? &maps.ox : (ty == J_G1 ? &maps.h2 : &maps.act);
                    const CUtensorMap* mB = ty == J_G0 ? &maps.wo : (ty == J_G1 ? &maps.w1 : &maps.w2);
                    const int didx = ty == J_G0 ? C_REC + b : (ty == J_G1 ? C_LN + b : C_G1 + b);
                    const uint32_t dtgt = ty == J_G0 ? 96u : (ty == J_G1 ? (uint32_t)njr(b) : 12u);
                    int pre = 0;
                    if (!cnt_ge(didx, dtgt)) {
                        pre = nk < G_STAGES ? nk : G_STAGES;
                        uint32_t s2 = st, p2 = ph;
                        for (int i = 0; i < pre; i++) {
                            mbar_wait(bars + 64 + s2 * 8, p2);
                            const uint32_t a = sb + s2 * G_STAGE_BYTES;
                            mbar_expect(bars + s2 * 8, G_STAGE_BYTES);
                            tma2d(a + 16384, mB, n * 128, (k0 + i) * 64, bars + s2 * 8);
                            tma2d(a + 16384 + 8192, mB, n * 128 + 64, (k0 + i) * 64, bars + s2 * 8);
                            if (++s2 == G_STAGES) { s2 = 0; p2 ^= 1; }
                        }
                        cnt_wait(didx, dtgt);
                    }
                    asm volatile("fence.proxy.async;" ::: "memory");
                    T2(1024 + ji * 4 + 1);
                    for (int i = 0; i < nk; i++) {
                        const uint32_t a = sb + st * G_STAGE_BYTES;
                        if (i >= pre) {
                            mbar_wait(bars + 64 + st * 8, ph);
                            mbar_expect(bars + st * 8, G_STAGE_BYTES);
                        }
                        tma2d(a, mA, (k0 + i) * 64, b * 128, bars + st * 8);
                        if (i >= pre) {
                            tma2d(a + 16384, mB, n * 128, (k0 + i) * 64, bars + st * 8);
                            tma2d(a + 16384 + 8192, mB, n * 128 + 64, (k0 + i) * 64, bars + st * 8);
                        }
                        if (++st == G_STAGES) { st = 0; ph ^= 1; }
                    }
                } else {
                    if (ty == J_LN) { bulk_pf(xin + (size_t)(b * 128 + n * nk * 8) * DM, nk * 8 * DM * 2); cnt_wait(C_MOD, 40u); cnt_wait(C_G0 + b, 5u * sp0(b)); }
                    else if (ty == J_FIN) cnt_wait(C_G2 + b, 5u * sp2(b));
                    if (ji < 1200) T2(1024 + ji * 4 + 1);
                    mbar_arrive(bars + 128 + sl * 8);
                    if (ty == J_END) break;
                }
            }
        }
    } else {
        const int cw = wg - 1, ct = tid - 128, cwarp = ct >> 5;
        uint32_t st = 0, ph = 0;
        float* smod = red + 512;
        bool have_mod = false;
        auto load_mod = [&]() {
            for (int i = ct; i < DM; i += 256) *(float4*)(smod + i * 4) = __ldcg((const float4*)(g_mod + 2 * DM + i * 4));
            bar_sync(1, 256);
            have_mod = true;
        };
        {
            if (ct == 0) red[0] = cnt_ge(C_MOD, 40u) ? 1.0f : 0.0f;
            bar_sync(1, 256);
            const bool rdy = red[0] != 0.0f;
            bar_sync(1, 256);
            if (rdy) load_mod();
        }
        for (uint32_t it = 0;; it++) {
            const uint32_t sl = it & 1;
            mbar_wait(bars + 128 + sl * 8, (it >> 1) & 1);
            const uint32_t job = lds1(bars + 160 + sl * 4);
            __syncwarp();
            if (lane == 0) mbar_arrive(bars + 144 + sl * 8);
            const int ty = job & 7, b = (job >> 3) & 15, n = (job >> 7) & 15, k0 = (job >> 11) & 127, nk = (job >> 18) & 127, ks = (job >> 25) & 15;
            if (ty == J_END) break;
            int sig = -1;
            if (ty == J_G0 || ty == J_G1 || ty == J_G2) {
                float d[64];
                #pragma unroll
                for (int i = 0; i < 64; i++) d[i] = 0.f;
                uint32_t pst = 0;
                for (int kb = 0; kb < nk; kb++) {
                    mbar_wait(bars + st * 8, ph);
                    const uint32_t a = sb + st * G_STAGE_BYTES;
                    const uint64_t da = make_desc(a + cw * 8192, 16, 1024, 1);
                    const uint64_t db = make_desc(a + 16384, 8192, 1024, 1);
                    wg_fence();
                    #pragma unroll
                    for (int k = 0; k < 4; k++) wg_ss128(d, da + (uint64_t)(k * 2), db + (uint64_t)(k * 128), 1);
                    wg_commit();
                    if (kb > 0) {
                        wg_wait<1>();
                        if (lane == 0) mbar_arrive(bars + 64 + pst * 8);
                    }
                    pst = st;
                    if (++st == G_STAGES) { st = 0; ph ^= 1; }
                }
                wg_wait<0>();
                if (lane == 0) mbar_arrive(bars + 64 + pst * 8);
                const int g = lane >> 2, t = lane & 3;
                if (ty == J_G1) {
                    #pragma unroll
                    for (int hf = 0; hf < 2; hf++) {
                        bf16* o = g_act + (size_t)(b * 128 + cwarp * 16 + g + 8 * hf) * FF + n * 128 + 8 * t;
                        #pragma unroll
                        for (int q = 0; q < 4; q++) {
                            uint32_t u[4];
                            #pragma unroll
                            for (int i = 0; i < 4; i++) {
                                const float a0 = bfr(d[4 * (4 * q + i) + 2 * hf]), a1 = bfr(d[4 * (4 * q + i) + 2 * hf + 1]);
                                u[i] = pack2(__fdividef(a0, 1.0f + __expf(-a0)), __fdividef(a1, 1.0f + __expf(-a1)));
                            }
                            const bool o1 = t & 1, o2 = t & 2;
                            uint32_t x0 = __shfl_xor_sync(0xffffffffu, o1 ? u[0] : u[1], 1), x1 = __shfl_xor_sync(0xffffffffu, o1 ? u[2] : u[3], 1);
                            if (o1) { u[0] = x0; u[2] = x1; } else { u[1] = x0; u[3] = x1; }
                            x0 = __shfl_xor_sync(0xffffffffu, o2 ? u[0] : u[2], 2); x1 = __shfl_xor_sync(0xffffffffu, o2 ? u[1] : u[3], 2);
                            if (o2) { u[0] = x0; u[1] = x1; } else { u[2] = x0; u[3] = x1; }
                            *(uint4*)(o + q * 32) = make_uint4(u[0], u[1], u[2], u[3]);
                        }
                    }
                    sig = C_G1 + b;
                } else {
                    float* o = (ty == J_G0 ? g_p0 : g_p2) + ((size_t)((b % PRING) * PMAX + ks) * 128 + cwarp * 16 + g) * DM + n * 128 + 2 * t;
                    #pragma unroll
                    for (int hf = 0; hf < 2; hf++) {
                        #pragma unroll
                        for (int j = 0; j < 16; j++)
                            *(float2*)(o + hf * 8 * DM + j * 8) = make_float2(d[4 * j + 2 * hf], d[4 * j + 2 * hf + 1]);
                    }
                    sig = (ty == J_G0 ? C_G0 : C_G2) + b;
                }
            } else if (ty == J_MOD) {
                mod_chunk<256, 2>(cvec, wmod, k0 * 64, ct, red);
                sig = C_MOD;
            } else {
                const bool ln = ty == J_LN;
                if (!have_mod) load_mod();
                const float* gm = smod + (ln ? 0 : 3) * DM + lane * 4;
                for (int r = 0; r < nk; r++) {
                    const int lr = (n * nk + r) * 8 + cwarp, row = b * 128 + lr;
                    const float* pp = (ln ? g_p0 : g_p2) + ((size_t)((b % PRING) * PMAX) * 128 + lr) * DM + lane * 4;
                    const bf16* xs = (ln ? xin : (const bf16*)g_x1) + (size_t)row * DM + lane * 4;
                    float v[5][4];
                    uint2 xv[5];
                    #pragma unroll
                    for (int i = 0; i < 5; i++) {
                        xv[i] = __ldcg((const uint2*)(xs + i * 128));
                        v[i][0] = 0.f; v[i][1] = 0.f; v[i][2] = 0.f; v[i][3] = 0.f;
                    }
                    if (ks == 3) {
                        float4 a[3][5];
                        #pragma unroll
                        for (int q = 0; q < 3; q++) {
                            #pragma unroll
                            for (int i = 0; i < 5; i++) a[q][i] = __ldcg((const float4*)(pp + (size_t)q * 128 * DM + i * 128));
                        }
                        #pragma unroll
                        for (int q = 0; q < 3; q++) {
                            #pragma unroll
                            for (int i = 0; i < 5; i++) { v[i][0] += a[q][i].x; v[i][1] += a[q][i].y; v[i][2] += a[q][i].z; v[i][3] += a[q][i].w; }
                        }
                    } else {
                        for (int q0 = 0; q0 < ks; q0 += 6) {
                            float4 a[6][5];
                            #pragma unroll
                            for (int q = 0; q < 6; q++) {
                                #pragma unroll
                                for (int i = 0; i < 5; i++) a[q][i] = __ldcg((const float4*)(pp + (size_t)(q0 + q) * 128 * DM + i * 128));
                            }
                            #pragma unroll
                            for (int q = 0; q < 6; q++) {
                                #pragma unroll
                                for (int i = 0; i < 5; i++) { v[i][0] += a[q][i].x; v[i][1] += a[q][i].y; v[i][2] += a[q][i].z; v[i][3] += a[q][i].w; }
                            }
                        }
                    }
                    bf16* dst = (ln ? (bf16*)g_x1 : outp) + (size_t)row * DM + lane * 4;
                    #pragma unroll
                    for (int i = 0; i < 5; i++) {
                        const float4 gg = *(const float4*)(gm + i * 128);
                        const uint32_t o0 = pack2(bflo(xv[i].x) + bfr(gg.x * bfr(v[i][0])), bfhi(xv[i].x) + bfr(gg.y * bfr(v[i][1])));
                        const uint32_t o1 = pack2(bflo(xv[i].y) + bfr(gg.z * bfr(v[i][2])), bfhi(xv[i].y) + bfr(gg.w * bfr(v[i][3])));
                        *(uint2*)(dst + i * 128) = make_uint2(o0, o1);
                        v[i][0] = bflo(o0); v[i][1] = bfhi(o0); v[i][2] = bflo(o1); v[i][3] = bfhi(o1);
                    }
                    if (ln) {
                        float mb, sd;
                        ln_stats(v, mb, sd);
                        #pragma unroll
                        for (int i = 0; i < 5; i++) {
                            const float4 sh = *(const float4*)(gm + DM + i * 128), sc = *(const float4*)(gm + 2 * DM + i * 128);
                            *(uint2*)(g_h2 + (size_t)row * DM + lane * 4 + i * 128) = ln_apply(v[i], mb, sd, sc, sh);
                        }
                    }
                }
                if (ln) sig = C_LN + b; else if (b < 16 - PRING) sig = C_FIN + b;
            }
            if (sig >= 0) {
                bar_sync(1, 256);
                if (ct == 0) signal_cnt(sig);
            }
            if (ct == 0) T2(1024 + ji * 4 + 2);
        }
    }
}

typedef CUresult (*EncodeFn)(CUtensorMap*, CUtensorMapDataType, cuuint32_t, void*, const cuuint64_t*, const cuuint64_t*,
                             const cuuint32_t*, const cuuint32_t*, CUtensorMapInterleave, CUtensorMapSwizzle,
                             CUtensorMapL2promotion, CUtensorMapFloatOOBfill);

static void make_map(EncodeFn fn, CUtensorMap* m, const void* ptr, uint64_t inner, uint64_t outer, uint32_t bi, uint32_t bo,
                     CUtensorMapSwizzle sw = CU_TENSOR_MAP_SWIZZLE_128B) {
    cuuint64_t dims[2] = {inner, outer};
    cuuint64_t strides[1] = {inner * 2};
    cuuint32_t box[2] = {bi, bo};
    cuuint32_t es[2] = {1, 1};
    fn(m, CU_TENSOR_MAP_DATA_TYPE_BFLOAT16, 2, (void*)ptr, dims, strides, box, es, CU_TENSOR_MAP_INTERLEAVE_NONE,
       sw, CU_TENSOR_MAP_L2_PROMOTION_L2_256B, CU_TENSOR_MAP_FLOAT_OOB_FILL_NONE);
}

extern "C" void kernel_launch(void* const* d_in, const int* in_sizes, int n_in, void* d_out, int out_size) {
    const bf16* x = (const bf16*)d_in[0];
    const bf16* mem0 = (const bf16*)d_in[1];
    const bf16* Wq = (const bf16*)d_in[2];
    const bf16* Wk = (const bf16*)d_in[3];
    const bf16* Wv = (const bf16*)d_in[4];
    const bf16* Wo = (const bf16*)d_in[5];
    const bf16* w1 = (const bf16*)d_in[8];
    const bf16* w2 = (const bf16*)d_in[9];
    const bf16* c = (const bf16*)d_in[10];
    const bf16* wmod = (const bf16*)d_in[11];
    bf16* out = (bf16*)d_out;

    static EncodeFn enc = nullptr;
    static void *p_ox, *p_x1, *p_h2, *p_act;
    if (!enc) {
        cudaDriverEntryPointQueryResult qr;
        void* f = nullptr;
        cudaGetDriverEntryPoint("cuTensorMapEncodeTiled", &f, cudaEnableDefault, &qr);
        enc = (EncodeFn)f;
        cudaGetSymbolAddress(&p_ox, g_ox);
        cudaGetSymbolAddress(&p_x1, g_x1);
        cudaGetSymbolAddress(&p_h2, g_h2);
        cudaGetSymbolAddress(&p_act, g_act);
        cudaFuncSetAttribute(k_rec, cudaFuncAttributeMaxDynamicSharedMemorySize, SM_TOTAL);
        cudaFuncSetAttribute(k_side, cudaFuncAttributeMaxDynamicSharedMemorySize, G_SMEM);
    }
    RMaps rm;
    make_map(enc, &rm.wq, Wq, HD, DM, 64, 128);
    make_map(enc, &rm.wk, Wk, HD, DM, 64, 128);
    make_map(enc, &rm.wv, Wv, HD, DM, 64, 128);
    make_map(enc, &rm.wo, Wo, DM, HD, 16, 64, CU_TENSOR_MAP_SWIZZLE_32B);
    SMaps m;
    make_map(enc, &m.ox, p_ox, HD, SEQ, 64, 128);
    make_map(enc, &m.wo, Wo, DM, HD, 64, 64);
    make_map(enc, &m.h2, p_h2, DM, SEQ, 64, 128);
    make_map(enc, &m.w1, w1, FF, DM, 64, 64);
    make_map(enc, &m.act, p_act, FF, SEQ, 64, 128);
    make_map(enc, &m.w2, w2, DM, FF, 64, 64);

    cudaStream_t st = cudaStreamPerThread;
    {
        cudaLaunchConfig_t cfg = {};
        cfg.gridDim = dim3(96); cfg.blockDim = dim3(512); cfg.dynamicSmemBytes = SM_TOTAL; cfg.stream = st;
        cudaLaunchAttribute at[2];
        at[0].id = cudaLaunchAttributeClusterDimension;
        at[0].val.clusterDim.x = 3; at[0].val.clusterDim.y = 1; at[0].val.clusterDim.z = 1;
        cfg.attrs = at; cfg.numAttrs = 1;
        cudaLaunchKernelEx(&cfg, k_rec, rm, mem0, Wo, x, c, wmod);
    }
    {
        cudaLaunchConfig_t cfg = {};
        cfg.gridDim = dim3(SIDE_CTAS); cfg.blockDim = dim3(384); cfg.dynamicSmemBytes = G_SMEM; cfg.stream = st;
        cudaLaunchAttribute at[1];
        at[0].id = cudaLaunchAttributeProgrammaticStreamSerialization;
        at[0].val.programmaticStreamSerializationAllowed = 1;
        cfg.attrs = at; cfg.numAttrs = 1;
        cudaLaunchKernelEx(&cfg, k_side, m, x, c, wmod, out);
    }
}
```

```cpp
#include <cuda_runtime.h>
#include <cuda_bf16.h>
#include <cuda.h>
#include <stdint.h>

typedef __nv_bfloat16 bf16;
#define VX_THROTTLE 1
#define H1_DELAY 400
#define H1_BACK 0
#define VM_THROTTLE 1
#define PRE_TRIG 0
#define SIDE_CTAS 132

constexpr int SEQ = 2048, DM = 640, NH = 32, DH = 192, NSEG = 64, FF = 1536, HD = NH * DH;

__device__ __align__(128) float g_mod[6 * DM];
__device__ __align__(1024) bf16 g_ht[(size_t)SEQ * DM];
__device__ __align__(1024) bf16 g_ox[(size_t)SEQ * HD];
__device__ __align__(1024) bf16 g_x1[(size_t)SEQ * DM];
__device__ __align__(1024) bf16 g_h2[(size_t)SEQ * DM];
__device__ __align__(1024) bf16 g_act[(size_t)SEQ * FF];
__device__ __align__(8192) uint32_t g_buf1[80 * 2 * 2048];
__device__ __align__(8192) uint32_t g_buf2[4 * 3 * 2048];
__device__ uint32_t g_choice[128];
__device__ uint32_t g_epoch;
__device__ uint32_t g_hflag[64];
__device__ __align__(128) uint32_t g_modx[2 * DM];
#define T2(i)
#define T3(i)
enum { C_Q = 0, C_MOD = 1, C_REC = 2, C_G0 = 18, C_LN = 34, C_G1 = 50, C_G2 = 66, C_FIN = 82, C_NUM = 98 };
__device__ __align__(128) uint32_t g_cnt[C_NUM * 32];
constexpr int PMAX = 12;
constexpr int PRING = 4;
__device__ __align__(1024) float g_p0[(size_t)PRING * PMAX * 128 * DM];
__device__ __align__(1024) float g_p2[(size_t)PRING * PMAX * 128 * DM];
#define TR(k)

#define FRESH(x) asm volatile("" : "+r"(x))
__device__ __forceinline__ float bfr(float x) { uint32_t r; asm("cvt.rn.bf16x2.f32 %0, %1, %2;" : "=r"(r) : "f"(x), "f"(0.0f)); return __uint_as_float(r); }
__device__ __forceinline__ uint32_t pack2(float a, float b) {
    uint32_t r; asm("cvt.rn.bf16x2.f32 %0, %1, %2;" : "=r"(r) : "f"(b), "f"(a)); return r;
}
__device__ __forceinline__ float bflo(uint32_t v) { return __uint_as_float(v << 16); }
__device__ __forceinline__ float bfhi(uint32_t v) { return __uint_as_float(v & 0xffff0000u); }
__device__ __forceinline__ float ex2(float x) { float r; asm("ex2.approx.ftz.f32 %0, %1;" : "=f"(r) : "f"(x)); return r; }
__device__ __forceinline__ float rcpf(float x) { float r; asm("rcp.approx.ftz.f32 %0, %1;" : "=f"(r) : "f"(x)); return r; }
__device__ __forceinline__ void score2(float& a, float& b) {
    const float SCALE = 0.07216878364870322f;
    uint32_t u = pack2(a, b);
    u = pack2(bflo(u) * SCALE, bfhi(u) * SCALE);
    a = bflo(u); b = bfhi(u);
}
__device__ __forceinline__ uint32_t smem_u32(const void* p) { return (uint32_t)__cvta_generic_to_shared(p); }

__device__ __forceinline__ void mbar_init(uint32_t bar, uint32_t cnt) {
    asm volatile("mbarrier.init.shared::cta.b64 [%0], %1;" :: "r"(bar), "r"(cnt) : "memory");
}
__device__ __forceinline__ void mbar_arrive(uint32_t bar) {
    asm volatile("mbarrier.arrive.shared::cta.b64 _, [%0];" :: "r"(bar) : "memory");
}
__device__ __forceinline__ void mbar_expect(uint32_t bar, uint32_t bytes) {
    asm volatile("mbarrier.arrive.expect_tx.shared::cta.b64 _, [%0], %1;" :: "r"(bar), "r"(bytes) : "memory");
}
__device__ __forceinline__ bool mbar_try(uint32_t bar, uint32_t parity) {
    uint32_t ok;
    asm volatile("{\n\t.reg .pred p;\n\tmbarrier.try_wait.parity.shared::cta.b64 p, [%1], %2;\n\tselp.u32 %0, 1, 0, p;\n\t}"
                 : "=r"(ok) : "r"(bar), "r"(parity) : "memory");
    return ok != 0;
}
__device__ __forceinline__ bool mbar_try_cluster(uint32_t bar, uint32_t parity) {
    uint32_t ok;
    asm volatile("{\n\t.reg .pred p;\n\tmbarrier.try_wait.parity.acquire.cluster.shared::cta.b64 p, [%1], %2;\n\tselp.u32 %0, 1, 0, p;\n\t}"
                 : "=r"(ok) : "r"(bar), "r"(parity) : "memory");
    return ok != 0;
}
__device__ __forceinline__ void mbar_wait(uint32_t bar, uint32_t parity) {
    uint32_t guard = 0;
    while (!mbar_try(bar, parity)) { if (++guard > (1u << 22)) __trap(); }
}
__device__ __forceinline__ void mbar_wait_cluster(uint32_t bar, uint32_t parity) {
    uint32_t guard = 0;
    while (!mbar_try_cluster(bar, parity)) { if (++guard > (1u << 22)) __trap(); }
}
__device__ __forceinline__ void bar_sync(int id, int n) { asm volatile("bar.sync %0, %1;" :: "r"(id), "r"(n) : "memory"); }
__device__ __forceinline__ void bar_arrive(int id, int n) { asm volatile("bar.arrive %0, %1;" :: "r"(id), "r"(n) : "memory"); }
__device__ __forceinline__ void sts1(uint32_t a, uint32_t v) { asm volatile("st.shared.u32 [%0], %1;" :: "r"(a), "r"(v) : "memory"); }
__device__ __forceinline__ uint32_t lds1(uint32_t a) { uint32_t v; asm volatile("ld.shared.u32 %0, [%1];" : "=r"(v) : "r"(a) : "memory"); return v; }
__device__ __forceinline__ void fence_async() { asm volatile("fence.proxy.async.shared::cta;" ::: "memory"); }
__device__ __forceinline__ void cluster_sync() {
    asm volatile("barrier.cluster.arrive.release.aligned;\n\tbarrier.cluster.wait.acquire.aligned;" ::: "memory");
}
__device__ __forceinline__ uint32_t mapa(uint32_t a, uint32_t rank) {
    uint32_t r; asm("mapa.shared::cluster.u32 %0, %1, %2;" : "=r"(r) : "r"(a), "r"(rank)); return r;
}
__device__ __forceinline__ void st_async1(uint32_t a, uint32_t v, uint32_t bar) {
    asm volatile("st.async.weak.shared::cluster.mbarrier::complete_tx::bytes.b32 [%0], %1, [%2];" :: "r"(a), "r"(v), "r"(bar) : "memory");
}
__device__ __forceinline__ void st_async2(uint32_t a, float x, float y, uint32_t bar) {
    asm volatile("st.async.weak.shared::cluster.mbarrier::complete_tx::bytes.v2.f32 [%0], {%1,%2}, [%3];" :: "r"(a), "f"(x), "f"(y), "r"(bar) : "memory");
}
__device__ __forceinline__ void st_async4(uint32_t a, const float* c, uint32_t bar) {
    asm volatile("st.async.weak.shared::cluster.mbarrier::complete_tx::bytes.v4.f32 [%0], {%1,%2,%3,%4}, [%5];"
                 :: "r"(a), "f"(c[0]), "f"(c[1]), "f"(c[2]), "f"(c[3]), "r"(bar) : "memory");
}
__device__ __forceinline__ void bulk_g2s(uint32_t dst, const void* src, uint32_t bytes, uint32_t bar) {
    asm volatile("cp.async.bulk.shared::cluster.global.mbarrier::complete_tx::bytes [%0], [%1], %2, [%3];"
                 :: "r"(dst), "l"(src), "r"(bytes), "r"(bar) : "memory");
}
__device__ __forceinline__ void cpa16(uint32_t s, const void* g) {
    asm volatile("cp.async.cg.shared.global [%0], [%1], 16;" :: "r"(s), "l"(g) : "memory");
}
__device__ __forceinline__ void cpa_wait_all() { asm volatile("cp.async.wait_all;" ::: "memory"); }
__device__ __forceinline__ void ldsm4(uint32_t* r, uint32_t a) {
    asm volatile("ldmatrix.sync.aligned.m8n8.x4.shared.b16 {%0,%1,%2,%3}, [%4];" : "=r"(r[0]), "=r"(r[1]), "=r"(r[2]), "=r"(r[3]) : "r"(a) : "memory");
}
__device__ __forceinline__ void ldsm4t(uint32_t* r, uint32_t a) {
    asm volatile("ldmatrix.sync.aligned.m8n8.x4.trans.shared.b16 {%0,%1,%2,%3}, [%4];" : "=r"(r[0]), "=r"(r[1]), "=r"(r[2]), "=r"(r[3]) : "r"(a) : "memory");
}
__device__ __forceinline__ void stsm2t(uint32_t a, uint32_t r0, uint32_t r1) {
    asm volatile("stmatrix.sync.aligned.m8n8.x2.trans.shared.b16 [%0], {%1,%2};" :: "r"(a), "r"(r0), "r"(r1) : "memory");
}
__device__ __forceinline__ void stsm4t(uint32_t a, uint32_t r0, uint32_t r1, uint32_t r2, uint32_t r3) {
    asm volatile("stmatrix.sync.aligned.m8n8.x4.trans.shared.b16 [%0], {%1,%2,%3,%4};" :: "r"(a), "r"(r0), "r"(r1), "r"(r2), "r"(r3) : "memory");
}
__device__ __forceinline__ uint32_t movm(uint32_t v) {
    uint32_t r; asm volatile("movmatrix.sync.aligned.m8n8.trans.b16 %0, %1;" : "=r"(r) : "r"(v)); return r;
}
__device__ __forceinline__ void mma16(float* c, uint32_t a0, uint32_t a1, uint32_t a2, uint32_t a3, uint32_t b0, uint32_t b1) {
    asm volatile("mma.sync.aligned.m16n8k16.row.col.f32.bf16.bf16.f32 {%0,%1,%2,%3}, {%4,%5,%6,%7}, {%8,%9}, {%0,%1,%2,%3};"
                 : "+f"(c[0]), "+f"(c[1]), "+f"(c[2]), "+f"(c[3]) : "r"(a0), "r"(a1), "r"(a2), "r"(a3), "r"(b0), "r"(b1));
}
__device__ __forceinline__ void mma8(float* c, uint32_t a0, uint32_t a1, uint32_t b0) {
    asm volatile("mma.sync.aligned.m16n8k8.row.col.f32.bf16.bf16.f32 {%0,%1,%2,%3}, {%4,%5}, {%6}, {%0,%1,%2,%3};"
                 : "+f"(c[0]), "+f"(c[1]), "+f"(c[2]), "+f"(c[3]) : "r"(a0), "r"(a1), "r"(b0));
}
__host__ __device__ constexpr uint64_t make_desc(uint32_t saddr, uint32_t lbo, uint32_t sbo, uint32_t layout) {
    return (uint64_t)((saddr & 0x3FFFF) >> 4) | ((uint64_t)(lbo >> 4) << 16) | ((uint64_t)(sbo >> 4) << 32) | ((uint64_t)layout << 62);
}
__device__ __forceinline__ void wg_fence() { asm volatile("wgmma.fence.sync.aligned;" ::: "memory"); }
__device__ __forceinline__ void wg_commit() { asm volatile("wgmma.commit_group.sync.aligned;" ::: "memory"); }
template <int N> __device__ __forceinline__ void wg_wait() { asm volatile("wgmma.wait_group.sync.aligned %0;" :: "n"(N) : "memory"); }

#define D16(C) C(d[0]), C(d[1]), C(d[2]), C(d[3]), C(d[4]), C(d[5]), C(d[6]), C(d[7]), \
               C(d[8]), C(d[9]), C(d[10]), C(d[11]), C(d[12]), C(d[13]), C(d[14]), C(d[15])
#define DREG16 "{%0,%1,%2,%3,%4,%5,%6,%7,%8,%9,%10,%11,%12,%13,%14,%15}"
__device__ __forceinline__ void wg_rs32(float* d, const uint32_t* a, uint64_t db, bool acc) {
    if (acc)
        asm volatile("wgmma.mma_async.sync.aligned.m64n32k16.f32.bf16.bf16 " DREG16 ", {%16,%17,%18,%19}, %20, 1, 1, 1, 0;"
            : D16("+f") : "r"(a[0]), "r"(a[1]), "r"(a[2]), "r"(a[3]), "l"(db));
    else
        asm volatile("wgmma.mma_async.sync.aligned.m64n32k16.f32.bf16.bf16 " DREG16 ", {%16,%17,%18,%19}, %20, 0, 1, 1, 0;"
            : D16("=f") : "r"(a[0]), "r"(a[1]), "r"(a[2]), "r"(a[3]), "l"(db));
}
__device__ __forceinline__ void wg_ss32(float* d, uint64_t da, uint64_t db, bool acc) {
    if (acc)
        asm volatile("wgmma.mma_async.sync.aligned.m64n32k16.f32.bf16.bf16 " DREG16 ", %16, %17, 1, 1, 1, 1, 0;"
            : D16("+f") : "l"(da), "l"(db));
    else
        asm volatile("wgmma.mma_async.sync.aligned.m64n32k16.f32.bf16.bf16 " DREG16 ", %16, %17, 0, 1, 1, 1, 0;"
            : D16("=f") : "l"(da), "l"(db));
}
__device__ __forceinline__ void wg_ss8(float* d, uint64_t da, uint64_t db, bool acc) {
    if (acc)
        asm volatile("wgmma.mma_async.sync.aligned.m64n8k16.f32.bf16.bf16 {%0,%1,%2,%3}, %4, %5, 1, 1, 1, 1, 1;"
            : "+f"(d[0]), "+f"(d[1]), "+f"(d[2]), "+f"(d[3]) : "l"(da), "l"(db));
    else
        asm volatile("wgmma.mma_async.sync.aligned.m64n8k16.f32.bf16.bf16 {%0,%1,%2,%3}, %4, %5, 0, 1, 1, 1, 1;"
            : "=f"(d[0]), "=f"(d[1]), "=f"(d[2]), "=f"(d[3]) : "l"(da), "l"(db));
}
template <int OFF> __device__ __forceinline__ void ldsm4t_i(uint32_t* r, uint32_t a) {
    asm volatile("ldmatrix.sync.aligned.m8n8.x4.trans.shared.b16 {%0,%1,%2,%3}, [%4+%5];"
                 : "=r"(r[0]), "=r"(r[1]), "=r"(r[2]), "=r"(r[3]) : "r"(a), "n"(OFF) : "memory");
}

__device__ __forceinline__ uint4 ld_relaxed4(const void* p) {
    uint4 v;
    asm volatile("ld.relaxed.gpu.global.v4.u32 {%0,%1,%2,%3}, [%4];" : "=r"(v.x), "=r"(v.y), "=r"(v.z), "=r"(v.w) : "l"(p) : "memory");
    return v;
}
__device__ __forceinline__ void st_relaxed2(void* p, uint32_t a, uint32_t b) {
    asm volatile("st.relaxed.gpu.global.v2.u32 [%0], {%1,%2};" :: "l"(p), "r"(a), "r"(b) : "memory");
}
__device__ __forceinline__ void st_relaxed2_off(void* base, uint32_t off, uint32_t a, uint32_t b) {
    asm volatile("{\n\t.reg .u64 ad;\n\tcvt.u64.u32 ad, %1;\n\tadd.u64 ad, ad, %0;\n\tst.relaxed.gpu.global.v2.u32 [ad], {%2,%3};\n\t}"
                 :: "l"(base), "r"(off), "r"(a), "r"(b) : "memory");
}
__device__ __forceinline__ void st_relaxed1(void* p, uint32_t a) {
    asm volatile("st.relaxed.gpu.global.u32 [%0], %1;" :: "l"(p), "r"(a) : "memory");
}
__device__ __forceinline__ uint32_t ld_acquire1(const uint32_t* p) {
    uint32_t v; asm volatile("ld.acquire.gpu.global.u32 %0, [%1];" : "=r"(v) : "l"(p) : "memory"); return v;
}
__device__ __forceinline__ void st_release1(uint32_t* p, uint32_t a) {
    asm volatile("st.release.gpu.global.u32 [%0], %1;" :: "l"(p), "r"(a) : "memory");
}
__device__ __forceinline__ uint4 lds4(uint32_t s) {
    uint4 v; asm volatile("ld.shared.v4.u32 {%0,%1,%2,%3}, [%4];" : "=r"(v.x), "=r"(v.y), "=r"(v.z), "=r"(v.w) : "r"(s) : "memory"); return v;
}
__device__ __forceinline__ void sts4(uint32_t s, const uint4& v) {
    asm volatile("st.shared.v4.u32 [%0], {%1,%2,%3,%4};" :: "r"(s), "r"(v.x), "r"(v.y), "r"(v.z), "r"(v.w) : "memory");
}
__device__ __forceinline__ float4 lds4f(uint32_t s) {
    float4 v; asm volatile("ld.shared.v4.f32 {%0,%1,%2,%3}, [%4];" : "=f"(v.x), "=f"(v.y), "=f"(v.z), "=f"(v.w) : "r"(s) : "memory"); return v;
}
__device__ __forceinline__ uint2 lds2(uint32_t s) {
    uint2 v; asm volatile("ld.shared.v2.u32 {%0,%1}, [%2];" : "=r"(v.x), "=r"(v.y) : "r"(s) : "memory"); return v;
}
__device__ __forceinline__ float2 lds2f(uint32_t s) {
    float2 v; asm volatile("ld.shared.v2.f32 {%0,%1}, [%2];" : "=f"(v.x), "=f"(v.y) : "r"(s) : "memory"); return v;
}
__device__ __forceinline__ uint32_t clk32() { uint32_t c; asm volatile("mov.u32 %0, %%clock;" : "=r"(c) :: "memory"); return c; }
__device__ __forceinline__ uint32_t tagw(float v, uint32_t tag) { return ((__float_as_uint(v) + 8u) & ~15u) | tag; }
__device__ __forceinline__ bool ok4(const uint4& v, uint32_t tag) { return (((v.x ^ tag) | (v.y ^ tag) | (v.z ^ tag) | (v.w ^ tag)) & 15u) == 0; }
__device__ __forceinline__ bool oks(const uint4& v) { return v.x != 0xFFFFFFFFu && v.y != 0xFFFFFFFFu && v.z != 0xFFFFFFFFu && v.w != 0xFFFFFFFFu; }
__device__ __forceinline__ float uf(uint32_t x) { return __uint_as_float(x & ~15u); }

template <int NT, int BAR>
__device__ __forceinline__ void mod_chunk(const bf16* __restrict__ c, const bf16* __restrict__ wmod, int col0, int tid, float* red) {
    constexpr int RG = NT / 8, NP = DM / RG;
    const int cc = tid & 7, rg = tid >> 3;
    uint4 w[NP];
    #pragma unroll
    for (int i = 0; i < NP; i++) w[i] = __ldg((const uint4*)(wmod + (size_t)(rg + i * RG) * (6 * DM) + col0 + cc * 8));
    float a[8];
    #pragma unroll
    for (int j = 0; j < 8; j++) a[j] = 0.f;
    #pragma unroll
    for (int i = 0; i < NP; i++) {
        const float v = __bfloat162float(c[rg + i * RG]);
        const float sv = bfr(__fdividef(v, 1.0f + __expf(-v)));
        a[0] += sv * bflo(w[i].x); a[1] += sv * bfhi(w[i].x); a[2] += sv * bflo(w[i].y); a[3] += sv * bfhi(w[i].y);
        a[4] += sv * bflo(w[i].z); a[5] += sv * bfhi(w[i].z); a[6] += sv * bflo(w[i].w); a[7] += sv * bfhi(w[i].w);
    }
    #pragma unroll
    for (int j = 0; j < 8; j++) {
        a[j] += __shfl_xor_sync(0xffffffffu, a[j], 8);
        a[j] += __shfl_xor_sync(0xffffffffu, a[j], 16);
    }
    if ((tid & 31) < 8) {
        float* d = red + (tid >> 5) * 64 + cc * 8;
        *(float4*)d = make_float4(a[0], a[1], a[2], a[3]);
        *(float4*)(d + 4) = make_float4(a[4], a[5], a[6], a[7]);
    }
    bar_sync(BAR, NT);
    if (tid < 64) {
        float s = 0.f;
        #pragma unroll
        for (int i = 0; i < NT / 32; i++) s += red[i * 64 + tid];
        g_mod[col0 + tid] = bfr(s);
    }
}

__device__ __forceinline__ void ln_stats(const float (*v)[4], float& mb, float& sd) {
    float s = 0.f;
    #pragma unroll
    for (int i = 0; i < 5; i++) s += (v[i][0] + v[i][1]) + (v[i][2] + v[i][3]);
    #pragma unroll
    for (int o = 16; o > 0; o >>= 1) s += __shfl_xor_sync(0xffffffffu, s, o);
    const float mean = s * (1.0f / DM);
    float q = 0.f;
    #pragma unroll
    for (int i = 0; i < 5; i++) {
        #pragma unroll
        for (int j = 0; j < 4; j++) { const float d = v[i][j] - mean; q += d * d; }
    }
    #pragma unroll
    for (int o = 16; o > 0; o >>= 1) q += __shfl_xor_sync(0xffffffffu, q, o);
    mb = bfr(mean);
    const float var = bfr(q * (1.0f / DM));
    sd = 1.0f / bfr(sqrtf(bfr(var + 1e-5f)));
}
__device__ __forceinline__ uint2 ln_apply(const float* v, float mb, float rs, const float4& sc, const float4& sh) {
    const float o0 = bfr(bfr(bfr(v[0] - mb) * rs) * bfr(1.0f + sc.x)) + sh.x;
    const float o1 = bfr(bfr(bfr(v[1] - mb) * rs) * bfr(1.0f + sc.y)) + sh.y;
    const float o2 = bfr(bfr(bfr(v[2] - mb) * rs) * bfr(1.0f + sc.z)) + sh.z;
    const float o3 = bfr(bfr(bfr(v[3] - mb) * rs) * bfr(1.0f + sc.w)) + sh.w;
    return make_uint2(pack2(o0, o1), pack2(o2, o3));
}

constexpr int SM_WV = 0;
constexpr int SM_HB = 81920;
constexpr int SM_WO = SM_HB + 40960;
constexpr int SM_QX = SM_WO + 77824;
constexpr int SM_KS = SM_QX + 4096;
constexpr int SM_QM = SM_KS + 5120;
constexpr int SM_XS = SM_QM + 1024;
constexpr int SM_MS = SM_XS + 12288;
constexpr int SM_OS = SM_MS + 3840;
constexpr int SM_PM = SM_OS + 3072;
constexpr int SM_BAR = SM_PM + 640;
constexpr int SM_CH = SM_BAR + 128;
constexpr int SM_TOTAL = SM_CH + 128;
static_assert(SM_TOTAL <= 232448, "smem");

enum { B_MEM_FULL = 0, B_MEM_FREE, B_HLO_FULL, B_HHI_FULL, B_HLO_FREE, B_HHI_FREE, B_MS, B_O, B_XS, B_O1, B_XSFREE, B_WQ, B_WK, B_WV, B_WO };

__device__ __forceinline__ int probe_blk(uint32_t* blk) {
    uint32_t t0 = 0xffffffffu, t1 = 0xffffffffu, acc = 0;
    for (int rep = 0; rep < 3; rep++) {
        #pragma unroll
        for (int pg = 0; pg < 2; pg++) {
            uint32_t c0 = clk32();
            uint32_t v = atomicOr(blk + pg * 1024 + acc, 0u);
            acc = (v == 0x12345678u) ? 1u : 0u;
            asm volatile("" :: "r"(acc) : "memory");
            uint32_t c1 = clk32() + acc;
            uint32_t d = c1 - c0;
            if (rep > 0) { if (pg == 0) t0 = min(t0, d); else t1 = min(t1, d); }
        }
    }
    return t1 < t0 ? 1 : 0;
}

__device__ __forceinline__ uint32_t wo_tile_off(int w) {
    if (w < 8) return w * 6144;
    if (w < 12) return 8 * 6144 + (w - 8) * 4096;
    return 8 * 6144 + 4 * 4096 + (w - 12) * 6144;
}

template <int NRES, int NPRE>
__device__ __forceinline__ void wo_phase(uint32_t sb, int w, int lane, const uint32_t (*res)[4], uint32_t parity,
                                         uint32_t tag, int tile, int h) {
    FRESH(lane);
    const int er = (lane & 7) + 8 * (lane >> 4);
    const uint32_t aaddr = sb + SM_WO + wo_tile_off(w) + er * 32 + ((((lane >> 3) & 1) ^ ((er >> 2) & 1)) << 4);
    const uint32_t baddr = sb + SM_OS + lane * 16;
    float c0[4] = {0.f, 0.f, 0.f, 0.f}, c1[4] = {0.f, 0.f, 0.f, 0.f};
    uint32_t pre[NPRE > 4 ? NPRE : 4][4];
    if (NPRE >= 4) {
        #pragma unroll
        for (int i = 0; i < 4; i++) ldsm4t(pre[i], aaddr + i * 512);
        mbar_wait(sb + SM_BAR + B_O1 * 8, parity);
        uint32_t b[2][4];
        ldsm4t(b[0], baddr);
        ldsm4t(b[1], baddr + 512);
        #pragma unroll
        for (int kp = 0; kp < 2; kp++) {
            mma16(c0, pre[2 * kp][0], pre[2 * kp][1], pre[2 * kp][2], pre[2 * kp][3], b[kp][0], b[kp][1]);
            mma16(c1, pre[2 * kp + 1][0], pre[2 * kp + 1][1], pre[2 * kp + 1][2], pre[2 * kp + 1][3], b[kp][2], b[kp][3]);
        }
    } else {
        #pragma unroll
        for (int i = 0; i < 2; i++) ldsm4t(pre[i], aaddr + i * 512);
        mbar_wait(sb + SM_BAR + B_O1 * 8, parity);
        #pragma unroll
        for (int kp = 0; kp < 2; kp++) {
            uint32_t b[4];
            ldsm4t(b, baddr + kp * 512);
            if (kp == 1) { ldsm4t(pre[0], aaddr + 2 * 512); ldsm4t(pre[1], aaddr + 3 * 512); }
            mma16(c0, pre[0][0], pre[0][1], pre[0][2], pre[0][3], b[0], b[1]);
            mma16(c1, pre[1][0], pre[1][1], pre[1][2], pre[1][3], b[2], b[3]);
        }
    }
    #pragma unroll
    for (int i = 0; i < NPRE; i++) ldsm4t(pre[i], aaddr + (4 + i) * 512);
    uint32_t off0, off1;
    {
        uint32_t ch;
        asm volatile("ld.shared.u16 %0, [%1];" : "=r"(ch) : "r"(sb + SM_CH + 2 * tile) : "memory");
        const int j = h >> 4;
        const uint32_t base = (uint32_t)((tile * 4 + j) * 8192 + (h & 15) * 256 + lane * 8);
        ch >>= j;
        off0 = base + (ch & 1) * 4096;
        off1 = base + 16384 + (ch & 256) * 16;
    }
    mbar_wait(sb + SM_BAR + B_O * 8, parity);
    if (NRES == 4) {
        uint32_t b[4][4];
        #pragma unroll
        for (int i = 0; i < 4; i++) ldsm4t(b[i], baddr + (2 + i) * 512);
        #pragma unroll
        for (int i = 0; i < 2; i++) {
            mma16(c0, res[2 * i][0], res[2 * i][1], res[2 * i][2], res[2 * i][3], b[i][0], b[i][1]);
            mma16(c1, res[2 * i + 1][0], res[2 * i + 1][1], res[2 * i + 1][2], res[2 * i + 1][3], b[i][2], b[i][3]);
        }
        #pragma unroll
        for (int i = 0; i < 2; i++) {
            mma16(c0, pre[2 * i][0], pre[2 * i][1], pre[2 * i][2], pre[2 * i][3], b[2 + i][0], b[2 + i][1]);
            mma16(c1, pre[2 * i + 1][0], pre[2 * i + 1][1], pre[2 * i + 1][2], pre[2 * i + 1][3], b[2 + i][2], b[2 + i][3]);
        }
    } else if (NPRE == 4) {
        uint32_t b[2][4];
        #pragma unroll
        for (int hh = 0; hh < 2; hh++) {
            ldsm4t(b[0], baddr + (2 + 2 * hh) * 512);
            ldsm4t(b[1], baddr + (3 + 2 * hh) * 512);
            if (hh) {
                #pragma unroll
                for (int i = 0; i < 4; i++) ldsm4t(pre[i], aaddr + (8 + i) * 512);
            }
            #pragma unroll
            for (int i = 0; i < 2; i++) {
                mma16(c0, pre[2 * i][0], pre[2 * i][1], pre[2 * i][2], pre[2 * i][3], b[i][0], b[i][1]);
                mma16(c1, pre[2 * i + 1][0], pre[2 * i + 1][1], pre[2 * i + 1][2], pre[2 * i + 1][3], b[i][2], b[i][3]);
            }
        }
    }
    st_relaxed2_off(g_buf1, off0, tagw(c0[0] + c1[0], tag), tagw(c0[1] + c1[1], tag));
    st_relaxed2_off(g_buf1, off1, tagw(c0[2] + c1[2], tag), tagw(c0[3] + c1[3], tag));
}

template <int NT, bool MASK>
__device__ __forceinline__ void softmax_core(float (*sc)[2], int g, int t, uint32_t* pb) {
    const float L2E = 1.4426950408889634f;
    #pragma unroll
    for (int j = 0; j < NT; j++) score2(sc[j][0], sc[j][1]);
    if (MASK) {
        const float NEG = -999292928.0f;
        if (2 * t > g) sc[NT - 1][0] = NEG;
        if (2 * t + 1 > g) sc[NT - 1][1] = NEG;
    }
    float m[NT];
    #pragma unroll
    for (int j = 0; j < NT; j++) m[j] = fmaxf(sc[j][0], sc[j][1]);
    float mx = m[0];
    #pragma unroll
    for (int j = 1; j < NT; j++) mx = fmaxf(mx, m[j]);
    mx = fmaxf(mx, __shfl_xor_sync(0xffffffffu, mx, 1));
    mx = fmaxf(mx, __shfl_xor_sync(0xffffffffu, mx, 2));
    float s0 = 0.f, s1 = 0.f;
    #pragma unroll
    for (int j = 0; j < NT; j++) {
        sc[j][0] = ex2((sc[j][0] - mx) * L2E); sc[j][1] = ex2((sc[j][1] - mx) * L2E);
        s0 += sc[j][0]; s1 += sc[j][1];
    }
    s0 += s1;
    s0 += __shfl_xor_sync(0xffffffffu, s0, 1);
    s0 += __shfl_xor_sync(0xffffffffu, s0, 2);
    const float iv = rcpf(s0);
    #pragma unroll
    for (int j = 0; j < NT; j++) pb[j] = pack2(sc[j][0] * iv, sc[j][1] * iv);
}
template <int NT>
__device__ __forceinline__ void xsoftmax(uint32_t a, int g, int t) {
    float sc[NT][2];
    #pragma unroll
    for (int j = 0; j < NT; j++) {
        float2 v0 = lds2f(a + j * 512), v1 = lds2f(a + j * 512 + 4096), v2 = lds2f(a + j * 512 + 8192);
        sc[j][0] = v0.x + v1.x + v2.x; sc[j][1] = v0.y + v1.y + v2.y;
    }
    uint32_t pb[NT];
    softmax_core<NT, true>(sc, g, t, pb);
    #pragma unroll
    for (int j = 0; j < NT; j += 2) {
        if (j + 1 < NT) asm volatile("st.shared.v2.u32 [%0], {%1,%2};" :: "r"(a + j * 512), "r"(pb[j]), "r"(pb[j + 1]) : "memory");
        else sts1(a + j * 512, pb[j]);
    }
}
template <int NJ>
__device__ __forceinline__ void xscores(uint32_t sb, int p, int mi, int j0, int lane) {
    FRESH(lane);
    const int r = lane & 7, cq = lane >> 3;
    const int qrow = mi * 16 + r + 8 * (cq & 1);
    uint32_t kb[NJ][8];
    float d[NJ][4];
    #pragma unroll
    for (int j = 0; j < NJ; j++) {
        ldsm4(kb[j], sb + SM_KS + ((j0 + j) * 8 + r) * 128 + ((cq ^ r) << 4));
        ldsm4(kb[j] + 4, sb + SM_KS + ((j0 + j) * 8 + r) * 128 + (((cq + 4) ^ r) << 4));
        d[j][0] = 0.f; d[j][1] = 0.f; d[j][2] = 0.f; d[j][3] = 0.f;
    }
    #pragma unroll
    for (int kt = 0; kt < 4; kt++) {
        uint32_t a[4];
        ldsm4(a, sb + SM_QX + qrow * 128 + (((2 * kt + (cq >> 1)) ^ r) << 4));
        #pragma unroll
        for (int j = 0; j < NJ; j++) mma16(d[j], a[0], a[1], a[2], a[3], kb[j][2 * kt], kb[j][2 * kt + 1]);
    }
    const uint32_t la = sb + SM_XS + p * 4096 + (mi * 3 + j0) * 512 + lane * 16;
    #pragma unroll
    for (int rk = 0; rk < 3; rk++) {
        const uint32_t ra = mapa(la, rk), rb = mapa(sb + SM_BAR + B_XS * 8, rk);
        #pragma unroll
        for (int j = 0; j < NJ; j++) st_async4(ra + j * 512, d[j], rb);
    }
}
__device__ __forceinline__ void mbar_arrive_remote(uint32_t bar) {
    asm volatile("mbarrier.arrive.relaxed.cluster.shared::cluster.b64 _, [%0];" :: "r"(bar) : "memory");
}

__device__ __forceinline__ void tma2d(uint32_t dst, const CUtensorMap* map, int c0, int c1, uint32_t bar) {
    asm volatile("cp.async.bulk.tensor.2d.shared::cluster.global.mbarrier::complete_tx::bytes [%0], [%1, {%2, %3}], [%4];"
                 :: "r"(dst), "l"(map), "r"(c0), "r"(c1), "r"(bar) : "memory");
}
__device__ __forceinline__ void tma2d_pf(const CUtensorMap* map, int c0, int c1) {
    asm volatile("cp.async.bulk.prefetch.tensor.2d.L2.global [%0, {%1, %2}];" :: "l"(map), "r"(c0), "r"(c1) : "memory");
}
__device__ __forceinline__ void bulk_pf(const void* p, uint32_t bytes) {
    asm volatile("cp.async.bulk.prefetch.L2.global [%0], %1;" :: "l"(p), "r"(bytes) : "memory");
}
struct RMaps { CUtensorMap wq, wk, wv, wo; };
__device__ __forceinline__ void signal_cnt(int idx) {
    asm volatile("fence.proxy.async.global;\n\tred.release.gpu.global.add.u32 [%0], 1;" :: "l"(g_cnt + idx * 32) : "memory");
}

__global__ void __launch_bounds__(512, 1)
k_rec(const __grid_constant__ RMaps maps, const bf16* __restrict__ mem0, const bf16* __restrict__ Wo,
      const bf16* __restrict__ xin, const bf16* __restrict__ cvec, const bf16* __restrict__ wmod) {
    extern __shared__ __align__(1024) uint8_t smem_raw[];
    constexpr uint32_t SBC = 1024;
    const uint32_t sb = smem_u32(smem_raw);
    if ((sb & 0xFFFFFFu) != SBC) __trap();
    int lane = __shfl_sync(0xffffffffu, threadIdx.x & 31, threadIdx.x & 31);
    const int warp = __shfl_sync(0xffffffffu, threadIdx.x >> 5, 0), wg = warp >> 2;
    const int tid = warp * 32 + lane;
    const int b = blockIdx.x, h = b / 3, p = b % 3;
    const int g = lane >> 2, t = lane & 3;
    const int tile0 = p == 0 ? 0 : (p == 1 ? 14 : 27);
    const int ntile = p == 0 ? 14 : 13;
    const uint32_t bar = sb + SM_BAR;

    if (tid == 0) T2(100 + b);
    if (tid == 0) {
        mbar_init(bar + B_MEM_FULL * 8, 4);
        mbar_init(bar + B_MEM_FREE * 8, 12);
        mbar_init(bar + B_HLO_FULL * 8, 1);
        mbar_init(bar + B_HHI_FULL * 8, 1);
        mbar_init(bar + B_HLO_FREE * 8, 12);
        mbar_init(bar + B_HHI_FREE * 8, 12);
        mbar_init(bar + B_MS * 8, 1);
        mbar_init(bar + B_O * 8, 1);
        mbar_init(bar + B_XS * 8, 1);
        mbar_init(bar + B_O1 * 8, 4);
        mbar_init(bar + B_XSFREE * 8, 12);
        mbar_init(bar + B_WQ * 8, 1);
        mbar_init(bar + B_WK * 8, 1);
        mbar_init(bar + B_WV * 8, 1);
        mbar_init(bar + B_WO * 8, 1);
        asm volatile("fence.mbarrier_init.release.cluster;" ::: "memory");
        mbar_expect(bar + B_WQ * 8, 81920);
        mbar_expect(bar + B_WK * 8, 81920);
        #pragma unroll
        for (int i = 0; i < 5; i++) {
            tma2d(sb + SM_WO + i * 16384, &maps.wq, h * DH + p * 64, i * 128, bar + B_WQ * 8);
            tma2d(sb + SM_WV + i * 16384, &maps.wk, h * DH + p * 64, i * 128, bar + B_WK * 8);
        }
        mbar_expect(bar + B_MS * 8, 3840);
        mbar_expect(bar + B_O * 8, 2048);
        mbar_expect(bar + B_XS * 8, 12288);
    }
    __syncwarp();
    asm volatile("barrier.cluster.arrive.relaxed.aligned;\n\tbarrier.cluster.wait.acquire.aligned;" ::: "memory");
    if (warp == 0) T3(0);

    if (wg < 2) {
        asm volatile("setmaxnreg.inc.sync.aligned.u32 200;");
        const int w = warp & 3;
        {
            const uint32_t tag = *(volatile uint32_t*)&g_epoch + 1u;
            uint4 wm[5];
            float cv[5];
            if (b < 80) {
                #pragma unroll
                for (int i = 0; i < 5; i++) {
                    wm[i] = __ldg((const uint4*)(wmod + (size_t)((tid >> 1) + 128 * i) * (6 * DM) + b * 16 + (tid & 1) * 8));
                    cv[i] = __bfloat162float(cvec[(tid >> 1) + 128 * i]);
                }
            }
            uint2 xr[8][5];
            const int seg1 = b < NSEG - 1 ? b + 1 : 0;
            #pragma unroll
            for (int r = 0; r < 8; r++) {
                const bf16* src = xin + (size_t)((r < 4 ? 0 : seg1) * 32 + warp * 4 + (r & 3)) * DM + lane * 4;
                #pragma unroll
                for (int i = 0; i < 5; i++) xr[r][i] = __ldg((const uint2*)(src + i * 128));
            }
            if (b < 80) {
                float a[8];
                #pragma unroll
                for (int j = 0; j < 8; j++) a[j] = 0.f;
                #pragma unroll
                for (int i = 0; i < 5; i++) {
                    const float sv = bfr(__fdividef(cv[i], 1.0f + __expf(-cv[i])));
                    a[0] += sv * bflo(wm[i].x); a[1] += sv * bfhi(wm[i].x); a[2] += sv * bflo(wm[i].y); a[3] += sv * bfhi(wm[i].y);
                    a[4] += sv * bflo(wm[i].z); a[5] += sv * bfhi(wm[i].z); a[6] += sv * bflo(wm[i].w); a[7] += sv * bfhi(wm[i].w);
                }
                #pragma unroll
                for (int j = 0; j < 8; j++) {
                    #pragma unroll
                    for (int o = 2; o < 32; o <<= 1) a[j] += __shfl_xor_sync(0xffffffffu, a[j], o);
                }
                if (lane < 2) {
                    const uint32_t d = sb + SM_QM + warp * 64 + lane * 32;
                    sts4(d, make_uint4(__float_as_uint(a[0]), __float_as_uint(a[1]), __float_as_uint(a[2]), __float_as_uint(a[3])));
                    sts4(d + 16, make_uint4(__float_as_uint(a[4]), __float_as_uint(a[5]), __float_as_uint(a[6]), __float_as_uint(a[7])));
                }
                bar_sync(1, 256);
                if (tid < 8) {
                    float s0 = 0.f, s1 = 0.f;
                    #pragma unroll
                    for (int i = 0; i < 8; i++) { const float2 v = lds2f(sb + SM_QM + i * 64 + tid * 8); s0 += v.x; s1 += v.y; }
                    st_relaxed2(g_modx + (b * 8 + tid) * 2, pack2(s0, s1), tag);
                }
            }
            if (tid == 32) {
                #pragma unroll
                for (int i = 0; i < 5; i++) tma2d_pf(&maps.wv, h * DH + p * 64, i * 128);
            }
            if (tid >= 64) bulk_pf(Wo + ((size_t)h * DH + (tid - 64)) * DM + tile0 * 16, ntile * 32);
            float mb[8], rs[8];
            #pragma unroll
            for (int r = 0; r < 8; r++) {
                float v[5][4];
                #pragma unroll
                for (int i = 0; i < 5; i++) { v[i][0] = bflo(xr[r][i].x); v[i][1] = bfhi(xr[r][i].x); v[i][2] = bflo(xr[r][i].y); v[i][3] = bfhi(xr[r][i].y); }
                ln_stats(v, mb[r], rs[r]);
            }
            T3(12);
            #pragma unroll
            for (int u = 0; u < 2; u++) {
                const int idx = tid + u * 256;
                if (idx < 320) {
                    uint4 v; uint32_t guard = 0;
                    while (true) {
                        v = ld_relaxed4(g_modx + idx * 4);
                        if (v.y == tag && v.w == tag) break;
                        __nanosleep(50);
                        if (++guard > (1u << 22)) __trap();
                    }
                    asm volatile("st.shared.v2.u32 [%0], {%1,%2};" :: "r"(sb + SM_KS + idx * 8), "r"(v.x), "r"(v.z) : "memory");
                }
            }
            bar_sync(1, 256);
            T3(13);
            #pragma unroll
            for (int i = 0; i < 5; i++) {
                const int col = (i * 32 + lane) * 4;
                const uint2 u0 = lds2(sb + SM_KS + col * 2), u1 = lds2(sb + SM_KS + 1280 + col * 2);
                const float4 sh = make_float4(bflo(u0.x), bfhi(u0.x), bflo(u0.y), bfhi(u0.y));
                const float4 sc = make_float4(bflo(u1.x), bfhi(u1.x), bflo(u1.y), bfhi(u1.y));
                #pragma unroll
                for (int r = 0; r < 8; r++) {
                    const float v[4] = {bflo(xr[r][i].x), bfhi(xr[r][i].x), bflo(xr[r][i].y), bfhi(xr[r][i].y)};
                    const int row = warp * 4 + (r & 3);
                    const uint32_t off = (col >> 6) * 4096 + row * 128 + ((((col >> 3) & 7) ^ (row & 7)) << 4) + (col & 4) * 2;
                    const uint2 o = ln_apply(v, mb[r], rs[r], sc, sh);
                    if (r < 4) asm volatile("st.shared.v2.u32 [%0], {%1,%2};" :: "r"(sb + SM_HB + off), "r"(o.x), "r"(o.y) : "memory");
                    else if (b < NSEG - 1) *(uint2*)((char*)g_ht + (size_t)seg1 * 40960 + off) = o;
                }
            }
            fence_async();
            bar_sync(1, 256);
            if (tid == 0) { mbar_arrive(bar + B_HLO_FULL * 8); mbar_arrive(bar + B_HHI_FULL * 8); }
            if (tid == 224 && b < NSEG - 1) {
                asm volatile("fence.proxy.async.global;" ::: "memory");
                st_release1(&g_hflag[seg1], tag);
            }
            __syncwarp();
        }
        uint32_t wa[40][4];
        {
            mbar_wait(bar + (wg == 0 ? B_WQ : B_WK) * 8, 0);
            if (w == 0) T3(1 + wg);
            const int r = lane & 7;
            const uint32_t wsrc = sb + (wg == 0 ? SM_WO : SM_WV) + (r + ((lane >> 4) << 3)) * 128 + (((2 * w + ((lane >> 3) & 1)) ^ r) << 4);
            #pragma unroll
            for (int kt = 0; kt < 40; kt++) ldsm4t(wa[kt], wsrc + kt * 2048);
            fence_async();
            bar_arrive(10 + wg, 256);
        }

        const uint32_t dstx = sb + (wg == 0 ? SM_QX : SM_KS + 1024);

        for (int s = -1; s < NSEG; s++) {
            const uint32_t par = s & 1;
            FRESH(lane);
            const int g = lane >> 2, t = lane & 3, tid = warp * 32 + lane;
            if (s >= 0) {
                mbar_wait(bar + B_MEM_FULL * 8, par);
                TR(0);
                float c[4][4];
                #pragma unroll
                for (int i = 0; i < 4; i++) { c[i][0] = 0.f; c[i][1] = 0.f; c[i][2] = 0.f; c[i][3] = 0.f; }
                uint32_t maddr = sb + lane * 16;
                asm volatile("" : "+r"(maddr));
                #pragma unroll
                for (int kp = 0; kp < 20; kp++) {
                    uint32_t bb[4];
                    ldsm4t(bb, maddr + (SM_HB + kp * 512));
                    mma16(c[(kp & 1) * 2], wa[2 * kp][0], wa[2 * kp][1], wa[2 * kp][2], wa[2 * kp][3], bb[0], bb[1]);
                    mma16(c[(kp & 1) * 2 + 1], wa[2 * kp + 1][0], wa[2 * kp + 1][1], wa[2 * kp + 1][2], wa[2 * kp + 1][3], bb[2], bb[3]);
                }
                {
                    const int tok = lane & 7, ch = 2 * w + ((lane >> 3) & 1);
                    stsm2t(sb + (wg == 0 ? SM_QM : SM_KS) + tok * 128 + ((ch ^ tok) << 4),
                           pack2((c[0][0] + c[1][0]) + (c[2][0] + c[3][0]), (c[0][1] + c[1][1]) + (c[2][1] + c[3][1])),
                           pack2((c[0][2] + c[1][2]) + (c[2][2] + c[3][2]), (c[0][3] + c[1][3]) + (c[2][3] + c[3][3])));
                }
                __syncwarp();
                if (lane == 0) mbar_arrive(bar + B_MEM_FREE * 8);
                TR(1);
                bar_sync(1, 256);
                if (warp < 5) {
                    const int r = lane & 7, cq = lane >> 3;
                    uint32_t a[8], kb[8];
                    ldsm4(a, sb + SM_QM + r * 128 + ((cq ^ r) << 4));
                    ldsm4(kb, sb + SM_KS + (warp * 8 + r) * 128 + ((cq ^ r) << 4));
                    ldsm4(a + 4, sb + SM_QM + r * 128 + (((cq + 4) ^ r) << 4));
                    ldsm4(kb + 4, sb + SM_KS + (warp * 8 + r) * 128 + (((cq + 4) ^ r) << 4));
                    float d0[4] = {0.f, 0.f, 0.f, 0.f}, d1[4] = {0.f, 0.f, 0.f, 0.f};
                    mma16(d0, a[0], 0u, a[1], 0u, kb[0], kb[1]);
                    mma16(d1, a[2], 0u, a[3], 0u, kb[2], kb[3]);
                    mma16(d0, a[4], 0u, a[5], 0u, kb[4], kb[5]);
                    mma16(d1, a[6], 0u, a[7], 0u, kb[6], kb[7]);
                    const uint32_t la = sb + SM_MS + p * 1280 + warp * 256 + lane * 8;
                    #pragma unroll
                    for (int rk = 0; rk < 3; rk++)
                        st_async2(mapa(la, rk), d0[0] + d1[0], d0[1] + d1[1], mapa(bar + B_MS * 8, rk));
                    bar_arrive(4, 352);
                } else if (warp < 7) {
                    xscores<1>(sb, p, warp - 5, 0, lane);
                    bar_arrive(4, 352);
                }
                TR(2);
                if (s < NSEG - 1) {
                    wo_phase<0, 4>(sb, warp, lane, nullptr, par, (uint32_t)(s % 15) + 1u, tile0 + warp, h);
                    TR(4);
                }
            }
            if (s < NSEG - 1) {
                FRESH(lane);
                const uint32_t hp = (s + 1) & 1;
                float d[16];
                const uint64_t db0 = make_desc(SBC + SM_HB, 16, 1024, 1);
                mbar_wait(bar + B_HHI_FULL * 8, hp);
                if (s < 0 && warp == 0) T3(10);
                {
                    const int r = lane & 7, mq = lane >> 3;
                    const uint32_t ha = sb + SM_HB + 9 * 4096 + (8 * (mq >> 1) + r) * 128 + (((6 + (mq & 1)) ^ r) << 4);
                    uint32_t b0[4], b1[4];
                    ldsm4(b0, ha);
                    ldsm4(b1, ha + 2048);
                    #pragma unroll
                    for (int i = 0; i < 16; i++) d[i] = 0.f;
                    mma16(d + 0, wa[39][0], wa[39][1], wa[39][2], wa[39][3], b0[0], b0[1]);
                    mma16(d + 4, wa[39][0], wa[39][1], wa[39][2], wa[39][3], b0[2], b0[3]);
                    mma16(d + 8, wa[39][0], wa[39][1], wa[39][2], wa[39][3], b1[0], b1[1]);
                    mma16(d + 12, wa[39][0], wa[39][1], wa[39][2], wa[39][3], b1[2], b1[3]);
                    asm volatile("" : "+f"(d[0]), "+f"(d[4]), "+f"(d[8]), "+f"(d[12]) :: "memory");
                }
                if (s >= 0) bar_arrive(6, 512);
                mbar_wait(bar + B_HLO_FULL * 8, hp);
                bar_sync(9, 384);
                TR(6);
                wg_fence();
                #pragma unroll
                for (int kt = 0; kt < 12; kt++) wg_rs32(d, wa[kt], db0 + (uint64_t)(((kt >> 2) * 4096 + (kt & 3) * 32) >> 4), 1);
                wg_commit();
                #pragma unroll
                for (int kt = 12; kt < 39; kt++) wg_rs32(d, wa[kt], db0 + (uint64_t)(((kt >> 2) * 4096 + (kt & 3) * 32) >> 4), 1);
                wg_commit();
                wg_wait<1>();
                if (lane == 0) mbar_arrive(bar + B_HLO_FREE * 8);
                wg_wait<0>();
                if (lane == 0) mbar_arrive(bar + B_HHI_FREE * 8);
                TR(7);
                const int mi = lane >> 3, r = lane & 7;
                #pragma unroll
                for (int jj = 0; jj < 2; jj++) {
                    const int tok = 8 * (2 * jj + (mi >> 1)) + r, ch = 2 * w + (mi & 1);
                    stsm4t(dstx + tok * 128 + ((ch ^ r) << 4),
                           pack2(d[8 * jj + 0], d[8 * jj + 1]), pack2(d[8 * jj + 2], d[8 * jj + 3]),
                           pack2(d[8 * jj + 4], d[8 * jj + 5]), pack2(d[8 * jj + 6], d[8 * jj + 7]));
                }
                bar_arrive(8, 384);
                if (s < 0 && warp == 0) T3(11);
                if (s < 0) { bar_sync(0, 512); asm volatile("griddepcontrol.launch_dependents;" ::: "memory"); }
            }
        }
    } else if (wg == 2) {
        asm volatile("setmaxnreg.dec.sync.aligned.u32 64;");
        const int w = warp & 3;
        uint32_t res[4][4];
        {
            const bf16* src = Wo + ((size_t)h * DH + ((p + 1) % 3) * 64) * DM + (tile0 + warp) * 16 + 2 * t;
            #pragma unroll
            for (int kt = 0; kt < 4; kt++) {
                res[kt][0] = __ldg((const uint32_t*)(src + (size_t)(kt * 16 + g) * DM));
                res[kt][1] = __ldg((const uint32_t*)(src + (size_t)(kt * 16 + g) * DM + 8));
                res[kt][2] = __ldg((const uint32_t*)(src + (size_t)(kt * 16 + 8 + g) * DM));
                res[kt][3] = __ldg((const uint32_t*)(src + (size_t)(kt * 16 + 8 + g) * DM + 8));
            }
            #pragma unroll
            for (int kt = 0; kt < 4; kt++) {
                #pragma unroll
                for (int i = 0; i < 4; i++) res[kt][i] = movm(res[kt][i]);
            }
        }
        bar_sync(11, 256);
        if (tid == 256) {
            fence_async();
            mbar_expect(bar + B_WV * 8, 81920);
            #pragma unroll
            for (int i = 0; i < 5; i++) tma2d(sb + SM_WV + i * 16384, &maps.wv, h * DH + p * 64, i * 128, bar + B_WV * 8);
        }
        mbar_wait(bar + B_WV * 8, 0);
        if (w == 0) T3(3);
        const uint64_t da0 = make_desc(SBC + SM_WV, 16, 1024, 1);
        uint32_t vx[8], vm0 = 0, vm1 = 0;
        #pragma unroll
        for (int i = 0; i < 8; i++) vx[i] = 0;

        for (int s = -1; s < NSEG; s++) {
            FRESH(lane);
            const int g = lane >> 2, t = lane & 3, tid = warp * 32 + lane;
            if (s >= 0) {
                const uint32_t par = s & 1;
                mbar_wait(bar + B_MEM_FULL * 8, par);
                bar_sync(4, 352);
                TR(0);
                float dv[4];
                {
                    const uint64_t dbm = make_desc(SBC + SM_HB, 128, 128, 0);
                    wg_fence();
                    #pragma unroll
                    for (int kt = 0; kt < 40; kt++) {
                        wg_ss8(dv, da0 + (uint64_t)(kt * 128), dbm + (uint64_t)(kt * 16), kt > 0);
                        wg_commit();
                        if (kt < 39) wg_wait<1>();
                    }
                    wg_commit();
                }
                TR(1);
                bar_sync(5, 160);
                TR(2);
                uint32_t pb[5];
                #pragma unroll
                for (int j = 0; j < 5; j++) pb[j] = lds1(sb + SM_PM + j * 128 + lane * 4);
                float o0[4] = {0.f, 0.f, 0.f, 0.f}, o1[4] = {0.f, 0.f, 0.f, 0.f}, o2[4] = {0.f, 0.f, 0.f, 0.f};
                wg_wait<0>();
                TR(3);
                mma16(o0, vx[0], vx[1], vx[2], vx[3], pb[1], pb[2]);
                mma16(o1, vx[4], vx[5], vx[6], vx[7], pb[3], pb[4]);
                vm0 = pack2(dv[0], dv[1]); vm1 = pack2(dv[2], dv[3]);
                mma8(o2, vm0, vm1, pb[0]);
                if (s < NSEG - 1) {
                    const uint32_t q0 = pack2(o0[0] + o1[0] + o2[0], o0[1] + o1[1] + o2[1]), q1 = pack2(o0[2] + o1[2] + o2[2], o0[3] + o1[3] + o2[3]);
                    const uint32_t la = sb + SM_OS + (w * 16 + g) * 16 + t * 4;
                    #pragma unroll
                    for (int i = 1; i < 3; i++) {
                        const uint32_t rk = (p + i) % 3;
                        const uint32_t ra = mapa(la + (3 - i) * 1024, rk), rb = mapa(bar + B_O * 8, rk);
                        st_async1(ra, q0, rb);
                        st_async1(ra + 128, q1, rb);
                    }
                    sts1(la, q0);
                    sts1(la + 128, q1);
                    __syncwarp();
                    if (lane == 0) { mbar_arrive(bar + B_O1 * 8); mbar_arrive(bar + B_MEM_FREE * 8); }
                }
                TR(5);
                if (s < NSEG - 1) {
                    wo_phase<4, 4>(sb, warp, lane, res, par, (uint32_t)(s % 15) + 1u, tile0 + warp, h);
                    TR(4);
                    if (tid == 256) mbar_expect(bar + B_O * 8, 2048);
                }
                if (s < NSEG - 1) bar_sync(6, 512);
            }
            uint32_t vn[8];
            #pragma unroll
            for (int i = 0; i < 8; i++) vn[i] = 0;
            if (s < NSEG - 1) {
            float d[16];
            const uint32_t hp = (s + 1) & 1;
            const uint64_t db0 = make_desc(SBC + SM_HB, 16, 1024, 1);
            mbar_wait(bar + B_HHI_FULL * 8, hp);
            TR(6);
            wg_fence();
            #pragma unroll
            for (int kt = 12; kt < 40; kt++) wg_ss32(d, da0 + (uint64_t)(kt * 128), db0 + (uint64_t)(((kt >> 2) * 4096 + (kt & 3) * 32) >> 4), kt > 12);
            wg_commit();
            mbar_wait(bar + B_HLO_FULL * 8, hp);
            wg_fence();
            #pragma unroll
            for (int kt = 0; kt < 9; kt++) wg_ss32(d, da0 + (uint64_t)(kt * 128), db0 + (uint64_t)(((kt >> 2) * 4096 + (kt & 3) * 32) >> 4), 1);
            wg_commit();
            #pragma unroll
            for (int kt = 9; kt < 12; kt++) wg_ss32(d, da0 + (uint64_t)(kt * 128), db0 + (uint64_t)(((kt >> 2) * 4096 + (kt & 3) * 32) >> 4), 1);
            wg_commit();
            wg_wait<1>();
            bar_arrive(9, 384);
            wg_wait<0>();
            if (lane == 0) mbar_arrive(bar + B_HLO_FREE * 8);
            TR(7);
            if (lane == 0) mbar_arrive(bar + B_HHI_FREE * 8);
            #pragma unroll
            for (int i = 0; i < 8; i++) vn[i] = pack2(d[2 * i], d[2 * i + 1]);
            }
            if (s >= 0) {
                {
                    FRESH(lane);
                    mbar_wait(bar + B_XS * 8, s & 1);
                    if (w == 0 && lane == 0) mbar_expect(bar + B_XS * 8, 12288);
                    const uint32_t a = sb + SM_XS + (w >> 1) * 1536 + lane * 16 + (w & 1) * 8;
                    if (w == 0) xsoftmax<2>(a, lane >> 2, lane & 3);
                    else if (w == 1) xsoftmax<3>(a, lane >> 2, lane & 3);
                    else if (w == 2) xsoftmax<4>(a, lane >> 2, lane & 3);
                    else xsoftmax<5>(a, lane >> 2, lane & 3);
                }
                TR(8);
                bar_sync(7, 128);
                FRESH(lane);
                bf16* orow = g_ox + (size_t)(s * 32 + (lane >> 2)) * HD + h * DH + p * 64 + w * 16 + 2 * (lane & 3);
                {
                    const uint32_t pa = sb + SM_XS + lane * 16;
                    #pragma unroll
                    for (int mi = 0; mi < 2; mi++) {
                        float oa[4] = {0.f, 0.f, 0.f, 0.f}, ob[4] = {0.f, 0.f, 0.f, 0.f};
                        if (mi == 0) {
                            const uint4 p0 = lds4(pa);
                            const uint32_t p3 = lds1(pa + 1024 + 8);
                            mma8(oa, vm0, vm1, p0.x);
                            mma8(ob, vm0, vm1, p0.z);
                            mma16(oa, vx[0], vx[1], vx[2], vx[3], p0.y, 0u);
                            mma16(ob, vx[0], vx[1], vx[2], vx[3], p0.w, p3);
                        } else {
                            const uint4 p1 = lds4(pa + 1536), p2 = lds4(pa + 2560);
                            const uint32_t p4 = lds1(pa + 3584 + 8);
                            mma8(oa, vm0, vm1, p1.x);
                            mma8(ob, vm0, vm1, p1.z);
                            mma16(oa, vx[0], vx[1], vx[2], vx[3], p1.y, p2.x);
                            mma16(ob, vx[0], vx[1], vx[2], vx[3], p1.w, p2.z);
                            mma16(oa, vx[4], vx[5], vx[6], vx[7], p2.y, 0u);
                            mma16(ob, vx[4], vx[5], vx[6], vx[7], p2.w, p4);
                            if (lane < 3) mbar_arrive_remote(mapa(bar + B_XSFREE * 8, lane));
                        }
                        const uint32_t u0 = movm(pack2(oa[0], oa[1])), u1 = movm(pack2(oa[2], oa[3]));
                        const uint32_t u2 = movm(pack2(ob[0], ob[1])), u3 = movm(pack2(ob[2], ob[3]));
                        bf16* dst = orow + (size_t)(16 * mi) * HD;
                        *(uint32_t*)dst = u0;
                        *(uint32_t*)(dst + 8) = u1;
                        *(uint32_t*)(dst + 8 * HD) = u2;
                        *(uint32_t*)(dst + 8 * HD + 8) = u3;
                    }
                }
                TR(9);
                if (s == NSEG - 1) {
                    bar_sync(7, 128);
                    if (w == 3 && lane == 0) { signal_cnt(C_REC + 15); T2(400 + b); }
                    break;
                }
            }
            #pragma unroll
            for (int i = 0; i < 8; i++) vx[i] = vn[i];
            if (s >= 0) mbar_wait_cluster(bar + B_XSFREE * 8, s & 1);
            bar_sync(8, 384);
            TR(10);
            if (w < 3) xscores<2>(sb, p, w > 0, w == 2 ? 3 : 1, lane);
            else if ((s & 3) == 3 && s >= 0 && lane == 0) signal_cnt(C_REC + (s >> 2));
            __syncwarp();
            TR(11);
            if (s < 0) { bar_sync(0, 512); asm volatile("griddepcontrol.launch_dependents;" ::: "memory"); }
        }
    } else {
        asm volatile("setmaxnreg.dec.sync.aligned.u32 48;");
        const int w = warp & 3, lt = tid & 127;
        const uint32_t epoch = *(volatile uint32_t*)&g_epoch + 1u;
        if (b == 91) { if (lt < C_NUM) g_cnt[lt * 32] = 0u; __threadfence(); }
        if (b < 80) {
            #pragma unroll
            for (int i = 0; i < 2; i++) {
                const int idx = lt + i * 128, sl = idx >> 6, pg = (idx >> 5) & 1, wd = idx & 31;
                st_relaxed1(g_buf2 + (sl * 3 + (b >> 5)) * 2048 + pg * 1024 + (b & 31) * 32 + wd, 0xFFFFFFFFu);
            }
            __threadfence();
        }
        if (lane == 0 && w < 3) {
            int c = 0;
            if (w == 0) c = probe_blk(g_buf2 + 640 + (b & 31) * 8);
            else if (b < 80) c = probe_blk(g_buf1 + (b * 2 + (w - 1)) * 2048);
            else if (b < 92 && w == 1) c = probe_blk(g_buf2 + (b - 80) * 2048 + 960);
            asm volatile("st.shared.u8 [%0], %1;" :: "r"(sb + SM_CH + 96 + w), "r"(c) : "memory");
        }
        if (w == 0) T3(4);
        bar_sync(3, 128);
        uint32_t selmask;
        {
            const uint32_t c3 = lds1(sb + SM_CH + 96);
            const uint32_t cr = c3 & 1u, c1 = (c3 >> 8) & 1u, c2 = (c3 >> 16) & 1u;
            if (lt == 0 && b < 92) st_release1(&g_choice[b], (epoch << 2) | (b < 80 ? (c1 | (c2 << 1)) : (c1 ^ cr)));
            bar_sync(10, 256);
            if (w == 3) {
                if (lane == 0) { fence_async(); mbar_expect(bar + B_WO * 8, ntile * 6144 - 8192); }
                __syncwarp();
                if (lane < ntile) {
                    #pragma unroll
                    for (int e3 = 0; e3 < 3; e3++) {
                        const bool part = lane >= 8 && lane < 12;
                        if (part && e3 == 1) continue;
                        tma2d(sb + SM_WO + wo_tile_off(lane) + ((part && e3 == 2) ? 1 : e3) * 2048, &maps.wo,
                              (tile0 + lane) * 16, h * DH + ((e3 + p) % 3) * 64, bar + B_WO * 8);
                    }
                }
                __syncwarp();
            }
            if (w == 0) T3(5);
            if (lt < 92) {
                uint32_t v, guard = 0;
                while (true) {
                    v = ld_acquire1(&g_choice[lt]);
                    if ((v >> 2) == (epoch & 0x3fffffffu)) break;
                    __nanosleep(100);
                    if (++guard > (1u << 22)) __trap();
                }
                asm volatile("st.shared.u8 [%0], %1;" :: "r"(sb + SM_CH + lt), "r"(v & 3u) : "memory");
            }
            if (w == 0) T3(6);
            bar_sync(3, 128);
            selmask = (c1 << 12) | (c2 << 13);
            for (int i = 0; i < 12; i++) {
                uint32_t c; asm volatile("ld.shared.u8 %0, [%1];" : "=r"(c) : "r"(sb + SM_CH + 80 + i) : "memory");
                selmask |= ((c ^ cr) & 1u) << i;
            }
        }
        mbar_wait(bar + B_WO * 8, 0);
        if (w == 0) T3(8);
        bar_sync(0, 512);
        if (w == 0) T3(9);
        asm volatile("griddepcontrol.launch_dependents;" ::: "memory");
        const bool has_tile = (12 + w) < ntile;
        for (int s = 0; s < NSEG; s++) {
            const uint32_t par = s & 1;
            FRESH(lane);
            const int g = lane >> 2, t = lane & 3, lt = w * 32 + lane;
            if (s == 0) {
                mbar_wait(bar + B_HLO_FREE * 8, par);
                for (int k = lt; k < DM; k += 128) {
                    uint32_t v[4];
                    #pragma unroll
                    for (int i = 0; i < 4; i++) {
                        uint32_t lo = *(const uint16_t*)(mem0 + (2 * i) * DM + k), hi = *(const uint16_t*)(mem0 + (2 * i + 1) * DM + k);
                        v[i] = lo | (hi << 16);
                    }
                    asm volatile("st.shared.v4.u32 [%0], {%1,%2,%3,%4};" :: "r"(sb + SM_HB + k * 16), "r"(v[0]), "r"(v[1]), "r"(v[2]), "r"(v[3]) : "memory");
                }
            } else {
                const int sl = s & 3;
                const char* q = (const char*)g_buf2 + sl * 3 * 8192 + lt * 16;
                const uint32_t sm = selmask >> (sl * 3);
                const char* q0 = q + (sm & 1) * 4096;
                const char* q1 = q + 8192 + (sm & 2) * 2048;
                const char* q2 = q + 16384 + (sm & 4) * 1024;
                const uint32_t dst = sb + SM_HB + lt * 16;
                uint32_t guard = 0;
                mbar_wait(bar + B_HLO_FREE * 8, par);
                TR(10);
                while (true) {
                    const uint4 v0 = ld_relaxed4(q0), v1 = ld_relaxed4(q0 + 2048), v2 = ld_relaxed4(q1), v3 = ld_relaxed4(q1 + 2048), v4 = ld_relaxed4(q2);
                    sts4(dst, v0); sts4(dst + 2048, v1); sts4(dst + 4096, v2); sts4(dst + 6144, v3); sts4(dst + 8192, v4);
                    if (__all_sync(0xffffffffu, oks(v0) && oks(v1) && oks(v2) && oks(v3) && oks(v4))) break;
                    if (++guard > (1u << 22)) __trap();
                }
            }
            fence_async();
            __syncwarp();
            if (lane == 0) mbar_arrive(bar + B_MEM_FULL * 8);
            if (b == 0 && lt == 0) T2(300 + s);
            if (s == 0 && lt == 0) T2(200 + b);
            TR(0);
            if (w == 2) {
                mbar_wait(bar + B_MS * 8, par);
                TR(1);
                if (lane == 0) mbar_expect(bar + B_MS * 8, 3840);
                uint32_t pb[5];
                float sc[5][2];
                {
                    const uint32_t a = sb + SM_MS + lane * 8;
                    float2 u[5], v[5];
                    #pragma unroll
                    for (int j = 0; j < 5; j++) { u[j] = lds2f(a + j * 256); v[j] = lds2f(a + j * 256 + 1280); }
                    #pragma unroll
                    for (int j = 0; j < 5; j++) { sc[j][0] = u[j].x + v[j].x; sc[j][1] = u[j].y + v[j].y; }
                    #pragma unroll
                    for (int j = 0; j < 5; j++) u[j] = lds2f(a + j * 256 + 2560);
                    #pragma unroll
                    for (int j = 0; j < 5; j++) { sc[j][0] += u[j].x; sc[j][1] += u[j].y; }
                }
                softmax_core<5, false>(sc, g, t, pb);
                #pragma unroll
                for (int j = 0; j < 5; j++) sts1(sb + SM_PM + j * 128 + lane * 4, pb[j]);
                bar_arrive(5, 160);
                TR(2);
            }
            const uint32_t tag = (uint32_t)(s % 15) + 1u;
            if (s < NSEG - 1) {
                if (w == 3) {
                    const char* src = (const char*)g_ht + (size_t)(s + 1) * 40960;
                    if (s == 0) {
                        uint32_t guard = 0;
                        while (true) {
                            const uint32_t f0 = lane > 0 ? ld_acquire1(&g_hflag[lane]) : epoch, f1 = ld_acquire1(&g_hflag[32 + lane]);
                            if (__all_sync(0xffffffffu, f0 == epoch && f1 == epoch)) break;
                            if (++guard > (1u << 22)) __trap();
                        }
                        asm volatile("fence.proxy.async.global;" ::: "memory");
                    }
                    mbar_wait(bar + B_HHI_FREE * 8, par);
                    if (lane == 0) {
                        mbar_expect(bar + B_HHI_FULL * 8, 28672);
                        bulk_g2s(sb + SM_HB + 12288, src + 12288, 28672, sb + SM_BAR + B_HHI_FULL * 8);
                    }
                    mbar_wait(bar + B_MEM_FREE * 8, par);
                    if (lane == 0) {
                        mbar_expect(bar + B_HLO_FULL * 8, 12288);
                        bulk_g2s(sb + SM_HB, src, 12288, sb + SM_BAR + B_HLO_FULL * 8);
                    }
                    __syncwarp();
                }
                if (has_tile) wo_phase<0, 4>(sb, warp, lane, nullptr, par, tag, tile0 + warp, h);
                TR(4);
                bar_sync(6, 512);
            }
            if (s < NSEG - 1) {
                { const uint32_t c0 = clk32(); while (clk32() - c0 < H1_DELAY); }
                if (b < 80) {
                    FRESH(lane);
                    const char* rin0 = (const char*)g_buf1 + (size_t)(b * 2) * 8192 + ((selmask >> 12) & 1) * 4096 + (lane >> 2) * 256 + w * 64 + (lane & 3) * 16;
                    const char* rin1 = (const char*)g_buf1 + (size_t)(b * 2 + 1) * 8192 + ((selmask >> 13) & 1) * 4096 + (lane >> 2) * 256 + w * 64 + (lane & 3) * 16;
                    const int col = b * 8 + 2 * w + ((lane >> 1) & 1), wd = 2 * (lane & 1) + (lane >> 4);
                    const int sl = (lane & 8) ? ((s + 3) & 3) : ((s + 1) & 3);
                    uint32_t* dst = g_buf2 + (sl * 3 + (col >> 8)) * 2048 + ((lane >> 2) & 1) * 1024 + (col & 255) * 4 + wd;
                    asm volatile("" : "+l"(dst));
                    uint4 v0, v1, v2, v3;
                    uint32_t guard = 0;
                    while (true) {
                        v0 = ld_relaxed4(rin0); v1 = ld_relaxed4(rin0 + 2048);
                        v2 = ld_relaxed4(rin1); v3 = ld_relaxed4(rin1 + 2048);
                        if (__all_sync(0xffffffffu, ok4(v0, tag) && ok4(v1, tag) && ok4(v2, tag) && ok4(v3, tag))) break;
                        if (++guard > (1u << 22)) __trap();
                    }
                    TR(11);
                    const float a0 = (uf(v0.x) + uf(v1.x)) + (uf(v2.x) + uf(v3.x)), a1 = (uf(v0.y) + uf(v1.y)) + (uf(v2.y) + uf(v3.y));
                    const float a2 = (uf(v0.z) + uf(v1.z)) + (uf(v2.z) + uf(v3.z)), a3 = (uf(v0.w) + uf(v1.w)) + (uf(v2.w) + uf(v3.w));
                    const bool u16 = lane & 16;
                    float m0 = (u16 ? a2 : a0) + __shfl_xor_sync(0xffffffffu, u16 ? a0 : a2, 16);
                    float m1 = (u16 ? a3 : a1) + __shfl_xor_sync(0xffffffffu, u16 ? a1 : a3, 16);
                    m0 += __shfl_xor_sync(0xffffffffu, m0, 8); m1 += __shfl_xor_sync(0xffffffffu, m1, 8);
                    m0 += __shfl_xor_sync(0xffffffffu, m0, 4); m1 += __shfl_xor_sync(0xffffffffu, m1, 4);
                    st_relaxed1(dst, (lane & 8) ? 0xFFFFFFFFu : pack2(m0, m1));
                    TR(12);
                }
            }
        }
    }
    cluster_sync();
}

constexpr int G_STAGES = 6;
constexpr int G_STAGE_BYTES = 32768;
constexpr int G_SMEM = G_STAGES * G_STAGE_BYTES + 1024 + 256 + 2048 + 10240;

__device__ __forceinline__ void wg_ss128(float* d, uint64_t da, uint64_t db, int sc) {
    asm volatile("{\n\t.reg .pred p;\n\tsetp.ne.b32 p, %66, 0;\n\t"
        "wgmma.mma_async.sync.aligned.m64n128k16.f32.bf16.bf16 "
        "{%0,%1,%2,%3,%4,%5,%6,%7,%8,%9,%10,%11,%12,%13,%14,%15,%16,%17,%18,%19,%20,%21,%22,%23,%24,%25,%26,%27,%28,%29,%30,%31,"
        "%32,%33,%34,%35,%36,%37,%38,%39,%40,%41,%42,%43,%44,%45,%46,%47,%48,%49,%50,%51,%52,%53,%54,%55,%56,%57,%58,%59,%60,%61,%62,%63}, "
        "%64, %65, p, 1, 1, 0, 1;\n\t}"
        : "+f"(d[0]), "+f"(d[1]), "+f"(d[2]), "+f"(d[3]), "+f"(d[4]), "+f"(d[5]), "+f"(d[6]), "+f"(d[7]),
          "+f"(d[8]), "+f"(d[9]), "+f"(d[10]), "+f"(d[11]), "+f"(d[12]), "+f"(d[13]), "+f"(d[14]), "+f"(d[15]),
          "+f"(d[16]), "+f"(d[17]), "+f"(d[18]), "+f"(d[19]), "+f"(d[20]), "+f"(d[21]), "+f"(d[22]), "+f"(d[23]),
          "+f"(d[24]), "+f"(d[25]), "+f"(d[26]), "+f"(d[27]), "+f"(d[28]), "+f"(d[29]), "+f"(d[30]), "+f"(d[31]),
          "+f"(d[32]), "+f"(d[33]), "+f"(d[34]), "+f"(d[35]), "+f"(d[36]), "+f"(d[37]), "+f"(d[38]), "+f"(d[39]),
          "+f"(d[40]), "+f"(d[41]), "+f"(d[42]), "+f"(d[43]), "+f"(d[44]), "+f"(d[45]), "+f"(d[46]), "+f"(d[47]),
          "+f"(d[48]), "+f"(d[49]), "+f"(d[50]), "+f"(d[51]), "+f"(d[52]), "+f"(d[53]), "+f"(d[54]), "+f"(d[55]),
          "+f"(d[56]), "+f"(d[57]), "+f"(d[58]), "+f"(d[59]), "+f"(d[60]), "+f"(d[61]), "+f"(d[62]), "+f"(d[63])
        : "l"(da), "l"(db), "r"(sc));
}

#define SP0_LAST 12
#define SP2_LAST 6
enum { J_MOD = 0, J_G0, J_LN, J_G1, J_G2, J_FIN, J_END };
__host__ __device__ constexpr int sp0(int b) { return b >= 15 ? SP0_LAST : 3; }
__host__ __device__ constexpr int sp2(int b) { return b >= 15 ? SP2_LAST : 3; }
__host__ __device__ constexpr int njr(int b) { return b >= 15 ? 16 : 8; }
struct JobTab { uint32_t n; uint32_t j[1200]; };
constexpr uint32_t mkjob(int ty, int b, int n, int k0, int nk, int ks) {
    return (uint32_t)(ty | (b << 3) | (n << 7) | (k0 << 11) | (nk << 18) | (ks << 25));
}
constexpr void add_jobs(JobTab& t, int ty, int b) {
    if (b < 0) return;
    if (ty == J_G0) { for (int ks = 0; ks < sp0(b); ks++) for (int n = 0; n < 5; n++) t.j[t.n++] = mkjob(ty, b, n, ks * (96 / sp0(b)), 96 / sp0(b), ks); }
    else if (ty == J_G2) { for (int ks = 0; ks < sp2(b); ks++) for (int n = 0; n < 5; n++) t.j[t.n++] = mkjob(ty, b, n, ks * (24 / sp2(b)), 24 / sp2(b), ks); }
    else if (ty == J_G1) { for (int n = 0; n < 12; n++) t.j[t.n++] = mkjob(ty, b, n, 0, 10, 0); }
    else { for (int n = 0; n < njr(b); n++) t.j[t.n++] = mkjob(ty, b, n, 0, 16 / njr(b), ty == J_LN ? sp0(b) : sp2(b)); }
}
constexpr JobTab make_tab() {
    JobTab t = {};
    for (int i = 20; i < 60; i++) t.j[t.n++] = mkjob(J_MOD, 0, 0, i, 0, 0);
    for (int b = 0; b < 15; b++) {
        add_jobs(t, J_G0, b); add_jobs(t, J_G1, b - 1); add_jobs(t, J_FIN, b - 2); add_jobs(t, J_G2, b - 1); add_jobs(t, J_LN, b);
    }
    add_jobs(t, J_FIN, 13); add_jobs(t, J_G1, 14);
    add_jobs(t, J_G0, 15); add_jobs(t, J_G2, 14); add_jobs(t, J_LN, 15); add_jobs(t, J_FIN, 14);
    add_jobs(t, J_G1, 15); add_jobs(t, J_G2, 15); add_jobs(t, J_FIN, 15);
    return t;
}
__constant__ JobTab c_jobs = make_tab();

__device__ __forceinline__ bool cnt_ge(int idx, uint32_t target) { return ld_acquire1(g_cnt + idx * 32) >= target; }
__device__ __forceinline__ void cnt_wait(int idx, uint32_t target) {
    uint32_t guard = 0;
    while (!cnt_ge(idx, target)) { __nanosleep(64); if (++guard > (1u << 22)) __trap(); }
}

struct SMaps { CUtensorMap ox, wo, h2, w1, act, w2; };

__global__ void __launch_bounds__(384, 1)
k_side(const __grid_constant__ SMaps maps, const bf16* __restrict__ xin, const bf16* __restrict__ cvec,
       const bf16* __restrict__ wmod, bf16* __restrict__ outp) {
    extern __shared__ uint8_t smem_raw[];
    const uint32_t sb = (smem_u32(smem_raw) + 1023u) & ~1023u;
    const uint32_t bars = sb + G_STAGES * G_STAGE_BYTES;
    float* red = (float*)(smem_raw + (bars + 256 - smem_u32(smem_raw)));
    const int tid = threadIdx.x, lane = tid & 31, wg = tid >> 7;
    if (tid == 0) T2(500 + blockIdx.x);
    if (tid == 0) {
        for (int i = 0; i < G_STAGES; i++) { mbar_init(bars + i * 8, 1); mbar_init(bars + 64 + i * 8, 8); }
        for (int i = 0; i < 2; i++) { mbar_init(bars + 128 + i * 8, 1); mbar_init(bars + 144 + i * 8, 8); }
        asm volatile("fence.mbarrier_init.release.cluster;" ::: "memory");
    }
    __syncthreads();
    if (wg == 0) {
        if (tid == 0) {
            uint32_t st = 0, ph = 1;
            for (uint32_t it = 0;; it++) {
                const uint32_t ji = atomicAdd(g_cnt + C_Q * 32, 1u);
                const uint32_t job = ji < c_jobs.n ? c_jobs.j[ji] : (uint32_t)J_END;
                if (ji == 0) g_epoch = g_epoch + 1u;
                const int ty = job & 7, b = (job >> 3) & 15, n = (job >> 7) & 15, k0 = (job >> 11) & 127, nk = (job >> 18) & 127;
                const uint32_t sl = it & 1;
                mbar_wait(bars + 144 + sl * 8, ((it >> 1) & 1) ^ 1);
                sts1(bars + 160 + sl * 4, job);
                if (ty == J_G0 || ty == J_G1 || ty == J_G2) {
                    if (b >= PRING && ty != J_G1) cnt_wait((ty == J_G0 ? C_LN : C_FIN) + b - PRING, njr(b - PRING));
                    mbar_arrive(bars + 128 + sl * 8);
                    const CUtensorMap* mA = ty == J_G0 ? &maps.ox : (ty == J_G1 ? &maps.h2 : &maps.act);
                    const CUtensorMap* mB = ty == J_G0 ? &maps.wo : (ty == J_G1 ? &maps.w1 : &maps.w2);
                    const int didx = ty == J_G0 ? C_REC + b : (ty == J_G1 ? C_LN + b : C_G1 + b);
                    const uint32_t dtgt = ty == J_G0 ? 96u : (ty == J_G1 ? (uint32_t)njr(b) : 12u);
                    int pre = 0;
                    if (!cnt_ge(didx, dtgt)) {
                        pre = nk < G_STAGES ? nk : G_STAGES;
                        uint32_t s2 = st, p2 = ph;
                        for (int i = 0; i < pre; i++) {
                            mbar_wait(bars + 64 + s2 * 8, p2);
                            const uint32_t a = sb + s2 * G_STAGE_BYTES;
                            mbar_expect(bars + s2 * 8, G_STAGE_BYTES);
                            tma2d(a + 16384, mB, n * 128, (k0 + i) * 64, bars + s2 * 8);
                            tma2d(a + 16384 + 8192, mB, n * 128 + 64, (k0 + i) * 64, bars + s2 * 8);
                            if (++s2 == G_STAGES) { s2 = 0; p2 ^= 1; }
                        }
                        cnt_wait(didx, dtgt);
                    }
                    asm volatile("fence.proxy.async.global;" ::: "memory");
                    T2(1024 + ji * 4 + 1);
                    for (int i = 0; i < nk; i++) {
                        const uint32_t a = sb + st * G_STAGE_BYTES;
                        if (i >= pre) {
                            mbar_wait(bars + 64 + st * 8, ph);
                            mbar_expect(bars + st * 8, G_STAGE_BYTES);
                        }
                        tma2d(a, mA, (k0 + i) * 64, b * 128, bars + st * 8);
                        if (i >= pre) {
                            tma2d(a + 16384, mB, n * 128, (k0 + i) * 64, bars + st * 8);
                            tma2d(a + 16384 + 8192, mB, n * 128 + 64, (k0 + i) * 64, bars + st * 8);
                        }
                        if (++st == G_STAGES) { st = 0; ph ^= 1; }
                    }
                } else {
                    if (ty == J_LN) { bulk_pf(xin + (size_t)(b * 128 + n * nk * 8) * DM, nk * 8 * DM * 2); cnt_wait(C_MOD, 40u); cnt_wait(C_G0 + b, 5u * sp0(b)); }
                    else if (ty == J_FIN) cnt_wait(C_G2 + b, 5u * sp2(b));
                    if (ji < 1200) T2(1024 + ji * 4 + 1);
                    mbar_arrive(bars + 128 + sl * 8);
                    if (ty == J_END) break;
                }
            }
        }
    } else {
        const int cw = wg - 1, ct = tid - 128, cwarp = ct >> 5;
        uint32_t st = 0, ph = 0;
        float* smod = red + 512;
        bool have_mod = false;
        auto load_mod = [&]() {
            for (int i = ct; i < DM; i += 256) *(float4*)(smod + i * 4) = __ldcg((const float4*)(g_mod + 2 * DM + i * 4));
            bar_sync(1, 256);
            have_mod = true;
        };
        {
            if (ct == 0) red[0] = cnt_ge(C_MOD, 40u) ? 1.0f : 0.0f;
            bar_sync(1, 256);
            const bool rdy = red[0] != 0.0f;
            bar_sync(1, 256);
            if (rdy) load_mod();
        }
        for (uint32_t it = 0;; it++) {
            const uint32_t sl = it & 1;
            mbar_wait(bars + 128 + sl * 8, (it >> 1) & 1);
            const uint32_t job = lds1(bars + 160 + sl * 4);
            __syncwarp();
            if (lane == 0) mbar_arrive(bars + 144 + sl * 8);
            const int ty = job & 7, b = (job >> 3) & 15, n = (job >> 7) & 15, k0 = (job >> 11) & 127, nk = (job >> 18) & 127, ks = (job >> 25) & 15;
            if (ty == J_END) break;
            int sig = -1;
            if (ty == J_G0 || ty == J_G1 || ty == J_G2) {
                float d[64];
                #pragma unroll
                for (int i = 0; i < 64; i++) d[i] = 0.f;
                uint32_t pst = 0;
                for (int kb = 0; kb < nk; kb++) {
                    mbar_wait(bars + st * 8, ph);
                    const uint32_t a = sb + st * G_STAGE_BYTES;
                    const uint64_t da = make_desc(a + cw * 8192, 16, 1024, 1);
                    const uint64_t db = make_desc(a + 16384, 8192, 1024, 1);
                    wg_fence();
                    #pragma unroll
                    for (int k = 0; k < 4; k++) wg_ss128(d, da + (uint64_t)(k * 2), db + (uint64_t)(k * 128), 1);
                    wg_commit();
                    if (kb > 0) {
                        wg_wait<1>();
                        if (lane == 0) mbar_arrive(bars + 64 + pst * 8);
                    }
                    pst = st;
                    if (++st == G_STAGES) { st = 0; ph ^= 1; }
                }
                wg_wait<0>();
                if (lane == 0) mbar_arrive(bars + 64 + pst * 8);
                const int g = lane >> 2, t = lane & 3;
                if (ty == J_G1) {
                    #pragma unroll
                    for (int hf = 0; hf < 2; hf++) {
                        bf16* o = g_act + (size_t)(b * 128 + cwarp * 16 + g + 8 * hf) * FF + n * 128 + 8 * t;
                        #pragma unroll
                        for (int q = 0; q < 4; q++) {
                            uint32_t u[4];
                            #pragma unroll
                            for (int i = 0; i < 4; i++) {
                                const float a0 = bfr(d[4 * (4 * q + i) + 2 * hf]), a1 = bfr(d[4 * (4 * q + i) + 2 * hf + 1]);
                                u[i] = pack2(__fdividef(a0, 1.0f + __expf(-a0)), __fdividef(a1, 1.0f + __expf(-a1)));
                            }
                            const bool o1 = t & 1, o2 = t & 2;
                            uint32_t x0 = __shfl_xor_sync(0xffffffffu, o1 ? u[0] : u[1], 1), x1 = __shfl_xor_sync(0xffffffffu, o1 ? u[2] : u[3], 1);
                            if (o1) { u[0] = x0; u[2] = x1; } else { u[1] = x0; u[3] = x1; }
                            x0 = __shfl_xor_sync(0xffffffffu, o2 ? u[0] : u[2], 2); x1 = __shfl_xor_sync(0xffffffffu, o2 ? u[1] : u[3], 2);
                            if (o2) { u[0] = x0; u[1] = x1; } else { u[2] = x0; u[3] = x1; }
                            *(uint4*)(o + q * 32) = make_uint4(u[0], u[1], u[2], u[3]);
                        }
                    }
                    sig = C_G1 + b;
                } else {
                    float* o = (ty == J_G0 ? g_p0 : g_p2) + ((size_t)((b % PRING) * PMAX + ks) * 128 + cwarp * 16 + g) * DM + n * 128 + 2 * t;
                    #pragma unroll
                    for (int hf = 0; hf < 2; hf++) {
                        #pragma unroll
                        for (int j = 0; j < 16; j++)
                            *(float2*)(o + hf * 8 * DM + j * 8) = make_float2(d[4 * j + 2 * hf], d[4 * j + 2 * hf + 1]);
                    }
                    sig = (ty == J_G0 ? C_G0 : C_G2) + b;
                }
            } else if (ty == J_MOD) {
                mod_chunk<256, 2>(cvec, wmod, k0 * 64, ct, red);
                sig = C_MOD;
            } else {
                const bool ln = ty == J_LN;
                if (!have_mod) load_mod();
                const float* gm = smod + (ln ? 0 : 3) * DM + lane * 4;
                for (int r = 0; r < nk; r++) {
                    const int lr = (n * nk + r) * 8 + cwarp, row = b * 128 + lr;
                    const float* pp = (ln ? g_p0 : g_p2) + ((size_t)((b % PRING) * PMAX) * 128 + lr) * DM + lane * 4;
                    const bf16* xs = (ln ? xin : (const bf16*)g_x1) + (size_t)row * DM + lane * 4;
                    float v[5][4];
                    uint2 xv[5];
                    #pragma unroll
                    for (int i = 0; i < 5; i++) {
                        xv[i] = __ldcg((const uint2*)(xs + i * 128));
                        v[i][0] = 0.f; v[i][1] = 0.f; v[i][2] = 0.f; v[i][3] = 0.f;
                    }
                    if (ks == 3) {
                        float4 a[3][5];
                        #pragma unroll
                        for (int q = 0; q < 3; q++) {
                            #pragma unroll
                            for (int i = 0; i < 5; i++) a[q][i] = __ldcg((const float4*)(pp + (size_t)q * 128 * DM + i * 128));
                        }
                        #pragma unroll
                        for (int q = 0; q < 3; q++) {
                            #pragma unroll
                            for (int i = 0; i < 5; i++) { v[i][0] += a[q][i].x; v[i][1] += a[q][i].y; v[i][2] += a[q][i].z; v[i][3] += a[q][i].w; }
                        }
                    } else {
                        for (int q0 = 0; q0 < ks; q0 += 6) {
                            float4 a[6][5];
                            #pragma unroll
                            for (int q = 0; q < 6; q++) {
                                #pragma unroll
                                for (int i = 0; i < 5; i++) a[q][i] = __ldcg((const float4*)(pp + (size_t)(q0 + q) * 128 * DM + i * 128));
                            }
                            #pragma unroll
                            for (int q = 0; q < 6; q++) {
                                #pragma unroll
                                for (int i = 0; i < 5; i++) { v[i][0] += a[q][i].x; v[i][1] += a[q][i].y; v[i][2] += a[q][i].z; v[i][3] += a[q][i].w; }
                            }
                        }
                    }
                    bf16* dst = (ln ? (bf16*)g_x1 : outp) + (size_t)row * DM + lane * 4;
                    #pragma unroll
                    for (int i = 0; i < 5; i++) {
                        const float4 gg = *(const float4*)(gm + i * 128);
                        const uint32_t o0 = pack2(bflo(xv[i].x) + bfr(gg.x * bfr(v[i][0])), bfhi(xv[i].x) + bfr(gg.y * bfr(v[i][1])));
                        const uint32_t o1 = pack2(bflo(xv[i].y) + bfr(gg.z * bfr(v[i][2])), bfhi(xv[i].y) + bfr(gg.w * bfr(v[i][3])));
                        *(uint2*)(dst + i * 128) = make_uint2(o0, o1);
                        v[i][0] = bflo(o0); v[i][1] = bfhi(o0); v[i][2] = bflo(o1); v[i][3] = bfhi(o1);
                    }
                    if (ln) {
                        float mb, sd;
                        ln_stats(v, mb, sd);
                        #pragma unroll
                        for (int i = 0; i < 5; i++) {
                            const float4 sh = *(const float4*)(gm + DM + i * 128), sc = *(const float4*)(gm + 2 * DM + i * 128);
                            *(uint2*)(g_h2 + (size_t)row * DM + lane * 4 + i * 128) = ln_apply(v[i], mb, sd, sc, sh);
                        }
                    }
                }
                if (ln) sig = C_LN + b; else if (b < 16 - PRING) sig = C_FIN + b;
            }
            if (sig >= 0) {
                bar_sync(1, 256);
                if (ct == 0) signal_cnt(sig);
            }
            if (ct == 0) T2(1024 + ji * 4 + 2);
        }
    }
}

typedef CUresult (*EncodeFn)(CUtensorMap*, CUtensorMapDataType, cuuint32_t, void*, const cuuint64_t*, const cuuint64_t*,
                             const cuuint32_t*, const cuuint32_t*, CUtensorMapInterleave, CUtensorMapSwizzle,
                             CUtensorMapL2promotion, CUtensorMapFloatOOBfill);

static void make_map(EncodeFn fn, CUtensorMap* m, const void* ptr, uint64_t inner, uint64_t outer, uint32_t bi, uint32_t bo,
                     CUtensorMapSwizzle sw = CU_TENSOR_MAP_SWIZZLE_128B) {
    cuuint64_t dims[2] = {inner, outer};
    cuuint64_t strides[1] = {inner * 2};
    cuuint32_t box[2] = {bi, bo};
    cuuint32_t es[2] = {1, 1};
    fn(m, CU_TENSOR_MAP_DATA_TYPE_BFLOAT16, 2, (void*)ptr, dims, strides, box, es, CU_TENSOR_MAP_INTERLEAVE_NONE,
       sw, CU_TENSOR_MAP_L2_PROMOTION_L2_256B, CU_TENSOR_MAP_FLOAT_OOB_FILL_NONE);
}

extern "C" void kernel_launch(void* const* d_in, const int* in_sizes, int n_in, void* d_out, int out_size) {
    const bf16* x = (const bf16*)d_in[0];
    const bf16* mem0 = (const bf16*)d_in[1];
    const bf16* Wq = (const bf16*)d_in[2];
    const bf16* Wk = (const bf16*)d_in[3];
    const bf16* Wv = (const bf16*)d_in[4];
    const bf16* Wo = (const bf16*)d_in[5];
    const bf16* w1 = (const bf16*)d_in[8];
    const bf16* w2 = (const bf16*)d_in[9];
    const bf16* c = (const bf16*)d_in[10];
    const bf16* wmod = (const bf16*)d_in[11];
    bf16* out = (bf16*)d_out;

    static EncodeFn enc = nullptr;
    static void *p_ox, *p_x1, *p_h2, *p_act;
    if (!enc) {
        cudaDriverEntryPointQueryResult qr;
        void* f = nullptr;
        cudaGetDriverEntryPoint("cuTensorMapEncodeTiled", &f, cudaEnableDefault, &qr);
        enc = (EncodeFn)f;
        cudaGetSymbolAddress(&p_ox, g_ox);
        cudaGetSymbolAddress(&p_x1, g_x1);
        cudaGetSymbolAddress(&p_h2, g_h2);
        cudaGetSymbolAddress(&p_act, g_act);
        cudaFuncSetAttribute(k_rec, cudaFuncAttributeMaxDynamicSharedMemorySize, SM_TOTAL);
        cudaFuncSetAttribute(k_side, cudaFuncAttributeMaxDynamicSharedMemorySize, G_SMEM);
    }
    RMaps rm;
    make_map(enc, &rm.wq, Wq, HD, DM, 64, 128);
    make_map(enc, &rm.wk, Wk, HD, DM, 64, 128);
    make_map(enc, &rm.wv, Wv, HD, DM, 64, 128);
    make_map(enc, &rm.wo, Wo, DM, HD, 16, 64, CU_TENSOR_MAP_SWIZZLE_32B);
    SMaps m;
    make_map(enc, &m.ox, p_ox, HD, SEQ, 64, 128);
    make_map(enc, &m.wo, Wo, DM, HD, 64, 64);
    make_map(enc, &m.h2, p_h2, DM, SEQ, 64, 128);
    make_map(enc, &m.w1, w1, FF, DM, 64, 64);
    make_map(enc, &m.act, p_act, FF, SEQ, 64, 128);
    make_map(enc, &m.w2, w2, DM, FF, 64, 64);

    cudaStream_t st = cudaStreamPerThread;
    {
        cudaLaunchConfig_t cfg = {};
        cfg.gridDim = dim3(96); cfg.blockDim = dim3(512); cfg.dynamicSmemBytes = SM_TOTAL; cfg.stream = st;
        cudaLaunchAttribute at[2];
        at[0].id = cudaLaunchAttributeClusterDimension;
        at[0].val.clusterDim.x = 3; at[0].val.clusterDim.y = 1; at[0].val.clusterDim.z = 1;
        cfg.attrs = at; cfg.numAttrs = 1;
        cudaLaunchKernelEx(&cfg, k_rec, rm, mem0, Wo, x, c, wmod);
    }
    {
        cudaLaunchConfig_t cfg = {};
        cfg.gridDim = dim3(SIDE_CTAS); cfg.blockDim = dim3(384); cfg.dynamicSmemBytes = G_SMEM; cfg.stream = st;
        cudaLaunchAttribute at[1];
        at[0].id = cudaLaunchAttributeProgrammaticStreamSerialization;
        at[0].val.programmaticStreamSerializationAllowed = 1;
        cfg.attrs = at; cfg.numAttrs = 1;
        cudaLaunchKernelEx(&cfg, k_side, m, x, c, wmod, out);
    }
}
```

```cpp
#include <cuda_runtime.h>
#include <cuda_bf16.h>
#include <cuda.h>
#include <stdint.h>

typedef __nv_bfloat16 bf16;
#define VX_THROTTLE 1
#define H1_DELAY 400
#define H1_BACK 0
#define VM_THROTTLE 1
#define PRE_TRIG 0
#define SIDE_CTAS 132

constexpr int SEQ = 2048, DM = 640, NH = 32, DH = 192, NSEG = 64, FF = 1536, HD = NH * DH;

__device__ __align__(128) float g_mod[6 * DM];
__device__ __align__(1024) bf16 g_ht[(size_t)SEQ * DM];
__device__ __align__(1024) bf16 g_ox[(size_t)SEQ * HD];
__device__ __align__(1024) bf16 g_x1[(size_t)SEQ * DM];
__device__ __align__(1024) bf16 g_h2[(size_t)SEQ * DM];
__device__ __align__(1024) bf16 g_act[(size_t)SEQ * FF];
__device__ __align__(8192) uint32_t g_buf1[80 * 2 * 2048];
__device__ __align__(8192) uint32_t g_buf2[4 * 3 * 2048];
__device__ uint32_t g_choice[128];
__device__ uint32_t g_epoch;
__device__ uint32_t g_hflag[64];
__device__ __align__(128) uint32_t g_modx[2 * DM];
#define T2(i)
#define T3(i)
enum { C_Q = 0, C_MOD = 1, C_REC = 2, C_G0 = 18, C_LN = 34, C_G1 = 50, C_G2 = 66, C_FIN = 82, C_NUM = 98 };
__device__ __align__(128) uint32_t g_cnt[C_NUM * 32];
constexpr int PMAX = 12;
constexpr int PRING = 4;
__device__ __align__(1024) float g_p0[(size_t)PRING * PMAX * 128 * DM];
__device__ __align__(1024) float g_p2[(size_t)PRING * PMAX * 128 * DM];
#define TR(k)

#define FRESH(x) asm volatile("" : "+r"(x))
__device__ __forceinline__ float bfr(float x) { uint32_t r; asm("cvt.rn.bf16x2.f32 %0, %1, %2;" : "=r"(r) : "f"(x), "f"(0.0f)); return __uint_as_float(r); }
__device__ __forceinline__ uint32_t pack2(float a, float b) {
    uint32_t r; asm("cvt.rn.bf16x2.f32 %0, %1, %2;" : "=r"(r) : "f"(b), "f"(a)); return r;
}
__device__ __forceinline__ float bflo(uint32_t v) { return __uint_as_float(v << 16); }
__device__ __forceinline__ float bfhi(uint32_t v) { return __uint_as_float(v & 0xffff0000u); }
__device__ __forceinline__ float ex2(float x) { float r; asm("ex2.approx.ftz.f32 %0, %1;" : "=f"(r) : "f"(x)); return r; }
__device__ __forceinline__ float rcpf(float x) { float r; asm("rcp.approx.ftz.f32 %0, %1;" : "=f"(r) : "f"(x)); return r; }
__device__ __forceinline__ void score2(float& a, float& b) {
    const float SCALE = 0.07216878364870322f;
    uint32_t u = pack2(a, b);
    u = pack2(bflo(u) * SCALE, bfhi(u) * SCALE);
    a = bflo(u); b = bfhi(u);
}
__device__ __forceinline__ uint32_t smem_u32(const void* p) { return (uint32_t)__cvta_generic_to_shared(p); }

__device__ __forceinline__ void mbar_init(uint32_t bar, uint32_t cnt) {
    asm volatile("mbarrier.init.shared::cta.b64 [%0], %1;" :: "r"(bar), "r"(cnt) : "memory");
}
__device__ __forceinline__ void mbar_arrive(uint32_t bar) {
    asm volatile("mbarrier.arrive.shared::cta.b64 _, [%0];" :: "r"(bar) : "memory");
}
__device__ __forceinline__ void mbar_expect(uint32_t bar, uint32_t bytes) {
    asm volatile("mbarrier.arrive.expect_tx.shared::cta.b64 _, [%0], %1;" :: "r"(bar), "r"(bytes) : "memory");
}
__device__ __forceinline__ bool mbar_try(uint32_t bar, uint32_t parity) {
    uint32_t ok;
    asm volatile("{\n\t.reg .pred p;\n\tmbarrier.try_wait.parity.shared::cta.b64 p, [%1], %2;\n\tselp.u32 %0, 1, 0, p;\n\t}"
                 : "=r"(ok) : "r"(bar), "r"(parity) : "memory");
    return ok != 0;
}
__device__ __forceinline__ bool mbar_try_cluster(uint32_t bar, uint32_t parity) {
    uint32_t ok;
    asm volatile("{\n\t.reg .pred p;\n\tmbarrier.try_wait.parity.acquire.cluster.shared::cta.b64 p, [%1], %2;\n\tselp.u32 %0, 1, 0, p;\n\t}"
                 : "=r"(ok) : "r"(bar), "r"(parity) : "memory");
    return ok != 0;
}
__device__ __forceinline__ void mbar_wait(uint32_t bar, uint32_t parity) {
    uint32_t guard = 0;
    while (!mbar_try(bar, parity)) { if (++guard > (1u << 22)) __trap(); }
}
__device__ __forceinline__ void mbar_wait_cluster(uint32_t bar, uint32_t parity) {
    uint32_t guard = 0;
    while (!mbar_try_cluster(bar, parity)) { if (++guard > (1u << 22)) __trap(); }
}
__device__ __forceinline__ void bar_sync(int id, int n) { asm volatile("bar.sync %0, %1;" :: "r"(id), "r"(n) : "memory"); }
__device__ __forceinline__ void bar_arrive(int id, int n) { asm volatile("bar.arrive %0, %1;" :: "r"(id), "r"(n) : "memory"); }
__device__ __forceinline__ void sts1(uint32_t a, uint32_t v) { asm volatile("st.shared.u32 [%0], %1;" :: "r"(a), "r"(v) : "memory"); }
__device__ __forceinline__ uint32_t lds1(uint32_t a) { uint32_t v; asm volatile("ld.shared.u32 %0, [%1];" : "=r"(v) : "r"(a) : "memory"); return v; }
__device__ __forceinline__ void fence_async() { asm volatile("fence.proxy.async.shared::cta;" ::: "memory"); }
__device__ __forceinline__ void cluster_sync() {
    asm volatile("barrier.cluster.arrive.release.aligned;\n\tbarrier.cluster.wait.acquire.aligned;" ::: "memory");
}
__device__ __forceinline__ uint32_t mapa(uint32_t a, uint32_t rank) {
    uint32_t r; asm("mapa.shared::cluster.u32 %0, %1, %2;" : "=r"(r) : "r"(a), "r"(rank)); return r;
}
__device__ __forceinline__ void st_async1(uint32_t a, uint32_t v, uint32_t bar) {
    asm volatile("st.async.weak.shared::cluster.mbarrier::complete_tx::bytes.b32 [%0], %1, [%2];" :: "r"(a), "r"(v), "r"(bar) : "memory");
}
__device__ __forceinline__ void st_async2(uint32_t a, float x, float y, uint32_t bar) {
    asm volatile("st.async.weak.shared::cluster.mbarrier::complete_tx::bytes.v2.f32 [%0], {%1,%2}, [%3];" :: "r"(a), "f"(x), "f"(y), "r"(bar) : "memory");
}
__device__ __forceinline__ void st_async4(uint32_t a, const float* c, uint32_t bar) {
    asm volatile("st.async.weak.shared::cluster.mbarrier::complete_tx::bytes.v4.f32 [%0], {%1,%2,%3,%4}, [%5];"
                 :: "r"(a), "f"(c[0]), "f"(c[1]), "f"(c[2]), "f"(c[3]), "r"(bar) : "memory");
}
__device__ __forceinline__ void bulk_g2s(uint32_t dst, const void* src, uint32_t bytes, uint32_t bar) {
    asm volatile("cp.async.bulk.shared::cluster.global.mbarrier::complete_tx::bytes [%0], [%1], %2, [%3];"
                 :: "r"(dst), "l"(src), "r"(bytes), "r"(bar) : "memory");
}
__device__ __forceinline__ void cpa16(uint32_t s, const void* g) {
    asm volatile("cp.async.cg.shared.global [%0], [%1], 16;" :: "r"(s), "l"(g) : "memory");
}
__device__ __forceinline__ void cpa_wait_all() { asm volatile("cp.async.wait_all;" ::: "memory"); }
__device__ __forceinline__ void ldsm4(uint32_t* r, uint32_t a) {
    asm volatile("ldmatrix.sync.aligned.m8n8.x4.shared.b16 {%0,%1,%2,%3}, [%4];" : "=r"(r[0]), "=r"(r[1]), "=r"(r[2]), "=r"(r[3]) : "r"(a) : "memory");
}
__device__ __forceinline__ void ldsm4t(uint32_t* r, uint32_t a) {
    asm volatile("ldmatrix.sync.aligned.m8n8.x4.trans.shared.b16 {%0,%1,%2,%3}, [%4];" : "=r"(r[0]), "=r"(r[1]), "=r"(r[2]), "=r"(r[3]) : "r"(a) : "memory");
}
__device__ __forceinline__ void stsm2t(uint32_t a, uint32_t r0, uint32_t r1) {
    asm volatile("stmatrix.sync.aligned.m8n8.x2.trans.shared.b16 [%0], {%1,%2};" :: "r"(a), "r"(r0), "r"(r1) : "memory");
}
__device__ __forceinline__ void stsm4t(uint32_t a, uint32_t r0, uint32_t r1, uint32_t r2, uint32_t r3) {
    asm volatile("stmatrix.sync.aligned.m8n8.x4.trans.shared.b16 [%0], {%1,%2,%3,%4};" :: "r"(a), "r"(r0), "r"(r1), "r"(r2), "r"(r3) : "memory");
}
__device__ __forceinline__ uint32_t movm(uint32_t v) {
    uint32_t r; asm volatile("movmatrix.sync.aligned.m8n8.trans.b16 %0, %1;" : "=r"(r) : "r"(v)); return r;
}
__device__ __forceinline__ void mma16(float* c, uint32_t a0, uint32_t a1, uint32_t a2, uint32_t a3, uint32_t b0, uint32_t b1) {
    asm volatile("mma.sync.aligned.m16n8k16.row.col.f32.bf16.bf16.f32 {%0,%1,%2,%3}, {%4,%5,%6,%7}, {%8,%9}, {%0,%1,%2,%3};"
                 : "+f"(c[0]), "+f"(c[1]), "+f"(c[2]), "+f"(c[3]) : "r"(a0), "r"(a1), "r"(a2), "r"(a3), "r"(b0), "r"(b1));
}
__device__ __forceinline__ void mma8(float* c, uint32_t a0, uint32_t a1, uint32_t b0) {
    asm volatile("mma.sync.aligned.m16n8k8.row.col.f32.bf16.bf16.f32 {%0,%1,%2,%3}, {%4,%5}, {%6}, {%0,%1,%2,%3};"
                 : "+f"(c[0]), "+f"(c[1]), "+f"(c[2]), "+f"(c[3]) : "r"(a0), "r"(a1), "r"(b0));
}
__host__ __device__ constexpr uint64_t make_desc(uint32_t saddr, uint32_t lbo, uint32_t sbo, uint32_t layout) {
    return (uint64_t)((saddr & 0x3FFFF) >> 4) | ((uint64_t)(lbo >> 4) << 16) | ((uint64_t)(sbo >> 4) << 32) | ((uint64_t)layout << 62);
}
__device__ __forceinline__ void wg_fence() { asm volatile("wgmma.fence.sync.aligned;" ::: "memory"); }
__device__ __forceinline__ void wg_commit() { asm volatile("wgmma.commit_group.sync.aligned;" ::: "memory"); }
template <int N> __device__ __forceinline__ void wg_wait() { asm volatile("wgmma.wait_group.sync.aligned %0;" :: "n"(N) : "memory"); }

#define D16(C) C(d[0]), C(d[1]), C(d[2]), C(d[3]), C(d[4]), C(d[5]), C(d[6]), C(d[7]), \
               C(d[8]), C(d[9]), C(d[10]), C(d[11]), C(d[12]), C(d[13]), C(d[14]), C(d[15])
#define DREG16 "{%0,%1,%2,%3,%4,%5,%6,%7,%8,%9,%10,%11,%12,%13,%14,%15}"
__device__ __forceinline__ void wg_rs32(float* d, const uint32_t* a, uint64_t db, bool acc) {
    if (acc)
        asm volatile("wgmma.mma_async.sync.aligned.m64n32k16.f32.bf16.bf16 " DREG16 ", {%16,%17,%18,%19}, %20, 1, 1, 1, 0;"
            : D16("+f") : "r"(a[0]), "r"(a[1]), "r"(a[2]), "r"(a[3]), "l"(db));
    else
        asm volatile("wgmma.mma_async.sync.aligned.m64n32k16.f32.bf16.bf16 " DREG16 ", {%16,%17,%18,%19}, %20, 0, 1, 1, 0;"
            : D16("=f") : "r"(a[0]), "r"(a[1]), "r"(a[2]), "r"(a[3]), "l"(db));
}
__device__ __forceinline__ void wg_ss32(float* d, uint64_t da, uint64_t db, bool acc) {
    if (acc)
        asm volatile("wgmma.mma_async.sync.aligned.m64n32k16.f32.bf16.bf16 " DREG16 ", %16, %17, 1, 1, 1, 1, 0;"
            : D16("+f") : "l"(da), "l"(db));
    else
        asm volatile("wgmma.mma_async.sync.aligned.m64n32k16.f32.bf16.bf16 " DREG16 ", %16, %17, 0, 1, 1, 1, 0;"
            : D16("=f") : "l"(da), "l"(db));
}
__device__ __forceinline__ void wg_ss8(float* d, uint64_t da, uint64_t db, bool acc) {
    if (acc)
        asm volatile("wgmma.mma_async.sync.aligned.m64n8k16.f32.bf16.bf16 {%0,%1,%2,%3}, %4, %5, 1, 1, 1, 1, 1;"
            : "+f"(d[0]), "+f"(d[1]), "+f"(d[2]), "+f"(d[3]) : "l"(da), "l"(db));
    else
        asm volatile("wgmma.mma_async.sync.aligned.m64n8k16.f32.bf16.bf16 {%0,%1,%2,%3}, %4, %5, 0, 1, 1, 1, 1;"
            : "=f"(d[0]), "=f"(d[1]), "=f"(d[2]), "=f"(d[3]) : "l"(da), "l"(db));
}
template <int OFF> __device__ __forceinline__ void ldsm4t_i(uint32_t* r, uint32_t a) {
    asm volatile("ldmatrix.sync.aligned.m8n8.x4.trans.shared.b16 {%0,%1,%2,%3}, [%4+%5];"
                 : "=r"(r[0]), "=r"(r[1]), "=r"(r[2]), "=r"(r[3]) : "r"(a), "n"(OFF) : "memory");
}

__device__ __forceinline__ uint4 ld_relaxed4(const void* p) {
    uint4 v;
    asm volatile("ld.relaxed.gpu.global.v4.u32 {%0,%1,%2,%3}, [%4];" : "=r"(v.x), "=r"(v.y), "=r"(v.z), "=r"(v.w) : "l"(p) : "memory");
    return v;
}
__device__ __forceinline__ void st_relaxed2(void* p, uint32_t a, uint32_t b) {
    asm volatile("st.relaxed.gpu.global.v2.u32 [%0], {%1,%2};" :: "l"(p), "r"(a), "r"(b) : "memory");
}
__device__ __forceinline__ void st_relaxed2_off(void* base, uint32_t off, uint32_t a, uint32_t b) {
    asm volatile("{\n\t.reg .u64 ad;\n\tcvt.u64.u32 ad, %1;\n\tadd.u64 ad, ad, %0;\n\tst.relaxed.gpu.global.v2.u32 [ad], {%2,%3};\n\t}"
                 :: "l"(base), "r"(off), "r"(a), "r"(b) : "memory");
}
__device__ __forceinline__ void st_relaxed1(void* p, uint32_t a) {
    asm volatile("st.relaxed.gpu.global.u32 [%0], %1;" :: "l"(p), "r"(a) : "memory");
}
__device__ __forceinline__ uint32_t ld_acquire1(const uint32_t* p) {
    uint32_t v; asm volatile("ld.acquire.gpu.global.u32 %0, [%1];" : "=r"(v) : "l"(p) : "memory"); return v;
}
__device__ __forceinline__ void st_release1(uint32_t* p, uint32_t a) {
    asm volatile("st.release.gpu.global.u32 [%0], %1;" :: "l"(p), "r"(a) : "memory");
}
__device__ __forceinline__ uint4 lds4(uint32_t s) {
    uint4 v; asm volatile("ld.shared.v4.u32 {%0,%1,%2,%3}, [%4];" : "=r"(v.x), "=r"(v.y), "=r"(v.z), "=r"(v.w) : "r"(s) : "memory"); return v;
}
__device__ __forceinline__ void sts4(uint32_t s, const uint4& v) {
    asm volatile("st.shared.v4.u32 [%0], {%1,%2,%3,%4};" :: "r"(s), "r"(v.x), "r"(v.y), "r"(v.z), "r"(v.w) : "memory");
}
__device__ __forceinline__ float4 lds4f(uint32_t s) {
    float4 v; asm volatile("ld.shared.v4.f32 {%0,%1,%2,%3}, [%4];" : "=f"(v.x), "=f"(v.y), "=f"(v.z), "=f"(v.w) : "r"(s) : "memory"); return v;
}
__device__ __forceinline__ uint2 lds2(uint32_t s) {
    uint2 v; asm volatile("ld.shared.v2.u32 {%0,%1}, [%2];" : "=r"(v.x), "=r"(v.y) : "r"(s) : "memory"); return v;
}
__device__ __forceinline__ float2 lds2f(uint32_t s) {
    float2 v; asm volatile("ld.shared.v2.f32 {%0,%1}, [%2];" : "=f"(v.x), "=f"(v.y) : "r"(s) : "memory"); return v;
}
__device__ __forceinline__ uint32_t clk32() { uint32_t c; asm volatile("mov.u32 %0, %%clock;" : "=r"(c) :: "memory"); return c; }
__device__ __forceinline__ uint32_t tagw(float v, uint32_t tag) { return ((__float_as_uint(v) + 8u) & ~15u) | tag; }
__device__ __forceinline__ bool ok4(const uint4& v, uint32_t tag) { return (((v.x ^ tag) | (v.y ^ tag) | (v.z ^ tag) | (v.w ^ tag)) & 15u) == 0; }
__device__ __forceinline__ bool oks(const uint4& v) { return v.x != 0xFFFFFFFFu && v.y != 0xFFFFFFFFu && v.z != 0xFFFFFFFFu && v.w != 0xFFFFFFFFu; }
__device__ __forceinline__ float uf(uint32_t x) { return __uint_as_float(x & ~15u); }

template <int NT, int BAR>
__device__ __forceinline__ void mod_chunk(const bf16* __restrict__ c, const bf16* __restrict__ wmod, int col0, int tid, float* red) {
    constexpr int RG = NT / 8, NP = DM / RG;
    const int cc = tid & 7, rg = tid >> 3;
    uint4 w[NP];
    #pragma unroll
    for (int i = 0; i < NP; i++) w[i] = __ldg((const uint4*)(wmod + (size_t)(rg + i * RG) * (6 * DM) + col0 + cc * 8));
    float a[8];
    #pragma unroll
    for (int j = 0; j < 8; j++) a[j] = 0.f;
    #pragma unroll
    for (int i = 0; i < NP; i++) {
        const float v = __bfloat162float(c[rg + i * RG]);
        const float sv = bfr(__fdividef(v, 1.0f + __expf(-v)));
        a[0] += sv * bflo(w[i].x); a[1] += sv * bfhi(w[i].x); a[2] += sv * bflo(w[i].y); a[3] += sv * bfhi(w[i].y);
        a[4] += sv * bflo(w[i].z); a[5] += sv * bfhi(w[i].z); a[6] += sv * bflo(w[i].w); a[7] += sv * bfhi(w[i].w);
    }
    #pragma unroll
    for (int j = 0; j < 8; j++) {
        a[j] += __shfl_xor_sync(0xffffffffu, a[j], 8);
        a[j] += __shfl_xor_sync(0xffffffffu, a[j], 16);
    }
    if ((tid & 31) < 8) {
        float* d = red + (tid >> 5) * 64 + cc * 8;
        *(float4*)d = make_float4(a[0], a[1], a[2], a[3]);
        *(float4*)(d + 4) = make_float4(a[4], a[5], a[6], a[7]);
    }
    bar_sync(BAR, NT);
    if (tid < 64) {
        float s = 0.f;
        #pragma unroll
        for (int i = 0; i < NT / 32; i++) s += red[i * 64 + tid];
        g_mod[col0 + tid] = bfr(s);
    }
}

__device__ __forceinline__ void ln_stats(const float (*v)[4], float& mb, float& sd) {
    float s = 0.f;
    #pragma unroll
    for (int i = 0; i < 5; i++) s += (v[i][0] + v[i][1]) + (v[i][2] + v[i][3]);
    #pragma unroll
    for (int o = 16; o > 0; o >>= 1) s += __shfl_xor_sync(0xffffffffu, s, o);
    const float mean = s * (1.0f / DM);
    float q = 0.f;
    #pragma unroll
    for (int i = 0; i < 5; i++) {
        #pragma unroll
        for (int j = 0; j < 4; j++) { const float d = v[i][j] - mean; q += d * d; }
    }
    #pragma unroll
    for (int o = 16; o > 0; o >>= 1) q += __shfl_xor_sync(0xffffffffu, q, o);
    mb = bfr(mean);
    const float var = bfr(q * (1.0f / DM));
    sd = 1.0f / bfr(sqrtf(bfr(var + 1e-5f)));
}
__device__ __forceinline__ uint2 ln_apply(const float* v, float mb, float rs, const float4& sc, const float4& sh) {
    const float o0 = bfr(bfr(bfr(v[0] - mb) * rs) * bfr(1.0f + sc.x)) + sh.x;
    const float o1 = bfr(bfr(bfr(v[1] - mb) * rs) * bfr(1.0f + sc.y)) + sh.y;
    const float o2 = bfr(bfr(bfr(v[2] - mb) * rs) * bfr(1.0f + sc.z)) + sh.z;
    const float o3 = bfr(bfr(bfr(v[3] - mb) * rs) * bfr(1.0f + sc.w)) + sh.w;
    return make_uint2(pack2(o0, o1), pack2(o2, o3));
}

constexpr int SM_WV = 0;
constexpr int SM_HB = 81920;
constexpr int SM_WO = SM_HB + 40960;
constexpr int SM_QX = SM_WO + 77824;
constexpr int SM_KS = SM_QX + 4096;
constexpr int SM_QM = SM_KS + 5120;
constexpr int SM_XS = SM_QM + 1024;
constexpr int SM_MS = SM_XS + 12288;
constexpr int SM_OS = SM_MS + 3840;
constexpr int SM_PM = SM_OS + 3072;
constexpr int SM_BAR = SM_PM + 640;
constexpr int SM_CH = SM_BAR + 128;
constexpr int SM_TOTAL = SM_CH + 128;
static_assert(SM_TOTAL <= 232448, "smem");

enum { B_MEM_FULL = 0, B_MEM_FREE, B_HLO_FULL, B_HHI_FULL, B_HLO_FREE, B_HHI_FREE, B_MS, B_O, B_XS, B_O1, B_XSFREE, B_WQ, B_WK, B_WV, B_WO };

__device__ __forceinline__ int probe_blk(uint32_t* blk) {
    uint32_t t0 = 0xffffffffu, t1 = 0xffffffffu, acc = 0;
    for (int rep = 0; rep < 3; rep++) {
        #pragma unroll
        for (int pg = 0; pg < 2; pg++) {
            uint32_t c0 = clk32();
            uint32_t v = atomicOr(blk + pg * 1024 + acc, 0u);
            acc = (v == 0x12345678u) ? 1u : 0u;
            asm volatile("" :: "r"(acc) : "memory");
            uint32_t c1 = clk32() + acc;
            uint32_t d = c1 - c0;
            if (rep > 0) { if (pg == 0) t0 = min(t0, d); else t1 = min(t1, d); }
        }
    }
    return t1 < t0 ? 1 : 0;
}

__device__ __forceinline__ uint32_t wo_tile_off(int w) {
    if (w < 8) return w * 6144;
    if (w < 12) return 8 * 6144 + (w - 8) * 4096;
    return 8 * 6144 + 4 * 4096 + (w - 12) * 6144;
}

template <int NRES, int NPRE>
__device__ __forceinline__ void wo_phase(uint32_t sb, int w, int lane, const uint32_t (*res)[4], uint32_t parity,
                                         uint32_t tag, int tile, int h) {
    FRESH(lane);
    const int er = (lane & 7) + 8 * (lane >> 4);
    const uint32_t aaddr = sb + SM_WO + wo_tile_off(w) + er * 32 + ((((lane >> 3) & 1) ^ ((er >> 2) & 1)) << 4);
    const uint32_t baddr = sb + SM_OS + lane * 16;
    float c0[4] = {0.f, 0.f, 0.f, 0.f}, c1[4] = {0.f, 0.f, 0.f, 0.f};
    uint32_t pre[NPRE > 4 ? NPRE : 4][4];
    if (NPRE >= 4) {
        #pragma unroll
        for (int i = 0; i < 4; i++) ldsm4t(pre[i], aaddr + i * 512);
        mbar_wait(sb + SM_BAR + B_O1 * 8, parity);
        uint32_t b[2][4];
        ldsm4t(b[0], baddr);
        ldsm4t(b[1], baddr + 512);
        #pragma unroll
        for (int kp = 0; kp < 2; kp++) {
            mma16(c0, pre[2 * kp][0], pre[2 * kp][1], pre[2 * kp][2], pre[2 * kp][3], b[kp][0], b[kp][1]);
            mma16(c1, pre[2 * kp + 1][0], pre[2 * kp + 1][1], pre[2 * kp + 1][2], pre[2 * kp + 1][3], b[kp][2], b[kp][3]);
        }
    } else {
        #pragma unroll
        for (int i = 0; i < 2; i++) ldsm4t(pre[i], aaddr + i * 512);
        mbar_wait(sb + SM_BAR + B_O1 * 8, parity);
        #pragma unroll
        for (int kp = 0; kp < 2; kp++) {
            uint32_t b[4];
            ldsm4t(b, baddr + kp * 512);
            if (kp == 1) { ldsm4t(pre[0], aaddr + 2 * 512); ldsm4t(pre[1], aaddr + 3 * 512); }
            mma16(c0, pre[0][0], pre[0][1], pre[0][2], pre[0][3], b[0], b[1]);
            mma16(c1, pre[1][0], pre[1][1], pre[1][2], pre[1][3], b[2], b[3]);
        }
    }
    #pragma unroll
    for (int i = 0; i < NPRE; i++) ldsm4t(pre[i], aaddr + (4 + i) * 512);
    uint32_t off0, off1;
    {
        uint32_t ch;
        asm volatile("ld.shared.u16 %0, [%1];" : "=r"(ch) : "r"(sb + SM_CH + 2 * tile) : "memory");
        const int j = h >> 4;
        const uint32_t base = (uint32_t)((tile * 4 + j) * 8192 + (h & 15) * 256 + lane * 8);
        ch >>= j;
        off0 = base + (ch & 1) * 4096;
        off1 = base + 16384 + (ch & 256) * 16;
    }
    mbar_wait(sb + SM_BAR + B_O * 8, parity);
    if (NRES == 4) {
        uint32_t b[4][4];
        #pragma unroll
        for (int i = 0; i < 4; i++) ldsm4t(b[i], baddr + (2 + i) * 512);
        #pragma unroll
        for (int i = 0; i < 2; i++) {
            mma16(c0, res[2 * i][0], res[2 * i][1], res[2 * i][2], res[2 * i][3], b[i][0], b[i][1]);
            mma16(c1, res[2 * i + 1][0], res[2 * i + 1][1], res[2 * i + 1][2], res[2 * i + 1][3], b[i][2], b[i][3]);
        }
        #pragma unroll
        for (int i = 0; i < 2; i++) {
            mma16(c0, pre[2 * i][0], pre[2 * i][1], pre[2 * i][2], pre[2 * i][3], b[2 + i][0], b[2 + i][1]);
            mma16(c1, pre[2 * i + 1][0], pre[2 * i + 1][1], pre[2 * i + 1][2], pre[2 * i + 1][3], b[2 + i][2], b[2 + i][3]);
        }
    } else if (NPRE == 4) {
        uint32_t b[2][4];
        #pragma unroll
        for (int hh = 0; hh < 2; hh++) {
            ldsm4t(b[0], baddr + (2 + 2 * hh) * 512);
            ldsm4t(b[1], baddr + (3 + 2 * hh) * 512);
            if (hh) {
                #pragma unroll
                for (int i = 0; i < 4; i++) ldsm4t(pre[i], aaddr + (8 + i) * 512);
            }
            #pragma unroll
            for (int i = 0; i < 2; i++) {
                mma16(c0, pre[2 * i][0], pre[2 * i][1], pre[2 * i][2], pre[2 * i][3], b[i][0], b[i][1]);
                mma16(c1, pre[2 * i + 1][0], pre[2 * i + 1][1], pre[2 * i + 1][2], pre[2 * i + 1][3], b[i][2], b[i][3]);
            }
        }
    }
    st_relaxed2_off(g_buf1, off0, tagw(c0[0] + c1[0], tag), tagw(c0[1] + c1[1], tag));
    st_relaxed2_off(g_buf1, off1, tagw(c0[2] + c1[2], tag), tagw(c0[3] + c1[3], tag));
}

template <int NT, bool MASK>
__device__ __forceinline__ void softmax_core(float (*sc)[2], int g, int t, uint32_t* pb) {
    const float L2E = 1.4426950408889634f;
    #pragma unroll
    for (int j = 0; j < NT; j++) score2(sc[j][0], sc[j][1]);
    if (MASK) {
        const float NEG = -999292928.0f;
        if (2 * t > g) sc[NT - 1][0] = NEG;
        if (2 * t + 1 > g) sc[NT - 1][1] = NEG;
    }
    float m[NT];
    #pragma unroll
    for (int j = 0; j < NT; j++) m[j] = fmaxf(sc[j][0], sc[j][1]);
    float mx = m[0];
    #pragma unroll
    for (int j = 1; j < NT; j++) mx = fmaxf(mx, m[j]);
    mx = fmaxf(mx, __shfl_xor_sync(0xffffffffu, mx, 1));
    mx = fmaxf(mx, __shfl_xor_sync(0xffffffffu, mx, 2));
    float s0 = 0.f, s1 = 0.f;
    #pragma unroll
    for (int j = 0; j < NT; j++) {
        sc[j][0] = ex2((sc[j][0] - mx) * L2E); sc[j][1] = ex2((sc[j][1] - mx) * L2E);
        s0 += sc[j][0]; s1 += sc[j][1];
    }
    s0 += s1;
    s0 += __shfl_xor_sync(0xffffffffu, s0, 1);
    s0 += __shfl_xor_sync(0xffffffffu, s0, 2);
    const float iv = rcpf(s0);
    #pragma unroll
    for (int j = 0; j < NT; j++) pb[j] = pack2(sc[j][0] * iv, sc[j][1] * iv);
}
template <int NT>
__device__ __forceinline__ void xsoftmax(uint32_t a, int g, int t) {
    float sc[NT][2];
    #pragma unroll
    for (int j = 0; j < NT; j++) {
        float2 v0 = lds2f(a + j * 512), v1 = lds2f(a + j * 512 + 4096), v2 = lds2f(a + j * 512 + 8192);
        sc[j][0] = v0.x + v1.x + v2.x; sc[j][1] = v0.y + v1.y + v2.y;
    }
    uint32_t pb[NT];
    softmax_core<NT, true>(sc, g, t, pb);
    #pragma unroll
    for (int j = 0; j < NT; j += 2) {
        if (j + 1 < NT) asm volatile("st.shared.v2.u32 [%0], {%1,%2};" :: "r"(a + j * 512), "r"(pb[j]), "r"(pb[j + 1]) : "memory");
        else sts1(a + j * 512, pb[j]);
    }
}
template <int NJ>
__device__ __forceinline__ void xscores(uint32_t sb, int p, int mi, int j0, int lane) {
    FRESH(lane);
    const int r = lane & 7, cq = lane >> 3;
    const int qrow = mi * 16 + r + 8 * (cq & 1);
    uint32_t kb[NJ][8];
    float d[NJ][4];
    #pragma unroll
    for (int j = 0; j < NJ; j++) {
        ldsm4(kb[j], sb + SM_KS + ((j0 + j) * 8 + r) * 128 + ((cq ^ r) << 4));
        ldsm4(kb[j] + 4, sb + SM_KS + ((j0 + j) * 8 + r) * 128 + (((cq + 4) ^ r) << 4));
        d[j][0] = 0.f; d[j][1] = 0.f; d[j][2] = 0.f; d[j][3] = 0.f;
    }
    #pragma unroll
    for (int kt = 0; kt < 4; kt++) {
        uint32_t a[4];
        ldsm4(a, sb + SM_QX + qrow * 128 + (((2 * kt + (cq >> 1)) ^ r) << 4));
        #pragma unroll
        for (int j = 0; j < NJ; j++) mma16(d[j], a[0], a[1], a[2], a[3], kb[j][2 * kt], kb[j][2 * kt + 1]);
    }
    const uint32_t la = sb + SM_XS + p * 4096 + (mi * 3 + j0) * 512 + lane * 16;
    #pragma unroll
    for (int rk = 0; rk < 3; rk++) {
        const uint32_t ra = mapa(la, rk), rb = mapa(sb + SM_BAR + B_XS * 8, rk);
        #pragma unroll
        for (int j = 0; j < NJ; j++) st_async4(ra + j * 512, d[j], rb);
    }
}
__device__ __forceinline__ void mbar_arrive_remote(uint32_t bar) {
    asm volatile("mbarrier.arrive.relaxed.cluster.shared::cluster.b64 _, [%0];" :: "r"(bar) : "memory");
}

__device__ __forceinline__ void tma2d(uint32_t dst, const CUtensorMap* map, int c0, int c1, uint32_t bar) {
    asm volatile("cp.async.bulk.tensor.2d.shared::cluster.global.mbarrier::complete_tx::bytes [%0], [%1, {%2, %3}], [%4];"
                 :: "r"(dst), "l"(map), "r"(c0), "r"(c1), "r"(bar) : "memory");
}
__device__ __forceinline__ void tma2d_pf(const CUtensorMap* map, int c0, int c1) {
    asm volatile("cp.async.bulk.prefetch.tensor.2d.L2.global [%0, {%1, %2}];" :: "l"(map), "r"(c0), "r"(c1) : "memory");
}
__device__ __forceinline__ void bulk_pf(const void* p, uint32_t bytes) {
    asm volatile("cp.async.bulk.prefetch.L2.global [%0], %1;" :: "l"(p), "r"(bytes) : "memory");
}
struct RMaps { CUtensorMap wq, wk, wv, wo; };
__device__ __forceinline__ void signal_cnt(int idx) {
    asm volatile("fence.proxy.async.global;\n\tred.release.gpu.global.add.u32 [%0], 1;" :: "l"(g_cnt + idx * 32) : "memory");
}

__global__ void __launch_bounds__(512, 1)
k_rec(const __grid_constant__ RMaps maps, const bf16* __restrict__ mem0, const bf16* __restrict__ Wo,
      const bf16* __restrict__ xin, const bf16* __restrict__ cvec, const bf16* __restrict__ wmod) {
    extern __shared__ __align__(1024) uint8_t smem_raw[];
    constexpr uint32_t SBC = 1024;
    const uint32_t sb = smem_u32(smem_raw);
    if ((sb & 0xFFFFFFu) != SBC) __trap();
    int lane = __shfl_sync(0xffffffffu, threadIdx.x & 31, threadIdx.x & 31);
    const int warp = __shfl_sync(0xffffffffu, threadIdx.x >> 5, 0), wg = warp >> 2;
    const int tid = warp * 32 + lane;
    const int b = blockIdx.x, h = b / 3, p = b % 3;
    const int g = lane >> 2, t = lane & 3;
    const int tile0 = p == 0 ? 0 : (p == 1 ? 14 : 27);
    const int ntile = p == 0 ? 14 : 13;
    const uint32_t bar = sb + SM_BAR;

    if (tid == 0) T2(100 + b);
    if (tid == 0) {
        mbar_init(bar + B_MEM_FULL * 8, 4);
        mbar_init(bar + B_MEM_FREE * 8, 12);
        mbar_init(bar + B_HLO_FULL * 8, 1);
        mbar_init(bar + B_HHI_FULL * 8, 1);
        mbar_init(bar + B_HLO_FREE * 8, 12);
        mbar_init(bar + B_HHI_FREE * 8, 12);
        mbar_init(bar + B_MS * 8, 1);
        mbar_init(bar + B_O * 8, 1);
        mbar_init(bar + B_XS * 8, 1);
        mbar_init(bar + B_O1 * 8, 4);
        mbar_init(bar + B_XSFREE * 8, 12);
        mbar_init(bar + B_WQ * 8, 1);
        mbar_init(bar + B_WK * 8, 1);
        mbar_init(bar + B_WV * 8, 1);
        mbar_init(bar + B_WO * 8, 1);
        asm volatile("fence.mbarrier_init.release.cluster;" ::: "memory");
        mbar_expect(bar + B_WQ * 8, 81920);
        mbar_expect(bar + B_WK * 8, 81920);
        #pragma unroll
        for (int i = 0; i < 5; i++) {
            tma2d(sb + SM_WO + i * 16384, &maps.wq, h * DH + p * 64, i * 128, bar + B_WQ * 8);
            tma2d(sb + SM_WV + i * 16384, &maps.wk, h * DH + p * 64, i * 128, bar + B_WK * 8);
        }
        mbar_expect(bar + B_MS * 8, 3840);
        mbar_expect(bar + B_O * 8, 2048);
        mbar_expect(bar + B_XS * 8, 12288);
    }
    __syncwarp();
    asm volatile("barrier.cluster.arrive.relaxed.aligned;\n\tbarrier.cluster.wait.acquire.aligned;" ::: "memory");
    if (warp == 0) T3(0);

    if (wg < 3) {
        const uint32_t tag = *(volatile uint32_t*)&g_epoch + 1u;
        const int seg1 = b + 1, nrow = b < NSEG - 1 ? 64 : 32;
        const bf16* xl = xin + lane * 4;
        uint2 xn[5];
        #pragma unroll
        for (int i = 0; i < 5; i++) xn[i] = __ldg((const uint2*)(xl + (size_t)warp * DM + i * 128));
        if (wg == 2) {
            if (tid == 256) bulk_pf(xin, 32 * DM * 2);
            if (tid == 288 && b < NSEG - 1) bulk_pf(xin + (size_t)seg1 * 32 * DM, 32 * DM * 2);
        } else if (b < 80) {
            uint4 wm[5];
            float cv[5];
            #pragma unroll
            for (int i = 0; i < 5; i++) {
                wm[i] = __ldg((const uint4*)(wmod + (size_t)((tid >> 1) + 128 * i) * (6 * DM) + b * 16 + (tid & 1) * 8));
                cv[i] = __bfloat162float(cvec[(tid >> 1) + 128 * i]);
            }
            float a[8];
            #pragma unroll
            for (int j = 0; j < 8; j++) a[j] = 0.f;
            #pragma unroll
            for (int i = 0; i < 5; i++) {
                const float sv = bfr(__fdividef(cv[i], 1.0f + __expf(-cv[i])));
                a[0] += sv * bflo(wm[i].x); a[1] += sv * bfhi(wm[i].x); a[2] += sv * bflo(wm[i].y); a[3] += sv * bfhi(wm[i].y);
                a[4] += sv * bflo(wm[i].z); a[5] += sv * bfhi(wm[i].z); a[6] += sv * bflo(wm[i].w); a[7] += sv * bfhi(wm[i].w);
            }
            #pragma unroll 1
            for (int o = 2; o < 32; o <<= 1) {
                #pragma unroll
                for (int j = 0; j < 8; j++) a[j] += __shfl_xor_sync(0xffffffffu, a[j], o);
            }
            if (lane < 2) {
                const uint32_t d = sb + SM_QM + warp * 64 + lane * 32;
                sts4(d, make_uint4(__float_as_uint(a[0]), __float_as_uint(a[1]), __float_as_uint(a[2]), __float_as_uint(a[3])));
                sts4(d + 16, make_uint4(__float_as_uint(a[4]), __float_as_uint(a[5]), __float_as_uint(a[6]), __float_as_uint(a[7])));
            }
            bar_sync(1, 256);
            if (tid < 8) {
                float s0 = 0.f, s1 = 0.f;
                #pragma unroll
                for (int i = 0; i < 8; i++) { const float2 v = lds2f(sb + SM_QM + i * 64 + tid * 8); s0 += v.x; s1 += v.y; }
                st_relaxed2(g_modx + (b * 8 + tid) * 2, pack2(s0, s1), tag);
            }
        }
        if (tid >= 59 && tid < 64) tma2d_pf(&maps.wv, h * DH + p * 64, (tid - 59) * 128);
        if (tid >= 64 && tid < 256) bulk_pf(Wo + ((size_t)h * DH + (tid - 64)) * DM + tile0 * 16, ntile * 32);
        T3(12);
        if (tid < 320) {
            uint4 v; uint32_t guard = 0;
            while (true) {
                v = ld_relaxed4(g_modx + tid * 4);
                if (v.y == tag && v.w == tag) break;
                __nanosleep(50);
                if (++guard > (1u << 22)) __trap();
            }
            asm volatile("st.shared.v2.u32 [%0], {%1,%2};" :: "r"(sb + SM_KS + tid * 8), "r"(v.x), "r"(v.z) : "memory");
        }
        bar_sync(2, 384);
        T3(13);
        #pragma unroll 1
        for (int idx = warp; idx < nrow; idx += 12) {
            float v[5][4];
            #pragma unroll
            for (int i = 0; i < 5; i++) { v[i][0] = bflo(xn[i].x); v[i][1] = bfhi(xn[i].x); v[i][2] = bflo(xn[i].y); v[i][3] = bfhi(xn[i].y); }
            if (idx + 12 < nrow) {
                const int nx = idx + 12 < 32 ? idx + 12 : b * 32 + idx + 12;
                #pragma unroll
                for (int i = 0; i < 5; i++) xn[i] = __ldg((const uint2*)(xl + (size_t)nx * DM + i * 128));
            }
            float mb, rs;
            ln_stats(v, mb, rs);
            const int row = idx & 31;
            char* dst = (idx < 32 ? (char*)smem_raw + SM_HB : (char*)g_ht + (size_t)seg1 * 40960)
                        + (lane >> 4) * 4096 + row * 128 + ((((lane >> 1) & 7) ^ (row & 7)) << 4) + (lane & 1) * 8;
            #pragma unroll
            for (int i = 0; i < 5; i++) {
                const uint2 u0 = lds2(sb + SM_KS + i * 256 + lane * 8), u1 = lds2(sb + SM_KS + 1280 + i * 256 + lane * 8);
                const float4 sh = make_float4(bflo(u0.x), bfhi(u0.x), bflo(u0.y), bfhi(u0.y));
                const float4 sc = make_float4(bflo(u1.x), bfhi(u1.x), bflo(u1.y), bfhi(u1.y));
                *(uint2*)(dst + i * 8192) = ln_apply(v[i], mb, rs, sc, sh);
            }
        }
        fence_async();
        bar_sync(2, 384);
        if (tid == 0) { mbar_arrive(bar + B_HLO_FULL * 8); mbar_arrive(bar + B_HHI_FULL * 8); }
        if (tid == 352 && b < NSEG - 1) {
            asm volatile("fence.proxy.async.global;" ::: "memory");
            st_release1(&g_hflag[seg1], tag);
        }
        __syncwarp();
    }

    if (wg < 2) {
        asm volatile("setmaxnreg.inc.sync.aligned.u32 200;");
        const int w = warp & 3;
        uint32_t wa[40][4];
        {
            mbar_wait(bar + (wg == 0 ? B_WQ : B_WK) * 8, 0);
            if (w == 0) T3(1 + wg);
            const int r = lane & 7;
            const uint32_t wsrc = sb + (wg == 0 ? SM_WO : SM_WV) + (r + ((lane >> 4) << 3)) * 128 + (((2 * w + ((lane >> 3) & 1)) ^ r) << 4);
            #pragma unroll
            for (int kt = 0; kt < 40; kt++) ldsm4t(wa[kt], wsrc + kt * 2048);
            fence_async();
            bar_arrive(10 + wg, 256);
        }

        const uint32_t dstx = sb + (wg == 0 ? SM_QX : SM_KS + 1024);

        for (int s = -1; s < NSEG; s++) {
            const uint32_t par = s & 1;
            FRESH(lane);
            const int g = lane >> 2, t = lane & 3, tid = warp * 32 + lane;
            if (s >= 0) {
                mbar_wait(bar + B_MEM_FULL * 8, par);
                TR(0);
                float c[4][4];
                #pragma unroll
                for (int i = 0; i < 4; i++) { c[i][0] = 0.f; c[i][1] = 0.f; c[i][2] = 0.f; c[i][3] = 0.f; }
                uint32_t maddr = sb + lane * 16;
                asm volatile("" : "+r"(maddr));
                #pragma unroll
                for (int kp = 0; kp < 20; kp++) {
                    uint32_t bb[4];
                    ldsm4t(bb, maddr + (SM_HB + kp * 512));
                    mma16(c[(kp & 1) * 2], wa[2 * kp][0], wa[2 * kp][1], wa[2 * kp][2], wa[2 * kp][3], bb[0], bb[1]);
                    mma16(c[(kp & 1) * 2 + 1], wa[2 * kp + 1][0], wa[2 * kp + 1][1], wa[2 * kp + 1][2], wa[2 * kp + 1][3], bb[2], bb[3]);
                }
                {
                    const int tok = lane & 7, ch = 2 * w + ((lane >> 3) & 1);
                    stsm2t(sb + (wg == 0 ? SM_QM : SM_KS) + tok * 128 + ((ch ^ tok) << 4),
                           pack2((c[0][0] + c[1][0]) + (c[2][0] + c[3][0]), (c[0][1] + c[1][1]) + (c[2][1] + c[3][1])),
                           pack2((c[0][2] + c[1][2]) + (c[2][2] + c[3][2]), (c[0][3] + c[1][3]) + (c[2][3] + c[3][3])));
                }
                __syncwarp();
                if (lane == 0) mbar_arrive(bar + B_MEM_FREE * 8);
                TR(1);
                bar_sync(1, 256);
                if (warp < 5) {
                    const int r = lane & 7, cq = lane >> 3;
                    uint32_t a[8], kb[8];
                    ldsm4(a, sb + SM_QM + r * 128 + ((cq ^ r) << 4));
                    ldsm4(kb, sb + SM_KS + (warp * 8 + r) * 128 + ((cq ^ r) << 4));
                    ldsm4(a + 4, sb + SM_QM + r * 128 + (((cq + 4) ^ r) << 4));
                    ldsm4(kb + 4, sb + SM_KS + (warp * 8 + r) * 128 + (((cq + 4) ^ r) << 4));
                    float d0[4] = {0.f, 0.f, 0.f, 0.f}, d1[4] = {0.f, 0.f, 0.f, 0.f};
                    mma16(d0, a[0], 0u, a[1], 0u, kb[0], kb[1]);
                    mma16(d1, a[2], 0u, a[3], 0u, kb[2], kb[3]);
                    mma16(d0, a[4], 0u, a[5], 0u, kb[4], kb[5]);
                    mma16(d1, a[6], 0u, a[7], 0u, kb[6], kb[7]);
                    const uint32_t la = sb + SM_MS + p * 1280 + warp * 256 + lane * 8;
                    #pragma unroll
                    for (int rk = 0; rk < 3; rk++)
                        st_async2(mapa(la, rk), d0[0] + d1[0], d0[1] + d1[1], mapa(bar + B_MS * 8, rk));
                    bar_arrive(4, 352);
                } else if (warp < 7) {
                    xscores<1>(sb, p, warp - 5, 0, lane);
                    bar_arrive(4, 352);
                }
                TR(2);
                if (s < NSEG - 1) {
                    wo_phase<0, 4>(sb, warp, lane, nullptr, par, (uint32_t)(s % 15) + 1u, tile0 + warp, h);
                    TR(4);
                }
            }
            if (s < NSEG - 1) {
                FRESH(lane);
                const uint32_t hp = (s + 1) & 1;
                float d[16];
                const uint64_t db0 = make_desc(SBC + SM_HB, 16, 1024, 1);
                mbar_wait(bar + B_HHI_FULL * 8, hp);
                if (s < 0 && warp == 0) T3(10);
                {
                    const int r = lane & 7, mq = lane >> 3;
                    const uint32_t ha = sb + SM_HB + 9 * 4096 + (8 * (mq >> 1) + r) * 128 + (((6 + (mq & 1)) ^ r) << 4);
                    uint32_t b0[4], b1[4];
                    ldsm4(b0, ha);
                    ldsm4(b1, ha + 2048);
                    #pragma unroll
                    for (int i = 0; i < 16; i++) d[i] = 0.f;
                    mma16(d + 0, wa[39][0], wa[39][1], wa[39][2], wa[39][3], b0[0], b0[1]);
                    mma16(d + 4, wa[39][0], wa[39][1], wa[39][2], wa[39][3], b0[2], b0[3]);
                    mma16(d + 8, wa[39][0], wa[39][1], wa[39][2], wa[39][3], b1[0], b1[1]);
                    mma16(d + 12, wa[39][0], wa[39][1], wa[39][2], wa[39][3], b1[2], b1[3]);
                    asm volatile("" : "+f"(d[0]), "+f"(d[4]), "+f"(d[8]), "+f"(d[12]) :: "memory");
                }
                if (s >= 0) bar_arrive(6, 512);
                mbar_wait(bar + B_HLO_FULL * 8, hp);
                bar_sync(9, 384);
                TR(6);
                wg_fence();
                #pragma unroll
                for (int kt = 0; kt < 12; kt++) wg_rs32(d, wa[kt], db0 + (uint64_t)(((kt >> 2) * 4096 + (kt & 3) * 32) >> 4), 1);
                wg_commit();
                #pragma unroll
                for (int kt = 12; kt < 39; kt++) wg_rs32(d, wa[kt], db0 + (uint64_t)(((kt >> 2) * 4096 + (kt & 3) * 32) >> 4), 1);
                wg_commit();
                wg_wait<1>();
                if (lane == 0) mbar_arrive(bar + B_HLO_FREE * 8);
                wg_wait<0>();
                if (lane == 0) mbar_arrive(bar + B_HHI_FREE * 8);
                TR(7);
                const int mi = lane >> 3, r = lane & 7;
                #pragma unroll
                for (int jj = 0; jj < 2; jj++) {
                    const int tok = 8 * (2 * jj + (mi >> 1)) + r, ch = 2 * w + (mi & 1);
                    stsm4t(dstx + tok * 128 + ((ch ^ r) << 4),
                           pack2(d[8 * jj + 0], d[8 * jj + 1]), pack2(d[8 * jj + 2], d[8 * jj + 3]),
                           pack2(d[8 * jj + 4], d[8 * jj + 5]), pack2(d[8 * jj + 6], d[8 * jj + 7]));
                }
                bar_arrive(8, 384);
                if (s < 0 && warp == 0) T3(11);
                if (s < 0) { bar_sync(0, 512); asm volatile("griddepcontrol.launch_dependents;" ::: "memory"); }
            }
        }
    } else if (wg == 2) {
        asm volatile("setmaxnreg.dec.sync.aligned.u32 64;");
        const int w = warp & 3;
        uint32_t res[4][4];
        {
            const bf16* src = Wo + ((size_t)h * DH + ((p + 1) % 3) * 64) * DM + (tile0 + warp) * 16 + 2 * t;
            #pragma unroll
            for (int kt = 0; kt < 4; kt++) {
                res[kt][0] = __ldg((const uint32_t*)(src + (size_t)(kt * 16 + g) * DM));
                res[kt][1] = __ldg((const uint32_t*)(src + (size_t)(kt * 16 + g) * DM + 8));
                res[kt][2] = __ldg((const uint32_t*)(src + (size_t)(kt * 16 + 8 + g) * DM));
                res[kt][3] = __ldg((const uint32_t*)(src + (size_t)(kt * 16 + 8 + g) * DM + 8));
            }
            #pragma unroll
            for (int kt = 0; kt < 4; kt++) {
                #pragma unroll
                for (int i = 0; i < 4; i++) res[kt][i] = movm(res[kt][i]);
            }
        }
        bar_sync(11, 256);
        if (tid == 256) {
            fence_async();
            mbar_expect(bar + B_WV * 8, 81920);
            #pragma unroll
            for (int i = 0; i < 5; i++) tma2d(sb + SM_WV + i * 16384, &maps.wv, h * DH + p * 64, i * 128, bar + B_WV * 8);
        }
        mbar_wait(bar + B_WV * 8, 0);
        if (w == 0) T3(3);
        const uint64_t da0 = make_desc(SBC + SM_WV, 16, 1024, 1);
        uint32_t vx[8], vm0 = 0, vm1 = 0;
        #pragma unroll
        for (int i = 0; i < 8; i++) vx[i] = 0;

        for (int s = -1; s < NSEG; s++) {
            FRESH(lane);
            const int g = lane >> 2, t = lane & 3, tid = warp * 32 + lane;
            if (s >= 0) {
                const uint32_t par = s & 1;
                mbar_wait(bar + B_MEM_FULL * 8, par);
                bar_sync(4, 352);
                TR(0);
                float dv[4];
                {
                    const uint64_t dbm = make_desc(SBC + SM_HB, 128, 128, 0);
                    wg_fence();
                    #pragma unroll
                    for (int kt = 0; kt < 40; kt++) {
                        wg_ss8(dv, da0 + (uint64_t)(kt * 128), dbm + (uint64_t)(kt * 16), kt > 0);
                        wg_commit();
                        if (kt < 39) wg_wait<1>();
                    }
                    wg_commit();
                }
                TR(1);
                bar_sync(5, 160);
                TR(2);
                uint32_t pb[5];
                #pragma unroll
                for (int j = 0; j < 5; j++) pb[j] = lds1(sb + SM_PM + j * 128 + lane * 4);
                float o0[4] = {0.f, 0.f, 0.f, 0.f}, o1[4] = {0.f, 0.f, 0.f, 0.f}, o2[4] = {0.f, 0.f, 0.f, 0.f};
                wg_wait<0>();
                TR(3);
                mma16(o0, vx[0], vx[1], vx[2], vx[3], pb[1], pb[2]);
                mma16(o1, vx[4], vx[5], vx[6], vx[7], pb[3], pb[4]);
                vm0 = pack2(dv[0], dv[1]); vm1 = pack2(dv[2], dv[3]);
                mma8(o2, vm0, vm1, pb[0]);
                if (s < NSEG - 1) {
                    const uint32_t q0 = pack2(o0[0] + o1[0] + o2[0], o0[1] + o1[1] + o2[1]), q1 = pack2(o0[2] + o1[2] + o2[2], o0[3] + o1[3] + o2[3]);
                    const uint32_t la = sb + SM_OS + (w * 16 + g) * 16 + t * 4;
                    #pragma unroll
                    for (int i = 1; i < 3; i++) {
                        const uint32_t rk = (p + i) % 3;
                        const uint32_t ra = mapa(la + (3 - i) * 1024, rk), rb = mapa(bar + B_O * 8, rk);
                        st_async1(ra, q0, rb);
                        st_async1(ra + 128, q1, rb);
                    }
                    sts1(la, q0);
                    sts1(la + 128, q1);
                    __syncwarp();
                    if (lane == 0) { mbar_arrive(bar + B_O1 * 8); mbar_arrive(bar + B_MEM_FREE * 8); }
                }
                TR(5);
                if (s < NSEG - 1) {
                    wo_phase<4, 4>(sb, warp, lane, res, par, (uint32_t)(s % 15) + 1u, tile0 + warp, h);
                    TR(4);
                    if (tid == 256) mbar_expect(bar + B_O * 8, 2048);
                }
                if (s < NSEG - 1) bar_sync(6, 512);
            }
            uint32_t vn[8];
            #pragma unroll
            for (int i = 0; i < 8; i++) vn[i] = 0;
            if (s < NSEG - 1) {
            float d[16];
            const uint32_t hp = (s + 1) & 1;
            const uint64_t db0 = make_desc(SBC + SM_HB, 16, 1024, 1);
            mbar_wait(bar + B_HHI_FULL * 8, hp);
            TR(6);
            wg_fence();
            #pragma unroll
            for (int kt = 12; kt < 40; kt++) wg_ss32(d, da0 + (uint64_t)(kt * 128), db0 + (uint64_t)(((kt >> 2) * 4096 + (kt & 3) * 32) >> 4), kt > 12);
            wg_commit();
            mbar_wait(bar + B_HLO_FULL * 8, hp);
            wg_fence();
            #pragma unroll
            for (int kt = 0; kt < 9; kt++) wg_ss32(d, da0 + (uint64_t)(kt * 128), db0 + (uint64_t)(((kt >> 2) * 4096 + (kt & 3) * 32) >> 4), 1);
            wg_commit();
            #pragma unroll
            for (int kt = 9; kt < 12; kt++) wg_ss32(d, da0 + (uint64_t)(kt * 128), db0 + (uint64_t)(((kt >> 2) * 4096 + (kt & 3) * 32) >> 4), 1);
            wg_commit();
            wg_wait<1>();
            bar_arrive(9, 384);
            wg_wait<0>();
            if (lane == 0) mbar_arrive(bar + B_HLO_FREE * 8);
            TR(7);
            if (lane == 0) mbar_arrive(bar + B_HHI_FREE * 8);
            #pragma unroll
            for (int i = 0; i < 8; i++) vn[i] = pack2(d[2 * i], d[2 * i + 1]);
            }
            if (s >= 0) {
                {
                    FRESH(lane);
                    mbar_wait(bar + B_XS * 8, s & 1);
                    if (w == 0 && lane == 0) mbar_expect(bar + B_XS * 8, 12288);
                    const uint32_t a = sb + SM_XS + (w >> 1) * 1536 + lane * 16 + (w & 1) * 8;
                    if (w == 0) xsoftmax<2>(a, lane >> 2, lane & 3);
                    else if (w == 1) xsoftmax<3>(a, lane >> 2, lane & 3);
                    else if (w == 2) xsoftmax<4>(a, lane >> 2, lane & 3);
                    else xsoftmax<5>(a, lane >> 2, lane & 3);
                }
                TR(8);
                bar_sync(7, 128);
                FRESH(lane);
                bf16* orow = g_ox + (size_t)(s * 32 + (lane >> 2)) * HD + h * DH + p * 64 + w * 16 + 2 * (lane & 3);
                {
                    const uint32_t pa = sb + SM_XS + lane * 16;
                    #pragma unroll
                    for (int mi = 0; mi < 2; mi++) {
                        float oa[4] = {0.f, 0.f, 0.f, 0.f}, ob[4] = {0.f, 0.f, 0.f, 0.f};
                        if (mi == 0) {
                            const uint4 p0 = lds4(pa);
                            const uint32_t p3 = lds1(pa + 1024 + 8);
                            mma8(oa, vm0, vm1, p0.x);
                            mma8(ob, vm0, vm1, p0.z);
                            mma16(oa, vx[0], vx[1], vx[2], vx[3], p0.y, 0u);
                            mma16(ob, vx[0], vx[1], vx[2], vx[3], p0.w, p3);
                        } else {
                            const uint4 p1 = lds4(pa + 1536), p2 = lds4(pa + 2560);
                            const uint32_t p4 = lds1(pa + 3584 + 8);
                            mma8(oa, vm0, vm1, p1.x);
                            mma8(ob, vm0, vm1, p1.z);
                            mma16(oa, vx[0], vx[1], vx[2], vx[3], p1.y, p2.x);
                            mma16(ob, vx[0], vx[1], vx[2], vx[3], p1.w, p2.z);
                            mma16(oa, vx[4], vx[5], vx[6], vx[7], p2.y, 0u);
                            mma16(ob, vx[4], vx[5], vx[6], vx[7], p2.w, p4);
                            if (lane < 3) mbar_arrive_remote(mapa(bar + B_XSFREE * 8, lane));
                        }
                        const uint32_t u0 = movm(pack2(oa[0], oa[1])), u1 = movm(pack2(oa[2], oa[3]));
                        const uint32_t u2 = movm(pack2(ob[0], ob[1])), u3 = movm(pack2(ob[2], ob[3]));
                        bf16* dst = orow + (size_t)(16 * mi) * HD;
                        *(uint32_t*)dst = u0;
                        *(uint32_t*)(dst + 8) = u1;
                        *(uint32_t*)(dst + 8 * HD) = u2;
                        *(uint32_t*)(dst + 8 * HD + 8) = u3;
                    }
                }
                TR(9);
                if (s == NSEG - 1) {
                    bar_sync(7, 128);
                    if (w == 3 && lane == 0) { signal_cnt(C_REC + 15); T2(400 + b); }
                    break;
                }
            }
            #pragma unroll
            for (int i = 0; i < 8; i++) vx[i] = vn[i];
            if (s >= 0) mbar_wait_cluster(bar + B_XSFREE * 8, s & 1);
            bar_sync(8, 384);
            TR(10);
            if (w < 3) xscores<2>(sb, p, w > 0, w == 2 ? 3 : 1, lane);
            else if ((s & 3) == 3 && s >= 0 && lane == 0) signal_cnt(C_REC + (s >> 2));
            __syncwarp();
            TR(11);
            if (s < 0) { bar_sync(0, 512); asm volatile("griddepcontrol.launch_dependents;" ::: "memory"); }
        }
    } else {
        asm volatile("setmaxnreg.dec.sync.aligned.u32 48;");
        const int w = warp & 3, lt = tid & 127;
        const uint32_t epoch = *(volatile uint32_t*)&g_epoch + 1u;
        if (b == 91) { if (lt < C_NUM) g_cnt[lt * 32] = 0u; __threadfence(); }
        if (b < 80) {
            #pragma unroll
            for (int i = 0; i < 2; i++) {
                const int idx = lt + i * 128, sl = idx >> 6, pg = (idx >> 5) & 1, wd = idx & 31;
                st_relaxed1(g_buf2 + (sl * 3 + (b >> 5)) * 2048 + pg * 1024 + (b & 31) * 32 + wd, 0xFFFFFFFFu);
            }
            __threadfence();
        }
        if (lane == 0 && w < 3) {
            int c = 0;
            if (w == 0) c = probe_blk(g_buf2 + 640 + (b & 31) * 8);
            else if (b < 80) c = probe_blk(g_buf1 + (b * 2 + (w - 1)) * 2048);
            else if (b < 92 && w == 1) c = probe_blk(g_buf2 + (b - 80) * 2048 + 960);
            asm volatile("st.shared.u8 [%0], %1;" :: "r"(sb + SM_CH + 96 + w), "r"(c) : "memory");
        }
        if (w == 0) T3(4);
        bar_sync(3, 128);
        uint32_t selmask;
        {
            const uint32_t c3 = lds1(sb + SM_CH + 96);
            const uint32_t cr = c3 & 1u, c1 = (c3 >> 8) & 1u, c2 = (c3 >> 16) & 1u;
            if (lt == 0 && b < 92) st_release1(&g_choice[b], (epoch << 2) | (b < 80 ? (c1 | (c2 << 1)) : (c1 ^ cr)));
            bar_sync(10, 256);
            if (w == 3) {
                if (lane == 0) { fence_async(); mbar_expect(bar + B_WO * 8, ntile * 6144 - 8192); }
                __syncwarp();
                if (lane < ntile) {
                    #pragma unroll
                    for (int e3 = 0; e3 < 3; e3++) {
                        const bool part = lane >= 8 && lane < 12;
                        if (part && e3 == 1) continue;
                        tma2d(sb + SM_WO + wo_tile_off(lane) + ((part && e3 == 2) ? 1 : e3) * 2048, &maps.wo,
                              (tile0 + lane) * 16, h * DH + ((e3 + p) % 3) * 64, bar + B_WO * 8);
                    }
                }
                __syncwarp();
            }
            if (w == 0) T3(5);
            if (lt < 92) {
                uint32_t v, guard = 0;
                while (true) {
                    v = ld_acquire1(&g_choice[lt]);
                    if ((v >> 2) == (epoch & 0x3fffffffu)) break;
                    __nanosleep(100);
                    if (++guard > (1u << 22)) __trap();
                }
                asm volatile("st.shared.u8 [%0], %1;" :: "r"(sb + SM_CH + lt), "r"(v & 3u) : "memory");
            }
            if (w == 0) T3(6);
            bar_sync(3, 128);
            selmask = (c1 << 12) | (c2 << 13);
            for (int i = 0; i < 12; i++) {
                uint32_t c; asm volatile("ld.shared.u8 %0, [%1];" : "=r"(c) : "r"(sb + SM_CH + 80 + i) : "memory");
                selmask |= ((c ^ cr) & 1u) << i;
            }
        }
        mbar_wait(bar + B_WO * 8, 0);
        if (w == 0) T3(8);
        bar_sync(0, 512);
        if (w == 0) T3(9);
        asm volatile("griddepcontrol.launch_dependents;" ::: "memory");
        const bool has_tile = (12 + w) < ntile;
        for (int s = 0; s < NSEG; s++) {
            const uint32_t par = s & 1;
            FRESH(lane);
            const int g = lane >> 2, t = lane & 3, lt = w * 32 + lane;
            if (s == 0) {
                mbar_wait(bar + B_HLO_FREE * 8, par);
                for (int k = lt; k < DM; k += 128) {
                    uint32_t v[4];
                    #pragma unroll
                    for (int i = 0; i < 4; i++) {
                        uint32_t lo = *(const uint16_t*)(mem0 + (2 * i) * DM + k), hi = *(const uint16_t*)(mem0 + (2 * i + 1) * DM + k);
                        v[i] = lo | (hi << 16);
                    }
                    asm volatile("st.shared.v4.u32 [%0], {%1,%2,%3,%4};" :: "r"(sb + SM_HB + k * 16), "r"(v[0]), "r"(v[1]), "r"(v[2]), "r"(v[3]) : "memory");
                }
            } else {
                const int sl = s & 3;
                const char* q = (const char*)g_buf2 + sl * 3 * 8192 + lt * 16;
                const uint32_t sm = selmask >> (sl * 3);
                const char* q0 = q + (sm & 1) * 4096;
                const char* q1 = q + 8192 + (sm & 2) * 2048;
                const char* q2 = q + 16384 + (sm & 4) * 1024;
                const uint32_t dst = sb + SM_HB + lt * 16;
                uint32_t guard = 0;
                mbar_wait(bar + B_HLO_FREE * 8, par);
                TR(10);
                while (true) {
                    const uint4 v0 = ld_relaxed4(q0), v1 = ld_relaxed4(q0 + 2048), v2 = ld_relaxed4(q1), v3 = ld_relaxed4(q1 + 2048), v4 = ld_relaxed4(q2);
                    sts4(dst, v0); sts4(dst + 2048, v1); sts4(dst + 4096, v2); sts4(dst + 6144, v3); sts4(dst + 8192, v4);
                    if (__all_sync(0xffffffffu, oks(v0) && oks(v1) && oks(v2) && oks(v3) && oks(v4))) break;
                    if (++guard > (1u << 22)) __trap();
                }
            }
            fence_async();
            __syncwarp();
            if (lane == 0) mbar_arrive(bar + B_MEM_FULL * 8);
            if (b == 0 && lt == 0) T2(300 + s);
            if (s == 0 && lt == 0) T2(200 + b);
            TR(0);
            if (w == 2) {
                mbar_wait(bar + B_MS * 8, par);
                TR(1);
                if (lane == 0) mbar_expect(bar + B_MS * 8, 3840);
                uint32_t pb[5];
                float sc[5][2];
                {
                    const uint32_t a = sb + SM_MS + lane * 8;
                    float2 u[5], v[5];
                    #pragma unroll
                    for (int j = 0; j < 5; j++) { u[j] = lds2f(a + j * 256); v[j] = lds2f(a + j * 256 + 1280); }
                    #pragma unroll
                    for (int j = 0; j < 5; j++) { sc[j][0] = u[j].x + v[j].x; sc[j][1] = u[j].y + v[j].y; }
                    #pragma unroll
                    for (int j = 0; j < 5; j++) u[j] = lds2f(a + j * 256 + 2560);
                    #pragma unroll
                    for (int j = 0; j < 5; j++) { sc[j][0] += u[j].x; sc[j][1] += u[j].y; }
                }
                softmax_core<5, false>(sc, g, t, pb);
                #pragma unroll
                for (int j = 0; j < 5; j++) sts1(sb + SM_PM + j * 128 + lane * 4, pb[j]);
                bar_arrive(5, 160);
                TR(2);
            }
            const uint32_t tag = (uint32_t)(s % 15) + 1u;
            if (s < NSEG - 1) {
                if (w == 3) {
                    const char* src = (const char*)g_ht + (size_t)(s + 1) * 40960;
                    if (s == 0) {
                        uint32_t guard = 0;
                        while (true) {
                            const uint32_t f0 = lane > 0 ? ld_acquire1(&g_hflag[lane]) : epoch, f1 = ld_acquire1(&g_hflag[32 + lane]);
                            if (__all_sync(0xffffffffu, f0 == epoch && f1 == epoch)) break;
                            if (++guard > (1u << 22)) __trap();
                        }
                        asm volatile("fence.proxy.async.global;" ::: "memory");
                    }
                    mbar_wait(bar + B_HHI_FREE * 8, par);
                    if (lane == 0) {
                        mbar_expect(bar + B_HHI_FULL * 8, 28672);
                        bulk_g2s(sb + SM_HB + 12288, src + 12288, 28672, sb + SM_BAR + B_HHI_FULL * 8);
                    }
                    mbar_wait(bar + B_MEM_FREE * 8, par);
                    if (lane == 0) {
                        mbar_expect(bar + B_HLO_FULL * 8, 12288);
                        bulk_g2s(sb + SM_HB, src, 12288, sb + SM_BAR + B_HLO_FULL * 8);
                    }
                    __syncwarp();
                }
                if (has_tile) wo_phase<0, 4>(sb, warp, lane, nullptr, par, tag, tile0 + warp, h);
                TR(4);
                bar_sync(6, 512);
            }
            if (s < NSEG - 1) {
                { const uint32_t c0 = clk32(); while (clk32() - c0 < H1_DELAY); }
                if (b < 80) {
                    FRESH(lane);
                    const char* rin0 = (const char*)g_buf1 + (size_t)(b * 2) * 8192 + ((selmask >> 12) & 1) * 4096 + (lane >> 2) * 256 + w * 64 + (lane & 3) * 16;
                    const char* rin1 = (const char*)g_buf1 + (size_t)(b * 2 + 1) * 8192 + ((selmask >> 13) & 1) * 4096 + (lane >> 2) * 256 + w * 64 + (lane & 3) * 16;
                    const int col = b * 8 + 2 * w + ((lane >> 1) & 1), wd = 2 * (lane & 1) + (lane >> 4);
                    const int sl = (lane & 8) ? ((s + 3) & 3) : ((s + 1) & 3);
                    uint32_t* dst = g_buf2 + (sl * 3 + (col >> 8)) * 2048 + ((lane >> 2) & 1) * 1024 + (col & 255) * 4 + wd;
                    asm volatile("" : "+l"(dst));
                    uint4 v0, v1, v2, v3;
                    uint32_t guard = 0;
                    while (true) {
                        v0 = ld_relaxed4(rin0); v1 = ld_relaxed4(rin0 + 2048);
                        v2 = ld_relaxed4(rin1); v3 = ld_relaxed4(rin1 + 2048);
                        if (__all_sync(0xffffffffu, ok4(v0, tag) && ok4(v1, tag) && ok4(v2, tag) && ok4(v3, tag))) break;
                        if (++guard > (1u << 22)) __trap();
                    }
                    TR(11);
                    const float a0 = (uf(v0.x) + uf(v1.x)) + (uf(v2.x) + uf(v3.x)), a1 = (uf(v0.y) + uf(v1.y)) + (uf(v2.y) + uf(v3.y));
                    const float a2 = (uf(v0.z) + uf(v1.z)) + (uf(v2.z) + uf(v3.z)), a3 = (uf(v0.w) + uf(v1.w)) + (uf(v2.w) + uf(v3.w));
                    const bool u16 = lane & 16;
                    float m0 = (u16 ? a2 : a0) + __shfl_xor_sync(0xffffffffu, u16 ? a0 : a2, 16);
                    float m1 = (u16 ? a3 : a1) + __shfl_xor_sync(0xffffffffu, u16 ? a1 : a3, 16);
                    m0 += __shfl_xor_sync(0xffffffffu, m0, 8); m1 += __shfl_xor_sync(0xffffffffu, m1, 8);
                    m0 += __shfl_xor_sync(0xffffffffu, m0, 4); m1 += __shfl_xor_sync(0xffffffffu, m1, 4);
                    st_relaxed1(dst, (lane & 8) ? 0xFFFFFFFFu : pack2(m0, m1));
                    TR(12);
                }
            }
        }
    }
    cluster_sync();
}

constexpr int G_STAGES = 6;
constexpr int G_STAGE_BYTES = 32768;
constexpr int G_SMEM = G_STAGES * G_STAGE_BYTES + 1024 + 256 + 2048 + 10240;

__device__ __forceinline__ void wg_ss128(float* d, uint64_t da, uint64_t db, int sc) {
    asm volatile("{\n\t.reg .pred p;\n\tsetp.ne.b32 p, %66, 0;\n\t"
        "wgmma.mma_async.sync.aligned.m64n128k16.f32.bf16.bf16 "
        "{%0,%1,%2,%3,%4,%5,%6,%7,%8,%9,%10,%11,%12,%13,%14,%15,%16,%17,%18,%19,%20,%21,%22,%23,%24,%25,%26,%27,%28,%29,%30,%31,"
        "%32,%33,%34,%35,%36,%37,%38,%39,%40,%41,%42,%43,%44,%45,%46,%47,%48,%49,%50,%51,%52,%53,%54,%55,%56,%57,%58,%59,%60,%61,%62,%63}, "
        "%64, %65, p, 1, 1, 0, 1;\n\t}"
        : "+f"(d[0]), "+f"(d[1]), "+f"(d[2]), "+f"(d[3]), "+f"(d[4]), "+f"(d[5]), "+f"(d[6]), "+f"(d[7]),
          "+f"(d[8]), "+f"(d[9]), "+f"(d[10]), "+f"(d[11]), "+f"(d[12]), "+f"(d[13]), "+f"(d[14]), "+f"(d[15]),
          "+f"(d[16]), "+f"(d[17]), "+f"(d[18]), "+f"(d[19]), "+f"(d[20]), "+f"(d[21]), "+f"(d[22]), "+f"(d[23]),
          "+f"(d[24]), "+f"(d[25]), "+f"(d[26]), "+f"(d[27]), "+f"(d[28]), "+f"(d[29]), "+f"(d[30]), "+f"(d[31]),
          "+f"(d[32]), "+f"(d[33]), "+f"(d[34]), "+f"(d[35]), "+f"(d[36]), "+f"(d[37]), "+f"(d[38]), "+f"(d[39]),
          "+f"(d[40]), "+f"(d[41]), "+f"(d[42]), "+f"(d[43]), "+f"(d[44]), "+f"(d[45]), "+f"(d[46]), "+f"(d[47]),
          "+f"(d[48]), "+f"(d[49]), "+f"(d[50]), "+f"(d[51]), "+f"(d[52]), "+f"(d[53]), "+f"(d[54]), "+f"(d[55]),
          "+f"(d[56]), "+f"(d[57]), "+f"(d[58]), "+f"(d[59]), "+f"(d[60]), "+f"(d[61]), "+f"(d[62]), "+f"(d[63])
        : "l"(da), "l"(db), "r"(sc));
}

#define SP0_LAST 12
#define SP2_LAST 6
enum { J_MOD = 0, J_G0, J_LN, J_G1, J_G2, J_FIN, J_END };
__host__ __device__ constexpr int sp0(int b) { return b >= 15 ? SP0_LAST : 3; }
__host__ __device__ constexpr int sp2(int b) { return b >= 15 ? SP2_LAST : 3; }
__host__ __device__ constexpr int njr(int b) { return b >= 15 ? 16 : 8; }
struct JobTab { uint32_t n; uint32_t j[1200]; };
constexpr uint32_t mkjob(int ty, int b, int n, int k0, int nk, int ks) {
    return (uint32_t)(ty | (b << 3) | (n << 7) | (k0 << 11) | (nk << 18) | (ks << 25));
}
constexpr void add_jobs(JobTab& t, int ty, int b) {
    if (b < 0) return;
    if (ty == J_G0) { for (int ks = 0; ks < sp0(b); ks++) for (int n = 0; n < 5; n++) t.j[t.n++] = mkjob(ty, b, n, ks * (96 / sp0(b)), 96 / sp0(b), ks); }
    else if (ty == J_G2) { for (int ks = 0; ks < sp2(b); ks++) for (int n = 0; n < 5; n++) t.j[t.n++] = mkjob(ty, b, n, ks * (24 / sp2(b)), 24 / sp2(b), ks); }
    else if (ty == J_G1) { for (int n = 0; n < 12; n++) t.j[t.n++] = mkjob(ty, b, n, 0, 10, 0); }
    else { for (int n = 0; n < njr(b); n++) t.j[t.n++] = mkjob(ty, b, n, 0, 16 / njr(b), ty == J_LN ? sp0(b) : sp2(b)); }
}
constexpr JobTab make_tab() {
    JobTab t = {};
    for (int i = 20; i < 60; i++) t.j[t.n++] = mkjob(J_MOD, 0, 0, i, 0, 0);
    for (int b = 0; b < 15; b++) {
        add_jobs(t, J_G0, b); add_jobs(t, J_G1, b - 1); add_jobs(t, J_FIN, b - 2); add_jobs(t, J_G2, b - 1); add_jobs(t, J_LN, b);
    }
    add_jobs(t, J_FIN, 13); add_jobs(t, J_G1, 14);
    add_jobs(t, J_G0, 15); add_jobs(t, J_G2, 14); add_jobs(t, J_LN, 15); add_jobs(t, J_FIN, 14);
    add_jobs(t, J_G1, 15); add_jobs(t, J_G2, 15); add_jobs(t, J_FIN, 15);
    return t;
}
__constant__ JobTab c_jobs = make_tab();

__device__ __forceinline__ bool cnt_ge(int idx, uint32_t target) { return ld_acquire1(g_cnt + idx * 32) >= target; }
__device__ __forceinline__ void cnt_wait(int idx, uint32_t target) {
    uint32_t guard = 0;
    while (!cnt_ge(idx, target)) { __nanosleep(64); if (++guard > (1u << 22)) __trap(); }
}

struct SMaps { CUtensorMap ox, wo, h2, w1, act, w2; };

__global__ void __launch_bounds__(384, 1)
k_side(const __grid_constant__ SMaps maps, const bf16* __restrict__ xin, const bf16* __restrict__ cvec,
       const bf16* __restrict__ wmod, bf16* __restrict__ outp) {
    extern __shared__ uint8_t smem_raw[];
    const uint32_t sb = (smem_u32(smem_raw) + 1023u) & ~1023u;
    const uint32_t bars = sb + G_STAGES * G_STAGE_BYTES;
    float* red = (float*)(smem_raw + (bars + 256 - smem_u32(smem_raw)));
    const int tid = threadIdx.x, lane = tid & 31, wg = tid >> 7;
    if (tid == 0) T2(500 + blockIdx.x);
    if (tid == 0) {
        for (int i = 0; i < G_STAGES; i++) { mbar_init(bars + i * 8, 1); mbar_init(bars + 64 + i * 8, 8); }
        for (int i = 0; i < 2; i++) { mbar_init(bars + 128 + i * 8, 1); mbar_init(bars + 144 + i * 8, 8); }
        asm volatile("fence.mbarrier_init.release.cluster;" ::: "memory");
    }
    __syncthreads();
    if (wg == 0) {
        if (tid == 0) {
            uint32_t st = 0, ph = 1;
            for (uint32_t it = 0;; it++) {
                const uint32_t ji = atomicAdd(g_cnt + C_Q * 32, 1u);
                const uint32_t job = ji < c_jobs.n ? c_jobs.j[ji] : (uint32_t)J_END;
                if (ji == 0) g_epoch = g_epoch + 1u;
                const int ty = job & 7, b = (job >> 3) & 15, n = (job >> 7) & 15, k0 = (job >> 11) & 127, nk = (job >> 18) & 127;
                const uint32_t sl = it & 1;
                mbar_wait(bars + 144 + sl * 8, ((it >> 1) & 1) ^ 1);
                sts1(bars + 160 + sl * 4, job);
                if (ty == J_G0 || ty == J_G1 || ty == J_G2) {
                    if (b >= PRING && ty != J_G1) cnt_wait((ty == J_G0 ? C_LN : C_FIN) + b - PRING, njr(b - PRING));
                    mbar_arrive(bars + 128 + sl * 8);
                    const CUtensorMap* mA = ty == J_G0 ? &maps.ox : (ty == J_G1 ? &maps.h2 : &maps.act);
                    const CUtensorMap* mB = ty == J_G0 ? &maps.wo : (ty == J_G1 ? &maps.w1 : &maps.w2);
                    const int didx = ty == J_G0 ? C_REC + b : (ty == J_G1 ? C_LN + b : C_G1 + b);
                    const uint32_t dtgt = ty == J_G0 ? 96u : (ty == J_G1 ? (uint32_t)njr(b) : 12u);
                    int pre = 0;
                    if (!cnt_ge(didx, dtgt)) {
                        pre = nk < G_STAGES ? nk : G_STAGES;
                        uint32_t s2 = st, p2 = ph;
                        for (int i = 0; i < pre; i++) {
                            mbar_wait(bars + 64 + s2 * 8, p2);
                            const uint32_t a = sb + s2 * G_STAGE_BYTES;
                            mbar_expect(bars + s2 * 8, G_STAGE_BYTES);
                            tma2d(a + 16384, mB, n * 128, (k0 + i) * 64, bars + s2 * 8);
                            tma2d(a + 16384 + 8192, mB, n * 128 + 64, (k0 + i) * 64, bars + s2 * 8);
                            if (++s2 == G_STAGES) { s2 = 0; p2 ^= 1; }
                        }
                        cnt_wait(didx, dtgt);
                    }
                    asm volatile("fence.proxy.async.global;" ::: "memory");
                    T2(1024 + ji * 4 + 1);
                    for (int i = 0; i < nk; i++) {
                        const uint32_t a = sb + st * G_STAGE_BYTES;
                        if (i >= pre) {
                            mbar_wait(bars + 64 + st * 8, ph);
                            mbar_expect(bars + st * 8, G_STAGE_BYTES);
                        }
                        tma2d(a, mA, (k0 + i) * 64, b * 128, bars + st * 8);
                        if (i >= pre) {
                            tma2d(a + 16384, mB, n * 128, (k0 + i) * 64, bars + st * 8);
                            tma2d(a + 16384 + 8192, mB, n * 128 + 64, (k0 + i) * 64, bars + st * 8);
                        }
                        if (++st == G_STAGES) { st = 0; ph ^= 1; }
                    }
                } else {
                    if (ty == J_LN) { bulk_pf(xin + (size_t)(b * 128 + n * nk * 8) * DM, nk * 8 * DM * 2); cnt_wait(C_MOD, 40u); cnt_wait(C_G0 + b, 5u * sp0(b)); }
                    else if (ty == J_FIN) cnt_wait(C_G2 + b, 5u * sp2(b));
                    if (ji < 1200) T2(1024 + ji * 4 + 1);
                    mbar_arrive(bars + 128 + sl * 8);
                    if (ty == J_END) break;
                }
            }
        }
    } else {
        const int cw = wg - 1, ct = tid - 128, cwarp = ct >> 5;
        uint32_t st = 0, ph = 0;
        float* smod = red + 512;
        bool have_mod = false;
        auto load_mod = [&]() {
            for (int i = ct; i < DM; i += 256) *(float4*)(smod + i * 4) = __ldcg((const float4*)(g_mod + 2 * DM + i * 4));
            bar_sync(1, 256);
            have_mod = true;
        };
        {
            if (ct == 0) red[0] = cnt_ge(C_MOD, 40u) ? 1.0f : 0.0f;
            bar_sync(1, 256);
            const bool rdy = red[0] != 0.0f;
            bar_sync(1, 256);
            if (rdy) load_mod();
        }
        for (uint32_t it = 0;; it++) {
            const uint32_t sl = it & 1;
            mbar_wait(bars + 128 + sl * 8, (it >> 1) & 1);
            const uint32_t job = lds1(bars + 160 + sl * 4);
            __syncwarp();
            if (lane == 0) mbar_arrive(bars + 144 + sl * 8);
            const int ty = job & 7, b = (job >> 3) & 15, n = (job >> 7) & 15, k0 = (job >> 11) & 127, nk = (job >> 18) & 127, ks = (job >> 25) & 15;
            if (ty == J_END) break;
            int sig = -1;
            if (ty == J_G0 || ty == J_G1 || ty == J_G2) {
                float d[64];
                #pragma unroll
                for (int i = 0; i < 64; i++) d[i] = 0.f;
                uint32_t pst = 0;
                for (int kb = 0; kb < nk; kb++) {
                    mbar_wait(bars + st * 8, ph);
                    const uint32_t a = sb + st * G_STAGE_BYTES;
                    const uint64_t da = make_desc(a + cw * 8192, 16, 1024, 1);
                    const uint64_t db = make_desc(a + 16384, 8192, 1024, 1);
                    wg_fence();
                    #pragma unroll
                    for (int k = 0; k < 4; k++) wg_ss128(d, da + (uint64_t)(k * 2), db + (uint64_t)(k * 128), 1);
                    wg_commit();
                    if (kb > 0) {
                        wg_wait<1>();
                        if (lane == 0) mbar_arrive(bars + 64 + pst * 8);
                    }
                    pst = st;
                    if (++st == G_STAGES) { st = 0; ph ^= 1; }
                }
                wg_wait<0>();
                if (lane == 0) mbar_arrive(bars + 64 + pst * 8);
                const int g = lane >> 2, t = lane & 3;
                if (ty == J_G1) {
                    #pragma unroll
                    for (int hf = 0; hf < 2; hf++) {
                        bf16* o = g_act + (size_t)(b * 128 + cwarp * 16 + g + 8 * hf) * FF + n * 128 + 8 * t;
                        #pragma unroll
                        for (int q = 0; q < 4; q++) {
                            uint32_t u[4];
                            #pragma unroll
                            for (int i = 0; i < 4; i++) {
                                const float a0 = bfr(d[4 * (4 * q + i) + 2 * hf]), a1 = bfr(d[4 * (4 * q + i) + 2 * hf + 1]);
                                u[i] = pack2(__fdividef(a0, 1.0f + __expf(-a0)), __fdividef(a1, 1.0f + __expf(-a1)));
                            }
                            const bool o1 = t & 1, o2 = t & 2;
                            uint32_t x0 = __shfl_xor_sync(0xffffffffu, o1 ? u[0] : u[1], 1), x1 = __shfl_xor_sync(0xffffffffu, o1 ? u[2] : u[3], 1);
                            if (o1) { u[0] = x0; u[2] = x1; } else { u[1] = x0; u[3] = x1; }
                            x0 = __shfl_xor_sync(0xffffffffu, o2 ? u[0] : u[2], 2); x1 = __shfl_xor_sync(0xffffffffu, o2 ? u[1] : u[3], 2);
                            if (o2) { u[0] = x0; u[1] = x1; } else { u[2] = x0; u[3] = x1; }
                            *(uint4*)(o + q * 32) = make_uint4(u[0], u[1], u[2], u[3]);
                        }
                    }
                    sig = C_G1 + b;
                } else {
                    float* o = (ty == J_G0 ? g_p0 : g_p2) + ((size_t)((b % PRING) * PMAX + ks) * 128 + cwarp * 16 + g) * DM + n * 128 + 2 * t;
                    #pragma unroll
                    for (int hf = 0; hf < 2; hf++) {
                        #pragma unroll
                        for (int j = 0; j < 16; j++)
                            *(float2*)(o + hf * 8 * DM + j * 8) = make_float2(d[4 * j + 2 * hf], d[4 * j + 2 * hf + 1]);
                    }
                    sig = (ty == J_G0 ? C_G0 : C_G2) + b;
                }
            } else if (ty == J_MOD) {
                mod_chunk<256, 2>(cvec, wmod, k0 * 64, ct, red);
                sig = C_MOD;
            } else {
                const bool ln = ty == J_LN;
                if (!have_mod) load_mod();
                const float* gm = smod + (ln ? 0 : 3) * DM + lane * 4;
                for (int r = 0; r < nk; r++) {
                    const int lr = (n * nk + r) * 8 + cwarp, row = b * 128 + lr;
                    const float* pp = (ln ? g_p0 : g_p2) + ((size_t)((b % PRING) * PMAX) * 128 + lr) * DM + lane * 4;
                    const bf16* xs = (ln ? xin : (const bf16*)g_x1) + (size_t)row * DM + lane * 4;
                    float v[5][4];
                    uint2 xv[5];
                    #pragma unroll
                    for (int i = 0; i < 5; i++) {
                        xv[i] = __ldcg((const uint2*)(xs + i * 128));
                        v[i][0] = 0.f; v[i][1] = 0.f; v[i][2] = 0.f; v[i][3] = 0.f;
                    }
                    if (ks == 3) {
                        float4 a[3][5];
                        #pragma unroll
                        for (int q = 0; q < 3; q++) {
                            #pragma unroll
                            for (int i = 0; i < 5; i++) a[q][i] = __ldcg((const float4*)(pp + (size_t)q * 128 * DM + i * 128));
                        }
                        #pragma unroll
                        for (int q = 0; q < 3; q++) {
                            #pragma unroll
                            for (int i = 0; i < 5; i++) { v[i][0] += a[q][i].x; v[i][1] += a[q][i].y; v[i][2] += a[q][i].z; v[i][3] += a[q][i].w; }
                        }
                    } else {
                        for (int q0 = 0; q0 < ks; q0 += 6) {
                            float4 a[6][5];
                            #pragma unroll
                            for (int q = 0; q < 6; q++) {
                                #pragma unroll
                                for (int i = 0; i < 5; i++) a[q][i] = __ldcg((const float4*)(pp + (size_t)(q0 + q) * 128 * DM + i * 128));
                            }
                            #pragma unroll
                            for (int q = 0; q < 6; q++) {
                                #pragma unroll
                                for (int i = 0; i < 5; i++) { v[i][0] += a[q][i].x; v[i][1] += a[q][i].y; v[i][2] += a[q][i].z; v[i][3] += a[q][i].w; }
                            }
                        }
                    }
                    bf16* dst = (ln ? (bf16*)g_x1 : outp) + (size_t)row * DM + lane * 4;
                    #pragma unroll
                    for (int i = 0; i < 5; i++) {
                        const float4 gg = *(const float4*)(gm + i * 128);
                        const uint32_t o0 = pack2(bflo(xv[i].x) + bfr(gg.x * bfr(v[i][0])), bfhi(xv[i].x) + bfr(gg.y * bfr(v[i][1])));
                        const uint32_t o1 = pack2(bflo(xv[i].y) + bfr(gg.z * bfr(v[i][2])), bfhi(xv[i].y) + bfr(gg.w * bfr(v[i][3])));
                        *(uint2*)(dst + i * 128) = make_uint2(o0, o1);
                        v[i][0] = bflo(o0); v[i][1] = bfhi(o0); v[i][2] = bflo(o1); v[i][3] = bfhi(o1);
                    }
                    if (ln) {
                        float mb, sd;
                        ln_stats(v, mb, sd);
                        #pragma unroll
                        for (int i = 0; i < 5; i++) {
                            const float4 sh = *(const float4*)(gm + DM + i * 128), sc = *(const float4*)(gm + 2 * DM + i * 128);
                            *(uint2*)(g_h2 + (size_t)row * DM + lane * 4 + i * 128) = ln_apply(v[i], mb, sd, sc, sh);
                        }
                    }
                }
                if (ln) sig = C_LN + b; else if (b < 16 - PRING) sig = C_FIN + b;
            }
            if (sig >= 0) {
                bar_sync(1, 256);
                if (ct == 0) signal_cnt(sig);
            }
            if (ct == 0) T2(1024 + ji * 4 + 2);
        }
    }
}

typedef CUresult (*EncodeFn)(CUtensorMap*, CUtensorMapDataType, cuuint32_t, void*, const cuuint64_t*, const cuuint64_t*,
                             const cuuint32_t*, const cuuint32_t*, CUtensorMapInterleave, CUtensorMapSwizzle,
                             CUtensorMapL2promotion, CUtensorMapFloatOOBfill);

static void make_map(EncodeFn fn, CUtensorMap* m, const void* ptr, uint64_t inner, uint64_t outer, uint32_t bi, uint32_t bo,
                     CUtensorMapSwizzle sw = CU_TENSOR_MAP_SWIZZLE_128B) {
    cuuint64_t dims[2] = {inner, outer};
    cuuint64_t strides[1] = {inner * 2};
    cuuint32_t box[2] = {bi, bo};
    cuuint32_t es[2] = {1, 1};
    fn(m, CU_TENSOR_MAP_DATA_TYPE_BFLOAT16, 2, (void*)ptr, dims, strides, box, es, CU_TENSOR_MAP_INTERLEAVE_NONE,
       sw, CU_TENSOR_MAP_L2_PROMOTION_L2_256B, CU_TENSOR_MAP_FLOAT_OOB_FILL_NONE);
}

extern "C" void kernel_launch(void* const* d_in, const int* in_sizes, int n_in, void* d_out, int out_size) {
    const bf16* x = (const bf16*)d_in[0];
    const bf16* mem0 = (const bf16*)d_in[1];
    const bf16* Wq = (const bf16*)d_in[2];
    const bf16* Wk = (const bf16*)d_in[3];
    const bf16* Wv = (const bf16*)d_in[4];
    const bf16* Wo = (const bf16*)d_in[5];
    const bf16* w1 = (const bf16*)d_in[8];
    const bf16* w2 = (const bf16*)d_in[9];
    const bf16* c = (const bf16*)d_in[10];
    const bf16* wmod = (const bf16*)d_in[11];
    bf16* out = (bf16*)d_out;

    static EncodeFn enc = nullptr;
    static void *p_ox, *p_x1, *p_h2, *p_act;
    if (!enc) {
        cudaDriverEntryPointQueryResult qr;
        void* f = nullptr;
        cudaGetDriverEntryPoint("cuTensorMapEncodeTiled", &f, cudaEnableDefault, &qr);
        enc = (EncodeFn)f;
        cudaGetSymbolAddress(&p_ox, g_ox);
        cudaGetSymbolAddress(&p_x1, g_x1);
        cudaGetSymbolAddress(&p_h2, g_h2);
        cudaGetSymbolAddress(&p_act, g_act);
        cudaFuncSetAttribute(k_rec, cudaFuncAttributeMaxDynamicSharedMemorySize, SM_TOTAL);
        cudaFuncSetAttribute(k_side, cudaFuncAttributeMaxDynamicSharedMemorySize, G_SMEM);
    }
    RMaps rm;
    make_map(enc, &rm.wq, Wq, HD, DM, 64, 128);
    make_map(enc, &rm.wk, Wk, HD, DM, 64, 128);
    make_map(enc, &rm.wv, Wv, HD, DM, 64, 128);
    make_map(enc, &rm.wo, Wo, DM, HD, 16, 64, CU_TENSOR_MAP_SWIZZLE_32B);
    SMaps m;
    make_map(enc, &m.ox, p_ox, HD, SEQ, 64, 128);
    make_map(enc, &m.wo, Wo, DM, HD, 64, 64);
    make_map(enc, &m.h2, p_h2, DM, SEQ, 64, 128);
    make_map(enc, &m.w1, w1, FF, DM, 64, 64);
    make_map(enc, &m.act, p_act, FF, SEQ, 64, 128);
    make_map(enc, &m.w2, w2, DM, FF, 64, 64);

    cudaStream_t st = cudaStreamPerThread;
    {
        cudaLaunchConfig_t cfg = {};
        cfg.gridDim = dim3(96); cfg.blockDim = dim3(512); cfg.dynamicSmemBytes = SM_TOTAL; cfg.stream = st;
        cudaLaunchAttribute at[2];
        at[0].id = cudaLaunchAttributeClusterDimension;
        at[0].val.clusterDim.x = 3; at[0].val.clusterDim.y = 1; at[0].val.clusterDim.z = 1;
        cfg.attrs = at; cfg.numAttrs = 1;
        cudaLaunchKernelEx(&cfg, k_rec, rm, mem0, Wo, x, c, wmod);
    }
    {
        cudaLaunchConfig_t cfg = {};
        cfg.gridDim = dim3(SIDE_CTAS); cfg.blockDim = dim3(384); cfg.dynamicSmemBytes = G_SMEM; cfg.stream = st;
        cudaLaunchAttribute at[1];
        at[0].id = cudaLaunchAttributeProgrammaticStreamSerialization;
        at[0].val.programmaticStreamSerializationAllowed = 1;
        cfg.attrs = at; cfg.numAttrs = 1;
        cudaLaunchKernelEx(&cfg, k_side, m, x, c, wmod, out);
    }
}
```

```cpp
#include <cuda_runtime.h>
#include <cuda_bf16.h>
#include <cuda.h>
#include <stdint.h>

typedef __nv_bfloat16 bf16;
#define VX_THROTTLE 1
#define H1_DELAY 400
#define H1_BACK 0
#define VM_THROTTLE 1
#define PRE_TRIG 0
#define TMA_DELAY 300
#define PF_DELAY 1500
#define SIDE_CTAS 132

constexpr int SEQ = 2048, DM = 640, NH = 32, DH = 192, NSEG = 64, FF = 1536, HD = NH * DH;

__device__ __align__(128) float g_mod[6 * DM];
__device__ __align__(1024) bf16 g_ht[(size_t)SEQ * DM];
__device__ __align__(1024) bf16 g_ox[(size_t)SEQ * HD];
__device__ __align__(1024) bf16 g_x1[(size_t)SEQ * DM];
__device__ __align__(1024) bf16 g_h2[(size_t)SEQ * DM];
__device__ __align__(1024) bf16 g_act[(size_t)SEQ * FF];
__device__ __align__(8192) uint32_t g_buf1[80 * 2 * 2048];
__device__ __align__(8192) uint32_t g_buf2[4 * 3 * 2048];
__device__ uint32_t g_choice[128];
__device__ uint32_t g_epoch;
__device__ uint32_t g_hflag[64];
__device__ __align__(128) uint32_t g_modx[2 * DM];
#define T2(i)
#define T3(i)
enum { C_Q = 0, C_MOD = 1, C_REC = 2, C_G0 = 18, C_LN = 34, C_G1 = 50, C_G2 = 66, C_FIN = 82, C_NUM = 98 };
__device__ __align__(128) uint32_t g_cnt[C_NUM * 32];
constexpr int PMAX = 12;
constexpr int PRING = 4;
__device__ __align__(1024) float g_p0[(size_t)PRING * PMAX * 128 * DM];
__device__ __align__(1024) float g_p2[(size_t)PRING * PMAX * 128 * DM];
#define TR(k)

#define FRESH(x) asm volatile("" : "+r"(x))
__device__ __forceinline__ float bfr(float x) { uint32_t r; asm("cvt.rn.bf16x2.f32 %0, %1, %2;" : "=r"(r) : "f"(x), "f"(0.0f)); return __uint_as_float(r); }
__device__ __forceinline__ uint32_t pack2(float a, float b) {
    uint32_t r; asm("cvt.rn.bf16x2.f32 %0, %1, %2;" : "=r"(r) : "f"(b), "f"(a)); return r;
}
__device__ __forceinline__ float bflo(uint32_t v) { return __uint_as_float(v << 16); }
__device__ __forceinline__ float bfhi(uint32_t v) { return __uint_as_float(v & 0xffff0000u); }
__device__ __forceinline__ float ex2(float x) { float r; asm("ex2.approx.ftz.f32 %0, %1;" : "=f"(r) : "f"(x)); return r; }
__device__ __forceinline__ float rcpf(float x) { float r; asm("rcp.approx.ftz.f32 %0, %1;" : "=f"(r) : "f"(x)); return r; }
__device__ __forceinline__ void score2(float& a, float& b) {
    const float SCALE = 0.07216878364870322f;
    uint32_t u = pack2(a, b);
    u = pack2(bflo(u) * SCALE, bfhi(u) * SCALE);
    a = bflo(u); b = bfhi(u);
}
__device__ __forceinline__ uint32_t smem_u32(const void* p) { return (uint32_t)__cvta_generic_to_shared(p); }

__device__ __forceinline__ void mbar_init(uint32_t bar, uint32_t cnt) {
    asm volatile("mbarrier.init.shared::cta.b64 [%0], %1;" :: "r"(bar), "r"(cnt) : "memory");
}
__device__ __forceinline__ void mbar_arrive(uint32_t bar) {
    asm volatile("mbarrier.arrive.shared::cta.b64 _, [%0];" :: "r"(bar) : "memory");
}
__device__ __forceinline__ void mbar_expect(uint32_t bar, uint32_t bytes) {
    asm volatile("mbarrier.arrive.expect_tx.shared::cta.b64 _, [%0], %1;" :: "r"(bar), "r"(bytes) : "memory");
}
__device__ __forceinline__ bool mbar_try(uint32_t bar, uint32_t parity) {
    uint32_t ok;
    asm volatile("{\n\t.reg .pred p;\n\tmbarrier.try_wait.parity.shared::cta.b64 p, [%1], %2;\n\tselp.u32 %0, 1, 0, p;\n\t}"
                 : "=r"(ok) : "r"(bar), "r"(parity) : "memory");
    return ok != 0;
}
__device__ __forceinline__ bool mbar_try_cluster(uint32_t bar, uint32_t parity) {
    uint32_t ok;
    asm volatile("{\n\t.reg .pred p;\n\tmbarrier.try_wait.parity.acquire.cluster.shared::cta.b64 p, [%1], %2;\n\tselp.u32 %0, 1, 0, p;\n\t}"
                 : "=r"(ok) : "r"(bar), "r"(parity) : "memory");
    return ok != 0;
}
__device__ __forceinline__ void mbar_wait(uint32_t bar, uint32_t parity) {
    uint32_t guard = 0;
    while (!mbar_try(bar, parity)) { if (++guard > (1u << 22)) __trap(); }
}
__device__ __forceinline__ void mbar_wait_cluster(uint32_t bar, uint32_t parity) {
    uint32_t guard = 0;
    while (!mbar_try_cluster(bar, parity)) { if (++guard > (1u << 22)) __trap(); }
}
__device__ __forceinline__ void bar_sync(int id, int n) { asm volatile("bar.sync %0, %1;" :: "r"(id), "r"(n) : "memory"); }
__device__ __forceinline__ void bar_arrive(int id, int n) { asm volatile("bar.arrive %0, %1;" :: "r"(id), "r"(n) : "memory"); }
__device__ __forceinline__ void sts1(uint32_t a, uint32_t v) { asm volatile("st.shared.u32 [%0], %1;" :: "r"(a), "r"(v) : "memory"); }
__device__ __forceinline__ uint32_t lds1(uint32_t a) { uint32_t v; asm volatile("ld.shared.u32 %0, [%1];" : "=r"(v) : "r"(a) : "memory"); return v; }
__device__ __forceinline__ void fence_async() { asm volatile("fence.proxy.async.shared::cta;" ::: "memory"); }
__device__ __forceinline__ void cluster_sync() {
    asm volatile("barrier.cluster.arrive.release.aligned;\n\tbarrier.cluster.wait.acquire.aligned;" ::: "memory");
}
__device__ __forceinline__ uint32_t mapa(uint32_t a, uint32_t rank) {
    uint32_t r; asm("mapa.shared::cluster.u32 %0, %1, %2;" : "=r"(r) : "r"(a), "r"(rank)); return r;
}
__device__ __forceinline__ void st_async1(uint32_t a, uint32_t v, uint32_t bar) {
    asm volatile("st.async.weak.shared::cluster.mbarrier::complete_tx::bytes.b32 [%0], %1, [%2];" :: "r"(a), "r"(v), "r"(bar) : "memory");
}
__device__ __forceinline__ void st_async2(uint32_t a, float x, float y, uint32_t bar) {
    asm volatile("st.async.weak.shared::cluster.mbarrier::complete_tx::bytes.v2.f32 [%0], {%1,%2}, [%3];" :: "r"(a), "f"(x), "f"(y), "r"(bar) : "memory");
}
__device__ __forceinline__ void st_async4(uint32_t a, const float* c, uint32_t bar) {
    asm volatile("st.async.weak.shared::cluster.mbarrier::complete_tx::bytes.v4.f32 [%0], {%1,%2,%3,%4}, [%5];"
                 :: "r"(a), "f"(c[0]), "f"(c[1]), "f"(c[2]), "f"(c[3]), "r"(bar) : "memory");
}
__device__ __forceinline__ void bulk_g2s(uint32_t dst, const void* src, uint32_t bytes, uint32_t bar) {
    asm volatile("cp.async.bulk.shared::cluster.global.mbarrier::complete_tx::bytes [%0], [%1], %2, [%3];"
                 :: "r"(dst), "l"(src), "r"(bytes), "r"(bar) : "memory");
}
__device__ __forceinline__ void cpa16(uint32_t s, const void* g) {
    asm volatile("cp.async.cg.shared.global [%0], [%1], 16;" :: "r"(s), "l"(g) : "memory");
}
__device__ __forceinline__ void cpa_wait_all() { asm volatile("cp.async.wait_all;" ::: "memory"); }
__device__ __forceinline__ void ldsm4(uint32_t* r, uint32_t a) {
    asm volatile("ldmatrix.sync.aligned.m8n8.x4.shared.b16 {%0,%1,%2,%3}, [%4];" : "=r"(r[0]), "=r"(r[1]), "=r"(r[2]), "=r"(r[3]) : "r"(a) : "memory");
}
__device__ __forceinline__ void ldsm4t(uint32_t* r, uint32_t a) {
    asm volatile("ldmatrix.sync.aligned.m8n8.x4.trans.shared.b16 {%0,%1,%2,%3}, [%4];" : "=r"(r[0]), "=r"(r[1]), "=r"(r[2]), "=r"(r[3]) : "r"(a) : "memory");
}
__device__ __forceinline__ void stsm2t(uint32_t a, uint32_t r0, uint32_t r1) {
    asm volatile("stmatrix.sync.aligned.m8n8.x2.trans.shared.b16 [%0], {%1,%2};" :: "r"(a), "r"(r0), "r"(r1) : "memory");
}
__device__ __forceinline__ void stsm4t(uint32_t a, uint32_t r0, uint32_t r1, uint32_t r2, uint32_t r3) {
    asm volatile("stmatrix.sync.aligned.m8n8.x4.trans.shared.b16 [%0], {%1,%2,%3,%4};" :: "r"(a), "r"(r0), "r"(r1), "r"(r2), "r"(r3) : "memory");
}
__device__ __forceinline__ uint32_t movm(uint32_t v) {
    uint32_t r; asm volatile("movmatrix.sync.aligned.m8n8.trans.b16 %0, %1;" : "=r"(r) : "r"(v)); return r;
}
__device__ __forceinline__ void mma16(float* c, uint32_t a0, uint32_t a1, uint32_t a2, uint32_t a3, uint32_t b0, uint32_t b1) {
    asm volatile("mma.sync.aligned.m16n8k16.row.col.f32.bf16.bf16.f32 {%0,%1,%2,%3}, {%4,%5,%6,%7}, {%8,%9}, {%0,%1,%2,%3};"
                 : "+f"(c[0]), "+f"(c[1]), "+f"(c[2]), "+f"(c[3]) : "r"(a0), "r"(a1), "r"(a2), "r"(a3), "r"(b0), "r"(b1));
}
__device__ __forceinline__ void mma8(float* c, uint32_t a0, uint32_t a1, uint32_t b0) {
    asm volatile("mma.sync.aligned.m16n8k8.row.col.f32.bf16.bf16.f32 {%0,%1,%2,%3}, {%4,%5}, {%6}, {%0,%1,%2,%3};"
                 : "+f"(c[0]), "+f"(c[1]), "+f"(c[2]), "+f"(c[3]) : "r"(a0), "r"(a1), "r"(b0));
}
__host__ __device__ constexpr uint64_t make_desc(uint32_t saddr, uint32_t lbo, uint32_t sbo, uint32_t layout) {
    return (uint64_t)((saddr & 0x3FFFF) >> 4) | ((uint64_t)(lbo >> 4) << 16) | ((uint64_t)(sbo >> 4) << 32) | ((uint64_t)layout << 62);
}
__device__ __forceinline__ void wg_fence() { asm volatile("wgmma.fence.sync.aligned;" ::: "memory"); }
__device__ __forceinline__ void wg_commit() { asm volatile("wgmma.commit_group.sync.aligned;" ::: "memory"); }
template <int N> __device__ __forceinline__ void wg_wait() { asm volatile("wgmma.wait_group.sync.aligned %0;" :: "n"(N) : "memory"); }

#define D16(C) C(d[0]), C(d[1]), C(d[2]), C(d[3]), C(d[4]), C(d[5]), C(d[6]), C(d[7]), \
               C(d[8]), C(d[9]), C(d[10]), C(d[11]), C(d[12]), C(d[13]), C(d[14]), C(d[15])
#define DREG16 "{%0,%1,%2,%3,%4,%5,%6,%7,%8,%9,%10,%11,%12,%13,%14,%15}"
__device__ __forceinline__ void wg_rs32(float* d, const uint32_t* a, uint64_t db, bool acc) {
    if (acc)
        asm volatile("wgmma.mma_async.sync.aligned.m64n32k16.f32.bf16.bf16 " DREG16 ", {%16,%17,%18,%19}, %20, 1, 1, 1, 0;"
            : D16("+f") : "r"(a[0]), "r"(a[1]), "r"(a[2]), "r"(a[3]), "l"(db));
    else
        asm volatile("wgmma.mma_async.sync.aligned.m64n32k16.f32.bf16.bf16 " DREG16 ", {%16,%17,%18,%19}, %20, 0, 1, 1, 0;"
            : D16("=f") : "r"(a[0]), "r"(a[1]), "r"(a[2]), "r"(a[3]), "l"(db));
}
__device__ __forceinline__ void wg_ss32(float* d, uint64_t da, uint64_t db, bool acc) {
    if (acc)
        asm volatile("wgmma.mma_async.sync.aligned.m64n32k16.f32.bf16.bf16 " DREG16 ", %16, %17, 1, 1, 1, 1, 0;"
            : D16("+f") : "l"(da), "l"(db));
    else
        asm volatile("wgmma.mma_async.sync.aligned.m64n32k16.f32.bf16.bf16 " DREG16 ", %16, %17, 0, 1, 1, 1, 0;"
            : D16("=f") : "l"(da), "l"(db));
}
__device__ __forceinline__ void wg_ss8(float* d, uint64_t da, uint64_t db, bool acc) {
    if (acc)
        asm volatile("wgmma.mma_async.sync.aligned.m64n8k16.f32.bf16.bf16 {%0,%1,%2,%3}, %4, %5, 1, 1, 1, 1, 1;"
            : "+f"(d[0]), "+f"(d[1]), "+f"(d[2]), "+f"(d[3]) : "l"(da), "l"(db));
    else
        asm volatile("wgmma.mma_async.sync.aligned.m64n8k16.f32.bf16.bf16 {%0,%1,%2,%3}, %4, %5, 0, 1, 1, 1, 1;"
            : "=f"(d[0]), "=f"(d[1]), "=f"(d[2]), "=f"(d[3]) : "l"(da), "l"(db));
}
template <int OFF> __device__ __forceinline__ void ldsm4t_i(uint32_t* r, uint32_t a) {
    asm volatile("ldmatrix.sync.aligned.m8n8.x4.trans.shared.b16 {%0,%1,%2,%3}, [%4+%5];"
                 : "=r"(r[0]), "=r"(r[1]), "=r"(r[2]), "=r"(r[3]) : "r"(a), "n"(OFF) : "memory");
}

__device__ __forceinline__ uint4 ld_relaxed4(const void* p) {
    uint4 v;
    asm volatile("ld.relaxed.gpu.global.v4.u32 {%0,%1,%2,%3}, [%4];" : "=r"(v.x), "=r"(v.y), "=r"(v.z), "=r"(v.w) : "l"(p) : "memory");
    return v;
}
__device__ __forceinline__ void st_relaxed2(void* p, uint32_t a, uint32_t b) {
    asm volatile("st.relaxed.gpu.global.v2.u32 [%0], {%1,%2};" :: "l"(p), "r"(a), "r"(b) : "memory");
}
__device__ __forceinline__ void st_relaxed2_off(void* base, uint32_t off, uint32_t a, uint32_t b) {
    asm volatile("{\n\t.reg .u64 ad;\n\tcvt.u64.u32 ad, %1;\n\tadd.u64 ad, ad, %0;\n\tst.relaxed.gpu.global.v2.u32 [ad], {%2,%3};\n\t}"
                 :: "l"(base), "r"(off), "r"(a), "r"(b) : "memory");
}
__device__ __forceinline__ void st_relaxed1(void* p, uint32_t a) {
    asm volatile("st.relaxed.gpu.global.u32 [%0], %1;" :: "l"(p), "r"(a) : "memory");
}
__device__ __forceinline__ uint32_t ld_acquire1(const uint32_t* p) {
    uint32_t v; asm volatile("ld.acquire.gpu.global.u32 %0, [%1];" : "=r"(v) : "l"(p) : "memory"); return v;
}
__device__ __forceinline__ void st_release1(uint32_t* p, uint32_t a) {
    asm volatile("st.release.gpu.global.u32 [%0], %1;" :: "l"(p), "r"(a) : "memory");
}
__device__ __forceinline__ uint4 lds4(uint32_t s) {
    uint4 v; asm volatile("ld.shared.v4.u32 {%0,%1,%2,%3}, [%4];" : "=r"(v.x), "=r"(v.y), "=r"(v.z), "=r"(v.w) : "r"(s) : "memory"); return v;
}
__device__ __forceinline__ void sts4(uint32_t s, const uint4& v) {
    asm volatile("st.shared.v4.u32 [%0], {%1,%2,%3,%4};" :: "r"(s), "r"(v.x), "r"(v.y), "r"(v.z), "r"(v.w) : "memory");
}
__device__ __forceinline__ float4 lds4f(uint32_t s) {
    float4 v; asm volatile("ld.shared.v4.f32 {%0,%1,%2,%3}, [%4];" : "=f"(v.x), "=f"(v.y), "=f"(v.z), "=f"(v.w) : "r"(s) : "memory"); return v;
}
__device__ __forceinline__ uint2 lds2(uint32_t s) {
    uint2 v; asm volatile("ld.shared.v2.u32 {%0,%1}, [%2];" : "=r"(v.x), "=r"(v.y) : "r"(s) : "memory"); return v;
}
__device__ __forceinline__ float2 lds2f(uint32_t s) {
    float2 v; asm volatile("ld.shared.v2.f32 {%0,%1}, [%2];" : "=f"(v.x), "=f"(v.y) : "r"(s) : "memory"); return v;
}
__device__ __forceinline__ uint32_t clk32() { uint32_t c; asm volatile("mov.u32 %0, %%clock;" : "=r"(c) :: "memory"); return c; }
__device__ __forceinline__ uint32_t tagw(float v, uint32_t tag) { return ((__float_as_uint(v) + 8u) & ~15u) | tag; }
__device__ __forceinline__ bool ok4(const uint4& v, uint32_t tag) { return (((v.x ^ tag) | (v.y ^ tag) | (v.z ^ tag) | (v.w ^ tag)) & 15u) == 0; }
__device__ __forceinline__ bool oks(const uint4& v) { return v.x != 0xFFFFFFFFu && v.y != 0xFFFFFFFFu && v.z != 0xFFFFFFFFu && v.w != 0xFFFFFFFFu; }
__device__ __forceinline__ float uf(uint32_t x) { return __uint_as_float(x & ~15u); }

template <int NT, int BAR>
__device__ __forceinline__ void mod_chunk(const bf16* __restrict__ c, const bf16* __restrict__ wmod, int col0, int tid, float* red) {
    constexpr int RG = NT / 8, NP = DM / RG;
    const int cc = tid & 7, rg = tid >> 3;
    uint4 w[NP];
    #pragma unroll
    for (int i = 0; i < NP; i++) w[i] = __ldg((const uint4*)(wmod + (size_t)(rg + i * RG) * (6 * DM) + col0 + cc * 8));
    float a[8];
    #pragma unroll
    for (int j = 0; j < 8; j++) a[j] = 0.f;
    #pragma unroll
    for (int i = 0; i < NP; i++) {
        const float v = __bfloat162float(c[rg + i * RG]);
        const float sv = bfr(__fdividef(v, 1.0f + __expf(-v)));
        a[0] += sv * bflo(w[i].x); a[1] += sv * bfhi(w[i].x); a[2] += sv * bflo(w[i].y); a[3] += sv * bfhi(w[i].y);
        a[4] += sv * bflo(w[i].z); a[5] += sv * bfhi(w[i].z); a[6] += sv * bflo(w[i].w); a[7] += sv * bfhi(w[i].w);
    }
    #pragma unroll
    for (int j = 0; j < 8; j++) {
        a[j] += __shfl_xor_sync(0xffffffffu, a[j], 8);
        a[j] += __shfl_xor_sync(0xffffffffu, a[j], 16);
    }
    if ((tid & 31) < 8) {
        float* d = red + (tid >> 5) * 64 + cc * 8;
        *(float4*)d = make_float4(a[0], a[1], a[2], a[3]);
        *(float4*)(d + 4) = make_float4(a[4], a[5], a[6], a[7]);
    }
    bar_sync(BAR, NT);
    if (tid < 64) {
        float s = 0.f;
        #pragma unroll
        for (int i = 0; i < NT / 32; i++) s += red[i * 64 + tid];
        g_mod[col0 + tid] = bfr(s);
    }
}

__device__ __forceinline__ void ln_stats(const float (*v)[4], float& mb, float& sd) {
    float s = 0.f;
    #pragma unroll
    for (int i = 0; i < 5; i++) s += (v[i][0] + v[i][1]) + (v[i][2] + v[i][3]);
    #pragma unroll
    for (int o = 16; o > 0; o >>= 1) s += __shfl_xor_sync(0xffffffffu, s, o);
    const float mean = s * (1.0f / DM);
    float q = 0.f;
    #pragma unroll
    for (int i = 0; i < 5; i++) {
        #pragma unroll
        for (int j = 0; j < 4; j++) { const float d = v[i][j] - mean; q += d * d; }
    }
    #pragma unroll
    for (int o = 16; o > 0; o >>= 1) q += __shfl_xor_sync(0xffffffffu, q, o);
    mb = bfr(mean);
    const float var = bfr(q * (1.0f / DM));
    sd = 1.0f / bfr(sqrtf(bfr(var + 1e-5f)));
}
__device__ __forceinline__ uint2 ln_apply(const float* v, float mb, float rs, const float4& sc, const float4& sh) {
    const float o0 = bfr(bfr(bfr(v[0] - mb) * rs) * bfr(1.0f + sc.x)) + sh.x;
    const float o1 = bfr(bfr(bfr(v[1] - mb) * rs) * bfr(1.0f + sc.y)) + sh.y;
    const float o2 = bfr(bfr(bfr(v[2] - mb) * rs) * bfr(1.0f + sc.z)) + sh.z;
    const float o3 = bfr(bfr(bfr(v[3] - mb) * rs) * bfr(1.0f + sc.w)) + sh.w;
    return make_uint2(pack2(o0, o1), pack2(o2, o3));
}

constexpr int SM_WV = 0;
constexpr int SM_HB = 81920;
constexpr int SM_WO = SM_HB + 40960;
constexpr int SM_QX = SM_WO + 77824;
constexpr int SM_KS = SM_QX + 4096;
constexpr int SM_QM = SM_KS + 5120;
constexpr int SM_XS = SM_QM + 1024;
constexpr int SM_MS = SM_XS + 12288;
constexpr int SM_OS = SM_MS + 3840;
constexpr int SM_PM = SM_OS + 3072;
constexpr int SM_BAR = SM_PM + 640;
constexpr int SM_CH = SM_BAR + 128;
constexpr int SM_TOTAL = SM_CH + 128;
static_assert(SM_TOTAL <= 232448, "smem");

enum { B_MEM_FULL = 0, B_MEM_FREE, B_HLO_FULL, B_HHI_FULL, B_HLO_FREE, B_HHI_FREE, B_MS, B_O, B_XS, B_O1, B_XSFREE, B_WQ, B_WK, B_WV, B_WO };

__device__ __forceinline__ int probe_blk(uint32_t* blk) {
    uint32_t t0 = 0xffffffffu, t1 = 0xffffffffu, acc = 0;
    for (int rep = 0; rep < 3; rep++) {
        #pragma unroll
        for (int pg = 0; pg < 2; pg++) {
            uint32_t c0 = clk32();
            uint32_t v = atomicOr(blk + pg * 1024 + acc, 0u);
            acc = (v == 0x12345678u) ? 1u : 0u;
            asm volatile("" :: "r"(acc) : "memory");
            uint32_t c1 = clk32() + acc;
            uint32_t d = c1 - c0;
            if (rep > 0) { if (pg == 0) t0 = min(t0, d); else t1 = min(t1, d); }
        }
    }
    return t1 < t0 ? 1 : 0;
}

__device__ __forceinline__ uint32_t wo_tile_off(int w) {
    if (w < 8) return w * 6144;
    if (w < 12) return 8 * 6144 + (w - 8) * 4096;
    return 8 * 6144 + 4 * 4096 + (w - 12) * 6144;
}

template <int NRES, int NPRE>
__device__ __forceinline__ void wo_phase(uint32_t sb, int w, int lane, const uint32_t (*res)[4], uint32_t parity,
                                         uint32_t tag, int tile, int h) {
    FRESH(lane);
    const int er = (lane & 7) + 8 * (lane >> 4);
    const uint32_t aaddr = sb + SM_WO + wo_tile_off(w) + er * 32 + ((((lane >> 3) & 1) ^ ((er >> 2) & 1)) << 4);
    const uint32_t baddr = sb + SM_OS + lane * 16;
    float c0[4] = {0.f, 0.f, 0.f, 0.f}, c1[4] = {0.f, 0.f, 0.f, 0.f};
    uint32_t pre[NPRE > 4 ? NPRE : 4][4];
    if (NPRE >= 4) {
        #pragma unroll
        for (int i = 0; i < 4; i++) ldsm4t(pre[i], aaddr + i * 512);
        mbar_wait(sb + SM_BAR + B_O1 * 8, parity);
        uint32_t b[2][4];
        ldsm4t(b[0], baddr);
        ldsm4t(b[1], baddr + 512);
        #pragma unroll
        for (int kp = 0; kp < 2; kp++) {
            mma16(c0, pre[2 * kp][0], pre[2 * kp][1], pre[2 * kp][2], pre[2 * kp][3], b[kp][0], b[kp][1]);
            mma16(c1, pre[2 * kp + 1][0], pre[2 * kp + 1][1], pre[2 * kp + 1][2], pre[2 * kp + 1][3], b[kp][2], b[kp][3]);
        }
    } else {
        #pragma unroll
        for (int i = 0; i < 2; i++) ldsm4t(pre[i], aaddr + i * 512);
        mbar_wait(sb + SM_BAR + B_O1 * 8, parity);
        #pragma unroll
        for (int kp = 0; kp < 2; kp++) {
            uint32_t b[4];
            ldsm4t(b, baddr + kp * 512);
            if (kp == 1) { ldsm4t(pre[0], aaddr + 2 * 512); ldsm4t(pre[1], aaddr + 3 * 512); }
            mma16(c0, pre[0][0], pre[0][1], pre[0][2], pre[0][3], b[0], b[1]);
            mma16(c1, pre[1][0], pre[1][1], pre[1][2], pre[1][3], b[2], b[3]);
        }
    }
    #pragma unroll
    for (int i = 0; i < NPRE; i++) ldsm4t(pre[i], aaddr + (4 + i) * 512);
    uint32_t off0, off1;
    {
        uint32_t ch;
        asm volatile("ld.shared.u16 %0, [%1];" : "=r"(ch) : "r"(sb + SM_CH + 2 * tile) : "memory");
        const int j = h >> 4;
        const uint32_t base = (uint32_t)((tile * 4 + j) * 8192 + (h & 15) * 256 + lane * 8);
        ch >>= j;
        off0 = base + (ch & 1) * 4096;
        off1 = base + 16384 + (ch & 256) * 16;
    }
    mbar_wait(sb + SM_BAR + B_O * 8, parity);
    if (NRES == 4) {
        uint32_t b[4][4];
        #pragma unroll
        for (int i = 0; i < 4; i++) ldsm4t(b[i], baddr + (2 + i) * 512);
        #pragma unroll
        for (int i = 0; i < 2; i++) {
            mma16(c0, res[2 * i][0], res[2 * i][1], res[2 * i][2], res[2 * i][3], b[i][0], b[i][1]);
            mma16(c1, res[2 * i + 1][0], res[2 * i + 1][1], res[2 * i + 1][2], res[2 * i + 1][3], b[i][2], b[i][3]);
        }
        #pragma unroll
        for (int i = 0; i < 2; i++) {
            mma16(c0, pre[2 * i][0], pre[2 * i][1], pre[2 * i][2], pre[2 * i][3], b[2 + i][0], b[2 + i][1]);
            mma16(c1, pre[2 * i + 1][0], pre[2 * i + 1][1], pre[2 * i + 1][2], pre[2 * i + 1][3], b[2 + i][2], b[2 + i][3]);
        }
    } else if (NPRE == 4) {
        uint32_t b[2][4];
        #pragma unroll
        for (int hh = 0; hh < 2; hh++) {
            ldsm4t(b[0], baddr + (2 + 2 * hh) * 512);
            ldsm4t(b[1], baddr + (3 + 2 * hh) * 512);
            if (hh) {
                #pragma unroll
                for (int i = 0; i < 4; i++) ldsm4t(pre[i], aaddr + (8 + i) * 512);
            }
            #pragma unroll
            for (int i = 0; i < 2; i++) {
                mma16(c0, pre[2 * i][0], pre[2 * i][1], pre[2 * i][2], pre[2 * i][3], b[i][0], b[i][1]);
                mma16(c1, pre[2 * i + 1][0], pre[2 * i + 1][1], pre[2 * i + 1][2], pre[2 * i + 1][3], b[i][2], b[i][3]);
            }
        }
    }
    st_relaxed2_off(g_buf1, off0, tagw(c0[0] + c1[0], tag), tagw(c0[1] + c1[1], tag));
    st_relaxed2_off(g_buf1, off1, tagw(c0[2] + c1[2], tag), tagw(c0[3] + c1[3], tag));
}

template <int NT, bool MASK>
__device__ __forceinline__ void softmax_core(float (*sc)[2], int g, int t, uint32_t* pb) {
    const float L2E = 1.4426950408889634f;
    #pragma unroll
    for (int j = 0; j < NT; j++) score2(sc[j][0], sc[j][1]);
    if (MASK) {
        const float NEG = -999292928.0f;
        if (2 * t > g) sc[NT - 1][0] = NEG;
        if (2 * t + 1 > g) sc[NT - 1][1] = NEG;
    }
    float m[NT];
    #pragma unroll
    for (int j = 0; j < NT; j++) m[j] = fmaxf(sc[j][0], sc[j][1]);
    float mx = m[0];
    #pragma unroll
    for (int j = 1; j < NT; j++) mx = fmaxf(mx, m[j]);
    mx = fmaxf(mx, __shfl_xor_sync(0xffffffffu, mx, 1));
    mx = fmaxf(mx, __shfl_xor_sync(0xffffffffu, mx, 2));
    float s0 = 0.f, s1 = 0.f;
    #pragma unroll
    for (int j = 0; j < NT; j++) {
        sc[j][0] = ex2((sc[j][0] - mx) * L2E); sc[j][1] = ex2((sc[j][1] - mx) * L2E);
        s0 += sc[j][0]; s1 += sc[j][1];
    }
    s0 += s1;
    s0 += __shfl_xor_sync(0xffffffffu, s0, 1);
    s0 += __shfl_xor_sync(0xffffffffu, s0, 2);
    const float iv = rcpf(s0);
    #pragma unroll
    for (int j = 0; j < NT; j++) pb[j] = pack2(sc[j][0] * iv, sc[j][1] * iv);
}
template <int NT>
__device__ __forceinline__ void xsoftmax(uint32_t a, int g, int t) {
    float sc[NT][2];
    #pragma unroll
    for (int j = 0; j < NT; j++) {
        float2 v0 = lds2f(a + j * 512), v1 = lds2f(a + j * 512 + 4096), v2 = lds2f(a + j * 512 + 8192);
        sc[j][0] = v0.x + v1.x + v2.x; sc[j][1] = v0.y + v1.y + v2.y;
    }
    uint32_t pb[NT];
    softmax_core<NT, true>(sc, g, t, pb);
    #pragma unroll
    for (int j = 0; j < NT; j += 2) {
        if (j + 1 < NT) asm volatile("st.shared.v2.u32 [%0], {%1,%2};" :: "r"(a + j * 512), "r"(pb[j]), "r"(pb[j + 1]) : "memory");
        else sts1(a + j * 512, pb[j]);
    }
}
template <int NJ>
__device__ __forceinline__ void xscores(uint32_t sb, int p, int mi, int j0, int lane) {
    FRESH(lane);
    const int r = lane & 7, cq = lane >> 3;
    const int qrow = mi * 16 + r + 8 * (cq & 1);
    uint32_t kb[NJ][8];
    float d[NJ][4];
    #pragma unroll
    for (int j = 0; j < NJ; j++) {
        ldsm4(kb[j], sb + SM_KS + ((j0 + j) * 8 + r) * 128 + ((cq ^ r) << 4));
        ldsm4(kb[j] + 4, sb + SM_KS + ((j0 + j) * 8 + r) * 128 + (((cq + 4) ^ r) << 4));
        d[j][0] = 0.f; d[j][1] = 0.f; d[j][2] = 0.f; d[j][3] = 0.f;
    }
    #pragma unroll
    for (int kt = 0; kt < 4; kt++) {
        uint32_t a[4];
        ldsm4(a, sb + SM_QX + qrow * 128 + (((2 * kt + (cq >> 1)) ^ r) << 4));
        #pragma unroll
        for (int j = 0; j < NJ; j++) mma16(d[j], a[0], a[1], a[2], a[3], kb[j][2 * kt], kb[j][2 * kt + 1]);
    }
    const uint32_t la = sb + SM_XS + p * 4096 + (mi * 3 + j0) * 512 + lane * 16;
    #pragma unroll
    for (int rk = 0; rk < 3; rk++) {
        const uint32_t ra = mapa(la, rk), rb = mapa(sb + SM_BAR + B_XS * 8, rk);
        #pragma unroll
        for (int j = 0; j < NJ; j++) st_async4(ra + j * 512, d[j], rb);
    }
}
__device__ __forceinline__ void mbar_arrive_remote(uint32_t bar) {
    asm volatile("mbarrier.arrive.relaxed.cluster.shared::cluster.b64 _, [%0];" :: "r"(bar) : "memory");
}

__device__ __forceinline__ void tma2d(uint32_t dst, const CUtensorMap* map, int c0, int c1, uint32_t bar) {
    asm volatile("cp.async.bulk.tensor.2d.shared::cluster.global.mbarrier::complete_tx::bytes [%0], [%1, {%2, %3}], [%4];"
                 :: "r"(dst), "l"(map), "r"(c0), "r"(c1), "r"(bar) : "memory");
}
__device__ __forceinline__ void tma2d_pf(const CUtensorMap* map, int c0, int c1) {
    asm volatile("cp.async.bulk.prefetch.tensor.2d.L2.global [%0, {%1, %2}];" :: "l"(map), "r"(c0), "r"(c1) : "memory");
}
__device__ __forceinline__ void bulk_pf(const void* p, uint32_t bytes) {
    asm volatile("cp.async.bulk.prefetch.L2.global [%0], %1;" :: "l"(p), "r"(bytes) : "memory");
}
struct RMaps { CUtensorMap wq, wk, wv, wo, wop; };
__device__ __forceinline__ void signal_cnt(int idx) {
    asm volatile("fence.proxy.async.global;\n\tred.release.gpu.global.add.u32 [%0], 1;" :: "l"(g_cnt + idx * 32) : "memory");
}

__global__ void __launch_bounds__(512, 1)
k_rec(const __grid_constant__ RMaps maps, const bf16* __restrict__ mem0, const bf16* __restrict__ Wo,
      const bf16* __restrict__ xin, const bf16* __restrict__ cvec, const bf16* __restrict__ wmod) {
    extern __shared__ __align__(1024) uint8_t smem_raw[];
    constexpr uint32_t SBC = 1024;
    const uint32_t sb = smem_u32(smem_raw);
    if ((sb & 0xFFFFFFu) != SBC) __trap();
    int lane = __shfl_sync(0xffffffffu, threadIdx.x & 31, threadIdx.x & 31);
    const int warp = __shfl_sync(0xffffffffu, threadIdx.x >> 5, 0), wg = warp >> 2;
    const int tid = warp * 32 + lane;
    const int b = blockIdx.x, h = b / 3, p = b % 3;
    const int g = lane >> 2, t = lane & 3;
    const int tile0 = p == 0 ? 0 : (p == 1 ? 14 : 27);
    const int ntile = p == 0 ? 14 : 13;
    const uint32_t bar = sb + SM_BAR;

    if (tid == 0) T2(100 + b);
    if (tid == 0) {
        mbar_init(bar + B_MEM_FULL * 8, 4);
        mbar_init(bar + B_MEM_FREE * 8, 12);
        mbar_init(bar + B_HLO_FULL * 8, 1);
        mbar_init(bar + B_HHI_FULL * 8, 1);
        mbar_init(bar + B_HLO_FREE * 8, 12);
        mbar_init(bar + B_HHI_FREE * 8, 12);
        mbar_init(bar + B_MS * 8, 1);
        mbar_init(bar + B_O * 8, 1);
        mbar_init(bar + B_XS * 8, 1);
        mbar_init(bar + B_O1 * 8, 4);
        mbar_init(bar + B_XSFREE * 8, 12);
        mbar_init(bar + B_WQ * 8, 1);
        mbar_init(bar + B_WK * 8, 1);
        mbar_init(bar + B_WV * 8, 1);
        mbar_init(bar + B_WO * 8, 1);
        asm volatile("fence.mbarrier_init.release.cluster;" ::: "memory");
        mbar_expect(bar + B_MS * 8, 3840);
        mbar_expect(bar + B_O * 8, 2048);
        mbar_expect(bar + B_XS * 8, 12288);
    }
    __syncwarp();
    asm volatile("barrier.cluster.arrive.relaxed.aligned;\n\tbarrier.cluster.wait.acquire.aligned;" ::: "memory");
    if (warp == 0) T3(0);

    if (tid == 480) {
        __nanosleep(TMA_DELAY);
        mbar_expect(bar + B_WQ * 8, 81920);
        mbar_expect(bar + B_WK * 8, 81920);
        #pragma unroll 1
        for (int i = 0; i < 5; i++) {
            tma2d(sb + SM_WO + i * 16384, &maps.wq, h * DH + p * 64, i * 128, bar + B_WQ * 8);
            tma2d(sb + SM_WV + i * 16384, &maps.wk, h * DH + p * 64, i * 128, bar + B_WK * 8);
        }
        __nanosleep(PF_DELAY);
        #pragma unroll 1
        for (int i = 0; i < 5; i++) tma2d_pf(&maps.wv, h * DH + p * 64, i * 128);
        tma2d_pf(&maps.wop, tile0 * 16, h * DH);
    }
    if (wg < 3) {
        const uint32_t tag = *(volatile uint32_t*)&g_epoch + 1u;
        const int seg1 = b + 1, nrow = b < NSEG - 1 ? 64 : 32;
        const bf16* xl = xin + lane * 4;
        uint4 wm[5];
        float cv[5];
        if (wg < 2 && b < 80) {
            #pragma unroll
            for (int i = 0; i < 5; i++) {
                wm[i] = __ldg((const uint4*)(wmod + (size_t)((tid >> 1) + 128 * i) * (6 * DM) + b * 16 + (tid & 1) * 8));
                cv[i] = __bfloat162float(cvec[(tid >> 1) + 128 * i]);
            }
        }
        uint2 xn[6][5];
        #pragma unroll
        for (int r = 0; r < 6; r++) {
            const int idx = warp + 12 * r, nx = idx < 32 ? idx : (idx < nrow ? b * 32 + idx : 0);
            #pragma unroll
            for (int i = 0; i < 5; i++) xn[r][i] = __ldg((const uint2*)(xl + (size_t)nx * DM + i * 128));
        }
        if (wg < 2 && b < 80) {
            float a[8];
            #pragma unroll
            for (int j = 0; j < 8; j++) a[j] = 0.f;
            #pragma unroll
            for (int i = 0; i < 5; i++) {
                const float sv = bfr(__fdividef(cv[i], 1.0f + __expf(-cv[i])));
                a[0] += sv * bflo(wm[i].x); a[1] += sv * bfhi(wm[i].x); a[2] += sv * bflo(wm[i].y); a[3] += sv * bfhi(wm[i].y);
                a[4] += sv * bflo(wm[i].z); a[5] += sv * bfhi(wm[i].z); a[6] += sv * bflo(wm[i].w); a[7] += sv * bfhi(wm[i].w);
            }
            #pragma unroll 1
            for (int o = 2; o < 32; o <<= 1) {
                #pragma unroll
                for (int j = 0; j < 8; j++) a[j] += __shfl_xor_sync(0xffffffffu, a[j], o);
            }
            if (lane < 2) {
                const uint32_t d = sb + SM_QM + warp * 64 + lane * 32;
                sts4(d, make_uint4(__float_as_uint(a[0]), __float_as_uint(a[1]), __float_as_uint(a[2]), __float_as_uint(a[3])));
                sts4(d + 16, make_uint4(__float_as_uint(a[4]), __float_as_uint(a[5]), __float_as_uint(a[6]), __float_as_uint(a[7])));
            }
            bar_sync(1, 256);
            if (tid < 8) {
                float s0 = 0.f, s1 = 0.f;
                #pragma unroll
                for (int i = 0; i < 8; i++) { const float2 v = lds2f(sb + SM_QM + i * 64 + tid * 8); s0 += v.x; s1 += v.y; }
                st_relaxed2(g_modx + (b * 8 + tid) * 2, pack2(s0, s1), tag);
            }
        }
        T3(12);
        if (tid < 320) {
            uint4 v; uint32_t guard = 0;
            while (true) {
                v = ld_relaxed4(g_modx + tid * 4);
                if (v.y == tag && v.w == tag) break;
                __nanosleep(50);
                if (++guard > (1u << 22)) __trap();
            }
            asm volatile("st.shared.v2.u32 [%0], {%1,%2};" :: "r"(sb + SM_KS + tid * 8), "r"(v.x), "r"(v.z) : "memory");
        }
        bar_sync(2, 384);
        T3(13);
        #pragma unroll 1
        for (int idx = warp; idx < nrow; idx += 12) {
            float v[5][4];
            #pragma unroll
            for (int i = 0; i < 5; i++) {
                v[i][0] = bflo(xn[0][i].x); v[i][1] = bfhi(xn[0][i].x); v[i][2] = bflo(xn[0][i].y); v[i][3] = bfhi(xn[0][i].y);
                #pragma unroll
                for (int r = 0; r < 5; r++) xn[r][i] = xn[r + 1][i];
            }
            float mb, rs;
            ln_stats(v, mb, rs);
            const int row = idx & 31;
            char* dst = (idx < 32 ? (char*)smem_raw + SM_HB : (char*)g_ht + (size_t)seg1 * 40960)
                        + (lane >> 4) * 4096 + row * 128 + ((((lane >> 1) & 7) ^ (row & 7)) << 4) + (lane & 1) * 8;
            #pragma unroll
            for (int i = 0; i < 5; i++) {
                const uint2 u0 = lds2(sb + SM_KS + i * 256 + lane * 8), u1 = lds2(sb + SM_KS + 1280 + i * 256 + lane * 8);
                const float4 sh = make_float4(bflo(u0.x), bfhi(u0.x), bflo(u0.y), bfhi(u0.y));
                const float4 sc = make_float4(bflo(u1.x), bfhi(u1.x), bflo(u1.y), bfhi(u1.y));
                *(uint2*)(dst + i * 8192) = ln_apply(v[i], mb, rs, sc, sh);
            }
        }
        fence_async();
        bar_sync(2, 384);
        if (tid == 0) { mbar_arrive(bar + B_HLO_FULL * 8); mbar_arrive(bar + B_HHI_FULL * 8); }
        if (tid == 352 && b < NSEG - 1) {
            asm volatile("fence.proxy.async.global;" ::: "memory");
            st_release1(&g_hflag[seg1], tag);
        }
        __syncwarp();
    }

    if (wg < 2) {
        asm volatile("setmaxnreg.inc.sync.aligned.u32 200;");
        const int w = warp & 3;
        uint32_t wa[40][4];
        {
            mbar_wait(bar + (wg == 0 ? B_WQ : B_WK) * 8, 0);
            if (w == 0) T3(1 + wg);
            const int r = lane & 7;
            const uint32_t wsrc = sb + (wg == 0 ? SM_WO : SM_WV) + (r + ((lane >> 4) << 3)) * 128 + (((2 * w + ((lane >> 3) & 1)) ^ r) << 4);
            #pragma unroll
            for (int kt = 0; kt < 40; kt++) ldsm4t(wa[kt], wsrc + kt * 2048);
            fence_async();
            bar_arrive(10 + wg, 256);
        }

        const uint32_t dstx = sb + (wg == 0 ? SM_QX : SM_KS + 1024);

        for (int s = -1; s < NSEG; s++) {
            const uint32_t par = s & 1;
            FRESH(lane);
            const int g = lane >> 2, t = lane & 3, tid = warp * 32 + lane;
            if (s >= 0) {
                mbar_wait(bar + B_MEM_FULL * 8, par);
                TR(0);
                float c[4][4];
                #pragma unroll
                for (int i = 0; i < 4; i++) { c[i][0] = 0.f; c[i][1] = 0.f; c[i][2] = 0.f; c[i][3] = 0.f; }
                uint32_t maddr = sb + lane * 16;
                asm volatile("" : "+r"(maddr));
                #pragma unroll
                for (int kp = 0; kp < 20; kp++) {
                    uint32_t bb[4];
                    ldsm4t(bb, maddr + (SM_HB + kp * 512));
                    mma16(c[(kp & 1) * 2], wa[2 * kp][0], wa[2 * kp][1], wa[2 * kp][2], wa[2 * kp][3], bb[0], bb[1]);
                    mma16(c[(kp & 1) * 2 + 1], wa[2 * kp + 1][0], wa[2 * kp + 1][1], wa[2 * kp + 1][2], wa[2 * kp + 1][3], bb[2], bb[3]);
                }
                {
                    const int tok = lane & 7, ch = 2 * w + ((lane >> 3) & 1);
                    stsm2t(sb + (wg == 0 ? SM_QM : SM_KS) + tok * 128 + ((ch ^ tok) << 4),
                           pack2((c[0][0] + c[1][0]) + (c[2][0] + c[3][0]), (c[0][1] + c[1][1]) + (c[2][1] + c[3][1])),
                           pack2((c[0][2] + c[1][2]) + (c[2][2] + c[3][2]), (c[0][3] + c[1][3]) + (c[2][3] + c[3][3])));
                }
                __syncwarp();
                if (lane == 0) mbar_arrive(bar + B_MEM_FREE * 8);
                TR(1);
                bar_sync(1, 256);
                if (warp < 5) {
                    const int r = lane & 7, cq = lane >> 3;
                    uint32_t a[8], kb[8];
                    ldsm4(a, sb + SM_QM + r * 128 + ((cq ^ r) << 4));
                    ldsm4(kb, sb + SM_KS + (warp * 8 + r) * 128 + ((cq ^ r) << 4));
                    ldsm4(a + 4, sb + SM_QM + r * 128 + (((cq + 4) ^ r) << 4));
                    ldsm4(kb + 4, sb + SM_KS + (warp * 8 + r) * 128 + (((cq + 4) ^ r) << 4));
                    float d0[4] = {0.f, 0.f, 0.f, 0.f}, d1[4] = {0.f, 0.f, 0.f, 0.f};
                    mma16(d0, a[0], 0u, a[1], 0u, kb[0], kb[1]);
                    mma16(d1, a[2], 0u, a[3], 0u, kb[2], kb[3]);
                    mma16(d0, a[4], 0u, a[5], 0u, kb[4], kb[5]);
                    mma16(d1, a[6], 0u, a[7], 0u, kb[6], kb[7]);
                    const uint32_t la = sb + SM_MS + p * 1280 + warp * 256 + lane * 8;
                    #pragma unroll
                    for (int rk = 0; rk < 3; rk++)
                        st_async2(mapa(la, rk), d0[0] + d1[0], d0[1] + d1[1], mapa(bar + B_MS * 8, rk));
                    bar_arrive(4, 352);
                } else if (warp < 7) {
                    xscores<1>(sb, p, warp - 5, 0, lane);
                    bar_arrive(4, 352);
                }
                TR(2);
                if (s < NSEG - 1) {
                    wo_phase<0, 4>(sb, warp, lane, nullptr, par, (uint32_t)(s % 15) + 1u, tile0 + warp, h);
                    TR(4);
                }
            }
            if (s < NSEG - 1) {
                FRESH(lane);
                const uint32_t hp = (s + 1) & 1;
                float d[16];
                const uint64_t db0 = make_desc(SBC + SM_HB, 16, 1024, 1);
                mbar_wait(bar + B_HHI_FULL * 8, hp);
                if (s < 0 && warp == 0) T3(10);
                {
                    const int r = lane & 7, mq = lane >> 3;
                    const uint32_t ha = sb + SM_HB + 9 * 4096 + (8 * (mq >> 1) + r) * 128 + (((6 + (mq & 1)) ^ r) << 4);
                    uint32_t b0[4], b1[4];
                    ldsm4(b0, ha);
                    ldsm4(b1, ha + 2048);
                    #pragma unroll
                    for (int i = 0; i < 16; i++) d[i] = 0.f;
                    mma16(d + 0, wa[39][0], wa[39][1], wa[39][2], wa[39][3], b0[0], b0[1]);
                    mma16(d + 4, wa[39][0], wa[39][1], wa[39][2], wa[39][3], b0[2], b0[3]);
                    mma16(d + 8, wa[39][0], wa[39][1], wa[39][2], wa[39][3], b1[0], b1[1]);
                    mma16(d + 12, wa[39][0], wa[39][1], wa[39][2], wa[39][3], b1[2], b1[3]);
                    asm volatile("" : "+f"(d[0]), "+f"(d[4]), "+f"(d[8]), "+f"(d[12]) :: "memory");
                }
                if (s >= 0) bar_arrive(6, 512);
                mbar_wait(bar + B_HLO_FULL * 8, hp);
                bar_sync(9, 384);
                TR(6);
                wg_fence();
                #pragma unroll
                for (int kt = 0; kt < 12; kt++) wg_rs32(d, wa[kt], db0 + (uint64_t)(((kt >> 2) * 4096 + (kt & 3) * 32) >> 4), 1);
                wg_commit();
                #pragma unroll
                for (int kt = 12; kt < 39; kt++) wg_rs32(d, wa[kt], db0 + (uint64_t)(((kt >> 2) * 4096 + (kt & 3) * 32) >> 4), 1);
                wg_commit();
                wg_wait<1>();
                if (lane == 0) mbar_arrive(bar + B_HLO_FREE * 8);
                wg_wait<0>();
                if (lane == 0) mbar_arrive(bar + B_HHI_FREE * 8);
                TR(7);
                const int mi = lane >> 3, r = lane & 7;
                #pragma unroll
                for (int jj = 0; jj < 2; jj++) {
                    const int tok = 8 * (2 * jj + (mi >> 1)) + r, ch = 2 * w + (mi & 1);
                    stsm4t(dstx + tok * 128 + ((ch ^ r) << 4),
                           pack2(d[8 * jj + 0], d[8 * jj + 1]), pack2(d[8 * jj + 2], d[8 * jj + 3]),
                           pack2(d[8 * jj + 4], d[8 * jj + 5]), pack2(d[8 * jj + 6], d[8 * jj + 7]));
                }
                bar_arrive(8, 384);
                if (s < 0 && warp == 0) T3(11);
                if (s < 0) { bar_sync(0, 512); asm volatile("griddepcontrol.launch_dependents;" ::: "memory"); }
            }
        }
    } else if (wg == 2) {
        asm volatile("setmaxnreg.dec.sync.aligned.u32 64;");
        const int w = warp & 3;
        uint32_t res[4][4];
        {
            const bf16* src = Wo + ((size_t)h * DH + ((p + 1) % 3) * 64) * DM + (tile0 + warp) * 16 + 2 * t;
            #pragma unroll
            for (int kt = 0; kt < 4; kt++) {
                res[kt][0] = __ldg((const uint32_t*)(src + (size_t)(kt * 16 + g) * DM));
                res[kt][1] = __ldg((const uint32_t*)(src + (size_t)(kt * 16 + g) * DM + 8));
                res[kt][2] = __ldg((const uint32_t*)(src + (size_t)(kt * 16 + 8 + g) * DM));
                res[kt][3] = __ldg((const uint32_t*)(src + (size_t)(kt * 16 + 8 + g) * DM + 8));
            }
            #pragma unroll
            for (int kt = 0; kt < 4; kt++) {
                #pragma unroll
                for (int i = 0; i < 4; i++) res[kt][i] = movm(res[kt][i]);
            }
        }
        bar_sync(11, 256);
        if (tid == 256) {
            fence_async();
            mbar_expect(bar + B_WV * 8, 81920);
            #pragma unroll
            for (int i = 0; i < 5; i++) tma2d(sb + SM_WV + i * 16384, &maps.wv, h * DH + p * 64, i * 128, bar + B_WV * 8);
        }
        mbar_wait(bar + B_WV * 8, 0);
        if (w == 0) T3(3);
        const uint64_t da0 = make_desc(SBC + SM_WV, 16, 1024, 1);
        uint32_t vx[8], vm0 = 0, vm1 = 0;
        #pragma unroll
        for (int i = 0; i < 8; i++) vx[i] = 0;

        for (int s = -1; s < NSEG; s++) {
            FRESH(lane);
            const int g = lane >> 2, t = lane & 3, tid = warp * 32 + lane;
            if (s >= 0) {
                const uint32_t par = s & 1;
                mbar_wait(bar + B_MEM_FULL * 8, par);
                bar_sync(4, 352);
                TR(0);
                float dv[4];
                {
                    const uint64_t dbm = make_desc(SBC + SM_HB, 128, 128, 0);
                    wg_fence();
                    #pragma unroll
                    for (int kt = 0; kt < 40; kt++) {
                        wg_ss8(dv, da0 + (uint64_t)(kt * 128), dbm + (uint64_t)(kt * 16), kt > 0);
                        wg_commit();
                        if (kt < 39) wg_wait<1>();
                    }
                    wg_commit();
                }
                TR(1);
                bar_sync(5, 160);
                TR(2);
                uint32_t pb[5];
                #pragma unroll
                for (int j = 0; j < 5; j++) pb[j] = lds1(sb + SM_PM + j * 128 + lane * 4);
                float o0[4] = {0.f, 0.f, 0.f, 0.f}, o1[4] = {0.f, 0.f, 0.f, 0.f}, o2[4] = {0.f, 0.f, 0.f, 0.f};
                wg_wait<0>();
                TR(3);
                mma16(o0, vx[0], vx[1], vx[2], vx[3], pb[1], pb[2]);
                mma16(o1, vx[4], vx[5], vx[6], vx[7], pb[3], pb[4]);
                vm0 = pack2(dv[0], dv[1]); vm1 = pack2(dv[2], dv[3]);
                mma8(o2, vm0, vm1, pb[0]);
                if (s < NSEG - 1) {
                    const uint32_t q0 = pack2(o0[0] + o1[0] + o2[0], o0[1] + o1[1] + o2[1]), q1 = pack2(o0[2] + o1[2] + o2[2], o0[3] + o1[3] + o2[3]);
                    const uint32_t la = sb + SM_OS + (w * 16 + g) * 16 + t * 4;
                    #pragma unroll
                    for (int i = 1; i < 3; i++) {
                        const uint32_t rk = (p + i) % 3;
                        const uint32_t ra = mapa(la + (3 - i) * 1024, rk), rb = mapa(bar + B_O * 8, rk);
                        st_async1(ra, q0, rb);
                        st_async1(ra + 128, q1, rb);
                    }
                    sts1(la, q0);
                    sts1(la + 128, q1);
                    __syncwarp();
                    if (lane == 0) { mbar_arrive(bar + B_O1 * 8); mbar_arrive(bar + B_MEM_FREE * 8); }
                }
                TR(5);
                if (s < NSEG - 1) {
                    wo_phase<4, 4>(sb, warp, lane, res, par, (uint32_t)(s % 15) + 1u, tile0 + warp, h);
                    TR(4);
                    if (tid == 256) mbar_expect(bar + B_O * 8, 2048);
                }
                if (s < NSEG - 1) bar_sync(6, 512);
            }
            uint32_t vn[8];
            #pragma unroll
            for (int i = 0; i < 8; i++) vn[i] = 0;
            if (s < NSEG - 1) {
            float d[16];
            const uint32_t hp = (s + 1) & 1;
            const uint64_t db0 = make_desc(SBC + SM_HB, 16, 1024, 1);
            mbar_wait(bar + B_HHI_FULL * 8, hp);
            TR(6);
            wg_fence();
            #pragma unroll
            for (int kt = 12; kt < 40; kt++) wg_ss32(d, da0 + (uint64_t)(kt * 128), db0 + (uint64_t)(((kt >> 2) * 4096 + (kt & 3) * 32) >> 4), kt > 12);
            wg_commit();
            mbar_wait(bar + B_HLO_FULL * 8, hp);
            wg_fence();
            #pragma unroll
            for (int kt = 0; kt < 9; kt++) wg_ss32(d, da0 + (uint64_t)(kt * 128), db0 + (uint64_t)(((kt >> 2) * 4096 + (kt & 3) * 32) >> 4), 1);
            wg_commit();
            #pragma unroll
            for (int kt = 9; kt < 12; kt++) wg_ss32(d, da0 + (uint64_t)(kt * 128), db0 + (uint64_t)(((kt >> 2) * 4096 + (kt & 3) * 32) >> 4), 1);
            wg_commit();
            wg_wait<1>();
            bar_arrive(9, 384);
            wg_wait<0>();
            if (lane == 0) mbar_arrive(bar + B_HLO_FREE * 8);
            TR(7);
            if (lane == 0) mbar_arrive(bar + B_HHI_FREE * 8);
            #pragma unroll
            for (int i = 0; i < 8; i++) vn[i] = pack2(d[2 * i], d[2 * i + 1]);
            }
            if (s >= 0) {
                {
                    FRESH(lane);
                    mbar_wait(bar + B_XS * 8, s & 1);
                    if (w == 0 && lane == 0) mbar_expect(bar + B_XS * 8, 12288);
                    const uint32_t a = sb + SM_XS + (w >> 1) * 1536 + lane * 16 + (w & 1) * 8;
                    if (w == 0) xsoftmax<2>(a, lane >> 2, lane & 3);
                    else if (w == 1) xsoftmax<3>(a, lane >> 2, lane & 3);
                    else if (w == 2) xsoftmax<4>(a, lane >> 2, lane & 3);
                    else xsoftmax<5>(a, lane >> 2, lane & 3);
                }
                TR(8);
                bar_sync(7, 128);
                FRESH(lane);
                bf16* orow = g_ox + (size_t)(s * 32 + (lane >> 2)) * HD + h * DH + p * 64 + w * 16 + 2 * (lane & 3);
                {
                    const uint32_t pa = sb + SM_XS + lane * 16;
                    #pragma unroll
                    for (int mi = 0; mi < 2; mi++) {
                        float oa[4] = {0.f, 0.f, 0.f, 0.f}, ob[4] = {0.f, 0.f, 0.f, 0.f};
                        if (mi == 0) {
                            const uint4 p0 = lds4(pa);
                            const uint32_t p3 = lds1(pa + 1024 + 8);
                            mma8(oa, vm0, vm1, p0.x);
                            mma8(ob, vm0, vm1, p0.z);
                            mma16(oa, vx[0], vx[1], vx[2], vx[3], p0.y, 0u);
                            mma16(ob, vx[0], vx[1], vx[2], vx[3], p0.w, p3);
                        } else {
                            const uint4 p1 = lds4(pa + 1536), p2 = lds4(pa + 2560);
                            const uint32_t p4 = lds1(pa + 3584 + 8);
                            mma8(oa, vm0, vm1, p1.x);
                            mma8(ob, vm0, vm1, p1.z);
                            mma16(oa, vx[0], vx[1], vx[2], vx[3], p1.y, p2.x);
                            mma16(ob, vx[0], vx[1], vx[2], vx[3], p1.w, p2.z);
                            mma16(oa, vx[4], vx[5], vx[6], vx[7], p2.y, 0u);
                            mma16(ob, vx[4], vx[5], vx[6], vx[7], p2.w, p4);
                            if (lane < 3) mbar_arrive_remote(mapa(bar + B_XSFREE * 8, lane));
                        }
                        const uint32_t u0 = movm(pack2(oa[0], oa[1])), u1 = movm(pack2(oa[2], oa[3]));
                        const uint32_t u2 = movm(pack2(ob[0], ob[1])), u3 = movm(pack2(ob[2], ob[3]));
                        bf16* dst = orow + (size_t)(16 * mi) * HD;
                        *(uint32_t*)dst = u0;
                        *(uint32_t*)(dst + 8) = u1;
                        *(uint32_t*)(dst + 8 * HD) = u2;
                        *(uint32_t*)(dst + 8 * HD + 8) = u3;
                    }
                }
                TR(9);
                if (s == NSEG - 1) {
                    bar_sync(7, 128);
                    if (w == 3 && lane == 0) { signal_cnt(C_REC + 15); T2(400 + b); }
                    break;
                }
            }
            #pragma unroll
            for (int i = 0; i < 8; i++) vx[i] = vn[i];
            if (s >= 0) mbar_wait_cluster(bar + B_XSFREE * 8, s & 1);
            bar_sync(8, 384);
            TR(10);
            if (w < 3) xscores<2>(sb, p, w > 0, w == 2 ? 3 : 1, lane);
            else if ((s & 3) == 3 && s >= 0 && lane == 0) signal_cnt(C_REC + (s >> 2));
            __syncwarp();
            TR(11);
            if (s < 0) { bar_sync(0, 512); asm volatile("griddepcontrol.launch_dependents;" ::: "memory"); }
        }
    } else {
        asm volatile("setmaxnreg.dec.sync.aligned.u32 48;");
        const int w = warp & 3, lt = tid & 127;
        const uint32_t epoch = *(volatile uint32_t*)&g_epoch + 1u;
        if (b == 91) { if (lt < C_NUM) g_cnt[lt * 32] = 0u; __threadfence(); }
        if (b < 80) {
            #pragma unroll
            for (int i = 0; i < 2; i++) {
                const int idx = lt + i * 128, sl = idx >> 6, pg = (idx >> 5) & 1, wd = idx & 31;
                st_relaxed1(g_buf2 + (sl * 3 + (b >> 5)) * 2048 + pg * 1024 + (b & 31) * 32 + wd, 0xFFFFFFFFu);
            }
            __threadfence();
        }
        if (lane == 0 && w < 3) {
            int c = 0;
            if (w == 0) c = probe_blk(g_buf2 + 640 + (b & 31) * 8);
            else if (b < 80) c = probe_blk(g_buf1 + (b * 2 + (w - 1)) * 2048);
            else if (b < 92 && w == 1) c = probe_blk(g_buf2 + (b - 80) * 2048 + 960);
            asm volatile("st.shared.u8 [%0], %1;" :: "r"(sb + SM_CH + 96 + w), "r"(c) : "memory");
        }
        if (w == 0) T3(4);
        bar_sync(3, 128);
        uint32_t selmask;
        {
            const uint32_t c3 = lds1(sb + SM_CH + 96);
            const uint32_t cr = c3 & 1u, c1 = (c3 >> 8) & 1u, c2 = (c3 >> 16) & 1u;
            if (lt == 0 && b < 92) st_release1(&g_choice[b], (epoch << 2) | (b < 80 ? (c1 | (c2 << 1)) : (c1 ^ cr)));
            bar_sync(10, 256);
            if (w == 3) {
                if (lane == 0) { fence_async(); mbar_expect(bar + B_WO * 8, ntile * 6144 - 8192); }
                __syncwarp();
                if (lane < ntile) {
                    #pragma unroll
                    for (int e3 = 0; e3 < 3; e3++) {
                        const bool part = lane >= 8 && lane < 12;
                        if (part && e3 == 1) continue;
                        tma2d(sb + SM_WO + wo_tile_off(lane) + ((part && e3 == 2) ? 1 : e3) * 2048, &maps.wo,
                              (tile0 + lane) * 16, h * DH + ((e3 + p) % 3) * 64, bar + B_WO * 8);
                    }
                }
                __syncwarp();
            }
            if (w == 0) T3(5);
            if (lt < 92) {
                uint32_t v, guard = 0;
                while (true) {
                    v = ld_acquire1(&g_choice[lt]);
                    if ((v >> 2) == (epoch & 0x3fffffffu)) break;
                    __nanosleep(100);
                    if (++guard > (1u << 22)) __trap();
                }
                asm volatile("st.shared.u8 [%0], %1;" :: "r"(sb + SM_CH + lt), "r"(v & 3u) : "memory");
            }
            if (w == 0) T3(6);
            bar_sync(3, 128);
            selmask = (c1 << 12) | (c2 << 13);
            for (int i = 0; i < 12; i++) {
                uint32_t c; asm volatile("ld.shared.u8 %0, [%1];" : "=r"(c) : "r"(sb + SM_CH + 80 + i) : "memory");
                selmask |= ((c ^ cr) & 1u) << i;
            }
        }
        mbar_wait(bar + B_WO * 8, 0);
        if (w == 0) T3(8);
        bar_sync(0, 512);
        if (w == 0) T3(9);
        asm volatile("griddepcontrol.launch_dependents;" ::: "memory");
        const bool has_tile = (12 + w) < ntile;
        for (int s = 0; s < NSEG; s++) {
            const uint32_t par = s & 1;
            FRESH(lane);
            const int g = lane >> 2, t = lane & 3, lt = w * 32 + lane;
            if (s == 0) {
                mbar_wait(bar + B_HLO_FREE * 8, par);
                for (int k = lt; k < DM; k += 128) {
                    uint32_t v[4];
                    #pragma unroll
                    for (int i = 0; i < 4; i++) {
                        uint32_t lo = *(const uint16_t*)(mem0 + (2 * i) * DM + k), hi = *(const uint16_t*)(mem0 + (2 * i + 1) * DM + k);
                        v[i] = lo | (hi << 16);
                    }
                    asm volatile("st.shared.v4.u32 [%0], {%1,%2,%3,%4};" :: "r"(sb + SM_HB + k * 16), "r"(v[0]), "r"(v[1]), "r"(v[2]), "r"(v[3]) : "memory");
                }
            } else {
                const int sl = s & 3;
                const char* q = (const char*)g_buf2 + sl * 3 * 8192 + lt * 16;
                const uint32_t sm = selmask >> (sl * 3);
                const char* q0 = q + (sm & 1) * 4096;
                const char* q1 = q + 8192 + (sm & 2) * 2048;
                const char* q2 = q + 16384 + (sm & 4) * 1024;
                const uint32_t dst = sb + SM_HB + lt * 16;
                uint32_t guard = 0;
                mbar_wait(bar + B_HLO_FREE * 8, par);
                TR(10);
                while (true) {
                    const uint4 v0 = ld_relaxed4(q0), v1 = ld_relaxed4(q0 + 2048), v2 = ld_relaxed4(q1), v3 = ld_relaxed4(q1 + 2048), v4 = ld_relaxed4(q2);
                    sts4(dst, v0); sts4(dst + 2048, v1); sts4(dst + 4096, v2); sts4(dst + 6144, v3); sts4(dst + 8192, v4);
                    if (__all_sync(0xffffffffu, oks(v0) && oks(v1) && oks(v2) && oks(v3) && oks(v4))) break;
                    if (++guard > (1u << 22)) __trap();
                }
            }
            fence_async();
            __syncwarp();
            if (lane == 0) mbar_arrive(bar + B_MEM_FULL * 8);
            if (b == 0 && lt == 0) T2(300 + s);
            if (s == 0 && lt == 0) T2(200 + b);
            TR(0);
            if (w == 2) {
                mbar_wait(bar + B_MS * 8, par);
                TR(1);
                if (lane == 0) mbar_expect(bar + B_MS * 8, 3840);
                uint32_t pb[5];
                float sc[5][2];
                {
                    const uint32_t a = sb + SM_MS + lane * 8;
                    float2 u[5], v[5];
                    #pragma unroll
                    for (int j = 0; j < 5; j++) { u[j] = lds2f(a + j * 256); v[j] = lds2f(a + j * 256 + 1280); }
                    #pragma unroll
                    for (int j = 0; j < 5; j++) { sc[j][0] = u[j].x + v[j].x; sc[j][1] = u[j].y + v[j].y; }
                    #pragma unroll
                    for (int j = 0; j < 5; j++) u[j] = lds2f(a + j * 256 + 2560);
                    #pragma unroll
                    for (int j = 0; j < 5; j++) { sc[j][0] += u[j].x; sc[j][1] += u[j].y; }
                }
                softmax_core<5, false>(sc, g, t, pb);
                #pragma unroll
                for (int j = 0; j < 5; j++) sts1(sb + SM_PM + j * 128 + lane * 4, pb[j]);
                bar_arrive(5, 160);
                TR(2);
            }
            const uint32_t tag = (uint32_t)(s % 15) + 1u;
            if (s < NSEG - 1) {
                if (w == 3) {
                    const char* src = (const char*)g_ht + (size_t)(s + 1) * 40960;
                    if (s == 0) {
                        uint32_t guard = 0;
                        while (true) {
                            const uint32_t f0 = lane > 0 ? ld_acquire1(&g_hflag[lane]) : epoch, f1 = ld_acquire1(&g_hflag[32 + lane]);
                            if (__all_sync(0xffffffffu, f0 == epoch && f1 == epoch)) break;
                            if (++guard > (1u << 22)) __trap();
                        }
                        asm volatile("fence.proxy.async.global;" ::: "memory");
                    }
                    mbar_wait(bar + B_HHI_FREE * 8, par);
                    if (lane == 0) {
                        mbar_expect(bar + B_HHI_FULL * 8, 28672);
                        bulk_g2s(sb + SM_HB + 12288, src + 12288, 28672, sb + SM_BAR + B_HHI_FULL * 8);
                    }
                    mbar_wait(bar + B_MEM_FREE * 8, par);
                    if (lane == 0) {
                        mbar_expect(bar + B_HLO_FULL * 8, 12288);
                        bulk_g2s(sb + SM_HB, src, 12288, sb + SM_BAR + B_HLO_FULL * 8);
                    }
                    __syncwarp();
                }
                if (has_tile) wo_phase<0, 4>(sb, warp, lane, nullptr, par, tag, tile0 + warp, h);
                TR(4);
                bar_sync(6, 512);
            }
            if (s < NSEG - 1) {
                { const uint32_t c0 = clk32(); while (clk32() - c0 < H1_DELAY); }
                if (b < 80) {
                    FRESH(lane);
                    const char* rin0 = (const char*)g_buf1 + (size_t)(b * 2) * 8192 + ((selmask >> 12) & 1) * 4096 + (lane >> 2) * 256 + w * 64 + (lane & 3) * 16;
                    const char* rin1 = (const char*)g_buf1 + (size_t)(b * 2 + 1) * 8192 + ((selmask >> 13) & 1) * 4096 + (lane >> 2) * 256 + w * 64 + (lane & 3) * 16;
                    const int col = b * 8 + 2 * w + ((lane >> 1) & 1), wd = 2 * (lane & 1) + (lane >> 4);
                    const int sl = (lane & 8) ? ((s + 3) & 3) : ((s + 1) & 3);
                    uint32_t* dst = g_buf2 + (sl * 3 + (col >> 8)) * 2048 + ((lane >> 2) & 1) * 1024 + (col & 255) * 4 + wd;
                    asm volatile("" : "+l"(dst));
                    uint4 v0, v1, v2, v3;
                    uint32_t guard = 0;
                    while (true) {
                        v0 = ld_relaxed4(rin0); v1 = ld_relaxed4(rin0 + 2048);
                        v2 = ld_relaxed4(rin1); v3 = ld_relaxed4(rin1 + 2048);
                        if (__all_sync(0xffffffffu, ok4(v0, tag) && ok4(v1, tag) && ok4(v2, tag) && ok4(v3, tag))) break;
                        if (++guard > (1u << 22)) __trap();
                    }
                    TR(11);
                    const float a0 = (uf(v0.x) + uf(v1.x)) + (uf(v2.x) + uf(v3.x)), a1 = (uf(v0.y) + uf(v1.y)) + (uf(v2.y) + uf(v3.y));
                    const float a2 = (uf(v0.z) + uf(v1.z)) + (uf(v2.z) + uf(v3.z)), a3 = (uf(v0.w) + uf(v1.w)) + (uf(v2.w) + uf(v3.w));
                    const bool u16 = lane & 16;
                    float m0 = (u16 ? a2 : a0) + __shfl_xor_sync(0xffffffffu, u16 ? a0 : a2, 16);
                    float m1 = (u16 ? a3 : a1) + __shfl_xor_sync(0xffffffffu, u16 ? a1 : a3, 16);
                    m0 += __shfl_xor_sync(0xffffffffu, m0, 8); m1 += __shfl_xor_sync(0xffffffffu, m1, 8);
                    m0 += __shfl_xor_sync(0xffffffffu, m0, 4); m1 += __shfl_xor_sync(0xffffffffu, m1, 4);
                    st_relaxed1(dst, (lane & 8) ? 0xFFFFFFFFu : pack2(m0, m1));
                    TR(12);
                }
            }
        }
    }
    cluster_sync();
}

constexpr int G_STAGES = 6;
constexpr int G_STAGE_BYTES = 32768;
constexpr int G_SMEM = G_STAGES * G_STAGE_BYTES + 1024 + 256 + 2048 + 10240;

__device__ __forceinline__ void wg_ss128(float* d, uint64_t da, uint64_t db, int sc) {
    asm volatile("{\n\t.reg .pred p;\n\tsetp.ne.b32 p, %66, 0;\n\t"
        "wgmma.mma_async.sync.aligned.m64n128k16.f32.bf16.bf16 "
        "{%0,%1,%2,%3,%4,%5,%6,%7,%8,%9,%10,%11,%12,%13,%14,%15,%16,%17,%18,%19,%20,%21,%22,%23,%24,%25,%26,%27,%28,%29,%30,%31,"
        "%32,%33,%34,%35,%36,%37,%38,%39,%40,%41,%42,%43,%44,%45,%46,%47,%48,%49,%50,%51,%52,%53,%54,%55,%56,%57,%58,%59,%60,%61,%62,%63}, "
        "%64, %65, p, 1, 1, 0, 1;\n\t}"
        : "+f"(d[0]), "+f"(d[1]), "+f"(d[2]), "+f"(d[3]), "+f"(d[4]), "+f"(d[5]), "+f"(d[6]), "+f"(d[7]),
          "+f"(d[8]), "+f"(d[9]), "+f"(d[10]), "+f"(d[11]), "+f"(d[12]), "+f"(d[13]), "+f"(d[14]), "+f"(d[15]),
          "+f"(d[16]), "+f"(d[17]), "+f"(d[18]), "+f"(d[19]), "+f"(d[20]), "+f"(d[21]), "+f"(d[22]), "+f"(d[23]),
          "+f"(d[24]), "+f"(d[25]), "+f"(d[26]), "+f"(d[27]), "+f"(d[28]), "+f"(d[29]), "+f"(d[30]), "+f"(d[31]),
          "+f"(d[32]), "+f"(d[33]), "+f"(d[34]), "+f"(d[35]), "+f"(d[36]), "+f"(d[37]), "+f"(d[38]), "+f"(d[39]),
          "+f"(d[40]), "+f"(d[41]), "+f"(d[42]), "+f"(d[43]), "+f"(d[44]), "+f"(d[45]), "+f"(d[46]), "+f"(d[47]),
          "+f"(d[48]), "+f"(d[49]), "+f"(d[50]), "+f"(d[51]), "+f"(d[52]), "+f"(d[53]), "+f"(d[54]), "+f"(d[55]),
          "+f"(d[56]), "+f"(d[57]), "+f"(d[58]), "+f"(d[59]), "+f"(d[60]), "+f"(d[61]), "+f"(d[62]), "+f"(d[63])
        : "l"(da), "l"(db), "r"(sc));
}

#define SP0_LAST 12
#define SP2_LAST 6
enum { J_MOD = 0, J_G0, J_LN, J_G1, J_G2, J_FIN, J_END };
__host__ __device__ constexpr int sp0(int b) { return b >= 15 ? SP0_LAST : 3; }
__host__ __device__ constexpr int sp2(int b) { return b >= 15 ? SP2_LAST : 3; }
__host__ __device__ constexpr int njr(int b) { return b >= 15 ? 16 : 8; }
struct JobTab { uint32_t n; uint32_t j[1200]; };
constexpr uint32_t mkjob(int ty, int b, int n, int k0, int nk, int ks) {
    return (uint32_t)(ty | (b << 3) | (n << 7) | (k0 << 11) | (nk << 18) | (ks << 25));
}
constexpr void add_jobs(JobTab& t, int ty, int b) {
    if (b < 0) return;
    if (ty == J_G0) { for (int ks = 0; ks < sp0(b); ks++) for (int n = 0; n < 5; n++) t.j[t.n++] = mkjob(ty, b, n, ks * (96 / sp0(b)), 96 / sp0(b), ks); }
    else if (ty == J_G2) { for (int ks = 0; ks < sp2(b); ks++) for (int n = 0; n < 5; n++) t.j[t.n++] = mkjob(ty, b, n, ks * (24 / sp2(b)), 24 / sp2(b), ks); }
    else if (ty == J_G1) { for (int n = 0; n < 12; n++) t.j[t.n++] = mkjob(ty, b, n, 0, 10, 0); }
    else { for (int n = 0; n < njr(b); n++) t.j[t.n++] = mkjob(ty, b, n, 0, 16 / njr(b), ty == J_LN ? sp0(b) : sp2(b)); }
}
constexpr JobTab make_tab() {
    JobTab t = {};
    for (int i = 20; i < 60; i++) t.j[t.n++] = mkjob(J_MOD, 0, 0, i, 0, 0);
    for (int b = 0; b < 15; b++) {
        add_jobs(t, J_G0, b); add_jobs(t, J_G1, b - 1); add_jobs(t, J_FIN, b - 2); add_jobs(t, J_G2, b - 1); add_jobs(t, J_LN, b);
    }
    add_jobs(t, J_FIN, 13); add_jobs(t, J_G1, 14);
    add_jobs(t, J_G0, 15); add_jobs(t, J_G2, 14); add_jobs(t, J_LN, 15); add_jobs(t, J_FIN, 14);
    add_jobs(t, J_G1, 15); add_jobs(t, J_G2, 15); add_jobs(t, J_FIN, 15);
    return t;
}
__constant__ JobTab c_jobs = make_tab();

__device__ __forceinline__ bool cnt_ge(int idx, uint32_t target) { return ld_acquire1(g_cnt + idx * 32) >= target; }
__device__ __forceinline__ void cnt_wait(int idx, uint32_t target) {
    uint32_t guard = 0;
    while (!cnt_ge(idx, target)) { __nanosleep(64); if (++guard > (1u << 22)) __trap(); }
}

struct SMaps { CUtensorMap ox, wo, h2, w1, act, w2; };

__global__ void __launch_bounds__(384, 1)
k_side(const __grid_constant__ SMaps maps, const bf16* __restrict__ xin, const bf16* __restrict__ cvec,
       const bf16* __restrict__ wmod, bf16* __restrict__ outp) {
    extern __shared__ uint8_t smem_raw[];
    const uint32_t sb = (smem_u32(smem_raw) + 1023u) & ~1023u;
    const uint32_t bars = sb + G_STAGES * G_STAGE_BYTES;
    float* red = (float*)(smem_raw + (bars + 256 - smem_u32(smem_raw)));
    const int tid = threadIdx.x, lane = tid & 31, wg = tid >> 7;
    if (tid == 0) T2(500 + blockIdx.x);
    if (tid == 0) {
        for (int i = 0; i < G_STAGES; i++) { mbar_init(bars + i * 8, 1); mbar_init(bars + 64 + i * 8, 8); }
        for (int i = 0; i < 2; i++) { mbar_init(bars + 128 + i * 8, 1); mbar_init(bars + 144 + i * 8, 8); }
        asm volatile("fence.mbarrier_init.release.cluster;" ::: "memory");
    }
    __syncthreads();
    if (wg == 0) {
        if (tid == 0) {
            uint32_t st = 0, ph = 1;
            for (uint32_t it = 0;; it++) {
                const uint32_t ji = atomicAdd(g_cnt + C_Q * 32, 1u);
                const uint32_t job = ji < c_jobs.n ? c_jobs.j[ji] : (uint32_t)J_END;
                if (ji == 0) g_epoch = g_epoch + 1u;
                const int ty = job & 7, b = (job >> 3) & 15, n = (job >> 7) & 15, k0 = (job >> 11) & 127, nk = (job >> 18) & 127;
                const uint32_t sl = it & 1;
                mbar_wait(bars + 144 + sl * 8, ((it >> 1) & 1) ^ 1);
                sts1(bars + 160 + sl * 4, job);
                if (ty == J_G0 || ty == J_G1 || ty == J_G2) {
                    if (b >= PRING && ty != J_G1) cnt_wait((ty == J_G0 ? C_LN : C_FIN) + b - PRING, njr(b - PRING));
                    mbar_arrive(bars + 128 + sl * 8);
                    const CUtensorMap* mA = ty == J_G0 ? &maps.ox : (ty == J_G1 ? &maps.h2 : &maps.act);
                    const CUtensorMap* mB = ty == J_G0 ? &maps.wo : (ty == J_G1 ? &maps.w1 : &maps.w2);
                    const int didx = ty == J_G0 ? C_REC + b : (ty == J_G1 ? C_LN + b : C_G1 + b);
                    const uint32_t dtgt = ty == J_G0 ? 96u : (ty == J_G1 ? (uint32_t)njr(b) : 12u);
                    int pre = 0;
                    if (!cnt_ge(didx, dtgt)) {
                        pre = nk < G_STAGES ? nk : G_STAGES;
                        uint32_t s2 = st, p2 = ph;
                        for (int i = 0; i < pre; i++) {
                            mbar_wait(bars + 64 + s2 * 8, p2);
                            const uint32_t a = sb + s2 * G_STAGE_BYTES;
                            mbar_expect(bars + s2 * 8, G_STAGE_BYTES);
                            tma2d(a + 16384, mB, n * 128, (k0 + i) * 64, bars + s2 * 8);
                            tma2d(a + 16384 + 8192, mB, n * 128 + 64, (k0 + i) * 64, bars + s2 * 8);
                            if (++s2 == G_STAGES) { s2 = 0; p2 ^= 1; }
                        }
                        cnt_wait(didx, dtgt);
                    }
                    asm volatile("fence.proxy.async.global;" ::: "memory");
                    T2(1024 + ji * 4 + 1);
                    for (int i = 0; i < nk; i++) {
                        const uint32_t a = sb + st * G_STAGE_BYTES;
                        if (i >= pre) {
                            mbar_wait(bars + 64 + st * 8, ph);
                            mbar_expect(bars + st * 8, G_STAGE_BYTES);
                        }
                        tma2d(a, mA, (k0 + i) * 64, b * 128, bars + st * 8);
                        if (i >= pre) {
                            tma2d(a + 16384, mB, n * 128, (k0 + i) * 64, bars + st * 8);
                            tma2d(a + 16384 + 8192, mB, n * 128 + 64, (k0 + i) * 64, bars + st * 8);
                        }
                        if (++st == G_STAGES) { st = 0; ph ^= 1; }
                    }
                } else {
                    if (ty == J_LN) { bulk_pf(xin + (size_t)(b * 128 + n * nk * 8) * DM, nk * 8 * DM * 2); cnt_wait(C_MOD, 40u); cnt_wait(C_G0 + b, 5u * sp0(b)); }
                    else if (ty == J_FIN) cnt_wait(C_G2 + b, 5u * sp2(b));
                    if (ji < 1200) T2(1024 + ji * 4 + 1);
                    mbar_arrive(bars + 128 + sl * 8);
                    if (ty == J_END) break;
                }
            }
        }
    } else {
        const int cw = wg - 1, ct = tid - 128, cwarp = ct >> 5;
        uint32_t st = 0, ph = 0;
        float* smod = red + 512;
        bool have_mod = false;
        auto load_mod = [&]() {
            for (int i = ct; i < DM; i += 256) *(float4*)(smod + i * 4) = __ldcg((const float4*)(g_mod + 2 * DM + i * 4));
            bar_sync(1, 256);
            have_mod = true;
        };
        {
            if (ct == 0) red[0] = cnt_ge(C_MOD, 40u) ? 1.0f : 0.0f;
            bar_sync(1, 256);
            const bool rdy = red[0] != 0.0f;
            bar_sync(1, 256);
            if (rdy) load_mod();
        }
        for (uint32_t it = 0;; it++) {
            const uint32_t sl = it & 1;
            mbar_wait(bars + 128 + sl * 8, (it >> 1) & 1);
            const uint32_t job = lds1(bars + 160 + sl * 4);
            __syncwarp();
            if (lane == 0) mbar_arrive(bars + 144 + sl * 8);
            const int ty = job & 7, b = (job >> 3) & 15, n = (job >> 7) & 15, k0 = (job >> 11) & 127, nk = (job >> 18) & 127, ks = (job >> 25) & 15;
            if (ty == J_END) break;
            int sig = -1;
            if (ty == J_G0 || ty == J_G1 || ty == J_G2) {
                float d[64];
                #pragma unroll
                for (int i = 0; i < 64; i++) d[i] = 0.f;
                uint32_t pst = 0;
                for (int kb = 0; kb < nk; kb++) {
                    mbar_wait(bars + st * 8, ph);
                    const uint32_t a = sb + st * G_STAGE_BYTES;
                    const uint64_t da = make_desc(a + cw * 8192, 16, 1024, 1);
                    const uint64_t db = make_desc(a + 16384, 8192, 1024, 1);
                    wg_fence();
                    #pragma unroll
                    for (int k = 0; k < 4; k++) wg_ss128(d, da + (uint64_t)(k * 2), db + (uint64_t)(k * 128), 1);
                    wg_commit();
                    if (kb > 0) {
                        wg_wait<1>();
                        if (lane == 0) mbar_arrive(bars + 64 + pst * 8);
                    }
                    pst = st;
                    if (++st == G_STAGES) { st = 0; ph ^= 1; }
                }
                wg_wait<0>();
                if (lane == 0) mbar_arrive(bars + 64 + pst * 8);
                const int g = lane >> 2, t = lane & 3;
                if (ty == J_G1) {
                    #pragma unroll
                    for (int hf = 0; hf < 2; hf++) {
                        bf16* o = g_act + (size_t)(b * 128 + cwarp * 16 + g + 8 * hf) * FF + n * 128 + 8 * t;
                        #pragma unroll
                        for (int q = 0; q < 4; q++) {
                            uint32_t u[4];
                            #pragma unroll
                            for (int i = 0; i < 4; i++) {
                                const float a0 = bfr(d[4 * (4 * q + i) + 2 * hf]), a1 = bfr(d[4 * (4 * q + i) + 2 * hf + 1]);
                                u[i] = pack2(__fdividef(a0, 1.0f + __expf(-a0)), __fdividef(a1, 1.0f + __expf(-a1)));
                            }
                            const bool o1 = t & 1, o2 = t & 2;
                            uint32_t x0 = __shfl_xor_sync(0xffffffffu, o1 ? u[0] : u[1], 1), x1 = __shfl_xor_sync(0xffffffffu, o1 ? u[2] : u[3], 1);
                            if (o1) { u[0] = x0; u[2] = x1; } else { u[1] = x0; u[3] = x1; }
                            x0 = __shfl_xor_sync(0xffffffffu, o2 ? u[0] : u[2], 2); x1 = __shfl_xor_sync(0xffffffffu, o2 ? u[1] : u[3], 2);
                            if (o2) { u[0] = x0; u[1] = x1; } else { u[2] = x0; u[3] = x1; }
                            *(uint4*)(o + q * 32) = make_uint4(u[0], u[1], u[2], u[3]);
                        }
                    }
                    sig = C_G1 + b;
                } else {
                    float* o = (ty == J_G0 ? g_p0 : g_p2) + ((size_t)((b % PRING) * PMAX + ks) * 128 + cwarp * 16 + g) * DM + n * 128 + 2 * t;
                    #pragma unroll
                    for (int hf = 0; hf < 2; hf++) {
                        #pragma unroll
                        for (int j = 0; j < 16; j++)
                            *(float2*)(o + hf * 8 * DM + j * 8) = make_float2(d[4 * j + 2 * hf], d[4 * j + 2 * hf + 1]);
                    }
                    sig = (ty == J_G0 ? C_G0 : C_G2) + b;
                }
            } else if (ty == J_MOD) {
                mod_chunk<256, 2>(cvec, wmod, k0 * 64, ct, red);
                sig = C_MOD;
            } else {
                const bool ln = ty == J_LN;
                if (!have_mod) load_mod();
                const float* gm = smod + (ln ? 0 : 3) * DM + lane * 4;
                for (int r = 0; r < nk; r++) {
                    const int lr = (n * nk + r) * 8 + cwarp, row = b * 128 + lr;
                    const float* pp = (ln ? g_p0 : g_p2) + ((size_t)((b % PRING) * PMAX) * 128 + lr) * DM + lane * 4;
                    const bf16* xs = (ln ? xin : (const bf16*)g_x1) + (size_t)row * DM + lane * 4;
                    float v[5][4];
                    uint2 xv[5];
                    #pragma unroll
                    for (int i = 0; i < 5; i++) {
                        xv[i] = __ldcg((const uint2*)(xs + i * 128));
                        v[i][0] = 0.f; v[i][1] = 0.f; v[i][2] = 0.f; v[i][3] = 0.f;
                    }
                    if (ks == 3) {
                        float4 a[3][5];
                        #pragma unroll
                        for (int q = 0; q < 3; q++) {
                            #pragma unroll
                            for (int i = 0; i < 5; i++) a[q][i] = __ldcg((const float4*)(pp + (size_t)q * 128 * DM + i * 128));
                        }
                        #pragma unroll
                        for (int q = 0; q < 3; q++) {
                            #pragma unroll
                            for (int i = 0; i < 5; i++) { v[i][0] += a[q][i].x; v[i][1] += a[q][i].y; v[i][2] += a[q][i].z; v[i][3] += a[q][i].w; }
                        }
                    } else {
                        for (int q0 = 0; q0 < ks; q0 += 6) {
                            float4 a[6][5];
                            #pragma unroll
                            for (int q = 0; q < 6; q++) {
                                #pragma unroll
                                for (int i = 0; i < 5; i++) a[q][i] = __ldcg((const float4*)(pp + (size_t)(q0 + q) * 128 * DM + i * 128));
                            }
                            #pragma unroll
                            for (int q = 0; q < 6; q++) {
                                #pragma unroll
                                for (int i = 0; i < 5; i++) { v[i][0] += a[q][i].x; v[i][1] += a[q][i].y; v[i][2] += a[q][i].z; v[i][3] += a[q][i].w; }
                            }
                        }
                    }
                    bf16* dst = (ln ? (bf16*)g_x1 : outp) + (size_t)row * DM + lane * 4;
                    #pragma unroll
                    for (int i = 0; i < 5; i++) {
                        const float4 gg = *(const float4*)(gm + i * 128);
                        const uint32_t o0 = pack2(bflo(xv[i].x) + bfr(gg.x * bfr(v[i][0])), bfhi(xv[i].x) + bfr(gg.y * bfr(v[i][1])));
                        const uint32_t o1 = pack2(bflo(xv[i].y) + bfr(gg.z * bfr(v[i][2])), bfhi(xv[i].y) + bfr(gg.w * bfr(v[i][3])));
                        *(uint2*)(dst + i * 128) = make_uint2(o0, o1);
                        v[i][0] = bflo(o0); v[i][1] = bfhi(o0); v[i][2] = bflo(o1); v[i][3] = bfhi(o1);
                    }
                    if (ln) {
                        float mb, sd;
                        ln_stats(v, mb, sd);
                        #pragma unroll
                        for (int i = 0; i < 5; i++) {
                            const float4 sh = *(const float4*)(gm + DM + i * 128), sc = *(const float4*)(gm + 2 * DM + i * 128);
                            *(uint2*)(g_h2 + (size_t)row * DM + lane * 4 + i * 128) = ln_apply(v[i], mb, sd, sc, sh);
                        }
                    }
                }
                if (ln) sig = C_LN + b; else if (b < 16 - PRING) sig = C_FIN + b;
            }
            if (sig >= 0) {
                bar_sync(1, 256);
                if (ct == 0) signal_cnt(sig);
            }
            if (ct == 0) T2(1024 + ji * 4 + 2);
        }
    }
}

typedef CUresult (*EncodeFn)(CUtensorMap*, CUtensorMapDataType, cuuint32_t, void*, const cuuint64_t*, const cuuint64_t*,
                             const cuuint32_t*, const cuuint32_t*, CUtensorMapInterleave, CUtensorMapSwizzle,
                             CUtensorMapL2promotion, CUtensorMapFloatOOBfill);

static void make_map(EncodeFn fn, CUtensorMap* m, const void* ptr, uint64_t inner, uint64_t outer, uint32_t bi, uint32_t bo,
                     CUtensorMapSwizzle sw = CU_TENSOR_MAP_SWIZZLE_128B) {
    cuuint64_t dims[2] = {inner, outer};
    cuuint64_t strides[1] = {inner * 2};
    cuuint32_t box[2] = {bi, bo};
    cuuint32_t es[2] = {1, 1};
    fn(m, CU_TENSOR_MAP_DATA_TYPE_BFLOAT16, 2, (void*)ptr, dims, strides, box, es, CU_TENSOR_MAP_INTERLEAVE_NONE,
       sw, CU_TENSOR_MAP_L2_PROMOTION_L2_256B, CU_TENSOR_MAP_FLOAT_OOB_FILL_NONE);
}

extern "C" void kernel_launch(void* const* d_in, const int* in_sizes, int n_in, void* d_out, int out_size) {
    const bf16* x = (const bf16*)d_in[0];
    const bf16* mem0 = (const bf16*)d_in[1];
    const bf16* Wq = (const bf16*)d_in[2];
    const bf16* Wk = (const bf16*)d_in[3];
    const bf16* Wv = (const bf16*)d_in[4];
    const bf16* Wo = (const bf16*)d_in[5];
    const bf16* w1 = (const bf16*)d_in[8];
    const bf16* w2 = (const bf16*)d_in[9];
    const bf16* c = (const bf16*)d_in[10];
    const bf16* wmod = (const bf16*)d_in[11];
    bf16* out = (bf16*)d_out;

    static EncodeFn enc = nullptr;
    static void *p_ox, *p_x1, *p_h2, *p_act;
    if (!enc) {
        cudaDriverEntryPointQueryResult qr;
        void* f = nullptr;
        cudaGetDriverEntryPoint("cuTensorMapEncodeTiled", &f, cudaEnableDefault, &qr);
        enc = (EncodeFn)f;
        cudaGetSymbolAddress(&p_ox, g_ox);
        cudaGetSymbolAddress(&p_x1, g_x1);
        cudaGetSymbolAddress(&p_h2, g_h2);
        cudaGetSymbolAddress(&p_act, g_act);
        cudaFuncSetAttribute(k_rec, cudaFuncAttributeMaxDynamicSharedMemorySize, SM_TOTAL);
        cudaFuncSetAttribute(k_side, cudaFuncAttributeMaxDynamicSharedMemorySize, G_SMEM);
    }
    RMaps rm;
    make_map(enc, &rm.wq, Wq, HD, DM, 64, 128);
    make_map(enc, &rm.wk, Wk, HD, DM, 64, 128);
    make_map(enc, &rm.wv, Wv, HD, DM, 64, 128);
    make_map(enc, &rm.wo, Wo, DM, HD, 16, 64, CU_TENSOR_MAP_SWIZZLE_32B);
    make_map(enc, &rm.wop, Wo, DM, HD, 224, 192, CU_TENSOR_MAP_SWIZZLE_NONE);
    SMaps m;
    make_map(enc, &m.ox, p_ox, HD, SEQ, 64, 128);
    make_map(enc, &m.wo, Wo, DM, HD, 64, 64);
    make_map(enc, &m.h2, p_h2, DM, SEQ, 64, 128);
    make_map(enc, &m.w1, w1, FF, DM, 64, 64);
    make_map(enc, &m.act, p_act, FF, SEQ, 64, 128);
    make_map(enc, &m.w2, w2, DM, FF, 64, 64);

    cudaStream_t st = cudaStreamPerThread;
    {
        cudaLaunchConfig_t cfg = {};
        cfg.gridDim = dim3(96); cfg.blockDim = dim3(512); cfg.dynamicSmemBytes = SM_TOTAL; cfg.stream = st;
        cudaLaunchAttribute at[2];
        at[0].id = cudaLaunchAttributeClusterDimension;
        at[0].val.clusterDim.x = 3; at[0].val.clusterDim.y = 1; at[0].val.clusterDim.z = 1;
        cfg.attrs = at; cfg.numAttrs = 1;
        cudaLaunchKernelEx(&cfg, k_rec, rm, mem0, Wo, x, c, wmod);
    }
    {
        cudaLaunchConfig_t cfg = {};
        cfg.gridDim = dim3(SIDE_CTAS); cfg.blockDim = dim3(384); cfg.dynamicSmemBytes = G_SMEM; cfg.stream = st;
        cudaLaunchAttribute at[1];
        at[0].id = cudaLaunchAttributeProgrammaticStreamSerialization;
        at[0].val.programmaticStreamSerializationAllowed = 1;
        cfg.attrs = at; cfg.numAttrs = 1;
        cudaLaunchKernelEx(&cfg, k_side, m, x, c, wmod, out);
    }
}
```

```cpp
#include <cuda_runtime.h>
#include <cuda_bf16.h>
#include <cuda.h>
#include <stdint.h>

typedef __nv_bfloat16 bf16;
#define VX_THROTTLE 1
#define H1_DELAY 400
#define H1_BACK 0
#define VM_THROTTLE 1
#define PRE_TRIG 0
#define TMA_DELAY 300
#define PF_DELAY 1500
#define SIDE_CTAS 132

constexpr int SEQ = 2048, DM = 640, NH = 32, DH = 192, NSEG = 64, FF = 1536, HD = NH * DH;

__device__ __align__(128) float g_mod[6 * DM];
__device__ __align__(1024) bf16 g_ht[(size_t)SEQ * DM];
__device__ __align__(1024) bf16 g_ox[(size_t)SEQ * HD];
__device__ __align__(1024) bf16 g_x1[(size_t)SEQ * DM];
__device__ __align__(1024) bf16 g_h2[(size_t)SEQ * DM];
__device__ __align__(1024) bf16 g_act[(size_t)SEQ * FF];
__device__ __align__(8192) uint32_t g_buf1[80 * 2 * 2048];
__device__ __align__(8192) uint32_t g_buf2[4 * 3 * 2048];
__device__ uint32_t g_choice[128];
__device__ uint32_t g_epoch;
__device__ uint32_t g_hflag[64];
__device__ __align__(128) uint32_t g_modx[2 * DM];
#define T2(i)
#define T3(i)
enum { C_Q = 0, C_MOD = 1, C_REC = 2, C_G0 = 18, C_LN = 34, C_G1 = 50, C_G2 = 66, C_FIN = 82, C_NUM = 98 };
__device__ __align__(128) uint32_t g_cnt[C_NUM * 32];
constexpr int PMAX = 12;
constexpr int PRING = 4;
__device__ __align__(1024) float g_p0[(size_t)PRING * PMAX * 128 * DM];
__device__ __align__(1024) float g_p2[(size_t)PRING * PMAX * 128 * DM];
#define TR(k)

#define FRESH(x) asm volatile("" : "+r"(x))
__device__ __forceinline__ float bfr(float x) { uint32_t r; asm("cvt.rn.bf16x2.f32 %0, %1, %2;" : "=r"(r) : "f"(x), "f"(0.0f)); return __uint_as_float(r); }
__device__ __forceinline__ uint32_t pack2(float a, float b) {
    uint32_t r; asm("cvt.rn.bf16x2.f32 %0, %1, %2;" : "=r"(r) : "f"(b), "f"(a)); return r;
}
__device__ __forceinline__ float bflo(uint32_t v) { return __uint_as_float(v << 16); }
__device__ __forceinline__ float bfhi(uint32_t v) { return __uint_as_float(v & 0xffff0000u); }
__device__ __forceinline__ float ex2(float x) { float r; asm("ex2.approx.ftz.f32 %0, %1;" : "=f"(r) : "f"(x)); return r; }
__device__ __forceinline__ float rcpf(float x) { float r; asm("rcp.approx.ftz.f32 %0, %1;" : "=f"(r) : "f"(x)); return r; }
__device__ __forceinline__ void score2(float& a, float& b) {
    const float SCALE = 0.07216878364870322f;
    uint32_t u = pack2(a, b);
    u = pack2(bflo(u) * SCALE, bfhi(u) * SCALE);
    a = bflo(u); b = bfhi(u);
}
__device__ __forceinline__ uint32_t smem_u32(const void* p) { return (uint32_t)__cvta_generic_to_shared(p); }

__device__ __forceinline__ void mbar_init(uint32_t bar, uint32_t cnt) {
    asm volatile("mbarrier.init.shared::cta.b64 [%0], %1;" :: "r"(bar), "r"(cnt) : "memory");
}
__device__ __forceinline__ void mbar_arrive(uint32_t bar) {
    asm volatile("mbarrier.arrive.shared::cta.b64 _, [%0];" :: "r"(bar) : "memory");
}
__device__ __forceinline__ void mbar_expect(uint32_t bar, uint32_t bytes) {
    asm volatile("mbarrier.arrive.expect_tx.shared::cta.b64 _, [%0], %1;" :: "r"(bar), "r"(bytes) : "memory");
}
__device__ __forceinline__ bool mbar_try(uint32_t bar, uint32_t parity) {
    uint32_t ok;
    asm volatile("{\n\t.reg .pred p;\n\tmbarrier.try_wait.parity.shared::cta.b64 p, [%1], %2;\n\tselp.u32 %0, 1, 0, p;\n\t}"
                 : "=r"(ok) : "r"(bar), "r"(parity) : "memory");
    return ok != 0;
}
__device__ __forceinline__ bool mbar_try_cluster(uint32_t bar, uint32_t parity) {
    uint32_t ok;
    asm volatile("{\n\t.reg .pred p;\n\tmbarrier.try_wait.parity.acquire.cluster.shared::cta.b64 p, [%1], %2;\n\tselp.u32 %0, 1, 0, p;\n\t}"
                 : "=r"(ok) : "r"(bar), "r"(parity) : "memory");
    return ok != 0;
}
__device__ __forceinline__ void mbar_wait(uint32_t bar, uint32_t parity) {
    uint32_t guard = 0;
    while (!mbar_try(bar, parity)) { if (++guard > (1u << 22)) __trap(); }
}
__device__ __forceinline__ void mbar_wait_cluster(uint32_t bar, uint32_t parity) {
    uint32_t guard = 0;
    while (!mbar_try_cluster(bar, parity)) { if (++guard > (1u << 22)) __trap(); }
}
__device__ __forceinline__ void bar_sync(int id, int n) { asm volatile("bar.sync %0, %1;" :: "r"(id), "r"(n) : "memory"); }
__device__ __forceinline__ void bar_arrive(int id, int n) { asm volatile("bar.arrive %0, %1;" :: "r"(id), "r"(n) : "memory"); }
__device__ __forceinline__ void sts1(uint32_t a, uint32_t v) { asm volatile("st.shared.u32 [%0], %1;" :: "r"(a), "r"(v) : "memory"); }
__device__ __forceinline__ uint32_t lds1(uint32_t a) { uint32_t v; asm volatile("ld.shared.u32 %0, [%1];" : "=r"(v) : "r"(a) : "memory"); return v; }
__device__ __forceinline__ void fence_async() { asm volatile("fence.proxy.async.shared::cta;" ::: "memory"); }
__device__ __forceinline__ void cluster_sync() {
    asm volatile("barrier.cluster.arrive.release.aligned;\n\tbarrier.cluster.wait.acquire.aligned;" ::: "memory");
}
__device__ __forceinline__ uint32_t mapa(uint32_t a, uint32_t rank) {
    uint32_t r; asm("mapa.shared::cluster.u32 %0, %1, %2;" : "=r"(r) : "r"(a), "r"(rank)); return r;
}
__device__ __forceinline__ void st_async1(uint32_t a, uint32_t v, uint32_t bar) {
    asm volatile("st.async.weak.shared::cluster.mbarrier::complete_tx::bytes.b32 [%0], %1, [%2];" :: "r"(a), "r"(v), "r"(bar) : "memory");
}
__device__ __forceinline__ void st_async2(uint32_t a, float x, float y, uint32_t bar) {
    asm volatile("st.async.weak.shared::cluster.mbarrier::complete_tx::bytes.v2.f32 [%0], {%1,%2}, [%3];" :: "r"(a), "f"(x), "f"(y), "r"(bar) : "memory");
}
__device__ __forceinline__ void st_async4(uint32_t a, const float* c, uint32_t bar) {
    asm volatile("st.async.weak.shared::cluster.mbarrier::complete_tx::bytes.v4.f32 [%0], {%1,%2,%3,%4}, [%5];"
                 :: "r"(a), "f"(c[0]), "f"(c[1]), "f"(c[2]), "f"(c[3]), "r"(bar) : "memory");
}
__device__ __forceinline__ void bulk_g2s(uint32_t dst, const void* src, uint32_t bytes, uint32_t bar) {
    asm volatile("cp.async.bulk.shared::cluster.global.mbarrier::complete_tx::bytes [%0], [%1], %2, [%3];"
                 :: "r"(dst), "l"(src), "r"(bytes), "r"(bar) : "memory");
}
__device__ __forceinline__ void cpa16(uint32_t s, const void* g) {
    asm volatile("cp.async.cg.shared.global [%0], [%1], 16;" :: "r"(s), "l"(g) : "memory");
}
__device__ __forceinline__ void cpa_wait_all() { asm volatile("cp.async.wait_all;" ::: "memory"); }
__device__ __forceinline__ void ldsm4(uint32_t* r, uint32_t a) {
    asm volatile("ldmatrix.sync.aligned.m8n8.x4.shared.b16 {%0,%1,%2,%3}, [%4];" : "=r"(r[0]), "=r"(r[1]), "=r"(r[2]), "=r"(r[3]) : "r"(a) : "memory");
}
__device__ __forceinline__ void ldsm4t(uint32_t* r, uint32_t a) {
    asm volatile("ldmatrix.sync.aligned.m8n8.x4.trans.shared.b16 {%0,%1,%2,%3}, [%4];" : "=r"(r[0]), "=r"(r[1]), "=r"(r[2]), "=r"(r[3]) : "r"(a) : "memory");
}
__device__ __forceinline__ void stsm2t(uint32_t a, uint32_t r0, uint32_t r1) {
    asm volatile("stmatrix.sync.aligned.m8n8.x2.trans.shared.b16 [%0], {%1,%2};" :: "r"(a), "r"(r0), "r"(r1) : "memory");
}
__device__ __forceinline__ void stsm4t(uint32_t a, uint32_t r0, uint32_t r1, uint32_t r2, uint32_t r3) {
    asm volatile("stmatrix.sync.aligned.m8n8.x4.trans.shared.b16 [%0], {%1,%2,%3,%4};" :: "r"(a), "r"(r0), "r"(r1), "r"(r2), "r"(r3) : "memory");
}
__device__ __forceinline__ uint32_t movm(uint32_t v) {
    uint32_t r; asm volatile("movmatrix.sync.aligned.m8n8.trans.b16 %0, %1;" : "=r"(r) : "r"(v)); return r;
}
__device__ __forceinline__ void mma16(float* c, uint32_t a0, uint32_t a1, uint32_t a2, uint32_t a3, uint32_t b0, uint32_t b1) {
    asm volatile("mma.sync.aligned.m16n8k16.row.col.f32.bf16.bf16.f32 {%0,%1,%2,%3}, {%4,%5,%6,%7}, {%8,%9}, {%0,%1,%2,%3};"
                 : "+f"(c[0]), "+f"(c[1]), "+f"(c[2]), "+f"(c[3]) : "r"(a0), "r"(a1), "r"(a2), "r"(a3), "r"(b0), "r"(b1));
}
__device__ __forceinline__ void mma8(float* c, uint32_t a0, uint32_t a1, uint32_t b0) {
    asm volatile("mma.sync.aligned.m16n8k8.row.col.f32.bf16.bf16.f32 {%0,%1,%2,%3}, {%4,%5}, {%6}, {%0,%1,%2,%3};"
                 : "+f"(c[0]), "+f"(c[1]), "+f"(c[2]), "+f"(c[3]) : "r"(a0), "r"(a1), "r"(b0));
}
__host__ __device__ constexpr uint64_t make_desc(uint32_t saddr, uint32_t lbo, uint32_t sbo, uint32_t layout) {
    return (uint64_t)((saddr & 0x3FFFF) >> 4) | ((uint64_t)(lbo >> 4) << 16) | ((uint64_t)(sbo >> 4) << 32) | ((uint64_t)layout << 62);
}
__device__ __forceinline__ void wg_fence() { asm volatile("wgmma.fence.sync.aligned;" ::: "memory"); }
__device__ __forceinline__ void wg_commit() { asm volatile("wgmma.commit_group.sync.aligned;" ::: "memory"); }
template <int N> __device__ __forceinline__ void wg_wait() { asm volatile("wgmma.wait_group.sync.aligned %0;" :: "n"(N) : "memory"); }

#define D16(C) C(d[0]), C(d[1]), C(d[2]), C(d[3]), C(d[4]), C(d[5]), C(d[6]), C(d[7]), \
               C(d[8]), C(d[9]), C(d[10]), C(d[11]), C(d[12]), C(d[13]), C(d[14]), C(d[15])
#define DREG16 "{%0,%1,%2,%3,%4,%5,%6,%7,%8,%9,%10,%11,%12,%13,%14,%15}"
__device__ __forceinline__ void wg_rs32(float* d, const uint32_t* a, uint64_t db, bool acc) {
    if (acc)
        asm volatile("wgmma.mma_async.sync.aligned.m64n32k16.f32.bf16.bf16 " DREG16 ", {%16,%17,%18,%19}, %20, 1, 1, 1, 0;"
            : D16("+f") : "r"(a[0]), "r"(a[1]), "r"(a[2]), "r"(a[3]), "l"(db));
    else
        asm volatile("wgmma.mma_async.sync.aligned.m64n32k16.f32.bf16.bf16 " DREG16 ", {%16,%17,%18,%19}, %20, 0, 1, 1, 0;"
            : D16("=f") : "r"(a[0]), "r"(a[1]), "r"(a[2]), "r"(a[3]), "l"(db));
}
__device__ __forceinline__ void wg_ss32(float* d, uint64_t da, uint64_t db, bool acc) {
    if (acc)
        asm volatile("wgmma.mma_async.sync.aligned.m64n32k16.f32.bf16.bf16 " DREG16 ", %16, %17, 1, 1, 1, 1, 0;"
            : D16("+f") : "l"(da), "l"(db));
    else
        asm volatile("wgmma.mma_async.sync.aligned.m64n32k16.f32.bf16.bf16 " DREG16 ", %16, %17, 0, 1, 1, 1, 0;"
            : D16("=f") : "l"(da), "l"(db));
}
__device__ __forceinline__ void wg_ss8(float* d, uint64_t da, uint64_t db, bool acc) {
    if (acc)
        asm volatile("wgmma.mma_async.sync.aligned.m64n8k16.f32.bf16.bf16 {%0,%1,%2,%3}, %4, %5, 1, 1, 1, 1, 1;"
            : "+f"(d[0]), "+f"(d[1]), "+f"(d[2]), "+f"(d[3]) : "l"(da), "l"(db));
    else
        asm volatile("wgmma.mma_async.sync.aligned.m64n8k16.f32.bf16.bf16 {%0,%1,%2,%3}, %4, %5, 0, 1, 1, 1, 1;"
            : "=f"(d[0]), "=f"(d[1]), "=f"(d[2]), "=f"(d[3]) : "l"(da), "l"(db));
}
template <int OFF> __device__ __forceinline__ void ldsm4t_i(uint32_t* r, uint32_t a) {
    asm volatile("ldmatrix.sync.aligned.m8n8.x4.trans.shared.b16 {%0,%1,%2,%3}, [%4+%5];"
                 : "=r"(r[0]), "=r"(r[1]), "=r"(r[2]), "=r"(r[3]) : "r"(a), "n"(OFF) : "memory");
}

__device__ __forceinline__ uint4 ld_relaxed4(const void* p) {
    uint4 v;
    asm volatile("ld.relaxed.gpu.global.v4.u32 {%0,%1,%2,%3}, [%4];" : "=r"(v.x), "=r"(v.y), "=r"(v.z), "=r"(v.w) : "l"(p) : "memory");
    return v;
}
__device__ __forceinline__ void st_relaxed2(void* p, uint32_t a, uint32_t b) {
    asm volatile("st.relaxed.gpu.global.v2.u32 [%0], {%1,%2};" :: "l"(p), "r"(a), "r"(b) : "memory");
}
__device__ __forceinline__ void st_relaxed2_off(void* base, uint32_t off, uint32_t a, uint32_t b) {
    asm volatile("{\n\t.reg .u64 ad;\n\tcvt.u64.u32 ad, %1;\n\tadd.u64 ad, ad, %0;\n\tst.relaxed.gpu.global.v2.u32 [ad], {%2,%3};\n\t}"
                 :: "l"(base), "r"(off), "r"(a), "r"(b) : "memory");
}
__device__ __forceinline__ void st_relaxed1(void* p, uint32_t a) {
    asm volatile("st.relaxed.gpu.global.u32 [%0], %1;" :: "l"(p), "r"(a) : "memory");
}
__device__ __forceinline__ uint32_t ld_acquire1(const uint32_t* p) {
    uint32_t v; asm volatile("ld.acquire.gpu.global.u32 %0, [%1];" : "=r"(v) : "l"(p) : "memory"); return v;
}
__device__ __forceinline__ void st_release1(uint32_t* p, uint32_t a) {
    asm volatile("st.release.gpu.global.u32 [%0], %1;" :: "l"(p), "r"(a) : "memory");
}
__device__ __forceinline__ uint4 lds4(uint32_t s) {
    uint4 v; asm volatile("ld.shared.v4.u32 {%0,%1,%2,%3}, [%4];" : "=r"(v.x), "=r"(v.y), "=r"(v.z), "=r"(v.w) : "r"(s) : "memory"); return v;
}
__device__ __forceinline__ void sts4(uint32_t s, const uint4& v) {
    asm volatile("st.shared.v4.u32 [%0], {%1,%2,%3,%4};" :: "r"(s), "r"(v.x), "r"(v.y), "r"(v.z), "r"(v.w) : "memory");
}
__device__ __forceinline__ float4 lds4f(uint32_t s) {
    float4 v; asm volatile("ld.shared.v4.f32 {%0,%1,%2,%3}, [%4];" : "=f"(v.x), "=f"(v.y), "=f"(v.z), "=f"(v.w) : "r"(s) : "memory"); return v;
}
__device__ __forceinline__ uint2 lds2(uint32_t s) {
    uint2 v; asm volatile("ld.shared.v2.u32 {%0,%1}, [%2];" : "=r"(v.x), "=r"(v.y) : "r"(s) : "memory"); return v;
}
__device__ __forceinline__ float2 lds2f(uint32_t s) {
    float2 v; asm volatile("ld.shared.v2.f32 {%0,%1}, [%2];" : "=f"(v.x), "=f"(v.y) : "r"(s) : "memory"); return v;
}
__device__ __forceinline__ uint32_t clk32() { uint32_t c; asm volatile("mov.u32 %0, %%clock;" : "=r"(c) :: "memory"); return c; }
__device__ __forceinline__ uint32_t tagw(float v, uint32_t tag) { return ((__float_as_uint(v) + 8u) & ~15u) | tag; }
__device__ __forceinline__ bool ok4(const uint4& v, uint32_t tag) { return (((v.x ^ tag) | (v.y ^ tag) | (v.z ^ tag) | (v.w ^ tag)) & 15u) == 0; }
__device__ __forceinline__ bool oks(const uint4& v) { return v.x != 0xFFFFFFFFu && v.y != 0xFFFFFFFFu && v.z != 0xFFFFFFFFu && v.w != 0xFFFFFFFFu; }
__device__ __forceinline__ float uf(uint32_t x) { return __uint_as_float(x & ~15u); }

template <int NT, int BAR>
__device__ __forceinline__ void mod_chunk(const bf16* __restrict__ c, const bf16* __restrict__ wmod, int col0, int tid, float* red) {
    constexpr int RG = NT / 8, NP = DM / RG;
    const int cc = tid & 7, rg = tid >> 3;
    uint4 w[NP];
    #pragma unroll
    for (int i = 0; i < NP; i++) w[i] = __ldg((const uint4*)(wmod + (size_t)(rg + i * RG) * (6 * DM) + col0 + cc * 8));
    float a[8];
    #pragma unroll
    for (int j = 0; j < 8; j++) a[j] = 0.f;
    #pragma unroll
    for (int i = 0; i < NP; i++) {
        const float v = __bfloat162float(c[rg + i * RG]);
        const float sv = bfr(__fdividef(v, 1.0f + __expf(-v)));
        a[0] += sv * bflo(w[i].x); a[1] += sv * bfhi(w[i].x); a[2] += sv * bflo(w[i].y); a[3] += sv * bfhi(w[i].y);
        a[4] += sv * bflo(w[i].z); a[5] += sv * bfhi(w[i].z); a[6] += sv * bflo(w[i].w); a[7] += sv * bfhi(w[i].w);
    }
    #pragma unroll
    for (int j = 0; j < 8; j++) {
        a[j] += __shfl_xor_sync(0xffffffffu, a[j], 8);
        a[j] += __shfl_xor_sync(0xffffffffu, a[j], 16);
    }
    if ((tid & 31) < 8) {
        float* d = red + (tid >> 5) * 64 + cc * 8;
        *(float4*)d = make_float4(a[0], a[1], a[2], a[3]);
        *(float4*)(d + 4) = make_float4(a[4], a[5], a[6], a[7]);
    }
    bar_sync(BAR, NT);
    if (tid < 64) {
        float s = 0.f;
        #pragma unroll
        for (int i = 0; i < NT / 32; i++) s += red[i * 64 + tid];
        g_mod[col0 + tid] = bfr(s);
    }
}

__device__ __forceinline__ uint32_t hadd2(uint32_t a, uint32_t b) { uint32_t r; asm("add.rn.bf16x2 %0, %1, %2;" : "=r"(r) : "r"(a), "r"(b)); return r; }
__device__ __forceinline__ uint32_t hsub2(uint32_t a, uint32_t b) { uint32_t r; asm("sub.rn.bf16x2 %0, %1, %2;" : "=r"(r) : "r"(a), "r"(b)); return r; }
__device__ __forceinline__ uint32_t hmul2(uint32_t a, uint32_t b) { uint32_t r; asm("mul.rn.bf16x2 %0, %1, %2;" : "=r"(r) : "r"(a), "r"(b)); return r; }
__device__ __forceinline__ void ln_stats(const uint2* x, uint32_t& mb2, float& rs) {
    float v[5][4];
    float s = 0.f;
    #pragma unroll
    for (int i = 0; i < 5; i++) {
        v[i][0] = bflo(x[i].x); v[i][1] = bfhi(x[i].x); v[i][2] = bflo(x[i].y); v[i][3] = bfhi(x[i].y);
        s += (v[i][0] + v[i][1]) + (v[i][2] + v[i][3]);
    }
    #pragma unroll
    for (int o = 16; o > 0; o >>= 1) s += __shfl_xor_sync(0xffffffffu, s, o);
    const float mean = s * (1.0f / DM);
    float q0 = 0.f, q1 = 0.f;
    #pragma unroll
    for (int i = 0; i < 5; i++) {
        const float d0 = v[i][0] - mean, d1 = v[i][1] - mean, d2 = v[i][2] - mean, d3 = v[i][3] - mean;
        q0 += d0 * d0; q1 += d1 * d1; q0 += d2 * d2; q1 += d3 * d3;
    }
    float q = q0 + q1;
    #pragma unroll
    for (int o = 16; o > 0; o >>= 1) q += __shfl_xor_sync(0xffffffffu, q, o);
    mb2 = pack2(mean, mean);
    const float var = bfr(q * (1.0f / DM));
    rs = __frcp_rn(bfr(__fsqrt_rn(bfr(var + 1e-5f))));
}
__device__ __forceinline__ uint32_t ln_apply(uint32_t x, uint32_t mb2, float rs, uint32_t m1, uint32_t sh) {
    const uint32_t d = hsub2(x, mb2);
    return hadd2(hmul2(pack2(bflo(d) * rs, bfhi(d) * rs), m1), sh);
}

constexpr int SM_WV = 0;
constexpr int SM_HB = 81920;
constexpr int SM_WO = SM_HB + 40960;
constexpr int SM_QX = SM_WO + 77824;
constexpr int SM_KS = SM_QX + 4096;
constexpr int SM_QM = SM_KS + 5120;
constexpr int SM_XS = SM_QM + 1024;
constexpr int SM_MS = SM_XS + 12288;
constexpr int SM_OS = SM_MS + 3840;
constexpr int SM_PM = SM_OS + 3072;
constexpr int SM_BAR = SM_PM + 640;
constexpr int SM_CH = SM_BAR + 128;
constexpr int SM_TOTAL = SM_CH + 128;
static_assert(SM_TOTAL <= 232448, "smem");

enum { B_MEM_FULL = 0, B_MEM_FREE, B_HLO_FULL, B_HHI_FULL, B_HLO_FREE, B_HHI_FREE, B_MS, B_O, B_XS, B_O1, B_XSFREE, B_WQ, B_WK, B_WV, B_WO };

__device__ __forceinline__ int probe_blk(uint32_t* blk) {
    uint32_t t0 = 0xffffffffu, t1 = 0xffffffffu, acc = 0;
    for (int rep = 0; rep < 3; rep++) {
        #pragma unroll
        for (int pg = 0; pg < 2; pg++) {
            uint32_t c0 = clk32();
            uint32_t v = atomicOr(blk + pg * 1024 + acc, 0u);
            acc = (v == 0x12345678u) ? 1u : 0u;
            asm volatile("" :: "r"(acc) : "memory");
            uint32_t c1 = clk32() + acc;
            uint32_t d = c1 - c0;
            if (rep > 0) { if (pg == 0) t0 = min(t0, d); else t1 = min(t1, d); }
        }
    }
    return t1 < t0 ? 1 : 0;
}

__device__ __forceinline__ uint32_t wo_tile_off(int w) {
    if (w < 8) return w * 6144;
    if (w < 12) return 8 * 6144 + (w - 8) * 4096;
    return 8 * 6144 + 4 * 4096 + (w - 12) * 6144;
}

template <int NRES, int NPRE>
__device__ __forceinline__ void wo_phase(uint32_t sb, int w, int lane, const uint32_t (*res)[4], uint32_t parity,
                                         uint32_t tag, int tile, int h) {
    FRESH(lane);
    const int er = (lane & 7) + 8 * (lane >> 4);
    const uint32_t aaddr = sb + SM_WO + wo_tile_off(w) + er * 32 + ((((lane >> 3) & 1) ^ ((er >> 2) & 1)) << 4);
    const uint32_t baddr = sb + SM_OS + lane * 16;
    float c0[4] = {0.f, 0.f, 0.f, 0.f}, c1[4] = {0.f, 0.f, 0.f, 0.f};
    uint32_t pre[NPRE > 4 ? NPRE : 4][4];
    if (NPRE >= 4) {
        #pragma unroll
        for (int i = 0; i < 4; i++) ldsm4t(pre[i], aaddr + i * 512);
        mbar_wait(sb + SM_BAR + B_O1 * 8, parity);
        uint32_t b[2][4];
        ldsm4t(b[0], baddr);
        ldsm4t(b[1], baddr + 512);
        #pragma unroll
        for (int kp = 0; kp < 2; kp++) {
            mma16(c0, pre[2 * kp][0], pre[2 * kp][1], pre[2 * kp][2], pre[2 * kp][3], b[kp][0], b[kp][1]);
            mma16(c1, pre[2 * kp + 1][0], pre[2 * kp + 1][1], pre[2 * kp + 1][2], pre[2 * kp + 1][3], b[kp][2], b[kp][3]);
        }
    } else {
        #pragma unroll
        for (int i = 0; i < 2; i++) ldsm4t(pre[i], aaddr + i * 512);
        mbar_wait(sb + SM_BAR + B_O1 * 8, parity);
        #pragma unroll
        for (int kp = 0; kp < 2; kp++) {
            uint32_t b[4];
            ldsm4t(b, baddr + kp * 512);
            if (kp == 1) { ldsm4t(pre[0], aaddr + 2 * 512); ldsm4t(pre[1], aaddr + 3 * 512); }
            mma16(c0, pre[0][0], pre[0][1], pre[0][2], pre[0][3], b[0], b[1]);
            mma16(c1, pre[1][0], pre[1][1], pre[1][2], pre[1][3], b[2], b[3]);
        }
    }
    #pragma unroll
    for (int i = 0; i < NPRE; i++) ldsm4t(pre[i], aaddr + (4 + i) * 512);
    uint32_t off0, off1;
    {
        uint32_t ch;
        asm volatile("ld.shared.u16 %0, [%1];" : "=r"(ch) : "r"(sb + SM_CH + 2 * tile) : "memory");
        const int j = h >> 4;
        const uint32_t base = (uint32_t)((tile * 4 + j) * 8192 + (h & 15) * 256 + lane * 8);
        ch >>= j;
        off0 = base + (ch & 1) * 4096;
        off1 = base + 16384 + (ch & 256) * 16;
    }
    mbar_wait(sb + SM_BAR + B_O * 8, parity);
    if (NRES == 4) {
        uint32_t b[4][4];
        #pragma unroll
        for (int i = 0; i < 4; i++) ldsm4t(b[i], baddr + (2 + i) * 512);
        #pragma unroll
        for (int i = 0; i < 2; i++) {
            mma16(c0, res[2 * i][0], res[2 * i][1], res[2 * i][2], res[2 * i][3], b[i][0], b[i][1]);
            mma16(c1, res[2 * i + 1][0], res[2 * i + 1][1], res[2 * i + 1][2], res[2 * i + 1][3], b[i][2], b[i][3]);
        }
        #pragma unroll
        for (int i = 0; i < 2; i++) {
            mma16(c0, pre[2 * i][0], pre[2 * i][1], pre[2 * i][2], pre[2 * i][3], b[2 + i][0], b[2 + i][1]);
            mma16(c1, pre[2 * i + 1][0], pre[2 * i + 1][1], pre[2 * i + 1][2], pre[2 * i + 1][3], b[2 + i][2], b[2 + i][3]);
        }
    } else if (NPRE == 4) {
        uint32_t b[2][4];
        #pragma unroll
        for (int hh = 0; hh < 2; hh++) {
            ldsm4t(b[0], baddr + (2 + 2 * hh) * 512);
            ldsm4t(b[1], baddr + (3 + 2 * hh) * 512);
            if (hh) {
                #pragma unroll
                for (int i = 0; i < 4; i++) ldsm4t(pre[i], aaddr + (8 + i) * 512);
            }
            #pragma unroll
            for (int i = 0; i < 2; i++) {
                mma16(c0, pre[2 * i][0], pre[2 * i][1], pre[2 * i][2], pre[2 * i][3], b[i][0], b[i][1]);
                mma16(c1, pre[2 * i + 1][0], pre[2 * i + 1][1], pre[2 * i + 1][2], pre[2 * i + 1][3], b[i][2], b[i][3]);
            }
        }
    }
    st_relaxed2_off(g_buf1, off0, tagw(c0[0] + c1[0], tag), tagw(c0[1] + c1[1], tag));
    st_relaxed2_off(g_buf1, off1, tagw(c0[2] + c1[2], tag), tagw(c0[3] + c1[3], tag));
}

template <int NT, bool MASK>
__device__ __forceinline__ void softmax_core(float (*sc)[2], int g, int t, uint32_t* pb) {
    const float L2E = 1.4426950408889634f;
    #pragma unroll
    for (int j = 0; j < NT; j++) score2(sc[j][0], sc[j][1]);
    if (MASK) {
        const float NEG = -999292928.0f;
        if (2 * t > g) sc[NT - 1][0] = NEG;
        if (2 * t + 1 > g) sc[NT - 1][1] = NEG;
    }
    float m[NT];
    #pragma unroll
    for (int j = 0; j < NT; j++) m[j] = fmaxf(sc[j][0], sc[j][1]);
    float mx = m[0];
    #pragma unroll
    for (int j = 1; j < NT; j++) mx = fmaxf(mx, m[j]);
    mx = fmaxf(mx, __shfl_xor_sync(0xffffffffu, mx, 1));
    mx = fmaxf(mx, __shfl_xor_sync(0xffffffffu, mx, 2));
    float s0 = 0.f, s1 = 0.f;
    #pragma unroll
    for (int j = 0; j < NT; j++) {
        sc[j][0] = ex2((sc[j][0] - mx) * L2E); sc[j][1] = ex2((sc[j][1] - mx) * L2E);
        s0 += sc[j][0]; s1 += sc[j][1];
    }
    s0 += s1;
    s0 += __shfl_xor_sync(0xffffffffu, s0, 1);
    s0 += __shfl_xor_sync(0xffffffffu, s0, 2);
    const float iv = rcpf(s0);
    #pragma unroll
    for (int j = 0; j < NT; j++) pb[j] = pack2(sc[j][0] * iv, sc[j][1] * iv);
}
template <int NT>
__device__ __forceinline__ void xsoftmax(uint32_t a, int g, int t) {
    float sc[NT][2];
    #pragma unroll
    for (int j = 0; j < NT; j++) {
        float2 v0 = lds2f(a + j * 512), v1 = lds2f(a + j * 512 + 4096), v2 = lds2f(a + j * 512 + 8192);
        sc[j][0] = v0.x + v1.x + v2.x; sc[j][1] = v0.y + v1.y + v2.y;
    }
    uint32_t pb[NT];
    softmax_core<NT, true>(sc, g, t, pb);
    #pragma unroll
    for (int j = 0; j < NT; j += 2) {
        if (j + 1 < NT) asm volatile("st.shared.v2.u32 [%0], {%1,%2};" :: "r"(a + j * 512), "r"(pb[j]), "r"(pb[j + 1]) : "memory");
        else sts1(a + j * 512, pb[j]);
    }
}
template <int NJ>
__device__ __forceinline__ void xscores(uint32_t sb, int p, int mi, int j0, int lane) {
    FRESH(lane);
    const int r = lane & 7, cq = lane >> 3;
    const int qrow = mi * 16 + r + 8 * (cq & 1);
    uint32_t kb[NJ][8];
    float d[NJ][4];
    #pragma unroll
    for (int j = 0; j < NJ; j++) {
        ldsm4(kb[j], sb + SM_KS + ((j0 + j) * 8 + r) * 128 + ((cq ^ r) << 4));
        ldsm4(kb[j] + 4, sb + SM_KS + ((j0 + j) * 8 + r) * 128 + (((cq + 4) ^ r) << 4));
        d[j][0] = 0.f; d[j][1] = 0.f; d[j][2] = 0.f; d[j][3] = 0.f;
    }
    #pragma unroll
    for (int kt = 0; kt < 4; kt++) {
        uint32_t a[4];
        ldsm4(a, sb + SM_QX + qrow * 128 + (((2 * kt + (cq >> 1)) ^ r) << 4));
        #pragma unroll
        for (int j = 0; j < NJ; j++) mma16(d[j], a[0], a[1], a[2], a[3], kb[j][2 * kt], kb[j][2 * kt + 1]);
    }
    const uint32_t la = sb + SM_XS + p * 4096 + (mi * 3 + j0) * 512 + lane * 16;
    #pragma unroll
    for (int rk = 0; rk < 3; rk++) {
        const uint32_t ra = mapa(la, rk), rb = mapa(sb + SM_BAR + B_XS * 8, rk);
        #pragma unroll
        for (int j = 0; j < NJ; j++) st_async4(ra + j * 512, d[j], rb);
    }
}
__device__ __forceinline__ void mbar_arrive_remote(uint32_t bar) {
    asm volatile("mbarrier.arrive.relaxed.cluster.shared::cluster.b64 _, [%0];" :: "r"(bar) : "memory");
}

__device__ __forceinline__ void tma2d(uint32_t dst, const CUtensorMap* map, int c0, int c1, uint32_t bar) {
    asm volatile("cp.async.bulk.tensor.2d.shared::cluster.global.mbarrier::complete_tx::bytes [%0], [%1, {%2, %3}], [%4];"
                 :: "r"(dst), "l"(map), "r"(c0), "r"(c1), "r"(bar) : "memory");
}
__device__ __forceinline__ void tma2d_pf(const CUtensorMap* map, int c0, int c1) {
    asm volatile("cp.async.bulk.prefetch.tensor.2d.L2.global [%0, {%1, %2}];" :: "l"(map), "r"(c0), "r"(c1) : "memory");
}
__device__ __forceinline__ void bulk_pf(const void* p, uint32_t bytes) {
    asm volatile("cp.async.bulk.prefetch.L2.global [%0], %1;" :: "l"(p), "r"(bytes) : "memory");
}
struct RMaps { CUtensorMap wq, wk, wv, wo, wop; };
__device__ __forceinline__ void signal_cnt(int idx) {
    asm volatile("fence.proxy.async.global;\n\tred.release.gpu.global.add.u32 [%0], 1;" :: "l"(g_cnt + idx * 32) : "memory");
}

__global__ void __launch_bounds__(512, 1)
k_rec(const __grid_constant__ RMaps maps, const bf16* __restrict__ mem0, const bf16* __restrict__ Wo,
      const bf16* __restrict__ xin, const bf16* __restrict__ cvec, const bf16* __restrict__ wmod) {
    extern __shared__ __align__(1024) uint8_t smem_raw[];
    constexpr uint32_t SBC = 1024;
    const uint32_t sb = smem_u32(smem_raw);
    if ((sb & 0xFFFFFFu) != SBC) __trap();
    int lane = __shfl_sync(0xffffffffu, threadIdx.x & 31, threadIdx.x & 31);
    const int warp = __shfl_sync(0xffffffffu, threadIdx.x >> 5, 0), wg = warp >> 2;
    const int tid = warp * 32 + lane;
    const int b = blockIdx.x, h = b / 3, p = b % 3;
    const int g = lane >> 2, t = lane & 3;
    const int tile0 = p == 0 ? 0 : (p == 1 ? 14 : 27);
    const int ntile = p == 0 ? 14 : 13;
    const uint32_t bar = sb + SM_BAR;

    if (tid == 0) T2(100 + b);
    if (tid == 0) {
        mbar_init(bar + B_MEM_FULL * 8, 4);
        mbar_init(bar + B_MEM_FREE * 8, 12);
        mbar_init(bar + B_HLO_FULL * 8, 1);
        mbar_init(bar + B_HHI_FULL * 8, 1);
        mbar_init(bar + B_HLO_FREE * 8, 12);
        mbar_init(bar + B_HHI_FREE * 8, 12);
        mbar_init(bar + B_MS * 8, 1);
        mbar_init(bar + B_O * 8, 1);
        mbar_init(bar + B_XS * 8, 1);
        mbar_init(bar + B_O1 * 8, 4);
        mbar_init(bar + B_XSFREE * 8, 12);
        mbar_init(bar + B_WQ * 8, 1);
        mbar_init(bar + B_WK * 8, 1);
        mbar_init(bar + B_WV * 8, 1);
        mbar_init(bar + B_WO * 8, 1);
        asm volatile("fence.mbarrier_init.release.cluster;" ::: "memory");
        mbar_expect(bar + B_MS * 8, 3840);
        mbar_expect(bar + B_O * 8, 2048);
        mbar_expect(bar + B_XS * 8, 12288);
    }
    __syncwarp();
    asm volatile("barrier.cluster.arrive.relaxed.aligned;\n\tbarrier.cluster.wait.acquire.aligned;" ::: "memory");
    if (warp == 0) T3(0);

    if (tid == 480) {
        #pragma unroll 1
        for (int i = 0; i < 5; i++) {
            if (i > 0) mbar_wait(bar + B_WO * 8, (i - 1) & 1);
            mbar_expect(bar + B_WO * 8, 16384);
            tma2d(sb + SM_WO + i * 16384, &maps.wq, h * DH + p * 64, i * 128, bar + B_WO * 8);
            if (i > 0) mbar_wait(bar + B_WV * 8, (i - 1) & 1);
            mbar_expect(bar + B_WV * 8, 16384);
            tma2d(sb + SM_WV + i * 16384, &maps.wk, h * DH + p * 64, i * 128, bar + B_WV * 8);
        }
        mbar_wait(bar + B_WO * 8, 0);
        mbar_arrive(bar + B_WQ * 8);
        mbar_wait(bar + B_WV * 8, 0);
        mbar_arrive(bar + B_WK * 8);
        #pragma unroll 1
        for (int i = 0; i < 5; i++) tma2d_pf(&maps.wv, h * DH + p * 64, i * 128);
        tma2d_pf(&maps.wop, tile0 * 16, h * DH);
    }
    if (wg < 3) {
        const uint32_t tag = *(volatile uint32_t*)&g_epoch + 1u;
        const int seg1 = b + 1, nrow = b < NSEG - 1 ? 64 : 32;
        const bf16* xl = xin + lane * 4;
        uint4 wm[5];
        float cv[5];
        if (wg < 2 && b < 80) {
            #pragma unroll
            for (int i = 0; i < 5; i++) {
                wm[i] = __ldg((const uint4*)(wmod + (size_t)((tid >> 1) + 128 * i) * (6 * DM) + b * 16 + (tid & 1) * 8));
                cv[i] = __bfloat162float(cvec[(tid >> 1) + 128 * i]);
            }
        }
        uint2 xn[6][5];
        #pragma unroll
        for (int r = 0; r < 6; r++) {
            const int idx = warp + 12 * r, nx = idx < 32 ? idx : (idx < nrow ? b * 32 + idx : 0);
            #pragma unroll
            for (int i = 0; i < 5; i++) xn[r][i] = __ldg((const uint2*)(xl + (size_t)nx * DM + i * 128));
        }
        if (wg < 2 && b < 80) {
            float a[8];
            #pragma unroll
            for (int j = 0; j < 8; j++) a[j] = 0.f;
            #pragma unroll
            for (int i = 0; i < 5; i++) {
                const float sv = bfr(__fdividef(cv[i], 1.0f + __expf(-cv[i])));
                a[0] += sv * bflo(wm[i].x); a[1] += sv * bfhi(wm[i].x); a[2] += sv * bflo(wm[i].y); a[3] += sv * bfhi(wm[i].y);
                a[4] += sv * bflo(wm[i].z); a[5] += sv * bfhi(wm[i].z); a[6] += sv * bflo(wm[i].w); a[7] += sv * bfhi(wm[i].w);
            }
            #pragma unroll 1
            for (int o = 2; o < 32; o <<= 1) {
                #pragma unroll
                for (int j = 0; j < 8; j++) a[j] += __shfl_xor_sync(0xffffffffu, a[j], o);
            }
            if (lane < 2) {
                const uint32_t d = sb + SM_QM + warp * 64 + lane * 32;
                sts4(d, make_uint4(__float_as_uint(a[0]), __float_as_uint(a[1]), __float_as_uint(a[2]), __float_as_uint(a[3])));
                sts4(d + 16, make_uint4(__float_as_uint(a[4]), __float_as_uint(a[5]), __float_as_uint(a[6]), __float_as_uint(a[7])));
            }
            bar_sync(1, 256);
            if (tid < 8) {
                float s0 = 0.f, s1 = 0.f;
                #pragma unroll
                for (int i = 0; i < 8; i++) { const float2 v = lds2f(sb + SM_QM + i * 64 + tid * 8); s0 += v.x; s1 += v.y; }
                st_relaxed2(g_modx + (b * 8 + tid) * 2, pack2(s0, s1), tag);
            }
        }
        T3(12);
        if (tid < 320) {
            uint4 v; uint32_t guard = 0;
            while (true) {
                v = ld_relaxed4(g_modx + tid * 4);
                if (v.y == tag && v.w == tag) break;
                __nanosleep(50);
                if (++guard > (1u << 22)) __trap();
            }
            if (tid >= 160) { v.x = hadd2(v.x, 0x3f803f80u); v.z = hadd2(v.z, 0x3f803f80u); }
            asm volatile("st.shared.v2.u32 [%0], {%1,%2};" :: "r"(sb + SM_KS + tid * 8), "r"(v.x), "r"(v.z) : "memory");
        }
        bar_sync(2, 384);
        T3(13);
        #pragma unroll 1
        for (int idx = warp; idx < nrow; idx += 12) {
            uint32_t mb; float rs;
            ln_stats(xn[0], mb, rs);
            const int row = idx & 31;
            char* dst = (idx < 32 ? (char*)smem_raw + SM_HB : (char*)g_ht + (size_t)seg1 * 40960)
                        + (lane >> 4) * 4096 + row * 128 + ((((lane >> 1) & 7) ^ (row & 7)) << 4) + (lane & 1) * 8;
            #pragma unroll
            for (int i = 0; i < 5; i++) {
                const uint2 u0 = lds2(sb + SM_KS + i * 256 + lane * 8), u1 = lds2(sb + SM_KS + 1280 + i * 256 + lane * 8);
                *(uint2*)(dst + i * 8192) = make_uint2(ln_apply(xn[0][i].x, mb, rs, u1.x, u0.x), ln_apply(xn[0][i].y, mb, rs, u1.y, u0.y));
                #pragma unroll
                for (int r = 0; r < 5; r++) xn[r][i] = xn[r + 1][i];
            }
        }
        fence_async();
        bar_sync(2, 384);
        if (tid == 0) { mbar_arrive(bar + B_HLO_FULL * 8); mbar_arrive(bar + B_HHI_FULL * 8); }
        if (tid == 352 && b < NSEG - 1) {
            asm volatile("fence.proxy.async.global;" ::: "memory");
            st_release1(&g_hflag[seg1], tag);
        }
        __syncwarp();
    }

    if (wg < 2) {
        asm volatile("setmaxnreg.inc.sync.aligned.u32 200;");
        const int w = warp & 3;
        uint32_t wa[40][4];
        {
            mbar_wait(bar + (wg == 0 ? B_WQ : B_WK) * 8, 0);
            if (w == 0) T3(1 + wg);
            const int r = lane & 7;
            const uint32_t wsrc = sb + (wg == 0 ? SM_WO : SM_WV) + (r + ((lane >> 4) << 3)) * 128 + (((2 * w + ((lane >> 3) & 1)) ^ r) << 4);
            #pragma unroll
            for (int kt = 0; kt < 40; kt++) ldsm4t(wa[kt], wsrc + kt * 2048);
            fence_async();
            bar_arrive(10 + wg, 256);
        }

        const uint32_t dstx = sb + (wg == 0 ? SM_QX : SM_KS + 1024);

        for (int s = -1; s < NSEG; s++) {
            const uint32_t par = s & 1;
            FRESH(lane);
            const int g = lane >> 2, t = lane & 3, tid = warp * 32 + lane;
            if (s >= 0) {
                mbar_wait(bar + B_MEM_FULL * 8, par);
                TR(0);
                float c[4][4];
                #pragma unroll
                for (int i = 0; i < 4; i++) { c[i][0] = 0.f; c[i][1] = 0.f; c[i][2] = 0.f; c[i][3] = 0.f; }
                uint32_t maddr = sb + lane * 16;
                asm volatile("" : "+r"(maddr));
                #pragma unroll
                for (int kp = 0; kp < 20; kp++) {
                    uint32_t bb[4];
                    ldsm4t(bb, maddr + (SM_HB + kp * 512));
                    mma16(c[(kp & 1) * 2], wa[2 * kp][0], wa[2 * kp][1], wa[2 * kp][2], wa[2 * kp][3], bb[0], bb[1]);
                    mma16(c[(kp & 1) * 2 + 1], wa[2 * kp + 1][0], wa[2 * kp + 1][1], wa[2 * kp + 1][2], wa[2 * kp + 1][3], bb[2], bb[3]);
                }
                {
                    const int tok = lane & 7, ch = 2 * w + ((lane >> 3) & 1);
                    stsm2t(sb + (wg == 0 ? SM_QM : SM_KS) + tok * 128 + ((ch ^ tok) << 4),
                           pack2((c[0][0] + c[1][0]) + (c[2][0] + c[3][0]), (c[0][1] + c[1][1]) + (c[2][1] + c[3][1])),
                           pack2((c[0][2] + c[1][2]) + (c[2][2] + c[3][2]), (c[0][3] + c[1][3]) + (c[2][3] + c[3][3])));
                }
                __syncwarp();
                if (lane == 0) mbar_arrive(bar + B_MEM_FREE * 8);
                TR(1);
                bar_sync(1, 256);
                if (warp < 5) {
                    const int r = lane & 7, cq = lane >> 3;
                    uint32_t a[8], kb[8];
                    ldsm4(a, sb + SM_QM + r * 128 + ((cq ^ r) << 4));
                    ldsm4(kb, sb + SM_KS + (warp * 8 + r) * 128 + ((cq ^ r) << 4));
                    ldsm4(a + 4, sb + SM_QM + r * 128 + (((cq + 4) ^ r) << 4));
                    ldsm4(kb + 4, sb + SM_KS + (warp * 8 + r) * 128 + (((cq + 4) ^ r) << 4));
                    float d0[4] = {0.f, 0.f, 0.f, 0.f}, d1[4] = {0.f, 0.f, 0.f, 0.f};
                    mma16(d0, a[0], 0u, a[1], 0u, kb[0], kb[1]);
                    mma16(d1, a[2], 0u, a[3], 0u, kb[2], kb[3]);
                    mma16(d0, a[4], 0u, a[5], 0u, kb[4], kb[5]);
                    mma16(d1, a[6], 0u, a[7], 0u, kb[6], kb[7]);
                    const uint32_t la = sb + SM_MS + p * 1280 + warp * 256 + lane * 8;
                    #pragma unroll
                    for (int rk = 0; rk < 3; rk++)
                        st_async2(mapa(la, rk), d0[0] + d1[0], d0[1] + d1[1], mapa(bar + B_MS * 8, rk));
                    bar_arrive(4, 352);
                } else if (warp < 7) {
                    xscores<1>(sb, p, warp - 5, 0, lane);
                    bar_arrive(4, 352);
                }
                TR(2);
                if (s < NSEG - 1) {
                    wo_phase<0, 4>(sb, warp, lane, nullptr, par, (uint32_t)(s % 15) + 1u, tile0 + warp, h);
                    TR(4);
                }
            }
            if (s < NSEG - 1) {
                FRESH(lane);
                const uint32_t hp = (s + 1) & 1;
                float d[16];
                const uint64_t db0 = make_desc(SBC + SM_HB, 16, 1024, 1);
                mbar_wait(bar + B_HHI_FULL * 8, hp);
                if (s < 0 && warp == 0) T3(10);
                {
                    const int r = lane & 7, mq = lane >> 3;
                    const uint32_t ha = sb + SM_HB + 9 * 4096 + (8 * (mq >> 1) + r) * 128 + (((6 + (mq & 1)) ^ r) << 4);
                    uint32_t b0[4], b1[4];
                    ldsm4(b0, ha);
                    ldsm4(b1, ha + 2048);
                    #pragma unroll
                    for (int i = 0; i < 16; i++) d[i] = 0.f;
                    mma16(d + 0, wa[39][0], wa[39][1], wa[39][2], wa[39][3], b0[0], b0[1]);
                    mma16(d + 4, wa[39][0], wa[39][1], wa[39][2], wa[39][3], b0[2], b0[3]);
                    mma16(d + 8, wa[39][0], wa[39][1], wa[39][2], wa[39][3], b1[0], b1[1]);
                    mma16(d + 12, wa[39][0], wa[39][1], wa[39][2], wa[39][3], b1[2], b1[3]);
                    asm volatile("" : "+f"(d[0]), "+f"(d[4]), "+f"(d[8]), "+f"(d[12]) :: "memory");
                }
                if (s >= 0) bar_arrive(6, 512);
                mbar_wait(bar + B_HLO_FULL * 8, hp);
                bar_sync(9, 384);
                TR(6);
                wg_fence();
                #pragma unroll
                for (int kt = 0; kt < 12; kt++) wg_rs32(d, wa[kt], db0 + (uint64_t)(((kt >> 2) * 4096 + (kt & 3) * 32) >> 4), 1);
                wg_commit();
                #pragma unroll
                for (int kt = 12; kt < 39; kt++) wg_rs32(d, wa[kt], db0 + (uint64_t)(((kt >> 2) * 4096 + (kt & 3) * 32) >> 4), 1);
                wg_commit();
                wg_wait<1>();
                if (lane == 0) mbar_arrive(bar + B_HLO_FREE * 8);
                wg_wait<0>();
                if (lane == 0) mbar_arrive(bar + B_HHI_FREE * 8);
                TR(7);
                const int mi = lane >> 3, r = lane & 7;
                #pragma unroll
                for (int jj = 0; jj < 2; jj++) {
                    const int tok = 8 * (2 * jj + (mi >> 1)) + r, ch = 2 * w + (mi & 1);
                    stsm4t(dstx + tok * 128 + ((ch ^ r) << 4),
                           pack2(d[8 * jj + 0], d[8 * jj + 1]), pack2(d[8 * jj + 2], d[8 * jj + 3]),
                           pack2(d[8 * jj + 4], d[8 * jj + 5]), pack2(d[8 * jj + 6], d[8 * jj + 7]));
                }
                bar_arrive(8, 384);
                if (s < 0 && warp == 0) T3(11);
                if (s < 0) { bar_sync(0, 512); asm volatile("griddepcontrol.launch_dependents;" ::: "memory"); }
            }
        }
    } else if (wg == 2) {
        asm volatile("setmaxnreg.dec.sync.aligned.u32 64;");
        const int w = warp & 3;
        uint32_t res[4][4];
        {
            const bf16* src = Wo + ((size_t)h * DH + ((p + 1) % 3) * 64) * DM + (tile0 + warp) * 16 + 2 * t;
            #pragma unroll
            for (int kt = 0; kt < 4; kt++) {
                res[kt][0] = __ldg((const uint32_t*)(src + (size_t)(kt * 16 + g) * DM));
                res[kt][1] = __ldg((const uint32_t*)(src + (size_t)(kt * 16 + g) * DM + 8));
                res[kt][2] = __ldg((const uint32_t*)(src + (size_t)(kt * 16 + 8 + g) * DM));
                res[kt][3] = __ldg((const uint32_t*)(src + (size_t)(kt * 16 + 8 + g) * DM + 8));
            }
            #pragma unroll
            for (int kt = 0; kt < 4; kt++) {
                #pragma unroll
                for (int i = 0; i < 4; i++) res[kt][i] = movm(res[kt][i]);
            }
        }
        bar_sync(11, 256);
        if (tid == 256) {
            fence_async();
            mbar_expect(bar + B_WV * 8, 81920);
            #pragma unroll
            for (int i = 0; i < 5; i++) tma2d(sb + SM_WV + i * 16384, &maps.wv, h * DH + p * 64, i * 128, bar + B_WV * 8);
        }
        mbar_wait(bar + B_WV * 8, 1);
        if (w == 0) T3(3);
        const uint64_t da0 = make_desc(SBC + SM_WV, 16, 1024, 1);
        uint32_t vx[8], vm0 = 0, vm1 = 0;
        #pragma unroll
        for (int i = 0; i < 8; i++) vx[i] = 0;

        for (int s = -1; s < NSEG; s++) {
            FRESH(lane);
            const int g = lane >> 2, t = lane & 3, tid = warp * 32 + lane;
            if (s >= 0) {
                const uint32_t par = s & 1;
                mbar_wait(bar + B_MEM_FULL * 8, par);
                bar_sync(4, 352);
                TR(0);
                float dv[4];
                {
                    const uint64_t dbm = make_desc(SBC + SM_HB, 128, 128, 0);
                    wg_fence();
                    #pragma unroll
                    for (int kt = 0; kt < 40; kt++) {
                        wg_ss8(dv, da0 + (uint64_t)(kt * 128), dbm + (uint64_t)(kt * 16), kt > 0);
                        wg_commit();
                        if (kt < 39) wg_wait<1>();
                    }
                    wg_commit();
                }
                TR(1);
                bar_sync(5, 160);
                TR(2);
                uint32_t pb[5];
                #pragma unroll
                for (int j = 0; j < 5; j++) pb[j] = lds1(sb + SM_PM + j * 128 + lane * 4);
                float o0[4] = {0.f, 0.f, 0.f, 0.f}, o1[4] = {0.f, 0.f, 0.f, 0.f}, o2[4] = {0.f, 0.f, 0.f, 0.f};
                wg_wait<0>();
                TR(3);
                mma16(o0, vx[0], vx[1], vx[2], vx[3], pb[1], pb[2]);
                mma16(o1, vx[4], vx[5], vx[6], vx[7], pb[3], pb[4]);
                vm0 = pack2(dv[0], dv[1]); vm1 = pack2(dv[2], dv[3]);
                mma8(o2, vm0, vm1, pb[0]);
                if (s < NSEG - 1) {
                    const uint32_t q0 = pack2(o0[0] + o1[0] + o2[0], o0[1] + o1[1] + o2[1]), q1 = pack2(o0[2] + o1[2] + o2[2], o0[3] + o1[3] + o2[3]);
                    const uint32_t la = sb + SM_OS + (w * 16 + g) * 16 + t * 4;
                    #pragma unroll
                    for (int i = 1; i < 3; i++) {
                        const uint32_t rk = (p + i) % 3;
                        const uint32_t ra = mapa(la + (3 - i) * 1024, rk), rb = mapa(bar + B_O * 8, rk);
                        st_async1(ra, q0, rb);
                        st_async1(ra + 128, q1, rb);
                    }
                    sts1(la, q0);
                    sts1(la + 128, q1);
                    __syncwarp();
                    if (lane == 0) { mbar_arrive(bar + B_O1 * 8); mbar_arrive(bar + B_MEM_FREE * 8); }
                }
                TR(5);
                if (s < NSEG - 1) {
                    wo_phase<4, 4>(sb, warp, lane, res, par, (uint32_t)(s % 15) + 1u, tile0 + warp, h);
                    TR(4);
                    if (tid == 256) mbar_expect(bar + B_O * 8, 2048);
                }
                if (s < NSEG - 1) bar_sync(6, 512);
            }
            uint32_t vn[8];
            #pragma unroll
            for (int i = 0; i < 8; i++) vn[i] = 0;
            if (s < NSEG - 1) {
            float d[16];
            const uint32_t hp = (s + 1) & 1;
            const uint64_t db0 = make_desc(SBC + SM_HB, 16, 1024, 1);
            mbar_wait(bar + B_HHI_FULL * 8, hp);
            TR(6);
            wg_fence();
            #pragma unroll
            for (int kt = 12; kt < 40; kt++) wg_ss32(d, da0 + (uint64_t)(kt * 128), db0 + (uint64_t)(((kt >> 2) * 4096 + (kt & 3) * 32) >> 4), kt > 12);
            wg_commit();
            mbar_wait(bar + B_HLO_FULL * 8, hp);
            wg_fence();
            #pragma unroll
            for (int kt = 0; kt < 9; kt++) wg_ss32(d, da0 + (uint64_t)(kt * 128), db0 + (uint64_t)(((kt >> 2) * 4096 + (kt & 3) * 32) >> 4), 1);
            wg_commit();
            #pragma unroll
            for (int kt = 9; kt < 12; kt++) wg_ss32(d, da0 + (uint64_t)(kt * 128), db0 + (uint64_t)(((kt >> 2) * 4096 + (kt & 3) * 32) >> 4), 1);
            wg_commit();
            wg_wait<1>();
            bar_arrive(9, 384);
            wg_wait<0>();
            if (lane == 0) mbar_arrive(bar + B_HLO_FREE * 8);
            TR(7);
            if (lane == 0) mbar_arrive(bar + B_HHI_FREE * 8);
            #pragma unroll
            for (int i = 0; i < 8; i++) vn[i] = pack2(d[2 * i], d[2 * i + 1]);
            }
            if (s >= 0) {
                {
                    FRESH(lane);
                    mbar_wait(bar + B_XS * 8, s & 1);
                    if (w == 0 && lane == 0) mbar_expect(bar + B_XS * 8, 12288);
                    const uint32_t a = sb + SM_XS + (w >> 1) * 1536 + lane * 16 + (w & 1) * 8;
                    if (w == 0) xsoftmax<2>(a, lane >> 2, lane & 3);
                    else if (w == 1) xsoftmax<3>(a, lane >> 2, lane & 3);
                    else if (w == 2) xsoftmax<4>(a, lane >> 2, lane & 3);
                    else xsoftmax<5>(a, lane >> 2, lane & 3);
                }
                TR(8);
                bar_sync(7, 128);
                FRESH(lane);
                bf16* orow = g_ox + (size_t)(s * 32 + (lane >> 2)) * HD + h * DH + p * 64 + w * 16 + 2 * (lane & 3);
                {
                    const uint32_t pa = sb + SM_XS + lane * 16;
                    #pragma unroll
                    for (int mi = 0; mi < 2; mi++) {
                        float oa[4] = {0.f, 0.f, 0.f, 0.f}, ob[4] = {0.f, 0.f, 0.f, 0.f};
                        if (mi == 0) {
                            const uint4 p0 = lds4(pa);
                            const uint32_t p3 = lds1(pa + 1024 + 8);
                            mma8(oa, vm0, vm1, p0.x);
                            mma8(ob, vm0, vm1, p0.z);
                            mma16(oa, vx[0], vx[1], vx[2], vx[3], p0.y, 0u);
                            mma16(ob, vx[0], vx[1], vx[2], vx[3], p0.w, p3);
                        } else {
                            const uint4 p1 = lds4(pa + 1536), p2 = lds4(pa + 2560);
                            const uint32_t p4 = lds1(pa + 3584 + 8);
                            mma8(oa, vm0, vm1, p1.x);
                            mma8(ob, vm0, vm1, p1.z);
                            mma16(oa, vx[0], vx[1], vx[2], vx[3], p1.y, p2.x);
                            mma16(ob, vx[0], vx[1], vx[2], vx[3], p1.w, p2.z);
                            mma16(oa, vx[4], vx[5], vx[6], vx[7], p2.y, 0u);
                            mma16(ob, vx[4], vx[5], vx[6], vx[7], p2.w, p4);
                            if (lane < 3) mbar_arrive_remote(mapa(bar + B_XSFREE * 8, lane));
                        }
                        const uint32_t u0 = movm(pack2(oa[0], oa[1])), u1 = movm(pack2(oa[2], oa[3]));
                        const uint32_t u2 = movm(pack2(ob[0], ob[1])), u3 = movm(pack2(ob[2], ob[3]));
                        bf16* dst = orow + (size_t)(16 * mi) * HD;
                        *(uint32_t*)dst = u0;
                        *(uint32_t*)(dst + 8) = u1;
                        *(uint32_t*)(dst + 8 * HD) = u2;
                        *(uint32_t*)(dst + 8 * HD + 8) = u3;
                    }
                }
                TR(9);
                if (s == NSEG - 1) {
                    bar_sync(7, 128);
                    if (w == 3 && lane == 0) { signal_cnt(C_REC + 15); T2(400 + b); }
                    break;
                }
            }
            #pragma unroll
            for (int i = 0; i < 8; i++) vx[i] = vn[i];
            if (s >= 0) mbar_wait_cluster(bar + B_XSFREE * 8, s & 1);
            bar_sync(8, 384);
            TR(10);
            if (w < 3) xscores<2>(sb, p, w > 0, w == 2 ? 3 : 1, lane);
            else if ((s & 3) == 3 && s >= 0 && lane == 0) signal_cnt(C_REC + (s >> 2));
            __syncwarp();
            TR(11);
            if (s < 0) { bar_sync(0, 512); asm volatile("griddepcontrol.launch_dependents;" ::: "memory"); }
        }
    } else {
        asm volatile("setmaxnreg.dec.sync.aligned.u32 48;");
        const int w = warp & 3, lt = tid & 127;
        const uint32_t epoch = *(volatile uint32_t*)&g_epoch + 1u;
        if (b == 91) { if (lt < C_NUM) g_cnt[lt * 32] = 0u; __threadfence(); }
        if (b < 80) {
            #pragma unroll
            for (int i = 0; i < 2; i++) {
                const int idx = lt + i * 128, sl = idx >> 6, pg = (idx >> 5) & 1, wd = idx & 31;
                st_relaxed1(g_buf2 + (sl * 3 + (b >> 5)) * 2048 + pg * 1024 + (b & 31) * 32 + wd, 0xFFFFFFFFu);
            }
            __threadfence();
        }
        if (lane == 0 && w < 3) {
            int c = 0;
            if (w == 0) c = probe_blk(g_buf2 + 640 + (b & 31) * 8);
            else if (b < 80) c = probe_blk(g_buf1 + (b * 2 + (w - 1)) * 2048);
            else if (b < 92 && w == 1) c = probe_blk(g_buf2 + (b - 80) * 2048 + 960);
            asm volatile("st.shared.u8 [%0], %1;" :: "r"(sb + SM_CH + 96 + w), "r"(c) : "memory");
        }
        if (w == 0) T3(4);
        bar_sync(3, 128);
        uint32_t selmask;
        {
            const uint32_t c3 = lds1(sb + SM_CH + 96);
            const uint32_t cr = c3 & 1u, c1 = (c3 >> 8) & 1u, c2 = (c3 >> 16) & 1u;
            if (lt == 0 && b < 92) st_release1(&g_choice[b], (epoch << 2) | (b < 80 ? (c1 | (c2 << 1)) : (c1 ^ cr)));
            bar_sync(10, 256);
            if (w == 3) {
                if (lane == 0) { fence_async(); mbar_expect(bar + B_WO * 8, ntile * 6144 - 8192); }
                __syncwarp();
                if (lane < ntile) {
                    #pragma unroll
                    for (int e3 = 0; e3 < 3; e3++) {
                        const bool part = lane >= 8 && lane < 12;
                        if (part && e3 == 1) continue;
                        tma2d(sb + SM_WO + wo_tile_off(lane) + ((part && e3 == 2) ? 1 : e3) * 2048, &maps.wo,
                              (tile0 + lane) * 16, h * DH + ((e3 + p) % 3) * 64, bar + B_WO * 8);
                    }
                }
                __syncwarp();
            }
            if (w == 0) T3(5);
            if (lt < 92) {
                uint32_t v, guard = 0;
                while (true) {
                    v = ld_acquire1(&g_choice[lt]);
                    if ((v >> 2) == (epoch & 0x3fffffffu)) break;
                    __nanosleep(100);
                    if (++guard > (1u << 22)) __trap();
                }
                asm volatile("st.shared.u8 [%0], %1;" :: "r"(sb + SM_CH + lt), "r"(v & 3u) : "memory");
            }
            if (w == 0) T3(6);
            bar_sync(3, 128);
            selmask = (c1 << 12) | (c2 << 13);
            for (int i = 0; i < 12; i++) {
                uint32_t c; asm volatile("ld.shared.u8 %0, [%1];" : "=r"(c) : "r"(sb + SM_CH + 80 + i) : "memory");
                selmask |= ((c ^ cr) & 1u) << i;
            }
        }
        mbar_wait(bar + B_WO * 8, 1);
        if (w == 0) T3(8);
        bar_sync(0, 512);
        if (w == 0) T3(9);
        asm volatile("griddepcontrol.launch_dependents;" ::: "memory");
        const bool has_tile = (12 + w) < ntile;
        for (int s = 0; s < NSEG; s++) {
            const uint32_t par = s & 1;
            FRESH(lane);
            const int g = lane >> 2, t = lane & 3, lt = w * 32 + lane;
            if (s == 0) {
                mbar_wait(bar + B_HLO_FREE * 8, par);
                for (int k = lt; k < DM; k += 128) {
                    uint32_t v[4];
                    #pragma unroll
                    for (int i = 0; i < 4; i++) {
                        uint32_t lo = *(const uint16_t*)(mem0 + (2 * i) * DM + k), hi = *(const uint16_t*)(mem0 + (2 * i + 1) * DM + k);
                        v[i] = lo | (hi << 16);
                    }
                    asm volatile("st.shared.v4.u32 [%0], {%1,%2,%3,%4};" :: "r"(sb + SM_HB + k * 16), "r"(v[0]), "r"(v[1]), "r"(v[2]), "r"(v[3]) : "memory");
                }
            } else {
                const int sl = s & 3;
                const char* q = (const char*)g_buf2 + sl * 3 * 8192 + lt * 16;
                const uint32_t sm = selmask >> (sl * 3);
                const char* q0 = q + (sm & 1) * 4096;
                const char* q1 = q + 8192 + (sm & 2) * 2048;
                const char* q2 = q + 16384 + (sm & 4) * 1024;
                const uint32_t dst = sb + SM_HB + lt * 16;
                uint32_t guard = 0;
                mbar_wait(bar + B_HLO_FREE * 8, par);
                TR(10);
                while (true) {
                    const uint4 v0 = ld_relaxed4(q0), v1 = ld_relaxed4(q0 + 2048), v2 = ld_relaxed4(q1), v3 = ld_relaxed4(q1 + 2048), v4 = ld_relaxed4(q2);
                    sts4(dst, v0); sts4(dst + 2048, v1); sts4(dst + 4096, v2); sts4(dst + 6144, v3); sts4(dst + 8192, v4);
                    if (__all_sync(0xffffffffu, oks(v0) && oks(v1) && oks(v2) && oks(v3) && oks(v4))) break;
                    if (++guard > (1u << 22)) __trap();
                }
            }
            fence_async();
            __syncwarp();
            if (lane == 0) mbar_arrive(bar + B_MEM_FULL * 8);
            if (b == 0 && lt == 0) T2(300 + s);
            if (s == 0 && lt == 0) T2(200 + b);
            TR(0);
            if (w == 2) {
                mbar_wait(bar + B_MS * 8, par);
                TR(1);
                if (lane == 0) mbar_expect(bar + B_MS * 8, 3840);
                uint32_t pb[5];
                float sc[5][2];
                {
                    const uint32_t a = sb + SM_MS + lane * 8;
                    float2 u[5], v[5];
                    #pragma unroll
                    for (int j = 0; j < 5; j++) { u[j] = lds2f(a + j * 256); v[j] = lds2f(a + j * 256 + 1280); }
                    #pragma unroll
                    for (int j = 0; j < 5; j++) { sc[j][0] = u[j].x + v[j].x; sc[j][1] = u[j].y + v[j].y; }
                    #pragma unroll
                    for (int j = 0; j < 5; j++) u[j] = lds2f(a + j * 256 + 2560);
                    #pragma unroll
                    for (int j = 0; j < 5; j++) { sc[j][0] += u[j].x; sc[j][1] += u[j].y; }
                }
                softmax_core<5, false>(sc, g, t, pb);
                #pragma unroll
                for (int j = 0; j < 5; j++) sts1(sb + SM_PM + j * 128 + lane * 4, pb[j]);
                bar_arrive(5, 160);
                TR(2);
            }
            const uint32_t tag = (uint32_t)(s % 15) + 1u;
            if (s < NSEG - 1) {
                if (w == 3) {
                    const char* src = (const char*)g_ht + (size_t)(s + 1) * 40960;
                    if (s == 0) {
                        uint32_t guard = 0;
                        while (true) {
                            const uint32_t f0 = lane > 0 ? ld_acquire1(&g_hflag[lane]) : epoch, f1 = ld_acquire1(&g_hflag[32 + lane]);
                            if (__all_sync(0xffffffffu, f0 == epoch && f1 == epoch)) break;
                            if (++guard > (1u << 22)) __trap();
                        }
                        asm volatile("fence.proxy.async.global;" ::: "memory");
                    }
                    mbar_wait(bar + B_HHI_FREE * 8, par);
                    if (lane == 0) {
                        mbar_expect(bar + B_HHI_FULL * 8, 28672);
                        bulk_g2s(sb + SM_HB + 12288, src + 12288, 28672, sb + SM_BAR + B_HHI_FULL * 8);
                    }
                    mbar_wait(bar + B_MEM_FREE * 8, par);
                    if (lane == 0) {
                        mbar_expect(bar + B_HLO_FULL * 8, 12288);
                        bulk_g2s(sb + SM_HB, src, 12288, sb + SM_BAR + B_HLO_FULL * 8);
                    }
                    __syncwarp();
                }
                if (has_tile) wo_phase<0, 4>(sb, warp, lane, nullptr, par, tag, tile0 + warp, h);
                TR(4);
                bar_sync(6, 512);
            }
            if (s < NSEG - 1) {
                { const uint32_t c0 = clk32(); while (clk32() - c0 < H1_DELAY); }
                if (b < 80) {
                    FRESH(lane);
                    const char* rin0 = (const char*)g_buf1 + (size_t)(b * 2) * 8192 + ((selmask >> 12) & 1) * 4096 + (lane >> 2) * 256 + w * 64 + (lane & 3) * 16;
                    const char* rin1 = (const char*)g_buf1 + (size_t)(b * 2 + 1) * 8192 + ((selmask >> 13) & 1) * 4096 + (lane >> 2) * 256 + w * 64 + (lane & 3) * 16;
                    const int col = b * 8 + 2 * w + ((lane >> 1) & 1), wd = 2 * (lane & 1) + (lane >> 4);
                    const int sl = (lane & 8) ? ((s + 3) & 3) : ((s + 1) & 3);
                    uint32_t* dst = g_buf2 + (sl * 3 + (col >> 8)) * 2048 + ((lane >> 2) & 1) * 1024 + (col & 255) * 4 + wd;
                    asm volatile("" : "+l"(dst));
                    uint4 v0, v1, v2, v3;
                    uint32_t guard = 0;
                    while (true) {
                        v0 = ld_relaxed4(rin0); v1 = ld_relaxed4(rin0 + 2048);
                        v2 = ld_relaxed4(rin1); v3 = ld_relaxed4(rin1 + 2048);
                        if (__all_sync(0xffffffffu, ok4(v0, tag) && ok4(v1, tag) && ok4(v2, tag) && ok4(v3, tag))) break;
                        if (++guard > (1u << 22)) __trap();
                    }
                    TR(11);
                    const float a0 = (uf(v0.x) + uf(v1.x)) + (uf(v2.x) + uf(v3.x)), a1 = (uf(v0.y) + uf(v1.y)) + (uf(v2.y) + uf(v3.y));
                    const float a2 = (uf(v0.z) + uf(v1.z)) + (uf(v2.z) + uf(v3.z)), a3 = (uf(v0.w) + uf(v1.w)) + (uf(v2.w) + uf(v3.w));
                    const bool u16 = lane & 16;
                    float m0 = (u16 ? a2 : a0) + __shfl_xor_sync(0xffffffffu, u16 ? a0 : a2, 16);
                    float m1 = (u16 ? a3 : a1) + __shfl_xor_sync(0xffffffffu, u16 ? a1 : a3, 16);
                    m0 += __shfl_xor_sync(0xffffffffu, m0, 8); m1 += __shfl_xor_sync(0xffffffffu, m1, 8);
                    m0 += __shfl_xor_sync(0xffffffffu, m0, 4); m1 += __shfl_xor_sync(0xffffffffu, m1, 4);
                    st_relaxed1(dst, (lane & 8) ? 0xFFFFFFFFu : pack2(m0, m1));
                    TR(12);
                }
            }
        }
    }
    cluster_sync();
}

constexpr int G_STAGES = 6;
constexpr int G_STAGE_BYTES = 32768;
constexpr int G_SMEM = G_STAGES * G_STAGE_BYTES + 1024 + 256 + 2048 + 10240;

__device__ __forceinline__ void wg_ss128(float* d, uint64_t da, uint64_t db, int sc) {
    asm volatile("{\n\t.reg .pred p;\n\tsetp.ne.b32 p, %66, 0;\n\t"
        "wgmma.mma_async.sync.aligned.m64n128k16.f32.bf16.bf16 "
        "{%0,%1,%2,%3,%4,%5,%6,%7,%8,%9,%10,%11,%12,%13,%14,%15,%16,%17,%18,%19,%20,%21,%22,%23,%24,%25,%26,%27,%28,%29,%30,%31,"
        "%32,%33,%34,%35,%36,%37,%38,%39,%40,%41,%42,%43,%44,%45,%46,%47,%48,%49,%50,%51,%52,%53,%54,%55,%56,%57,%58,%59,%60,%61,%62,%63}, "
        "%64, %65, p, 1, 1, 0, 1;\n\t}"
        : "+f"(d[0]), "+f"(d[1]), "+f"(d[2]), "+f"(d[3]), "+f"(d[4]), "+f"(d[5]), "+f"(d[6]), "+f"(d[7]),
          "+f"(d[8]), "+f"(d[9]), "+f"(d[10]), "+f"(d[11]), "+f"(d[12]), "+f"(d[13]), "+f"(d[14]), "+f"(d[15]),
          "+f"(d[16]), "+f"(d[17]), "+f"(d[18]), "+f"(d[19]), "+f"(d[20]), "+f"(d[21]), "+f"(d[22]), "+f"(d[23]),
          "+f"(d[24]), "+f"(d[25]), "+f"(d[26]), "+f"(d[27]), "+f"(d[28]), "+f"(d[29]), "+f"(d[30]), "+f"(d[31]),
          "+f"(d[32]), "+f"(d[33]), "+f"(d[34]), "+f"(d[35]), "+f"(d[36]), "+f"(d[37]), "+f"(d[38]), "+f"(d[39]),
          "+f"(d[40]), "+f"(d[41]), "+f"(d[42]), "+f"(d[43]), "+f"(d[44]), "+f"(d[45]), "+f"(d[46]), "+f"(d[47]),
          "+f"(d[48]), "+f"(d[49]), "+f"(d[50]), "+f"(d[51]), "+f"(d[52]), "+f"(d[53]), "+f"(d[54]), "+f"(d[55]),
          "+f"(d[56]), "+f"(d[57]), "+f"(d[58]), "+f"(d[59]), "+f"(d[60]), "+f"(d[61]), "+f"(d[62]), "+f"(d[63])
        : "l"(da), "l"(db), "r"(sc));
}

#define SP0_LAST 12
#define SP2_LAST 6
enum { J_MOD = 0, J_G0, J_LN, J_G1, J_G2, J_FIN, J_END };
__host__ __device__ constexpr int sp0(int b) { return b >= 15 ? SP0_LAST : 3; }
__host__ __device__ constexpr int sp2(int b) { return b >= 15 ? SP2_LAST : 3; }
__host__ __device__ constexpr int njr(int b) { return b >= 15 ? 16 : 8; }
struct JobTab { uint32_t n; uint32_t j[1200]; };
constexpr uint32_t mkjob(int ty, int b, int n, int k0, int nk, int ks) {
    return (uint32_t)(ty | (b << 3) | (n << 7) | (k0 << 11) | (nk << 18) | (ks << 25));
}
constexpr void add_jobs(JobTab& t, int ty, int b) {
    if (b < 0) return;
    if (ty == J_G0) { for (int ks = 0; ks < sp0(b); ks++) for (int n = 0; n < 5; n++) t.j[t.n++] = mkjob(ty, b, n, ks * (96 / sp0(b)), 96 / sp0(b), ks); }
    else if (ty == J_G2) { for (int ks = 0; ks < sp2(b); ks++) for (int n = 0; n < 5; n++) t.j[t.n++] = mkjob(ty, b, n, ks * (24 / sp2(b)), 24 / sp2(b), ks); }
    else if (ty == J_G1) { for (int n = 0; n < 12; n++) t.j[t.n++] = mkjob(ty, b, n, 0, 10, 0); }
    else { for (int n = 0; n < njr(b); n++) t.j[t.n++] = mkjob(ty, b, n, 0, 16 / njr(b), ty == J_LN ? sp0(b) : sp2(b)); }
}
constexpr JobTab make_tab() {
    JobTab t = {};
    for (int i = 20; i < 60; i++) t.j[t.n++] = mkjob(J_MOD, 0, 0, i, 0, 0);
    for (int b = 0; b < 15; b++) {
        add_jobs(t, J_G0, b); add_jobs(t, J_G1, b - 1); add_jobs(t, J_FIN, b - 2); add_jobs(t, J_G2, b - 1); add_jobs(t, J_LN, b);
    }
    add_jobs(t, J_FIN, 13); add_jobs(t, J_G1, 14);
    add_jobs(t, J_G0, 15); add_jobs(t, J_G2, 14); add_jobs(t, J_LN, 15); add_jobs(t, J_FIN, 14);
    add_jobs(t, J_G1, 15); add_jobs(t, J_G2, 15); add_jobs(t, J_FIN, 15);
    return t;
}
__constant__ JobTab c_jobs = make_tab();

__device__ __forceinline__ bool cnt_ge(int idx, uint32_t target) { return ld_acquire1(g_cnt + idx * 32) >= target; }
__device__ __forceinline__ void cnt_wait(int idx, uint32_t target) {
    uint32_t guard = 0;
    while (!cnt_ge(idx, target)) { __nanosleep(64); if (++guard > (1u << 22)) __trap(); }
}

struct SMaps { CUtensorMap ox, wo, h2, w1, act, w2; };

__global__ void __launch_bounds__(384, 1)
k_side(const __grid_constant__ SMaps maps, const bf16* __restrict__ xin, const bf16* __restrict__ cvec,
       const bf16* __restrict__ wmod, bf16* __restrict__ outp) {
    extern __shared__ uint8_t smem_raw[];
    const uint32_t sb = (smem_u32(smem_raw) + 1023u) & ~1023u;
    const uint32_t bars = sb + G_STAGES * G_STAGE_BYTES;
    float* red = (float*)(smem_raw + (bars + 256 - smem_u32(smem_raw)));
    const int tid = threadIdx.x, lane = tid & 31, wg = tid >> 7;
    if (tid == 0) T2(500 + blockIdx.x);
    if (tid == 0) {
        for (int i = 0; i < G_STAGES; i++) { mbar_init(bars + i * 8, 1); mbar_init(bars + 64 + i * 8, 8); }
        for (int i = 0; i < 2; i++) { mbar_init(bars + 128 + i * 8, 1); mbar_init(bars + 144 + i * 8, 8); }
        asm volatile("fence.mbarrier_init.release.cluster;" ::: "memory");
    }
    __syncthreads();
    if (wg == 0) {
        if (tid == 0) {
            uint32_t st = 0, ph = 1;
            for (uint32_t it = 0;; it++) {
                const uint32_t ji = atomicAdd(g_cnt + C_Q * 32, 1u);
                const uint32_t job = ji < c_jobs.n ? c_jobs.j[ji] : (uint32_t)J_END;
                if (ji == 0) g_epoch = g_epoch + 1u;
                const int ty = job & 7, b = (job >> 3) & 15, n = (job >> 7) & 15, k0 = (job >> 11) & 127, nk = (job >> 18) & 127;
                const uint32_t sl = it & 1;
                mbar_wait(bars + 144 + sl * 8, ((it >> 1) & 1) ^ 1);
                sts1(bars + 160 + sl * 4, job);
                if (ty == J_G0 || ty == J_G1 || ty == J_G2) {
                    if (b >= PRING && ty != J_G1) cnt_wait((ty == J_G0 ? C_LN : C_FIN) + b - PRING, njr(b - PRING));
                    mbar_arrive(bars + 128 + sl * 8);
                    const CUtensorMap* mA = ty == J_G0 ? &maps.ox : (ty == J_G1 ? &maps.h2 : &maps.act);
                    const CUtensorMap* mB = ty == J_G0 ? &maps.wo : (ty == J_G1 ? &maps.w1 : &maps.w2);
                    const int didx = ty == J_G0 ? C_REC + b : (ty == J_G1 ? C_LN + b : C_G1 + b);
                    const uint32_t dtgt = ty == J_G0 ? 96u : (ty == J_G1 ? (uint32_t)njr(b) : 12u);
                    int pre = 0;
                    if (!cnt_ge(didx, dtgt)) {
                        pre = nk < G_STAGES ? nk : G_STAGES;
                        uint32_t s2 = st, p2 = ph;
                        for (int i = 0; i < pre; i++) {
                            mbar_wait(bars + 64 + s2 * 8, p2);
                            const uint32_t a = sb + s2 * G_STAGE_BYTES;
                            mbar_expect(bars + s2 * 8, G_STAGE_BYTES);
                            tma2d(a + 16384, mB, n * 128, (k0 + i) * 64, bars + s2 * 8);
                            tma2d(a + 16384 + 8192, mB, n * 128 + 64, (k0 + i) * 64, bars + s2 * 8);
                            if (++s2 == G_STAGES) { s2 = 0; p2 ^= 1; }
                        }
                        cnt_wait(didx, dtgt);
                    }
                    asm volatile("fence.proxy.async.global;" ::: "memory");
                    T2(1024 + ji * 4 + 1);
                    for (int i = 0; i < nk; i++) {
                        const uint32_t a = sb + st * G_STAGE_BYTES;
                        if (i >= pre) {
                            mbar_wait(bars + 64 + st * 8, ph);
                            mbar_expect(bars + st * 8, G_STAGE_BYTES);
                        }
                        tma2d(a, mA, (k0 + i) * 64, b * 128, bars + st * 8);
                        if (i >= pre) {
                            tma2d(a + 16384, mB, n * 128, (k0 + i) * 64, bars + st * 8);
                            tma2d(a + 16384 + 8192, mB, n * 128 + 64, (k0 + i) * 64, bars + st * 8);
                        }
                        if (++st == G_STAGES) { st = 0; ph ^= 1; }
                    }
                } else {
                    if (ty == J_LN) { bulk_pf(xin + (size_t)(b * 128 + n * nk * 8) * DM, nk * 8 * DM * 2); cnt_wait(C_MOD, 40u); cnt_wait(C_G0 + b, 5u * sp0(b)); }
                    else if (ty == J_FIN) cnt_wait(C_G2 + b, 5u * sp2(b));
                    if (ji < 1200) T2(1024 + ji * 4 + 1);
                    mbar_arrive(bars + 128 + sl * 8);
                    if (ty == J_END) break;
                }
            }
        }
    } else {
        const int cw = wg - 1, ct = tid - 128, cwarp = ct >> 5;
        uint32_t st = 0, ph = 0;
        uint2* smod = (uint2*)(red + 512);
        bool have_mod = false;
        auto load_mod = [&]() {
            for (int i = ct; i < DM; i += 256) {
                const float4 m = __ldcg((const float4*)(g_mod + 2 * DM + i * 4));
                const float o = (i >= 320 && i < 480) ? 1.0f : 0.0f;
                smod[i] = make_uint2(pack2(m.x + o, m.y + o), pack2(m.z + o, m.w + o));
            }
            bar_sync(1, 256);
            have_mod = true;
        };
        {
            if (ct == 0) red[0] = cnt_ge(C_MOD, 40u) ? 1.0f : 0.0f;
            bar_sync(1, 256);
            const bool rdy = red[0] != 0.0f;
            bar_sync(1, 256);
            if (rdy) load_mod();
        }
        for (uint32_t it = 0;; it++) {
            const uint32_t sl = it & 1;
            mbar_wait(bars + 128 + sl * 8, (it >> 1) & 1);
            const uint32_t job = lds1(bars + 160 + sl * 4);
            __syncwarp();
            if (lane == 0) mbar_arrive(bars + 144 + sl * 8);
            const int ty = job & 7, b = (job >> 3) & 15, n = (job >> 7) & 15, k0 = (job >> 11) & 127, nk = (job >> 18) & 127, ks = (job >> 25) & 15;
            if (ty == J_END) break;
            int sig = -1;
            if (ty == J_G0 || ty == J_G1 || ty == J_G2) {
                float d[64];
                #pragma unroll
                for (int i = 0; i < 64; i++) d[i] = 0.f;
                uint32_t pst = 0;
                for (int kb = 0; kb < nk; kb++) {
                    mbar_wait(bars + st * 8, ph);
                    const uint32_t a = sb + st * G_STAGE_BYTES;
                    const uint64_t da = make_desc(a + cw * 8192, 16, 1024, 1);
                    const uint64_t db = make_desc(a + 16384, 8192, 1024, 1);
                    wg_fence();
                    #pragma unroll
                    for (int k = 0; k < 4; k++) wg_ss128(d, da + (uint64_t)(k * 2), db + (uint64_t)(k * 128), 1);
                    wg_commit();
                    if (kb > 0) {
                        wg_wait<1>();
                        if (lane == 0) mbar_arrive(bars + 64 + pst * 8);
                    }
                    pst = st;
                    if (++st == G_STAGES) { st = 0; ph ^= 1; }
                }
                wg_wait<0>();
                if (lane == 0) mbar_arrive(bars + 64 + pst * 8);
                const int g = lane >> 2, t = lane & 3;
                if (ty == J_G1) {
                    #pragma unroll
                    for (int hf = 0; hf < 2; hf++) {
                        bf16* o = g_act + (size_t)(b * 128 + cwarp * 16 + g + 8 * hf) * FF + n * 128 + 8 * t;
                        #pragma unroll
                        for (int q = 0; q < 4; q++) {
                            uint32_t u[4];
                            #pragma unroll
                            for (int i = 0; i < 4; i++) {
                                const float a0 = bfr(d[4 * (4 * q + i) + 2 * hf]), a1 = bfr(d[4 * (4 * q + i) + 2 * hf + 1]);
                                u[i] = pack2(__fdividef(a0, 1.0f + __expf(-a0)), __fdividef(a1, 1.0f + __expf(-a1)));
                            }
                            const bool o1 = t & 1, o2 = t & 2;
                            uint32_t x0 = __shfl_xor_sync(0xffffffffu, o1 ? u[0] : u[1], 1), x1 = __shfl_xor_sync(0xffffffffu, o1 ? u[2] : u[3], 1);
                            if (o1) { u[0] = x0; u[2] = x1; } else { u[1] = x0; u[3] = x1; }
                            x0 = __shfl_xor_sync(0xffffffffu, o2 ? u[0] : u[2], 2); x1 = __shfl_xor_sync(0xffffffffu, o2 ? u[1] : u[3], 2);
                            if (o2) { u[0] = x0; u[1] = x1; } else { u[2] = x0; u[3] = x1; }
                            *(uint4*)(o + q * 32) = make_uint4(u[0], u[1], u[2], u[3]);
                        }
                    }
                    sig = C_G1 + b;
                } else {
                    float* o = (ty == J_G0 ? g_p0 : g_p2) + ((size_t)((b % PRING) * PMAX + ks) * 128 + cwarp * 16 + g) * DM + n * 128 + 2 * t;
                    #pragma unroll
                    for (int hf = 0; hf < 2; hf++) {
                        #pragma unroll
                        for (int j = 0; j < 16; j++)
                            *(float2*)(o + hf * 8 * DM + j * 8) = make_float2(d[4 * j + 2 * hf], d[4 * j + 2 * hf + 1]);
                    }
                    sig = (ty == J_G0 ? C_G0 : C_G2) + b;
                }
            } else if (ty == J_MOD) {
                mod_chunk<256, 2>(cvec, wmod, k0 * 64, ct, red);
                sig = C_MOD;
            } else {
                const bool ln = ty == J_LN;
                if (!have_mod) load_mod();
                const uint2* gm = smod + (ln ? 0 : 480) + lane;
                for (int r = 0; r < nk; r++) {
                    const int lr = (n * nk + r) * 8 + cwarp, row = b * 128 + lr;
                    const float* pp = (ln ? g_p0 : g_p2) + ((size_t)((b % PRING) * PMAX) * 128 + lr) * DM + lane * 4;
                    const bf16* xs = (ln ? xin : (const bf16*)g_x1) + (size_t)row * DM + lane * 4;
                    float v[5][4];
                    uint2 xv[5];
                    #pragma unroll
                    for (int i = 0; i < 5; i++) {
                        xv[i] = __ldcg((const uint2*)(xs + i * 128));
                        v[i][0] = 0.f; v[i][1] = 0.f; v[i][2] = 0.f; v[i][3] = 0.f;
                    }
                    if (ks == 3) {
                        float4 a[3][5];
                        #pragma unroll
                        for (int q = 0; q < 3; q++) {
                            #pragma unroll
                            for (int i = 0; i < 5; i++) a[q][i] = __ldcg((const float4*)(pp + (size_t)q * 128 * DM + i * 128));
                        }
                        #pragma unroll
                        for (int q = 0; q < 3; q++) {
                            #pragma unroll
                            for (int i = 0; i < 5; i++) { v[i][0] += a[q][i].x; v[i][1] += a[q][i].y; v[i][2] += a[q][i].z; v[i][3] += a[q][i].w; }
                        }
                    } else {
                        for (int q0 = 0; q0 < ks; q0 += 6) {
                            float4 a[6][5];
                            #pragma unroll
                            for (int q = 0; q < 6; q++) {
                                #pragma unroll
                                for (int i = 0; i < 5; i++) a[q][i] = __ldcg((const float4*)(pp + (size_t)(q0 + q) * 128 * DM + i * 128));
                            }
                            #pragma unroll
                            for (int q = 0; q < 6; q++) {
                                #pragma unroll
                                for (int i = 0; i < 5; i++) { v[i][0] += a[q][i].x; v[i][1] += a[q][i].y; v[i][2] += a[q][i].z; v[i][3] += a[q][i].w; }
                            }
                        }
                    }
                    bf16* dst = (ln ? (bf16*)g_x1 : outp) + (size_t)row * DM + lane * 4;
                    #pragma unroll
                    for (int i = 0; i < 5; i++) {
                        const uint2 gg = gm[i * 32];
                        xv[i].x = hadd2(xv[i].x, hmul2(gg.x, pack2(v[i][0], v[i][1])));
                        xv[i].y = hadd2(xv[i].y, hmul2(gg.y, pack2(v[i][2], v[i][3])));
                        *(uint2*)(dst + i * 128) = xv[i];
                    }
                    if (ln) {
                        uint32_t mb; float rs;
                        ln_stats(xv, mb, rs);
                        #pragma unroll
                        for (int i = 0; i < 5; i++) {
                            const uint2 sh = gm[160 + i * 32], m1 = gm[320 + i * 32];
                            *(uint2*)(g_h2 + (size_t)row * DM + lane * 4 + i * 128) =
                                make_uint2(ln_apply(xv[i].x, mb, rs, m1.x, sh.x), ln_apply(xv[i].y, mb, rs, m1.y, sh.y));
                        }
                    }
                }
                if (ln) sig = C_LN + b; else if (b < 16 - PRING) sig = C_FIN + b;
            }
            if (sig >= 0) {
                bar_sync(1, 256);
                if (ct == 0) signal_cnt(sig);
            }
            if (ct == 0) T2(1024 + ji * 4 + 2);
        }
    }
}

typedef CUresult (*EncodeFn)(CUtensorMap*, CUtensorMapDataType, cuuint32_t, void*, const cuuint64_t*, const cuuint64_t*,
                             const cuuint32_t*, const cuuint32_t*, CUtensorMapInterleave, CUtensorMapSwizzle,
                             CUtensorMapL2promotion, CUtensorMapFloatOOBfill);

static void make_map(EncodeFn fn, CUtensorMap* m, const void* ptr, uint64_t inner, uint64_t outer, uint32_t bi, uint32_t bo,
                     CUtensorMapSwizzle sw = CU_TENSOR_MAP_SWIZZLE_128B) {
    cuuint64_t dims[2] = {inner, outer};
    cuuint64_t strides[1] = {inner * 2};
    cuuint32_t box[2] = {bi, bo};
    cuuint32_t es[2] = {1, 1};
    fn(m, CU_TENSOR_MAP_DATA_TYPE_BFLOAT16, 2, (void*)ptr, dims, strides, box, es, CU_TENSOR_MAP_INTERLEAVE_NONE,
       sw, CU_TENSOR_MAP_L2_PROMOTION_L2_256B, CU_TENSOR_MAP_FLOAT_OOB_FILL_NONE);
}

extern "C" void kernel_launch(void* const* d_in, const int* in_sizes, int n_in, void* d_out, int out_size) {
    const bf16* x = (const bf16*)d_in[0];
    const bf16* mem0 = (const bf16*)d_in[1];
    const bf16* Wq = (const bf16*)d_in[2];
    const bf16* Wk = (const bf16*)d_in[3];
    const bf16* Wv = (const bf16*)d_in[4];
    const bf16* Wo = (const bf16*)d_in[5];
    const bf16* w1 = (const bf16*)d_in[8];
    const bf16* w2 = (const bf16*)d_in[9];
    const bf16* c = (const bf16*)d_in[10];
    const bf16* wmod = (const bf16*)d_in[11];
    bf16* out = (bf16*)d_out;

    static EncodeFn enc = nullptr;
    static void *p_ox, *p_x1, *p_h2, *p_act;
    if (!enc) {
        cudaDriverEntryPointQueryResult qr;
        void* f = nullptr;
        cudaGetDriverEntryPoint("cuTensorMapEncodeTiled", &f, cudaEnableDefault, &qr);
        enc = (EncodeFn)f;
        cudaGetSymbolAddress(&p_ox, g_ox);
        cudaGetSymbolAddress(&p_x1, g_x1);
        cudaGetSymbolAddress(&p_h2, g_h2);
        cudaGetSymbolAddress(&p_act, g_act);
        cudaFuncSetAttribute(k_rec, cudaFuncAttributeMaxDynamicSharedMemorySize, SM_TOTAL);
        cudaFuncSetAttribute(k_side, cudaFuncAttributeMaxDynamicSharedMemorySize, G_SMEM);
    }
    RMaps rm;
    make_map(enc, &rm.wq, Wq, HD, DM, 64, 128);
    make_map(enc, &rm.wk, Wk, HD, DM, 64, 128);
    make_map(enc, &rm.wv, Wv, HD, DM, 64, 128);
    make_map(enc, &rm.wo, Wo, DM, HD, 16, 64, CU_TENSOR_MAP_SWIZZLE_32B);
    make_map(enc, &rm.wop, Wo, DM, HD, 224, 192, CU_TENSOR_MAP_SWIZZLE_NONE);
    SMaps m;
    make_map(enc, &m.ox, p_ox, HD, SEQ, 64, 128);
    make_map(enc, &m.wo, Wo, DM, HD, 64, 64);
    make_map(enc, &m.h2, p_h2, DM, SEQ, 64, 128);
    make_map(enc, &m.w1, w1, FF, DM, 64, 64);
    make_map(enc, &m.act, p_act, FF, SEQ, 64, 128);
    make_map(enc, &m.w2, w2, DM, FF, 64, 64);

    cudaStream_t st = cudaStreamPerThread;
    {
        cudaLaunchConfig_t cfg = {};
        cfg.gridDim = dim3(96); cfg.blockDim = dim3(512); cfg.dynamicSmemBytes = SM_TOTAL; cfg.stream = st;
        cudaLaunchAttribute at[2];
        at[0].id = cudaLaunchAttributeClusterDimension;
        at[0].val.clusterDim.x = 3; at[0].val.clusterDim.y = 1; at[0].val.clusterDim.z = 1;
        cfg.attrs = at; cfg.numAttrs = 1;
        cudaLaunchKernelEx(&cfg, k_rec, rm, mem0, Wo, x, c, wmod);
    }
    {
        cudaLaunchConfig_t cfg = {};
        cfg.gridDim = dim3(SIDE_CTAS); cfg.blockDim = dim3(384); cfg.dynamicSmemBytes = G_SMEM; cfg.stream = st;
        cudaLaunchAttribute at[1];
        at[0].id = cudaLaunchAttributeProgrammaticStreamSerialization;
        at[0].val.programmaticStreamSerializationAllowed = 1;
        cfg.attrs = at; cfg.numAttrs = 1;
        cudaLaunchKernelEx(&cfg, k_side, m, x, c, wmod, out);
    }
}
```

```cpp
#include <cuda_runtime.h>
#include <cuda_bf16.h>
#include <cuda.h>
#include <stdint.h>

typedef __nv_bfloat16 bf16;
#define VX_THROTTLE 1
#define H1_DELAY 400
#define H1_BACK 0
#define VM_THROTTLE 1
#define PRE_TRIG 0
#define NPACE 4
#define PF_LATE 1
#define SIDE_CTAS 132

constexpr int SEQ = 2048, DM = 640, NH = 32, DH = 192, NSEG = 64, FF = 1536, HD = NH * DH;

__device__ __align__(128) float g_mod[6 * DM];
__device__ __align__(1024) bf16 g_ht[(size_t)SEQ * DM];
__device__ __align__(1024) bf16 g_ox[(size_t)SEQ * HD];
__device__ __align__(1024) bf16 g_x1[(size_t)SEQ * DM];
__device__ __align__(1024) bf16 g_h2[(size_t)SEQ * DM];
__device__ __align__(1024) bf16 g_act[(size_t)SEQ * FF];
__device__ __align__(8192) uint32_t g_buf1[80 * 2 * 2048];
__device__ __align__(8192) uint32_t g_buf2[4 * 3 * 2048];
__device__ uint32_t g_choice[128];
__device__ uint32_t g_epoch;
__device__ uint32_t g_hflag[64];
__device__ __align__(128) uint32_t g_modx[2 * DM];
#define T2(i)
#define T3(i)
enum { C_Q = 0, C_MOD = 1, C_REC = 2, C_G0 = 18, C_LN = 34, C_G1 = 50, C_G2 = 66, C_FIN = 82, C_NUM = 98 };
__device__ __align__(128) uint32_t g_cnt[C_NUM * 32];
constexpr int PMAX = 12;
constexpr int PRING = 4;
__device__ __align__(1024) float g_p0[(size_t)PRING * PMAX * 128 * DM];
__device__ __align__(1024) float g_p2[(size_t)PRING * PMAX * 128 * DM];
#define TR(k)

#define FRESH(x) asm volatile("" : "+r"(x))
__device__ __forceinline__ float bfr(float x) { uint32_t r; asm("cvt.rn.bf16x2.f32 %0, %1, %2;" : "=r"(r) : "f"(x), "f"(0.0f)); return __uint_as_float(r); }
__device__ __forceinline__ uint32_t pack2(float a, float b) {
    uint32_t r; asm("cvt.rn.bf16x2.f32 %0, %1, %2;" : "=r"(r) : "f"(b), "f"(a)); return r;
}
__device__ __forceinline__ float bflo(uint32_t v) { return __uint_as_float(v << 16); }
__device__ __forceinline__ float bfhi(uint32_t v) { return __uint_as_float(v & 0xffff0000u); }
__device__ __forceinline__ float ex2(float x) { float r; asm("ex2.approx.ftz.f32 %0, %1;" : "=f"(r) : "f"(x)); return r; }
__device__ __forceinline__ float rcpf(float x) { float r; asm("rcp.approx.ftz.f32 %0, %1;" : "=f"(r) : "f"(x)); return r; }
__device__ __forceinline__ void score2(float& a, float& b) {
    const float SCALE = 0.07216878364870322f;
    uint32_t u = pack2(a, b);
    u = pack2(bflo(u) * SCALE, bfhi(u) * SCALE);
    a = bflo(u); b = bfhi(u);
}
__device__ __forceinline__ uint32_t smem_u32(const void* p) { return (uint32_t)__cvta_generic_to_shared(p); }

__device__ __forceinline__ void mbar_init(uint32_t bar, uint32_t cnt) {
    asm volatile("mbarrier.init.shared::cta.b64 [%0], %1;" :: "r"(bar), "r"(cnt) : "memory");
}
__device__ __forceinline__ void mbar_arrive(uint32_t bar) {
    asm volatile("mbarrier.arrive.shared::cta.b64 _, [%0];" :: "r"(bar) : "memory");
}
__device__ __forceinline__ void mbar_expect(uint32_t bar, uint32_t bytes) {
    asm volatile("mbarrier.arrive.expect_tx.shared::cta.b64 _, [%0], %1;" :: "r"(bar), "r"(bytes) : "memory");
}
__device__ __forceinline__ bool mbar_try(uint32_t bar, uint32_t parity) {
    uint32_t ok;
    asm volatile("{\n\t.reg .pred p;\n\tmbarrier.try_wait.parity.shared::cta.b64 p, [%1], %2;\n\tselp.u32 %0, 1, 0, p;\n\t}"
                 : "=r"(ok) : "r"(bar), "r"(parity) : "memory");
    return ok != 0;
}
__device__ __forceinline__ bool mbar_try_cluster(uint32_t bar, uint32_t parity) {
    uint32_t ok;
    asm volatile("{\n\t.reg .pred p;\n\tmbarrier.try_wait.parity.acquire.cluster.shared::cta.b64 p, [%1], %2;\n\tselp.u32 %0, 1, 0, p;\n\t}"
                 : "=r"(ok) : "r"(bar), "r"(parity) : "memory");
    return ok != 0;
}
__device__ __forceinline__ void mbar_wait(uint32_t bar, uint32_t parity) {
    uint32_t guard = 0;
    while (!mbar_try(bar, parity)) { if (++guard > (1u << 22)) __trap(); }
}
__device__ __forceinline__ void mbar_wait_cluster(uint32_t bar, uint32_t parity) {
    uint32_t guard = 0;
    while (!mbar_try_cluster(bar, parity)) { if (++guard > (1u << 22)) __trap(); }
}
__device__ __forceinline__ void bar_sync(int id, int n) { asm volatile("bar.sync %0, %1;" :: "r"(id), "r"(n) : "memory"); }
__device__ __forceinline__ void bar_arrive(int id, int n) { asm volatile("bar.arrive %0, %1;" :: "r"(id), "r"(n) : "memory"); }
__device__ __forceinline__ void sts1(uint32_t a, uint32_t v) { asm volatile("st.shared.u32 [%0], %1;" :: "r"(a), "r"(v) : "memory"); }
__device__ __forceinline__ uint32_t lds1(uint32_t a) { uint32_t v; asm volatile("ld.shared.u32 %0, [%1];" : "=r"(v) : "r"(a) : "memory"); return v; }
__device__ __forceinline__ void fence_async() { asm volatile("fence.proxy.async.shared::cta;" ::: "memory"); }
__device__ __forceinline__ void cluster_sync() {
    asm volatile("barrier.cluster.arrive.release.aligned;\n\tbarrier.cluster.wait.acquire.aligned;" ::: "memory");
}
__device__ __forceinline__ uint32_t mapa(uint32_t a, uint32_t rank) {
    uint32_t r; asm("mapa.shared::cluster.u32 %0, %1, %2;" : "=r"(r) : "r"(a), "r"(rank)); return r;
}
__device__ __forceinline__ void st_async1(uint32_t a, uint32_t v, uint32_t bar) {
    asm volatile("st.async.weak.shared::cluster.mbarrier::complete_tx::bytes.b32 [%0], %1, [%2];" :: "r"(a), "r"(v), "r"(bar) : "memory");
}
__device__ __forceinline__ void st_async2(uint32_t a, float x, float y, uint32_t bar) {
    asm volatile("st.async.weak.shared::cluster.mbarrier::complete_tx::bytes.v2.f32 [%0], {%1,%2}, [%3];" :: "r"(a), "f"(x), "f"(y), "r"(bar) : "memory");
}
__device__ __forceinline__ void st_async4(uint32_t a, const float* c, uint32_t bar) {
    asm volatile("st.async.weak.shared::cluster.mbarrier::complete_tx::bytes.v4.f32 [%0], {%1,%2,%3,%4}, [%5];"
                 :: "r"(a), "f"(c[0]), "f"(c[1]), "f"(c[2]), "f"(c[3]), "r"(bar) : "memory");
}
__device__ __forceinline__ void bulk_g2s(uint32_t dst, const void* src, uint32_t bytes, uint32_t bar) {
    asm volatile("cp.async.bulk.shared::cluster.global.mbarrier::complete_tx::bytes [%0], [%1], %2, [%3];"
                 :: "r"(dst), "l"(src), "r"(bytes), "r"(bar) : "memory");
}
__device__ __forceinline__ void cpa16(uint32_t s, const void* g) {
    asm volatile("cp.async.cg.shared.global [%0], [%1], 16;" :: "r"(s), "l"(g) : "memory");
}
__device__ __forceinline__ void cpa_wait_all() { asm volatile("cp.async.wait_all;" ::: "memory"); }
__device__ __forceinline__ void ldsm4(uint32_t* r, uint32_t a) {
    asm volatile("ldmatrix.sync.aligned.m8n8.x4.shared.b16 {%0,%1,%2,%3}, [%4];" : "=r"(r[0]), "=r"(r[1]), "=r"(r[2]), "=r"(r[3]) : "r"(a) : "memory");
}
__device__ __forceinline__ void ldsm4t(uint32_t* r, uint32_t a) {
    asm volatile("ldmatrix.sync.aligned.m8n8.x4.trans.shared.b16 {%0,%1,%2,%3}, [%4];" : "=r"(r[0]), "=r"(r[1]), "=r"(r[2]), "=r"(r[3]) : "r"(a) : "memory");
}
__device__ __forceinline__ void stsm2t(uint32_t a, uint32_t r0, uint32_t r1) {
    asm volatile("stmatrix.sync.aligned.m8n8.x2.trans.shared.b16 [%0], {%1,%2};" :: "r"(a), "r"(r0), "r"(r1) : "memory");
}
__device__ __forceinline__ void stsm4t(uint32_t a, uint32_t r0, uint32_t r1, uint32_t r2, uint32_t r3) {
    asm volatile("stmatrix.sync.aligned.m8n8.x4.trans.shared.b16 [%0], {%1,%2,%3,%4};" :: "r"(a), "r"(r0), "r"(r1), "r"(r2), "r"(r3) : "memory");
}
__device__ __forceinline__ uint32_t movm(uint32_t v) {
    uint32_t r; asm volatile("movmatrix.sync.aligned.m8n8.trans.b16 %0, %1;" : "=r"(r) : "r"(v)); return r;
}
__device__ __forceinline__ void mma16(float* c, uint32_t a0, uint32_t a1, uint32_t a2, uint32_t a3, uint32_t b0, uint32_t b1) {
    asm volatile("mma.sync.aligned.m16n8k16.row.col.f32.bf16.bf16.f32 {%0,%1,%2,%3}, {%4,%5,%6,%7}, {%8,%9}, {%0,%1,%2,%3};"
                 : "+f"(c[0]), "+f"(c[1]), "+f"(c[2]), "+f"(c[3]) : "r"(a0), "r"(a1), "r"(a2), "r"(a3), "r"(b0), "r"(b1));
}
__device__ __forceinline__ void mma8(float* c, uint32_t a0, uint32_t a1, uint32_t b0) {
    asm volatile("mma.sync.aligned.m16n8k8.row.col.f32.bf16.bf16.f32 {%0,%1,%2,%3}, {%4,%5}, {%6}, {%0,%1,%2,%3};"
                 : "+f"(c[0]), "+f"(c[1]), "+f"(c[2]), "+f"(c[3]) : "r"(a0), "r"(a1), "r"(b0));
}
__host__ __device__ constexpr uint64_t make_desc(uint32_t saddr, uint32_t lbo, uint32_t sbo, uint32_t layout) {
    return (uint64_t)((saddr & 0x3FFFF) >> 4) | ((uint64_t)(lbo >> 4) << 16) | ((uint64_t)(sbo >> 4) << 32) | ((uint64_t)layout << 62);
}
__device__ __forceinline__ void wg_fence() { asm volatile("wgmma.fence.sync.aligned;" ::: "memory"); }
__device__ __forceinline__ void wg_commit() { asm volatile("wgmma.commit_group.sync.aligned;" ::: "memory"); }
template <int N> __device__ __forceinline__ void wg_wait() { asm volatile("wgmma.wait_group.sync.aligned %0;" :: "n"(N) : "memory"); }

#define D16(C) C(d[0]), C(d[1]), C(d[2]), C(d[3]), C(d[4]), C(d[5]), C(d[6]), C(d[7]), \
               C(d[8]), C(d[9]), C(d[10]), C(d[11]), C(d[12]), C(d[13]), C(d[14]), C(d[15])
#define DREG16 "{%0,%1,%2,%3,%4,%5,%6,%7,%8,%9,%10,%11,%12,%13,%14,%15}"
__device__ __forceinline__ void wg_rs32(float* d, const uint32_t* a, uint64_t db, bool acc) {
    if (acc)
        asm volatile("wgmma.mma_async.sync.aligned.m64n32k16.f32.bf16.bf16 " DREG16 ", {%16,%17,%18,%19}, %20, 1, 1, 1, 0;"
            : D16("+f") : "r"(a[0]), "r"(a[1]), "r"(a[2]), "r"(a[3]), "l"(db));
    else
        asm volatile("wgmma.mma_async.sync.aligned.m64n32k16.f32.bf16.bf16 " DREG16 ", {%16,%17,%18,%19}, %20, 0, 1, 1, 0;"
            : D16("=f") : "r"(a[0]), "r"(a[1]), "r"(a[2]), "r"(a[3]), "l"(db));
}
__device__ __forceinline__ void wg_ss32(float* d, uint64_t da, uint64_t db, bool acc) {
    if (acc)
        asm volatile("wgmma.mma_async.sync.aligned.m64n32k16.f32.bf16.bf16 " DREG16 ", %16, %17, 1, 1, 1, 1, 0;"
            : D16("+f") : "l"(da), "l"(db));
    else
        asm volatile("wgmma.mma_async.sync.aligned.m64n32k16.f32.bf16.bf16 " DREG16 ", %16, %17, 0, 1, 1, 1, 0;"
            : D16("=f") : "l"(da), "l"(db));
}
__device__ __forceinline__ void wg_ss8(float* d, uint64_t da, uint64_t db, bool acc) {
    if (acc)
        asm volatile("wgmma.mma_async.sync.aligned.m64n8k16.f32.bf16.bf16 {%0,%1,%2,%3}, %4, %5, 1, 1, 1, 1, 1;"
            : "+f"(d[0]), "+f"(d[1]), "+f"(d[2]), "+f"(d[3]) : "l"(da), "l"(db));
    else
        asm volatile("wgmma.mma_async.sync.aligned.m64n8k16.f32.bf16.bf16 {%0,%1,%2,%3}, %4, %5, 0, 1, 1, 1, 1;"
            : "=f"(d[0]), "=f"(d[1]), "=f"(d[2]), "=f"(d[3]) : "l"(da), "l"(db));
}
template <int OFF> __device__ __forceinline__ void ldsm4t_i(uint32_t* r, uint32_t a) {
    asm volatile("ldmatrix.sync.aligned.m8n8.x4.trans.shared.b16 {%0,%1,%2,%3}, [%4+%5];"
                 : "=r"(r[0]), "=r"(r[1]), "=r"(r[2]), "=r"(r[3]) : "r"(a), "n"(OFF) : "memory");
}

__device__ __forceinline__ uint4 ld_relaxed4(const void* p) {
    uint4 v;
    asm volatile("ld.relaxed.gpu.global.v4.u32 {%0,%1,%2,%3}, [%4];" : "=r"(v.x), "=r"(v.y), "=r"(v.z), "=r"(v.w) : "l"(p) : "memory");
    return v;
}
__device__ __forceinline__ void st_relaxed2(void* p, uint32_t a, uint32_t b) {
    asm volatile("st.relaxed.gpu.global.v2.u32 [%0], {%1,%2};" :: "l"(p), "r"(a), "r"(b) : "memory");
}
__device__ __forceinline__ void st_relaxed2_off(void* base, uint32_t off, uint32_t a, uint32_t b) {
    asm volatile("{\n\t.reg .u64 ad;\n\tcvt.u64.u32 ad, %1;\n\tadd.u64 ad, ad, %0;\n\tst.relaxed.gpu.global.v2.u32 [ad], {%2,%3};\n\t}"
                 :: "l"(base), "r"(off), "r"(a), "r"(b) : "memory");
}
__device__ __forceinline__ void st_relaxed1(void* p, uint32_t a) {
    asm volatile("st.relaxed.gpu.global.u32 [%0], %1;" :: "l"(p), "r"(a) : "memory");
}
__device__ __forceinline__ uint32_t ld_acquire1(const uint32_t* p) {
    uint32_t v; asm volatile("ld.acquire.gpu.global.u32 %0, [%1];" : "=r"(v) : "l"(p) : "memory"); return v;
}
__device__ __forceinline__ void st_release1(uint32_t* p, uint32_t a) {
    asm volatile("st.release.gpu.global.u32 [%0], %1;" :: "l"(p), "r"(a) : "memory");
}
__device__ __forceinline__ uint4 lds4(uint32_t s) {
    uint4 v; asm volatile("ld.shared.v4.u32 {%0,%1,%2,%3}, [%4];" : "=r"(v.x), "=r"(v.y), "=r"(v.z), "=r"(v.w) : "r"(s) : "memory"); return v;
}
__device__ __forceinline__ void sts4(uint32_t s, const uint4& v) {
    asm volatile("st.shared.v4.u32 [%0], {%1,%2,%3,%4};" :: "r"(s), "r"(v.x), "r"(v.y), "r"(v.z), "r"(v.w) : "memory");
}
__device__ __forceinline__ float4 lds4f(uint32_t s) {
    float4 v; asm volatile("ld.shared.v4.f32 {%0,%1,%2,%3}, [%4];" : "=f"(v.x), "=f"(v.y), "=f"(v.z), "=f"(v.w) : "r"(s) : "memory"); return v;
}
__device__ __forceinline__ uint2 lds2(uint32_t s) {
    uint2 v; asm volatile("ld.shared.v2.u32 {%0,%1}, [%2];" : "=r"(v.x), "=r"(v.y) : "r"(s) : "memory"); return v;
}
__device__ __forceinline__ float2 lds2f(uint32_t s) {
    float2 v; asm volatile("ld.shared.v2.f32 {%0,%1}, [%2];" : "=f"(v.x), "=f"(v.y) : "r"(s) : "memory"); return v;
}
__device__ __forceinline__ uint32_t clk32() { uint32_t c; asm volatile("mov.u32 %0, %%clock;" : "=r"(c) :: "memory"); return c; }
__device__ __forceinline__ uint32_t tagw(float v, uint32_t tag) { return ((__float_as_uint(v) + 8u) & ~15u) | tag; }
__device__ __forceinline__ bool ok4(const uint4& v, uint32_t tag) { return (((v.x ^ tag) | (v.y ^ tag) | (v.z ^ tag) | (v.w ^ tag)) & 15u) == 0; }
__device__ __forceinline__ bool oks(const uint4& v) { return v.x != 0xFFFFFFFFu && v.y != 0xFFFFFFFFu && v.z != 0xFFFFFFFFu && v.w != 0xFFFFFFFFu; }
__device__ __forceinline__ float uf(uint32_t x) { return __uint_as_float(x & ~15u); }

template <int NT, int BAR>
__device__ __forceinline__ void mod_chunk(const bf16* __restrict__ c, const bf16* __restrict__ wmod, int col0, int tid, float* red) {
    constexpr int RG = NT / 8, NP = DM / RG;
    const int cc = tid & 7, rg = tid >> 3;
    uint4 w[NP];
    #pragma unroll
    for (int i = 0; i < NP; i++) w[i] = __ldg((const uint4*)(wmod + (size_t)(rg + i * RG) * (6 * DM) + col0 + cc * 8));
    float a[8];
    #pragma unroll
    for (int j = 0; j < 8; j++) a[j] = 0.f;
    #pragma unroll
    for (int i = 0; i < NP; i++) {
        const float v = __bfloat162float(c[rg + i * RG]);
        const float sv = bfr(__fdividef(v, 1.0f + __expf(-v)));
        a[0] += sv * bflo(w[i].x); a[1] += sv * bfhi(w[i].x); a[2] += sv * bflo(w[i].y); a[3] += sv * bfhi(w[i].y);
        a[4] += sv * bflo(w[i].z); a[5] += sv * bfhi(w[i].z); a[6] += sv * bflo(w[i].w); a[7] += sv * bfhi(w[i].w);
    }
    #pragma unroll
    for (int j = 0; j < 8; j++) {
        a[j] += __shfl_xor_sync(0xffffffffu, a[j], 8);
        a[j] += __shfl_xor_sync(0xffffffffu, a[j], 16);
    }
    if ((tid & 31) < 8) {
        float* d = red + (tid >> 5) * 64 + cc * 8;
        *(float4*)d = make_float4(a[0], a[1], a[2], a[3]);
        *(float4*)(d + 4) = make_float4(a[4], a[5], a[6], a[7]);
    }
    bar_sync(BAR, NT);
    if (tid < 64) {
        float s = 0.f;
        #pragma unroll
        for (int i = 0; i < NT / 32; i++) s += red[i * 64 + tid];
        g_mod[col0 + tid] = bfr(s);
    }
}

__device__ __forceinline__ uint32_t hadd2(uint32_t a, uint32_t b) { uint32_t r; asm("add.rn.bf16x2 %0, %1, %2;" : "=r"(r) : "r"(a), "r"(b)); return r; }
__device__ __forceinline__ uint32_t hsub2(uint32_t a, uint32_t b) { uint32_t r; asm("sub.rn.bf16x2 %0, %1, %2;" : "=r"(r) : "r"(a), "r"(b)); return r; }
__device__ __forceinline__ uint32_t hmul2(uint32_t a, uint32_t b) { uint32_t r; asm("mul.rn.bf16x2 %0, %1, %2;" : "=r"(r) : "r"(a), "r"(b)); return r; }
__device__ __forceinline__ void ln_stats(const uint2* x, uint32_t& mb2, float& rs) {
    float v[5][4];
    float s = 0.f;
    #pragma unroll
    for (int i = 0; i < 5; i++) {
        v[i][0] = bflo(x[i].x); v[i][1] = bfhi(x[i].x); v[i][2] = bflo(x[i].y); v[i][3] = bfhi(x[i].y);
        s += (v[i][0] + v[i][1]) + (v[i][2] + v[i][3]);
    }
    #pragma unroll
    for (int o = 16; o > 0; o >>= 1) s += __shfl_xor_sync(0xffffffffu, s, o);
    const float mean = s * (1.0f / DM);
    float q0 = 0.f, q1 = 0.f;
    #pragma unroll
    for (int i = 0; i < 5; i++) {
        const float d0 = v[i][0] - mean, d1 = v[i][1] - mean, d2 = v[i][2] - mean, d3 = v[i][3] - mean;
        q0 += d0 * d0; q1 += d1 * d1; q0 += d2 * d2; q1 += d3 * d3;
    }
    float q = q0 + q1;
    #pragma unroll
    for (int o = 16; o > 0; o >>= 1) q += __shfl_xor_sync(0xffffffffu, q, o);
    mb2 = pack2(mean, mean);
    const float var = bfr(q * (1.0f / DM));
    rs = __frcp_rn(bfr(__fsqrt_rn(bfr(var + 1e-5f))));
}
__device__ __forceinline__ uint32_t ln_apply(uint32_t x, uint32_t mb2, float rs, uint32_t m1, uint32_t sh) {
    const uint32_t d = hsub2(x, mb2);
    return hadd2(hmul2(pack2(bflo(d) * rs, bfhi(d) * rs), m1), sh);
}

constexpr int SM_WV = 0;
constexpr int SM_HB = 81920;
constexpr int SM_WO = SM_HB + 40960;
constexpr int SM_QX = SM_WO + 77824;
constexpr int SM_KS = SM_QX + 4096;
constexpr int SM_QM = SM_KS + 5120;
constexpr int SM_XS = SM_QM + 1024;
constexpr int SM_MS = SM_XS + 12288;
constexpr int SM_OS = SM_MS + 3840;
constexpr int SM_PM = SM_OS + 3072;
constexpr int SM_BAR = SM_PM + 640;
constexpr int SM_CH = SM_BAR + 128;
constexpr int SM_TOTAL = SM_CH + 128;
static_assert(SM_TOTAL <= 232448, "smem");

enum { B_MEM_FULL = 0, B_MEM_FREE, B_HLO_FULL, B_HHI_FULL, B_HLO_FREE, B_HHI_FREE, B_MS, B_O, B_XS, B_O1, B_XSFREE, B_WQ, B_P0, B_WV, B_WO, B_P1 };

__device__ __forceinline__ int probe_blk(uint32_t* blk) {
    uint32_t t0 = 0xffffffffu, t1 = 0xffffffffu, acc = 0;
    for (int rep = 0; rep < 3; rep++) {
        #pragma unroll
        for (int pg = 0; pg < 2; pg++) {
            uint32_t c0 = clk32();
            uint32_t v = atomicOr(blk + pg * 1024 + acc, 0u);
            acc = (v == 0x12345678u) ? 1u : 0u;
            asm volatile("" :: "r"(acc) : "memory");
            uint32_t c1 = clk32() + acc;
            uint32_t d = c1 - c0;
            if (rep > 0) { if (pg == 0) t0 = min(t0, d); else t1 = min(t1, d); }
        }
    }
    return t1 < t0 ? 1 : 0;
}

__device__ __forceinline__ uint32_t wo_tile_off(int w) {
    if (w < 8) return w * 6144;
    if (w < 12) return 8 * 6144 + (w - 8) * 4096;
    return 8 * 6144 + 4 * 4096 + (w - 12) * 6144;
}

template <int NRES, int NPRE>
__device__ __forceinline__ void wo_phase(uint32_t sb, int w, int lane, const uint32_t (*res)[4], uint32_t parity,
                                         uint32_t tag, int tile, int h) {
    FRESH(lane);
    const int er = (lane & 7) + 8 * (lane >> 4);
    const uint32_t aaddr = sb + SM_WO + wo_tile_off(w) + er * 32 + ((((lane >> 3) & 1) ^ ((er >> 2) & 1)) << 4);
    const uint32_t baddr = sb + SM_OS + lane * 16;
    float c0[4] = {0.f, 0.f, 0.f, 0.f}, c1[4] = {0.f, 0.f, 0.f, 0.f};
    uint32_t pre[NPRE > 4 ? NPRE : 4][4];
    if (NPRE >= 4) {
        #pragma unroll
        for (int i = 0; i < 4; i++) ldsm4t(pre[i], aaddr + i * 512);
        mbar_wait(sb + SM_BAR + B_O1 * 8, parity);
        uint32_t b[2][4];
        ldsm4t(b[0], baddr);
        ldsm4t(b[1], baddr + 512);
        #pragma unroll
        for (int kp = 0; kp < 2; kp++) {
            mma16(c0, pre[2 * kp][0], pre[2 * kp][1], pre[2 * kp][2], pre[2 * kp][3], b[kp][0], b[kp][1]);
            mma16(c1, pre[2 * kp + 1][0], pre[2 * kp + 1][1], pre[2 * kp + 1][2], pre[2 * kp + 1][3], b[kp][2], b[kp][3]);
        }
    } else {
        #pragma unroll
        for (int i = 0; i < 2; i++) ldsm4t(pre[i], aaddr + i * 512);
        mbar_wait(sb + SM_BAR + B_O1 * 8, parity);
        #pragma unroll
        for (int kp = 0; kp < 2; kp++) {
            uint32_t b[4];
            ldsm4t(b, baddr + kp * 512);
            if (kp == 1) { ldsm4t(pre[0], aaddr + 2 * 512); ldsm4t(pre[1], aaddr + 3 * 512); }
            mma16(c0, pre[0][0], pre[0][1], pre[0][2], pre[0][3], b[0], b[1]);
            mma16(c1, pre[1][0], pre[1][1], pre[1][2], pre[1][3], b[2], b[3]);
        }
    }
    #pragma unroll
    for (int i = 0; i < NPRE; i++) ldsm4t(pre[i], aaddr + (4 + i) * 512);
    uint32_t off0, off1;
    {
        uint32_t ch;
        asm volatile("ld.shared.u16 %0, [%1];" : "=r"(ch) : "r"(sb + SM_CH + 2 * tile) : "memory");
        const int j = h >> 4;
        const uint32_t base = (uint32_t)((tile * 4 + j) * 8192 + (h & 15) * 256 + lane * 8);
        ch >>= j;
        off0 = base + (ch & 1) * 4096;
        off1 = base + 16384 + (ch & 256) * 16;
    }
    mbar_wait(sb + SM_BAR + B_O * 8, parity);
    if (NRES == 4) {
        uint32_t b[4][4];
        #pragma unroll
        for (int i = 0; i < 4; i++) ldsm4t(b[i], baddr + (2 + i) * 512);
        #pragma unroll
        for (int i = 0; i < 2; i++) {
            mma16(c0, res[2 * i][0], res[2 * i][1], res[2 * i][2], res[2 * i][3], b[i][0], b[i][1]);
            mma16(c1, res[2 * i + 1][0], res[2 * i + 1][1], res[2 * i + 1][2], res[2 * i + 1][3], b[i][2], b[i][3]);
        }
        #pragma unroll
        for (int i = 0; i < 2; i++) {
            mma16(c0, pre[2 * i][0], pre[2 * i][1], pre[2 * i][2], pre[2 * i][3], b[2 + i][0], b[2 + i][1]);
            mma16(c1, pre[2 * i + 1][0], pre[2 * i + 1][1], pre[2 * i + 1][2], pre[2 * i + 1][3], b[2 + i][2], b[2 + i][3]);
        }
    } else if (NPRE == 4) {
        uint32_t b[2][4];
        #pragma unroll
        for (int hh = 0; hh < 2; hh++) {
            ldsm4t(b[0], baddr + (2 + 2 * hh) * 512);
            ldsm4t(b[1], baddr + (3 + 2 * hh) * 512);
            if (hh) {
                #pragma unroll
                for (int i = 0; i < 4; i++) ldsm4t(pre[i], aaddr + (8 + i) * 512);
            }
            #pragma unroll
            for (int i = 0; i < 2; i++) {
                mma16(c0, pre[2 * i][0], pre[2 * i][1], pre[2 * i][2], pre[2 * i][3], b[i][0], b[i][1]);
                mma16(c1, pre[2 * i + 1][0], pre[2 * i + 1][1], pre[2 * i + 1][2], pre[2 * i + 1][3], b[i][2], b[i][3]);
            }
        }
    }
    st_relaxed2_off(g_buf1, off0, tagw(c0[0] + c1[0], tag), tagw(c0[1] + c1[1], tag));
    st_relaxed2_off(g_buf1, off1, tagw(c0[2] + c1[2], tag), tagw(c0[3] + c1[3], tag));
}

template <int NT, bool MASK>
__device__ __forceinline__ void softmax_core(float (*sc)[2], int g, int t, uint32_t* pb) {
    const float L2E = 1.4426950408889634f;
    #pragma unroll
    for (int j = 0; j < NT; j++) score2(sc[j][0], sc[j][1]);
    if (MASK) {
        const float NEG = -999292928.0f;
        if (2 * t > g) sc[NT - 1][0] = NEG;
        if (2 * t + 1 > g) sc[NT - 1][1] = NEG;
    }
    float m[NT];
    #pragma unroll
    for (int j = 0; j < NT; j++) m[j] = fmaxf(sc[j][0], sc[j][1]);
    float mx = m[0];
    #pragma unroll
    for (int j = 1; j < NT; j++) mx = fmaxf(mx, m[j]);
    mx = fmaxf(mx, __shfl_xor_sync(0xffffffffu, mx, 1));
    mx = fmaxf(mx, __shfl_xor_sync(0xffffffffu, mx, 2));
    float s0 = 0.f, s1 = 0.f;
    #pragma unroll
    for (int j = 0; j < NT; j++) {
        sc[j][0] = ex2((sc[j][0] - mx) * L2E); sc[j][1] = ex2((sc[j][1] - mx) * L2E);
        s0 += sc[j][0]; s1 += sc[j][1];
    }
    s0 += s1;
    s0 += __shfl_xor_sync(0xffffffffu, s0, 1);
    s0 += __shfl_xor_sync(0xffffffffu, s0, 2);
    const float iv = rcpf(s0);
    #pragma unroll
    for (int j = 0; j < NT; j++) pb[j] = pack2(sc[j][0] * iv, sc[j][1] * iv);
}
template <int NT>
__device__ __forceinline__ void xsoftmax(uint32_t a, int g, int t) {
    float sc[NT][2];
    #pragma unroll
    for (int j = 0; j < NT; j++) {
        float2 v0 = lds2f(a + j * 512), v1 = lds2f(a + j * 512 + 4096), v2 = lds2f(a + j * 512 + 8192);
        sc[j][0] = v0.x + v1.x + v2.x; sc[j][1] = v0.y + v1.y + v2.y;
    }
    uint32_t pb[NT];
    softmax_core<NT, true>(sc, g, t, pb);
    #pragma unroll
    for (int j = 0; j < NT; j += 2) {
        if (j + 1 < NT) asm volatile("st.shared.v2.u32 [%0], {%1,%2};" :: "r"(a + j * 512), "r"(pb[j]), "r"(pb[j + 1]) : "memory");
        else sts1(a + j * 512, pb[j]);
    }
}
template <int NJ>
__device__ __forceinline__ void xscores(uint32_t sb, int p, int mi, int j0, int lane) {
    FRESH(lane);
    const int r = lane & 7, cq = lane >> 3;
    const int qrow = mi * 16 + r + 8 * (cq & 1);
    uint32_t kb[NJ][8];
    float d[NJ][4];
    #pragma unroll
    for (int j = 0; j < NJ; j++) {
        ldsm4(kb[j], sb + SM_KS + ((j0 + j) * 8 + r) * 128 + ((cq ^ r) << 4));
        ldsm4(kb[j] + 4, sb + SM_KS + ((j0 + j) * 8 + r) * 128 + (((cq + 4) ^ r) << 4));
        d[j][0] = 0.f; d[j][1] = 0.f; d[j][2] = 0.f; d[j][3] = 0.f;
    }
    #pragma unroll
    for (int kt = 0; kt < 4; kt++) {
        uint32_t a[4];
        ldsm4(a, sb + SM_QX + qrow * 128 + (((2 * kt + (cq >> 1)) ^ r) << 4));
        #pragma unroll
        for (int j = 0; j < NJ; j++) mma16(d[j], a[0], a[1], a[2], a[3], kb[j][2 * kt], kb[j][2 * kt + 1]);
    }
    const uint32_t la = sb + SM_XS + p * 4096 + (mi * 3 + j0) * 512 + lane * 16;
    #pragma unroll
    for (int rk = 0; rk < 3; rk++) {
        const uint32_t ra = mapa(la, rk), rb = mapa(sb + SM_BAR + B_XS * 8, rk);
        #pragma unroll
        for (int j = 0; j < NJ; j++) st_async4(ra + j * 512, d[j], rb);
    }
}
__device__ __forceinline__ void mbar_arrive_remote(uint32_t bar) {
    asm volatile("mbarrier.arrive.relaxed.cluster.shared::cluster.b64 _, [%0];" :: "r"(bar) : "memory");
}

__device__ __forceinline__ void tma2d(uint32_t dst, const CUtensorMap* map, int c0, int c1, uint32_t bar) {
    asm volatile("cp.async.bulk.tensor.2d.shared::cluster.global.mbarrier::complete_tx::bytes [%0], [%1, {%2, %3}], [%4];"
                 :: "r"(dst), "l"(map), "r"(c0), "r"(c1), "r"(bar) : "memory");
}
__device__ __forceinline__ void tma2d_pf(const CUtensorMap* map, int c0, int c1) {
    asm volatile("cp.async.bulk.prefetch.tensor.2d.L2.global [%0, {%1, %2}];" :: "l"(map), "r"(c0), "r"(c1) : "memory");
}
__device__ __forceinline__ void bulk_pf(const void* p, uint32_t bytes) {
    asm volatile("cp.async.bulk.prefetch.L2.global [%0], %1;" :: "l"(p), "r"(bytes) : "memory");
}
struct RMaps { CUtensorMap wq, wk, wv, wo, wop; };
__device__ __forceinline__ void signal_cnt(int idx) {
    asm volatile("fence.proxy.async.global;\n\tred.release.gpu.global.add.u32 [%0], 1;" :: "l"(g_cnt + idx * 32) : "memory");
}

__global__ void __launch_bounds__(512, 1)
k_rec(const __grid_constant__ RMaps maps, const bf16* __restrict__ mem0, const bf16* __restrict__ Wo,
      const bf16* __restrict__ xin, const bf16* __restrict__ cvec, const bf16* __restrict__ wmod) {
    extern __shared__ __align__(1024) uint8_t smem_raw[];
    constexpr uint32_t SBC = 1024;
    const uint32_t sb = smem_u32(smem_raw);
    if ((sb & 0xFFFFFFu) != SBC) __trap();
    int lane = __shfl_sync(0xffffffffu, threadIdx.x & 31, threadIdx.x & 31);
    const int warp = __shfl_sync(0xffffffffu, threadIdx.x >> 5, 0), wg = warp >> 2;
    const int tid = warp * 32 + lane;
    const int b = blockIdx.x, h = b / 3, p = b % 3;
    const int g = lane >> 2, t = lane & 3;
    const int tile0 = p == 0 ? 0 : (p == 1 ? 14 : 27);
    const int ntile = p == 0 ? 14 : 13;
    const uint32_t bar = sb + SM_BAR;

    if (tid == 0) T2(100 + b);
    if (tid == 0) {
        mbar_init(bar + B_MEM_FULL * 8, 4);
        mbar_init(bar + B_MEM_FREE * 8, 12);
        mbar_init(bar + B_HLO_FULL * 8, 1);
        mbar_init(bar + B_HHI_FULL * 8, 1);
        mbar_init(bar + B_HLO_FREE * 8, 12);
        mbar_init(bar + B_HHI_FREE * 8, 12);
        mbar_init(bar + B_MS * 8, 1);
        mbar_init(bar + B_O * 8, 1);
        mbar_init(bar + B_XS * 8, 1);
        mbar_init(bar + B_O1 * 8, 4);
        mbar_init(bar + B_XSFREE * 8, 12);
        mbar_init(bar + B_WQ * 8, 1);
        mbar_init(bar + B_P0 * 8, 1);
        mbar_init(bar + B_P1 * 8, 1);
        mbar_init(bar + B_WV * 8, 1);
        mbar_init(bar + B_WO * 8, 1);
        asm volatile("fence.mbarrier_init.release.cluster;" ::: "memory");
        mbar_expect(bar + B_MS * 8, 3840);
        mbar_expect(bar + B_O * 8, 2048);
        mbar_expect(bar + B_XS * 8, 12288);
    }
    __syncwarp();
    asm volatile("barrier.cluster.arrive.relaxed.aligned;\n\tbarrier.cluster.wait.acquire.aligned;" ::: "memory");
    if (warp == 0) T3(0);

    if (tid == 480) {
        #pragma unroll 1
        for (int i = 0; i < 5; i++) {
            if (i > 0 && i <= NPACE) mbar_wait(bar + B_P0 * 8, (i - 1) & 1);
            if (i <= NPACE) mbar_expect(bar + B_P0 * 8, i == NPACE ? (5 - NPACE) * 16384 : 16384);
            tma2d(sb + SM_WO + i * 16384, &maps.wq, h * DH + p * 64, i * 128, bar + B_P0 * 8);
            if (i > 0 && i <= NPACE) mbar_wait(bar + B_P1 * 8, (i - 1) & 1);
            if (i <= NPACE) mbar_expect(bar + B_P1 * 8, i == NPACE ? (5 - NPACE) * 16384 : 16384);
            tma2d(sb + SM_WV + i * 16384, &maps.wk, h * DH + p * 64, i * 128, bar + B_P1 * 8);
        }
        mbar_wait(bar + B_P0 * 8, NPACE & 1);
        mbar_wait(bar + B_P1 * 8, NPACE & 1);
        mbar_arrive(bar + B_WQ * 8);
        #pragma unroll 1
        for (int i = 0; i < 5; i++) tma2d_pf(&maps.wv, h * DH + p * 64, i * 128);
        tma2d_pf(&maps.wop, tile0 * 16, h * DH);
    }
    __syncwarp();
    if (wg < 3) {
        const uint32_t tag = *(volatile uint32_t*)&g_epoch + 1u;
        const int seg1 = b + 1, nrow = b < NSEG - 1 ? 64 : 32;
        const bf16* xl = xin + lane * 4;
        uint4 wm[5];
        float cv[5];
        if (wg < 2 && b < 80) {
            #pragma unroll
            for (int i = 0; i < 5; i++) {
                wm[i] = __ldg((const uint4*)(wmod + (size_t)((tid >> 1) + 128 * i) * (6 * DM) + b * 16 + (tid & 1) * 8));
                cv[i] = __bfloat162float(cvec[(tid >> 1) + 128 * i]);
            }
        }
        uint2 xn[3][5];
        #pragma unroll
        for (int r = 0; r < 3; r++) {
            const int idx = warp + 12 * r, nx = idx < 32 ? idx : (idx < nrow ? b * 32 + idx : 0);
            #pragma unroll
            for (int i = 0; i < 5; i++) xn[r][i] = __ldg((const uint2*)(xl + (size_t)nx * DM + i * 128));
        }
        if (tid == 256 && b < NSEG - 1) bulk_pf(xin + (size_t)seg1 * 32 * DM, 32 * DM * 2);
        if (wg < 2 && b < 80) {
            float a[8];
            #pragma unroll
            for (int j = 0; j < 8; j++) a[j] = 0.f;
            #pragma unroll
            for (int i = 0; i < 5; i++) {
                const float sv = bfr(__fdividef(cv[i], 1.0f + __expf(-cv[i])));
                a[0] += sv * bflo(wm[i].x); a[1] += sv * bfhi(wm[i].x); a[2] += sv * bflo(wm[i].y); a[3] += sv * bfhi(wm[i].y);
                a[4] += sv * bflo(wm[i].z); a[5] += sv * bfhi(wm[i].z); a[6] += sv * bflo(wm[i].w); a[7] += sv * bfhi(wm[i].w);
            }
            #pragma unroll 1
            for (int o = 2; o < 32; o <<= 1) {
                #pragma unroll
                for (int j = 0; j < 8; j++) a[j] += __shfl_xor_sync(0xffffffffu, a[j], o);
            }
            if (lane < 2) {
                const uint32_t d = sb + SM_QM + warp * 64 + lane * 32;
                sts4(d, make_uint4(__float_as_uint(a[0]), __float_as_uint(a[1]), __float_as_uint(a[2]), __float_as_uint(a[3])));
                sts4(d + 16, make_uint4(__float_as_uint(a[4]), __float_as_uint(a[5]), __float_as_uint(a[6]), __float_as_uint(a[7])));
            }
            bar_sync(1, 256);
            if (tid < 8) {
                float s0 = 0.f, s1 = 0.f;
                #pragma unroll
                for (int i = 0; i < 8; i++) { const float2 v = lds2f(sb + SM_QM + i * 64 + tid * 8); s0 += v.x; s1 += v.y; }
                st_relaxed2(g_modx + (b * 8 + tid) * 2, pack2(s0, s1), tag);
            }
        }
        T3(12);
        if (tid < 320) {
            uint4 v; uint32_t guard = 0;
            while (true) {
                v = ld_relaxed4(g_modx + tid * 4);
                if (v.y == tag && v.w == tag) break;
                __nanosleep(50);
                if (++guard > (1u << 22)) __trap();
            }
            if (tid >= 160) { v.x = hadd2(v.x, 0x3f803f80u); v.z = hadd2(v.z, 0x3f803f80u); }
            asm volatile("st.shared.v2.u32 [%0], {%1,%2};" :: "r"(sb + SM_KS + tid * 8), "r"(v.x), "r"(v.z) : "memory");
        }
        bar_sync(2, 384);
        T3(13);
        #pragma unroll 1
        for (int idx = warp; idx < nrow; idx += 12) {
            uint32_t mb; float rs;
            ln_stats(xn[0], mb, rs);
            const int row = idx & 31;
            char* dst = (idx < 32 ? (char*)smem_raw + SM_HB : (char*)g_ht + (size_t)seg1 * 40960)
                        + (lane >> 4) * 4096 + row * 128 + ((((lane >> 1) & 7) ^ (row & 7)) << 4) + (lane & 1) * 8;
            #pragma unroll
            for (int i = 0; i < 5; i++) {
                const uint2 u0 = lds2(sb + SM_KS + i * 256 + lane * 8), u1 = lds2(sb + SM_KS + 1280 + i * 256 + lane * 8);
                *(uint2*)(dst + i * 8192) = make_uint2(ln_apply(xn[0][i].x, mb, rs, u1.x, u0.x), ln_apply(xn[0][i].y, mb, rs, u1.y, u0.y));
                xn[0][i] = xn[1][i]; xn[1][i] = xn[2][i];
                if (idx + 36 < nrow) xn[2][i] = __ldg((const uint2*)(xl + (size_t)(b * 32 + idx + 36) * DM + i * 128));
            }
        }
        fence_async();
        bar_sync(2, 384);
        T3(7);
        if (tid == 0) { mbar_arrive(bar + B_HLO_FULL * 8); mbar_arrive(bar + B_HHI_FULL * 8); }
        if (tid == 352 && b < NSEG - 1) {
            asm volatile("fence.proxy.async.global;" ::: "memory");
            st_release1(&g_hflag[seg1], tag);
        }
        __syncwarp();
    }

    if (wg < 2) {
        asm volatile("setmaxnreg.inc.sync.aligned.u32 200;");
        const int w = warp & 3;
        uint32_t wa[40][4];
        {
            mbar_wait(bar + B_WQ * 8, 0);
            if (w == 0) T3(1 + wg);
            const int r = lane & 7;
            const uint32_t wsrc = sb + (wg == 0 ? SM_WO : SM_WV) + (r + ((lane >> 4) << 3)) * 128 + (((2 * w + ((lane >> 3) & 1)) ^ r) << 4);
            #pragma unroll
            for (int kt = 0; kt < 40; kt++) ldsm4t(wa[kt], wsrc + kt * 2048);
            fence_async();
            bar_arrive(10 + wg, 256);
        }

        const uint32_t dstx = sb + (wg == 0 ? SM_QX : SM_KS + 1024);

        for (int s = -1; s < NSEG; s++) {
            const uint32_t par = s & 1;
            FRESH(lane);
            const int g = lane >> 2, t = lane & 3, tid = warp * 32 + lane;
            if (s >= 0) {
                mbar_wait(bar + B_MEM_FULL * 8, par);
                TR(0);
                float c[4][4];
                #pragma unroll
                for (int i = 0; i < 4; i++) { c[i][0] = 0.f; c[i][1] = 0.f; c[i][2] = 0.f; c[i][3] = 0.f; }
                uint32_t maddr = sb + lane * 16;
                asm volatile("" : "+r"(maddr));
                #pragma unroll
                for (int kp = 0; kp < 20; kp++) {
                    uint32_t bb[4];
                    ldsm4t(bb, maddr + (SM_HB + kp * 512));
                    mma16(c[(kp & 1) * 2], wa[2 * kp][0], wa[2 * kp][1], wa[2 * kp][2], wa[2 * kp][3], bb[0], bb[1]);
                    mma16(c[(kp & 1) * 2 + 1], wa[2 * kp + 1][0], wa[2 * kp + 1][1], wa[2 * kp + 1][2], wa[2 * kp + 1][3], bb[2], bb[3]);
                }
                {
                    const int tok = lane & 7, ch = 2 * w + ((lane >> 3) & 1);
                    stsm2t(sb + (wg == 0 ? SM_QM : SM_KS) + tok * 128 + ((ch ^ tok) << 4),
                           pack2((c[0][0] + c[1][0]) + (c[2][0] + c[3][0]), (c[0][1] + c[1][1]) + (c[2][1] + c[3][1])),
                           pack2((c[0][2] + c[1][2]) + (c[2][2] + c[3][2]), (c[0][3] + c[1][3]) + (c[2][3] + c[3][3])));
                }
                __syncwarp();
                if (lane == 0) mbar_arrive(bar + B_MEM_FREE * 8);
                TR(1);
                bar_sync(1, 256);
                if (warp < 5) {
                    const int r = lane & 7, cq = lane >> 3;
                    uint32_t a[8], kb[8];
                    ldsm4(a, sb + SM_QM + r * 128 + ((cq ^ r) << 4));
                    ldsm4(kb, sb + SM_KS + (warp * 8 + r) * 128 + ((cq ^ r) << 4));
                    ldsm4(a + 4, sb + SM_QM + r * 128 + (((cq + 4) ^ r) << 4));
                    ldsm4(kb + 4, sb + SM_KS + (warp * 8 + r) * 128 + (((cq + 4) ^ r) << 4));
                    float d0[4] = {0.f, 0.f, 0.f, 0.f}, d1[4] = {0.f, 0.f, 0.f, 0.f};
                    mma16(d0, a[0], 0u, a[1], 0u, kb[0], kb[1]);
                    mma16(d1, a[2], 0u, a[3], 0u, kb[2], kb[3]);
                    mma16(d0, a[4], 0u, a[5], 0u, kb[4], kb[5]);
                    mma16(d1, a[6], 0u, a[7], 0u, kb[6], kb[7]);
                    const uint32_t la = sb + SM_MS + p * 1280 + warp * 256 + lane * 8;
                    #pragma unroll
                    for (int rk = 0; rk < 3; rk++)
                        st_async2(mapa(la, rk), d0[0] + d1[0], d0[1] + d1[1], mapa(bar + B_MS * 8, rk));
                    bar_arrive(4, 352);
                } else if (warp < 7) {
                    xscores<1>(sb, p, warp - 5, 0, lane);
                    bar_arrive(4, 352);
                }
                TR(2);
                if (s < NSEG - 1) {
                    wo_phase<0, 4>(sb, warp, lane, nullptr, par, (uint32_t)(s % 15) + 1u, tile0 + warp, h);
                    TR(4);
                }
            }
            if (s < NSEG - 1) {
                FRESH(lane);
                const uint32_t hp = (s + 1) & 1;
                float d[16];
                const uint64_t db0 = make_desc(SBC + SM_HB, 16, 1024, 1);
                mbar_wait(bar + B_HHI_FULL * 8, hp);
                if (s < 0 && warp == 0) T3(10);
                {
                    const int r = lane & 7, mq = lane >> 3;
                    const uint32_t ha = sb + SM_HB + 9 * 4096 + (8 * (mq >> 1) + r) * 128 + (((6 + (mq & 1)) ^ r) << 4);
                    uint32_t b0[4], b1[4];
                    ldsm4(b0, ha);
                    ldsm4(b1, ha + 2048);
                    #pragma unroll
                    for (int i = 0; i < 16; i++) d[i] = 0.f;
                    mma16(d + 0, wa[39][0], wa[39][1], wa[39][2], wa[39][3], b0[0], b0[1]);
                    mma16(d + 4, wa[39][0], wa[39][1], wa[39][2], wa[39][3], b0[2], b0[3]);
                    mma16(d + 8, wa[39][0], wa[39][1], wa[39][2], wa[39][3], b1[0], b1[1]);
                    mma16(d + 12, wa[39][0], wa[39][1], wa[39][2], wa[39][3], b1[2], b1[3]);
                    asm volatile("" : "+f"(d[0]), "+f"(d[4]), "+f"(d[8]), "+f"(d[12]) :: "memory");
                }
                if (s >= 0) bar_arrive(6, 512);
                mbar_wait(bar + B_HLO_FULL * 8, hp);
                bar_sync(9, 384);
                TR(6);
                wg_fence();
                #pragma unroll
                for (int kt = 0; kt < 12; kt++) wg_rs32(d, wa[kt], db0 + (uint64_t)(((kt >> 2) * 4096 + (kt & 3) * 32) >> 4), 1);
                wg_commit();
                #pragma unroll
                for (int kt = 12; kt < 39; kt++) wg_rs32(d, wa[kt], db0 + (uint64_t)(((kt >> 2) * 4096 + (kt & 3) * 32) >> 4), 1);
                wg_commit();
                wg_wait<1>();
                if (lane == 0) mbar_arrive(bar + B_HLO_FREE * 8);
                wg_wait<0>();
                if (lane == 0) mbar_arrive(bar + B_HHI_FREE * 8);
                TR(7);
                const int mi = lane >> 3, r = lane & 7;
                #pragma unroll
                for (int jj = 0; jj < 2; jj++) {
                    const int tok = 8 * (2 * jj + (mi >> 1)) + r, ch = 2 * w + (mi & 1);
                    stsm4t(dstx + tok * 128 + ((ch ^ r) << 4),
                           pack2(d[8 * jj + 0], d[8 * jj + 1]), pack2(d[8 * jj + 2], d[8 * jj + 3]),
                           pack2(d[8 * jj + 4], d[8 * jj + 5]), pack2(d[8 * jj + 6], d[8 * jj + 7]));
                }
                bar_arrive(8, 384);
                if (s < 0 && warp == 0) T3(11);
                if (s < 0) { bar_sync(0, 512); asm volatile("griddepcontrol.launch_dependents;" ::: "memory"); }
            }
        }
    } else if (wg == 2) {
        asm volatile("setmaxnreg.dec.sync.aligned.u32 64;");
        const int w = warp & 3;
        uint32_t res[4][4];
        {
            const bf16* src = Wo + ((size_t)h * DH + ((p + 1) % 3) * 64) * DM + (tile0 + warp) * 16 + 2 * t;
            #pragma unroll
            for (int kt = 0; kt < 4; kt++) {
                res[kt][0] = __ldg((const uint32_t*)(src + (size_t)(kt * 16 + g) * DM));
                res[kt][1] = __ldg((const uint32_t*)(src + (size_t)(kt * 16 + g) * DM + 8));
                res[kt][2] = __ldg((const uint32_t*)(src + (size_t)(kt * 16 + 8 + g) * DM));
                res[kt][3] = __ldg((const uint32_t*)(src + (size_t)(kt * 16 + 8 + g) * DM + 8));
            }
            #pragma unroll
            for (int kt = 0; kt < 4; kt++) {
                #pragma unroll
                for (int i = 0; i < 4; i++) res[kt][i] = movm(res[kt][i]);
            }
        }
        bar_sync(11, 256);
        if (tid == 256) {
            fence_async();
            mbar_expect(bar + B_WV * 8, 81920);
            #pragma unroll
            for (int i = 0; i < 5; i++) tma2d(sb + SM_WV + i * 16384, &maps.wv, h * DH + p * 64, i * 128, bar + B_WV * 8);
        }
        mbar_wait(bar + B_WV * 8, 0);
        if (w == 0) T3(3);
        const uint64_t da0 = make_desc(SBC + SM_WV, 16, 1024, 1);
        uint32_t vx[8], vm0 = 0, vm1 = 0;
        #pragma unroll
        for (int i = 0; i < 8; i++) vx[i] = 0;

        for (int s = -1; s < NSEG; s++) {
            FRESH(lane);
            const int g = lane >> 2, t = lane & 3, tid = warp * 32 + lane;
            if (s >= 0) {
                const uint32_t par = s & 1;
                mbar_wait(bar + B_MEM_FULL * 8, par);
                bar_sync(4, 352);
                TR(0);
                float dv[4];
                {
                    const uint64_t dbm = make_desc(SBC + SM_HB, 128, 128, 0);
                    wg_fence();
                    #pragma unroll
                    for (int kt = 0; kt < 40; kt++) {
                        wg_ss8(dv, da0 + (uint64_t)(kt * 128), dbm + (uint64_t)(kt * 16), kt > 0);
                        wg_commit();
                        if (kt < 39) wg_wait<1>();
                    }
                    wg_commit();
                }
                TR(1);
                bar_sync(5, 160);
                TR(2);
                uint32_t pb[5];
                #pragma unroll
                for (int j = 0; j < 5; j++) pb[j] = lds1(sb + SM_PM + j * 128 + lane * 4);
                float o0[4] = {0.f, 0.f, 0.f, 0.f}, o1[4] = {0.f, 0.f, 0.f, 0.f}, o2[4] = {0.f, 0.f, 0.f, 0.f};
                wg_wait<0>();
                TR(3);
                mma16(o0, vx[0], vx[1], vx[2], vx[3], pb[1], pb[2]);
                mma16(o1, vx[4], vx[5], vx[6], vx[7], pb[3], pb[4]);
                vm0 = pack2(dv[0], dv[1]); vm1 = pack2(dv[2], dv[3]);
                mma8(o2, vm0, vm1, pb[0]);
                if (s < NSEG - 1) {
                    const uint32_t q0 = pack2(o0[0] + o1[0] + o2[0], o0[1] + o1[1] + o2[1]), q1 = pack2(o0[2] + o1[2] + o2[2], o0[3] + o1[3] + o2[3]);
                    const uint32_t la = sb + SM_OS + (w * 16 + g) * 16 + t * 4;
                    #pragma unroll
                    for (int i = 1; i < 3; i++) {
                        const uint32_t rk = (p + i) % 3;
                        const uint32_t ra = mapa(la + (3 - i) * 1024, rk), rb = mapa(bar + B_O * 8, rk);
                        st_async1(ra, q0, rb);
                        st_async1(ra + 128, q1, rb);
                    }
                    sts1(la, q0);
                    sts1(la + 128, q1);
                    __syncwarp();
                    if (lane == 0) { mbar_arrive(bar + B_O1 * 8); mbar_arrive(bar + B_MEM_FREE * 8); }
                }
                TR(5);
                if (s < NSEG - 1) {
                    wo_phase<4, 4>(sb, warp, lane, res, par, (uint32_t)(s % 15) + 1u, tile0 + warp, h);
                    TR(4);
                    if (tid == 256) mbar_expect(bar + B_O * 8, 2048);
                }
                if (s < NSEG - 1) bar_sync(6, 512);
            }
            uint32_t vn[8];
            #pragma unroll
            for (int i = 0; i < 8; i++) vn[i] = 0;
            if (s < NSEG - 1) {
            float d[16];
            const uint32_t hp = (s + 1) & 1;
            const uint64_t db0 = make_desc(SBC + SM_HB, 16, 1024, 1);
            mbar_wait(bar + B_HHI_FULL * 8, hp);
            TR(6);
            wg_fence();
            #pragma unroll
            for (int kt = 12; kt < 40; kt++) wg_ss32(d, da0 + (uint64_t)(kt * 128), db0 + (uint64_t)(((kt >> 2) * 4096 + (kt & 3) * 32) >> 4), kt > 12);
            wg_commit();
            mbar_wait(bar + B_HLO_FULL * 8, hp);
            wg_fence();
            #pragma unroll
            for (int kt = 0; kt < 9; kt++) wg_ss32(d, da0 + (uint64_t)(kt * 128), db0 + (uint64_t)(((kt >> 2) * 4096 + (kt & 3) * 32) >> 4), 1);
            wg_commit();
            #pragma unroll
            for (int kt = 9; kt < 12; kt++) wg_ss32(d, da0 + (uint64_t)(kt * 128), db0 + (uint64_t)(((kt >> 2) * 4096 + (kt & 3) * 32) >> 4), 1);
            wg_commit();
            wg_wait<1>();
            bar_arrive(9, 384);
            wg_wait<0>();
            if (lane == 0) mbar_arrive(bar + B_HLO_FREE * 8);
            TR(7);
            if (lane == 0) mbar_arrive(bar + B_HHI_FREE * 8);
            #pragma unroll
            for (int i = 0; i < 8; i++) vn[i] = pack2(d[2 * i], d[2 * i + 1]);
            }
            if (s >= 0) {
                {
                    FRESH(lane);
                    mbar_wait(bar + B_XS * 8, s & 1);
                    if (w == 0 && lane == 0) mbar_expect(bar + B_XS * 8, 12288);
                    const uint32_t a = sb + SM_XS + (w >> 1) * 1536 + lane * 16 + (w & 1) * 8;
                    if (w == 0) xsoftmax<2>(a, lane >> 2, lane & 3);
                    else if (w == 1) xsoftmax<3>(a, lane >> 2, lane & 3);
                    else if (w == 2) xsoftmax<4>(a, lane >> 2, lane & 3);
                    else xsoftmax<5>(a, lane >> 2, lane & 3);
                }
                TR(8);
                bar_sync(7, 128);
                FRESH(lane);
                bf16* orow = g_ox + (size_t)(s * 32 + (lane >> 2)) * HD + h * DH + p * 64 + w * 16 + 2 * (lane & 3);
                {
                    const uint32_t pa = sb + SM_XS + lane * 16;
                    #pragma unroll
                    for (int mi = 0; mi < 2; mi++) {
                        float oa[4] = {0.f, 0.f, 0.f, 0.f}, ob[4] = {0.f, 0.f, 0.f, 0.f};
                        if (mi == 0) {
                            const uint4 p0 = lds4(pa);
                            const uint32_t p3 = lds1(pa + 1024 + 8);
                            mma8(oa, vm0, vm1, p0.x);
                            mma8(ob, vm0, vm1, p0.z);
                            mma16(oa, vx[0], vx[1], vx[2], vx[3], p0.y, 0u);
                            mma16(ob, vx[0], vx[1], vx[2], vx[3], p0.w, p3);
                        } else {
                            const uint4 p1 = lds4(pa + 1536), p2 = lds4(pa + 2560);
                            const uint32_t p4 = lds1(pa + 3584 + 8);
                            mma8(oa, vm0, vm1, p1.x);
                            mma8(ob, vm0, vm1, p1.z);
                            mma16(oa, vx[0], vx[1], vx[2], vx[3], p1.y, p2.x);
                            mma16(ob, vx[0], vx[1], vx[2], vx[3], p1.w, p2.z);
                            mma16(oa, vx[4], vx[5], vx[6], vx[7], p2.y, 0u);
                            mma16(ob, vx[4], vx[5], vx[6], vx[7], p2.w, p4);
                            if (lane < 3) mbar_arrive_remote(mapa(bar + B_XSFREE * 8, lane));
                        }
                        const uint32_t u0 = movm(pack2(oa[0], oa[1])), u1 = movm(pack2(oa[2], oa[3]));
                        const uint32_t u2 = movm(pack2(ob[0], ob[1])), u3 = movm(pack2(ob[2], ob[3]));
                        bf16* dst = orow + (size_t)(16 * mi) * HD;
                        *(uint32_t*)dst = u0;
                        *(uint32_t*)(dst + 8) = u1;
                        *(uint32_t*)(dst + 8 * HD) = u2;
                        *(uint32_t*)(dst + 8 * HD + 8) = u3;
                    }
                }
                TR(9);
                if (s == NSEG - 1) {
                    bar_sync(7, 128);
                    if (w == 3 && lane == 0) { signal_cnt(C_REC + 15); T2(400 + b); }
                    break;
                }
            }
            #pragma unroll
            for (int i = 0; i < 8; i++) vx[i] = vn[i];
            if (s >= 0) mbar_wait_cluster(bar + B_XSFREE * 8, s & 1);
            bar_sync(8, 384);
            TR(10);
            if (w < 3) xscores<2>(sb, p, w > 0, w == 2 ? 3 : 1, lane);
            else if ((s & 3) == 3 && s >= 0 && lane == 0) signal_cnt(C_REC + (s >> 2));
            __syncwarp();
            TR(11);
            if (s < 0) { bar_sync(0, 512); asm volatile("griddepcontrol.launch_dependents;" ::: "memory"); }
        }
    } else {
        asm volatile("setmaxnreg.dec.sync.aligned.u32 48;");
        const int w = warp & 3, lt = tid & 127;
        const uint32_t epoch = *(volatile uint32_t*)&g_epoch + 1u;
        if (b == 91) { if (lt < C_NUM) g_cnt[lt * 32] = 0u; __threadfence(); }
        if (b < 80) {
            #pragma unroll
            for (int i = 0; i < 2; i++) {
                const int idx = lt + i * 128, sl = idx >> 6, pg = (idx >> 5) & 1, wd = idx & 31;
                st_relaxed1(g_buf2 + (sl * 3 + (b >> 5)) * 2048 + pg * 1024 + (b & 31) * 32 + wd, 0xFFFFFFFFu);
            }
            __threadfence();
        }
        if (lane == 0 && w < 3) {
            int c = 0;
            if (w == 0) c = probe_blk(g_buf2 + 640 + (b & 31) * 8);
            else if (b < 80) c = probe_blk(g_buf1 + (b * 2 + (w - 1)) * 2048);
            else if (b < 92 && w == 1) c = probe_blk(g_buf2 + (b - 80) * 2048 + 960);
            asm volatile("st.shared.u8 [%0], %1;" :: "r"(sb + SM_CH + 96 + w), "r"(c) : "memory");
        }
        if (w == 0) T3(4);
        bar_sync(3, 128);
        uint32_t selmask;
        {
            const uint32_t c3 = lds1(sb + SM_CH + 96);
            const uint32_t cr = c3 & 1u, c1 = (c3 >> 8) & 1u, c2 = (c3 >> 16) & 1u;
            if (lt == 0 && b < 92) st_release1(&g_choice[b], (epoch << 2) | (b < 80 ? (c1 | (c2 << 1)) : (c1 ^ cr)));
            bar_sync(10, 256);
            if (w == 3) {
                if (lane == 0) { fence_async(); mbar_expect(bar + B_WO * 8, ntile * 6144 - 8192); }
                __syncwarp();
                if (lane < ntile) {
                    #pragma unroll
                    for (int e3 = 0; e3 < 3; e3++) {
                        const bool part = lane >= 8 && lane < 12;
                        if (part && e3 == 1) continue;
                        tma2d(sb + SM_WO + wo_tile_off(lane) + ((part && e3 == 2) ? 1 : e3) * 2048, &maps.wo,
                              (tile0 + lane) * 16, h * DH + ((e3 + p) % 3) * 64, bar + B_WO * 8);
                    }
                }
                __syncwarp();
            }
            if (w == 0) T3(5);
            if (lt < 92) {
                uint32_t v, guard = 0;
                while (true) {
                    v = ld_acquire1(&g_choice[lt]);
                    if ((v >> 2) == (epoch & 0x3fffffffu)) break;
                    __nanosleep(100);
                    if (++guard > (1u << 22)) __trap();
                }
                asm volatile("st.shared.u8 [%0], %1;" :: "r"(sb + SM_CH + lt), "r"(v & 3u) : "memory");
            }
            if (w == 0) T3(6);
            bar_sync(3, 128);
            selmask = (c1 << 12) | (c2 << 13);
            for (int i = 0; i < 12; i++) {
                uint32_t c; asm volatile("ld.shared.u8 %0, [%1];" : "=r"(c) : "r"(sb + SM_CH + 80 + i) : "memory");
                selmask |= ((c ^ cr) & 1u) << i;
            }
        }
        mbar_wait(bar + B_WO * 8, 0);
        if (w == 0) T3(8);
        bar_sync(0, 512);
        if (w == 0) T3(9);
        asm volatile("griddepcontrol.launch_dependents;" ::: "memory");
        const bool has_tile = (12 + w) < ntile;
        for (int s = 0; s < NSEG; s++) {
            const uint32_t par = s & 1;
            FRESH(lane);
            const int g = lane >> 2, t = lane & 3, lt = w * 32 + lane;
            if (s == 0) {
                mbar_wait(bar + B_HLO_FREE * 8, par);
                for (int k = lt; k < DM; k += 128) {
                    uint32_t v[4];
                    #pragma unroll
                    for (int i = 0; i < 4; i++) {
                        uint32_t lo = *(const uint16_t*)(mem0 + (2 * i) * DM + k), hi = *(const uint16_t*)(mem0 + (2 * i + 1) * DM + k);
                        v[i] = lo | (hi << 16);
                    }
                    asm volatile("st.shared.v4.u32 [%0], {%1,%2,%3,%4};" :: "r"(sb + SM_HB + k * 16), "r"(v[0]), "r"(v[1]), "r"(v[2]), "r"(v[3]) : "memory");
                }
            } else {
                const int sl = s & 3;
                const char* q = (const char*)g_buf2 + sl * 3 * 8192 + lt * 16;
                const uint32_t sm = selmask >> (sl * 3);
                const char* q0 = q + (sm & 1) * 4096;
                const char* q1 = q + 8192 + (sm & 2) * 2048;
                const char* q2 = q + 16384 + (sm & 4) * 1024;
                const uint32_t dst = sb + SM_HB + lt * 16;
                uint32_t guard = 0;
                mbar_wait(bar + B_HLO_FREE * 8, par);
                TR(10);
                while (true) {
                    const uint4 v0 = ld_relaxed4(q0), v1 = ld_relaxed4(q0 + 2048), v2 = ld_relaxed4(q1), v3 = ld_relaxed4(q1 + 2048), v4 = ld_relaxed4(q2);
                    sts4(dst, v0); sts4(dst + 2048, v1); sts4(dst + 4096, v2); sts4(dst + 6144, v3); sts4(dst + 8192, v4);
                    if (__all_sync(0xffffffffu, oks(v0) && oks(v1) && oks(v2) && oks(v3) && oks(v4))) break;
                    if (++guard > (1u << 22)) __trap();
                }
            }
            fence_async();
            __syncwarp();
            if (lane == 0) mbar_arrive(bar + B_MEM_FULL * 8);
            if (b == 0 && lt == 0) T2(300 + s);
            if (s == 0 && lt == 0) T2(200 + b);
            TR(0);
            if (w == 2) {
                mbar_wait(bar + B_MS * 8, par);
                TR(1);
                if (lane == 0) mbar_expect(bar + B_MS * 8, 3840);
                uint32_t pb[5];
                float sc[5][2];
                {
                    const uint32_t a = sb + SM_MS + lane * 8;
                    float2 u[5], v[5];
                    #pragma unroll
                    for (int j = 0; j < 5; j++) { u[j] = lds2f(a + j * 256); v[j] = lds2f(a + j * 256 + 1280); }
                    #pragma unroll
                    for (int j = 0; j < 5; j++) { sc[j][0] = u[j].x + v[j].x; sc[j][1] = u[j].y + v[j].y; }
                    #pragma unroll
                    for (int j = 0; j < 5; j++) u[j] = lds2f(a + j * 256 + 2560);
                    #pragma unroll
                    for (int j = 0; j < 5; j++) { sc[j][0] += u[j].x; sc[j][1] += u[j].y; }
                }
                softmax_core<5, false>(sc, g, t, pb);
                #pragma unroll
                for (int j = 0; j < 5; j++) sts1(sb + SM_PM + j * 128 + lane * 4, pb[j]);
                bar_arrive(5, 160);
                TR(2);
            }
            const uint32_t tag = (uint32_t)(s % 15) + 1u;
            if (s < NSEG - 1) {
                if (w == 3) {
                    const char* src = (const char*)g_ht + (size_t)(s + 1) * 40960;
                    if (s == 0) {
                        uint32_t guard = 0;
                        while (true) {
                            const uint32_t f0 = lane > 0 ? ld_acquire1(&g_hflag[lane]) : epoch, f1 = ld_acquire1(&g_hflag[32 + lane]);
                            if (__all_sync(0xffffffffu, f0 == epoch && f1 == epoch)) break;
                            if (++guard > (1u << 22)) __trap();
                        }
                        asm volatile("fence.proxy.async.global;" ::: "memory");
                    }
                    mbar_wait(bar + B_HHI_FREE * 8, par);
                    if (lane == 0) {
                        mbar_expect(bar + B_HHI_FULL * 8, 28672);
                        bulk_g2s(sb + SM_HB + 12288, src + 12288, 28672, sb + SM_BAR + B_HHI_FULL * 8);
                    }
                    mbar_wait(bar + B_MEM_FREE * 8, par);
                    if (lane == 0) {
                        mbar_expect(bar + B_HLO_FULL * 8, 12288);
                        bulk_g2s(sb + SM_HB, src, 12288, sb + SM_BAR + B_HLO_FULL * 8);
                    }
                    __syncwarp();
                }
                if (has_tile) wo_phase<0, 4>(sb, warp, lane, nullptr, par, tag, tile0 + warp, h);
                TR(4);
                bar_sync(6, 512);
            }
            if (s < NSEG - 1) {
                { const uint32_t c0 = clk32(); while (clk32() - c0 < H1_DELAY); }
                if (b < 80) {
                    FRESH(lane);
                    const char* rin0 = (const char*)g_buf1 + (size_t)(b * 2) * 8192 + ((selmask >> 12) & 1) * 4096 + (lane >> 2) * 256 + w * 64 + (lane & 3) * 16;
                    const char* rin1 = (const char*)g_buf1 + (size_t)(b * 2 + 1) * 8192 + ((selmask >> 13) & 1) * 4096 + (lane >> 2) * 256 + w * 64 + (lane & 3) * 16;
                    const int col = b * 8 + 2 * w + ((lane >> 1) & 1), wd = 2 * (lane & 1) + (lane >> 4);
                    const int sl = (lane & 8) ? ((s + 3) & 3) : ((s + 1) & 3);
                    uint32_t* dst = g_buf2 + (sl * 3 + (col >> 8)) * 2048 + ((lane >> 2) & 1) * 1024 + (col & 255) * 4 + wd;
                    asm volatile("" : "+l"(dst));
                    uint4 v0, v1, v2, v3;
                    uint32_t guard = 0;
                    while (true) {
                        v0 = ld_relaxed4(rin0); v1 = ld_relaxed4(rin0 + 2048);
                        v2 = ld_relaxed4(rin1); v3 = ld_relaxed4(rin1 + 2048);
                        if (__all_sync(0xffffffffu, ok4(v0, tag) && ok4(v1, tag) && ok4(v2, tag) && ok4(v3, tag))) break;
                        if (++guard > (1u << 22)) __trap();
                    }
                    TR(11);
                    const float a0 = (uf(v0.x) + uf(v1.x)) + (uf(v2.x) + uf(v3.x)), a1 = (uf(v0.y) + uf(v1.y)) + (uf(v2.y) + uf(v3.y));
                    const float a2 = (uf(v0.z) + uf(v1.z)) + (uf(v2.z) + uf(v3.z)), a3 = (uf(v0.w) + uf(v1.w)) + (uf(v2.w) + uf(v3.w));
                    const bool u16 = lane & 16;
                    float m0 = (u16 ? a2 : a0) + __shfl_xor_sync(0xffffffffu, u16 ? a0 : a2, 16);
                    float m1 = (u16 ? a3 : a1) + __shfl_xor_sync(0xffffffffu, u16 ? a1 : a3, 16);
                    m0 += __shfl_xor_sync(0xffffffffu, m0, 8); m1 += __shfl_xor_sync(0xffffffffu, m1, 8);
                    m0 += __shfl_xor_sync(0xffffffffu, m0, 4); m1 += __shfl_xor_sync(0xffffffffu, m1, 4);
                    st_relaxed1(dst, (lane & 8) ? 0xFFFFFFFFu : pack2(m0, m1));
                    TR(12);
                }
            }
        }
    }
    cluster_sync();
}

constexpr int G_STAGES = 6;
constexpr int G_STAGE_BYTES = 32768;
constexpr int G_SMEM = G_STAGES * G_STAGE_BYTES + 1024 + 256 + 2048 + 10240;

__device__ __forceinline__ void wg_ss128(float* d, uint64_t da, uint64_t db, int sc) {
    asm volatile("{\n\t.reg .pred p;\n\tsetp.ne.b32 p, %66, 0;\n\t"
        "wgmma.mma_async.sync.aligned.m64n128k16.f32.bf16.bf16 "
        "{%0,%1,%2,%3,%4,%5,%6,%7,%8,%9,%10,%11,%12,%13,%14,%15,%16,%17,%18,%19,%20,%21,%22,%23,%24,%25,%26,%27,%28,%29,%30,%31,"
        "%32,%33,%34,%35,%36,%37,%38,%39,%40,%41,%42,%43,%44,%45,%46,%47,%48,%49,%50,%51,%52,%53,%54,%55,%56,%57,%58,%59,%60,%61,%62,%63}, "
        "%64, %65, p, 1, 1, 0, 1;\n\t}"
        : "+f"(d[0]), "+f"(d[1]), "+f"(d[2]), "+f"(d[3]), "+f"(d[4]), "+f"(d[5]), "+f"(d[6]), "+f"(d[7]),
          "+f"(d[8]), "+f"(d[9]), "+f"(d[10]), "+f"(d[11]), "+f"(d[12]), "+f"(d[13]), "+f"(d[14]), "+f"(d[15]),
          "+f"(d[16]), "+f"(d[17]), "+f"(d[18]), "+f"(d[19]), "+f"(d[20]), "+f"(d[21]), "+f"(d[22]), "+f"(d[23]),
          "+f"(d[24]), "+f"(d[25]), "+f"(d[26]), "+f"(d[27]), "+f"(d[28]), "+f"(d[29]), "+f"(d[30]), "+f"(d[31]),
          "+f"(d[32]), "+f"(d[33]), "+f"(d[34]), "+f"(d[35]), "+f"(d[36]), "+f"(d[37]), "+f"(d[38]), "+f"(d[39]),
          "+f"(d[40]), "+f"(d[41]), "+f"(d[42]), "+f"(d[43]), "+f"(d[44]), "+f"(d[45]), "+f"(d[46]), "+f"(d[47]),
          "+f"(d[48]), "+f"(d[49]), "+f"(d[50]), "+f"(d[51]), "+f"(d[52]), "+f"(d[53]), "+f"(d[54]), "+f"(d[55]),
          "+f"(d[56]), "+f"(d[57]), "+f"(d[58]), "+f"(d[59]), "+f"(d[60]), "+f"(d[61]), "+f"(d[62]), "+f"(d[63])
        : "l"(da), "l"(db), "r"(sc));
}

#define SP0_LAST 12
#define SP2_LAST 6
enum { J_MOD = 0, J_G0, J_LN, J_G1, J_G2, J_FIN, J_END };
__host__ __device__ constexpr int sp0(int b) { return b >= 15 ? SP0_LAST : 3; }
__host__ __device__ constexpr int sp2(int b) { return b >= 15 ? SP2_LAST : 3; }
__host__ __device__ constexpr int njr(int b) { return b >= 15 ? 16 : 8; }
struct JobTab { uint32_t n; uint32_t j[1200]; };
constexpr uint32_t mkjob(int ty, int b, int n, int k0, int nk, int ks) {
    return (uint32_t)(ty | (b << 3) | (n << 7) | (k0 << 11) | (nk << 18) | (ks << 25));
}
constexpr void add_jobs(JobTab& t, int ty, int b) {
    if (b < 0) return;
    if (ty == J_G0) { for (int ks = 0; ks < sp0(b); ks++) for (int n = 0; n < 5; n++) t.j[t.n++] = mkjob(ty, b, n, ks * (96 / sp0(b)), 96 / sp0(b), ks); }
    else if (ty == J_G2) { for (int ks = 0; ks < sp2(b); ks++) for (int n = 0; n < 5; n++) t.j[t.n++] = mkjob(ty, b, n, ks * (24 / sp2(b)), 24 / sp2(b), ks); }
    else if (ty == J_G1) { for (int n = 0; n < 12; n++) t.j[t.n++] = mkjob(ty, b, n, 0, 10, 0); }
    else { for (int n = 0; n < njr(b); n++) t.j[t.n++] = mkjob(ty, b, n, 0, 16 / njr(b), ty == J_LN ? sp0(b) : sp2(b)); }
}
constexpr JobTab make_tab() {
    JobTab t = {};
    for (int i = 20; i < 60; i++) t.j[t.n++] = mkjob(J_MOD, 0, 0, i, 0, 0);
    for (int b = 0; b < 15; b++) {
        add_jobs(t, J_G0, b); add_jobs(t, J_G1, b - 1); add_jobs(t, J_FIN, b - 2); add_jobs(t, J_G2, b - 1); add_jobs(t, J_LN, b);
    }
    add_jobs(t, J_FIN, 13); add_jobs(t, J_G1, 14);
    add_jobs(t, J_G0, 15); add_jobs(t, J_G2, 14); add_jobs(t, J_LN, 15); add_jobs(t, J_FIN, 14);
    add_jobs(t, J_G1, 15); add_jobs(t, J_G2, 15); add_jobs(t, J_FIN, 15);
    return t;
}
__constant__ JobTab c_jobs = make_tab();

__device__ __forceinline__ bool cnt_ge(int idx, uint32_t target) { return ld_acquire1(g_cnt + idx * 32) >= target; }
__device__ __forceinline__ void cnt_wait(int idx, uint32_t target) {
    uint32_t guard = 0;
    while (!cnt_ge(idx, target)) { __nanosleep(64); if (++guard > (1u << 22)) __trap(); }
}

struct SMaps { CUtensorMap ox, wo, h2, w1, act, w2; };

__global__ void __launch_bounds__(384, 1)
k_side(const __grid_constant__ SMaps maps, const bf16* __restrict__ xin, const bf16* __restrict__ cvec,
       const bf16* __restrict__ wmod, bf16* __restrict__ outp) {
    extern __shared__ uint8_t smem_raw[];
    const uint32_t sb = (smem_u32(smem_raw) + 1023u) & ~1023u;
    const uint32_t bars = sb + G_STAGES * G_STAGE_BYTES;
    float* red = (float*)(smem_raw + (bars + 256 - smem_u32(smem_raw)));
    const int tid = threadIdx.x, lane = tid & 31, wg = tid >> 7;
    if (tid == 0) T2(500 + blockIdx.x);
    if (tid == 0) {
        for (int i = 0; i < G_STAGES; i++) { mbar_init(bars + i * 8, 1); mbar_init(bars + 64 + i * 8, 8); }
        for (int i = 0; i < 2; i++) { mbar_init(bars + 128 + i * 8, 1); mbar_init(bars + 144 + i * 8, 8); }
        asm volatile("fence.mbarrier_init.release.cluster;" ::: "memory");
    }
    __syncthreads();
    if (wg == 0) {
        if (tid == 0) {
            uint32_t st = 0, ph = 1;
            for (uint32_t it = 0;; it++) {
                const uint32_t ji = atomicAdd(g_cnt + C_Q * 32, 1u);
                const uint32_t job = ji < c_jobs.n ? c_jobs.j[ji] : (uint32_t)J_END;
                if (ji == 0) g_epoch = g_epoch + 1u;
                const int ty = job & 7, b = (job >> 3) & 15, n = (job >> 7) & 15, k0 = (job >> 11) & 127, nk = (job >> 18) & 127;
                const uint32_t sl = it & 1;
                mbar_wait(bars + 144 + sl * 8, ((it >> 1) & 1) ^ 1);
                sts1(bars + 160 + sl * 4, job);
                if (ty == J_G0 || ty == J_G1 || ty == J_G2) {
                    if (b >= PRING && ty != J_G1) cnt_wait((ty == J_G0 ? C_LN : C_FIN) + b - PRING, njr(b - PRING));
                    mbar_arrive(bars + 128 + sl * 8);
                    const CUtensorMap* mA = ty == J_G0 ? &maps.ox : (ty == J_G1 ? &maps.h2 : &maps.act);
                    const CUtensorMap* mB = ty == J_G0 ? &maps.wo : (ty == J_G1 ? &maps.w1 : &maps.w2);
                    const int didx = ty == J_G0 ? C_REC + b : (ty == J_G1 ? C_LN + b : C_G1 + b);
                    const uint32_t dtgt = ty == J_G0 ? 96u : (ty == J_G1 ? (uint32_t)njr(b) : 12u);
                    int pre = 0;
                    if (!cnt_ge(didx, dtgt)) {
                        pre = nk < G_STAGES ? nk : G_STAGES;
                        uint32_t s2 = st, p2 = ph;
                        for (int i = 0; i < pre; i++) {
                            mbar_wait(bars + 64 + s2 * 8, p2);
                            const uint32_t a = sb + s2 * G_STAGE_BYTES;
                            mbar_expect(bars + s2 * 8, G_STAGE_BYTES);
                            tma2d(a + 16384, mB, n * 128, (k0 + i) * 64, bars + s2 * 8);
                            tma2d(a + 16384 + 8192, mB, n * 128 + 64, (k0 + i) * 64, bars + s2 * 8);
                            if (++s2 == G_STAGES) { s2 = 0; p2 ^= 1; }
                        }
                        cnt_wait(didx, dtgt);
                    }
                    asm volatile("fence.proxy.async.global;" ::: "memory");
                    T2(1024 + ji * 4 + 1);
                    for (int i = 0; i < nk; i++) {
                        const uint32_t a = sb + st * G_STAGE_BYTES;
                        if (i >= pre) {
                            mbar_wait(bars + 64 + st * 8, ph);
                            mbar_expect(bars + st * 8, G_STAGE_BYTES);
                        }
                        tma2d(a, mA, (k0 + i) * 64, b * 128, bars + st * 8);
                        if (i >= pre) {
                            tma2d(a + 16384, mB, n * 128, (k0 + i) * 64, bars + st * 8);
                            tma2d(a + 16384 + 8192, mB, n * 128 + 64, (k0 + i) * 64, bars + st * 8);
                        }
                        if (++st == G_STAGES) { st = 0; ph ^= 1; }
                    }
                } else {
                    if (ty == J_LN) { bulk_pf(xin + (size_t)(b * 128 + n * nk * 8) * DM, nk * 8 * DM * 2); cnt_wait(C_MOD, 40u); cnt_wait(C_G0 + b, 5u * sp0(b)); }
                    else if (ty == J_FIN) cnt_wait(C_G2 + b, 5u * sp2(b));
                    if (ji < 1200) T2(1024 + ji * 4 + 1);
                    mbar_arrive(bars + 128 + sl * 8);
                    if (ty == J_END) break;
                }
            }
        }
    } else {
        const int cw = wg - 1, ct = tid - 128, cwarp = ct >> 5;
        uint32_t st = 0, ph = 0;
        uint2* smod = (uint2*)(red + 512);
        bool have_mod = false;
        auto load_mod = [&]() {
            for (int i = ct; i < DM; i += 256) {
                const float4 m = __ldcg((const float4*)(g_mod + 2 * DM + i * 4));
                const float o = (i >= 320 && i < 480) ? 1.0f : 0.0f;
                smod[i] = make_uint2(pack2(m.x + o, m.y + o), pack2(m.z + o, m.w + o));
            }
            bar_sync(1, 256);
            have_mod = true;
        };
        {
            if (ct == 0) red[0] = cnt_ge(C_MOD, 40u) ? 1.0f : 0.0f;
            bar_sync(1, 256);
            const bool rdy = red[0] != 0.0f;
            bar_sync(1, 256);
            if (rdy) load_mod();
        }
        for (uint32_t it = 0;; it++) {
            const uint32_t sl = it & 1;
            mbar_wait(bars + 128 + sl * 8, (it >> 1) & 1);
            const uint32_t job = lds1(bars + 160 + sl * 4);
            __syncwarp();
            if (lane == 0) mbar_arrive(bars + 144 + sl * 8);
            const int ty = job & 7, b = (job >> 3) & 15, n = (job >> 7) & 15, k0 = (job >> 11) & 127, nk = (job >> 18) & 127, ks = (job >> 25) & 15;
            if (ty == J_END) break;
            int sig = -1;
            if (ty == J_G0 || ty == J_G1 || ty == J_G2) {
                float d[64];
                #pragma unroll
                for (int i = 0; i < 64; i++) d[i] = 0.f;
                uint32_t pst = 0;
                for (int kb = 0; kb < nk; kb++) {
                    mbar_wait(bars + st * 8, ph);
                    const uint32_t a = sb + st * G_STAGE_BYTES;
                    const uint64_t da = make_desc(a + cw * 8192, 16, 1024, 1);
                    const uint64_t db = make_desc(a + 16384, 8192, 1024, 1);
                    wg_fence();
                    #pragma unroll
                    for (int k = 0; k < 4; k++) wg_ss128(d, da + (uint64_t)(k * 2), db + (uint64_t)(k * 128), 1);
                    wg_commit();
                    if (kb > 0) {
                        wg_wait<1>();
                        if (lane == 0) mbar_arrive(bars + 64 + pst * 8);
                    }
                    pst = st;
                    if (++st == G_STAGES) { st = 0; ph ^= 1; }
                }
                wg_wait<0>();
                if (lane == 0) mbar_arrive(bars + 64 + pst * 8);
                const int g = lane >> 2, t = lane & 3;
                if (ty == J_G1) {
                    #pragma unroll
                    for (int hf = 0; hf < 2; hf++) {
                        bf16* o = g_act + (size_t)(b * 128 + cwarp * 16 + g + 8 * hf) * FF + n * 128 + 8 * t;
                        #pragma unroll
                        for (int q = 0; q < 4; q++) {
                            uint32_t u[4];
                            #pragma unroll
                            for (int i = 0; i < 4; i++) {
                                const float a0 = bfr(d[4 * (4 * q + i) + 2 * hf]), a1 = bfr(d[4 * (4 * q + i) + 2 * hf + 1]);
                                u[i] = pack2(__fdividef(a0, 1.0f + __expf(-a0)), __fdividef(a1, 1.0f + __expf(-a1)));
                            }
                            const bool o1 = t & 1, o2 = t & 2;
                            uint32_t x0 = __shfl_xor_sync(0xffffffffu, o1 ? u[0] : u[1], 1), x1 = __shfl_xor_sync(0xffffffffu, o1 ? u[2] : u[3], 1);
                            if (o1) { u[0] = x0; u[2] = x1; } else { u[1] = x0; u[3] = x1; }
                            x0 = __shfl_xor_sync(0xffffffffu, o2 ? u[0] : u[2], 2); x1 = __shfl_xor_sync(0xffffffffu, o2 ? u[1] : u[3], 2);
                            if (o2) { u[0] = x0; u[1] = x1; } else { u[2] = x0; u[3] = x1; }
                            *(uint4*)(o + q * 32) = make_uint4(u[0], u[1], u[2], u[3]);
                        }
                    }
                    sig = C_G1 + b;
                } else {
                    float* o = (ty == J_G0 ? g_p0 : g_p2) + ((size_t)((b % PRING) * PMAX + ks) * 128 + cwarp * 16 + g) * DM + n * 128 + 2 * t;
                    #pragma unroll
                    for (int hf = 0; hf < 2; hf++) {
                        #pragma unroll
                        for (int j = 0; j < 16; j++)
                            *(float2*)(o + hf * 8 * DM + j * 8) = make_float2(d[4 * j + 2 * hf], d[4 * j + 2 * hf + 1]);
                    }
                    sig = (ty == J_G0 ? C_G0 : C_G2) + b;
                }
            } else if (ty == J_MOD) {
                mod_chunk<256, 2>(cvec, wmod, k0 * 64, ct, red);
                sig = C_MOD;
            } else {
                const bool ln = ty == J_LN;
                if (!have_mod) load_mod();
                const uint2* gm = smod + (ln ? 0 : 480) + lane;
                for (int r = 0; r < nk; r++) {
                    const int lr = (n * nk + r) * 8 + cwarp, row = b * 128 + lr;
                    const float* pp = (ln ? g_p0 : g_p2) + ((size_t)((b % PRING) * PMAX) * 128 + lr) * DM + lane * 4;
                    const bf16* xs = (ln ? xin : (const bf16*)g_x1) + (size_t)row * DM + lane * 4;
                    float v[5][4];
                    uint2 xv[5];
                    #pragma unroll
                    for (int i = 0; i < 5; i++) {
                        xv[i] = __ldcg((const uint2*)(xs + i * 128));
                        v[i][0] = 0.f; v[i][1] = 0.f; v[i][2] = 0.f; v[i][3] = 0.f;
                    }
                    if (ks == 3) {
                        float4 a[3][5];
                        #pragma unroll
                        for (int q = 0; q < 3; q++) {
                            #pragma unroll
                            for (int i = 0; i < 5; i++) a[q][i] = __ldcg((const float4*)(pp + (size_t)q * 128 * DM + i * 128));
                        }
                        #pragma unroll
                        for (int q = 0; q < 3; q++) {
                            #pragma unroll
                            for (int i = 0; i < 5; i++) { v[i][0] += a[q][i].x; v[i][1] += a[q][i].y; v[i][2] += a[q][i].z; v[i][3] += a[q][i].w; }
                        }
                    } else {
                        for (int q0 = 0; q0 < ks; q0 += 6) {
                            float4 a[6][5];
                            #pragma unroll
                            for (int q = 0; q < 6; q++) {
                                #pragma unroll
                                for (int i = 0; i < 5; i++) a[q][i] = __ldcg((const float4*)(pp + (size_t)(q0 + q) * 128 * DM + i * 128));
                            }
                            #pragma unroll
                            for (int q = 0; q < 6; q++) {
                                #pragma unroll
                                for (int i = 0; i < 5; i++) { v[i][0] += a[q][i].x; v[i][1] += a[q][i].y; v[i][2] += a[q][i].z; v[i][3] += a[q][i].w; }
                            }
                        }
                    }
                    bf16* dst = (ln ? (bf16*)g_x1 : outp) + (size_t)row * DM + lane * 4;
                    #pragma unroll
                    for (int i = 0; i < 5; i++) {
                        const uint2 gg = gm[i * 32];
                        xv[i].x = hadd2(xv[i].x, hmul2(gg.x, pack2(v[i][0], v[i][1])));
                        xv[i].y = hadd2(xv[i].y, hmul2(gg.y, pack2(v[i][2], v[i][3])));
                        *(uint2*)(dst + i * 128) = xv[i];
                    }
                    if (ln) {
                        uint32_t mb; float rs;
                        ln_stats(xv, mb, rs);
                        #pragma unroll
                        for (int i = 0; i < 5; i++) {
                            const uint2 sh = gm[160 + i * 32], m1 = gm[320 + i * 32];
                            *(uint2*)(g_h2 + (size_t)row * DM + lane * 4 + i * 128) =
                                make_uint2(ln_apply(xv[i].x, mb, rs, m1.x, sh.x), ln_apply(xv[i].y, mb, rs, m1.y, sh.y));
                        }
                    }
                }
                if (ln) sig = C_LN + b; else if (b < 16 - PRING) sig = C_FIN + b;
            }
            if (sig >= 0) {
                bar_sync(1, 256);
                if (ct == 0) signal_cnt(sig);
            }
            if (ct == 0) T2(1024 + ji * 4 + 2);
        }
    }
}

typedef CUresult (*EncodeFn)(CUtensorMap*, CUtensorMapDataType, cuuint32_t, void*, const cuuint64_t*, const cuuint64_t*,
                             const cuuint32_t*, const cuuint32_t*, CUtensorMapInterleave, CUtensorMapSwizzle,
                             CUtensorMapL2promotion, CUtensorMapFloatOOBfill);

static void make_map(EncodeFn fn, CUtensorMap* m, const void* ptr, uint64_t inner, uint64_t outer, uint32_t bi, uint32_t bo,
                     CUtensorMapSwizzle sw = CU_TENSOR_MAP_SWIZZLE_128B) {
    cuuint64_t dims[2] = {inner, outer};
    cuuint64_t strides[1] = {inner * 2};
    cuuint32_t box[2] = {bi, bo};
    cuuint32_t es[2] = {1, 1};
    fn(m, CU_TENSOR_MAP_DATA_TYPE_BFLOAT16, 2, (void*)ptr, dims, strides, box, es, CU_TENSOR_MAP_INTERLEAVE_NONE,
       sw, CU_TENSOR_MAP_L2_PROMOTION_L2_256B, CU_TENSOR_MAP_FLOAT_OOB_FILL_NONE);
}

extern "C" void kernel_launch(void* const* d_in, const int* in_sizes, int n_in, void* d_out, int out_size) {
    const bf16* x = (const bf16*)d_in[0];
    const bf16* mem0 = (const bf16*)d_in[1];
    const bf16* Wq = (const bf16*)d_in[2];
    const bf16* Wk = (const bf16*)d_in[3];
    const bf16* Wv = (const bf16*)d_in[4];
    const bf16* Wo = (const bf16*)d_in[5];
    const bf16* w1 = (const bf16*)d_in[8];
    const bf16* w2 = (const bf16*)d_in[9];
    const bf16* c = (const bf16*)d_in[10];
    const bf16* wmod = (const bf16*)d_in[11];
    bf16* out = (bf16*)d_out;

    static EncodeFn enc = nullptr;
    static void *p_ox, *p_x1, *p_h2, *p_act;
    if (!enc) {
        cudaDriverEntryPointQueryResult qr;
        void* f = nullptr;
        cudaGetDriverEntryPoint("cuTensorMapEncodeTiled", &f, cudaEnableDefault, &qr);
        enc = (EncodeFn)f;
        cudaGetSymbolAddress(&p_ox, g_ox);
        cudaGetSymbolAddress(&p_x1, g_x1);
        cudaGetSymbolAddress(&p_h2, g_h2);
        cudaGetSymbolAddress(&p_act, g_act);
        cudaFuncSetAttribute(k_rec, cudaFuncAttributeMaxDynamicSharedMemorySize, SM_TOTAL);
        cudaFuncSetAttribute(k_side, cudaFuncAttributeMaxDynamicSharedMemorySize, G_SMEM);
    }
    RMaps rm;
    make_map(enc, &rm.wq, Wq, HD, DM, 64, 128);
    make_map(enc, &rm.wk, Wk, HD, DM, 64, 128);
    make_map(enc, &rm.wv, Wv, HD, DM, 64, 128);
    make_map(enc, &rm.wo, Wo, DM, HD, 16, 64, CU_TENSOR_MAP_SWIZZLE_32B);
    make_map(enc, &rm.wop, Wo, DM, HD, 224, 192, CU_TENSOR_MAP_SWIZZLE_NONE);
    SMaps m;
    make_map(enc, &m.ox, p_ox, HD, SEQ, 64, 128);
    make_map(enc, &m.wo, Wo, DM, HD, 64, 64);
    make_map(enc, &m.h2, p_h2, DM, SEQ, 64, 128);
    make_map(enc, &m.w1, w1, FF, DM, 64, 64);
    make_map(enc, &m.act, p_act, FF, SEQ, 64, 128);
    make_map(enc, &m.w2, w2, DM, FF, 64, 64);

    cudaStream_t st = cudaStreamPerThread;
    {
        cudaLaunchConfig_t cfg = {};
        cfg.gridDim = dim3(96); cfg.blockDim = dim3(512); cfg.dynamicSmemBytes = SM_TOTAL; cfg.stream = st;
        cudaLaunchAttribute at[2];
        at[0].id = cudaLaunchAttributeClusterDimension;
        at[0].val.clusterDim.x = 3; at[0].val.clusterDim.y = 1; at[0].val.clusterDim.z = 1;
        cfg.attrs = at; cfg.numAttrs = 1;
        cudaLaunchKernelEx(&cfg, k_rec, rm, mem0, Wo, x, c, wmod);
    }
    {
        cudaLaunchConfig_t cfg = {};
        cfg.gridDim = dim3(SIDE_CTAS); cfg.blockDim = dim3(384); cfg.dynamicSmemBytes = G_SMEM; cfg.stream = st;
        cudaLaunchAttribute at[1];
        at[0].id = cudaLaunchAttributeProgrammaticStreamSerialization;
        at[0].val.programmaticStreamSerializationAllowed = 1;
        cfg.attrs = at; cfg.numAttrs = 1;
        cudaLaunchKernelEx(&cfg, k_side, m, x, c, wmod, out);
    }
}
```

```cpp
#include <cuda_runtime.h>
#include <cuda_bf16.h>
#include <cuda.h>
#include <stdint.h>

typedef __nv_bfloat16 bf16;
#define VX_THROTTLE 1
#define H1_DELAY 400
#define H1_BACK 0
#define VM_THROTTLE 1
#define PRE_TRIG 0
#define NPACE 4
#define PF_LATE 1
#define SIDE_CTAS 132

constexpr int SEQ = 2048, DM = 640, NH = 32, DH = 192, NSEG = 64, FF = 1536, HD = NH * DH;

__device__ __align__(128) float g_mod[6 * DM];
__device__ __align__(1024) bf16 g_ht[(size_t)SEQ * DM];
__device__ __align__(1024) bf16 g_ox[(size_t)SEQ * HD];
__device__ __align__(1024) bf16 g_x1[(size_t)SEQ * DM];
__device__ __align__(1024) bf16 g_h2[(size_t)SEQ * DM];
__device__ __align__(1024) bf16 g_act[(size_t)SEQ * FF];
__device__ __align__(8192) uint32_t g_buf1[80 * 2 * 2048];
__device__ __align__(8192) uint32_t g_buf2[4 * 3 * 2048];
__device__ uint32_t g_choice[128];
__device__ uint32_t g_epoch;
__device__ uint32_t g_hflag[64];
__device__ __align__(128) uint32_t g_modx[2 * DM];
#define T2(i)
#define T3(i)
enum { C_Q = 0, C_MOD = 1, C_REC = 2, C_G0 = 18, C_LN = 34, C_G1 = 50, C_G2 = 66, C_FIN = 82, C_NUM = 98 };
__device__ __align__(128) uint32_t g_cnt[C_NUM * 32];
constexpr int PMAX = 12;
constexpr int PRING = 4;
__device__ __align__(1024) float g_p0[(size_t)PRING * PMAX * 128 * DM];
__device__ __align__(1024) float g_p2[(size_t)PRING * PMAX * 128 * DM];
#define TR(k)

#define FRESH(x) asm volatile("" : "+r"(x))
__device__ __forceinline__ float bfr(float x) { uint32_t r; asm("cvt.rn.bf16x2.f32 %0, %1, %2;" : "=r"(r) : "f"(x), "f"(0.0f)); return __uint_as_float(r); }
__device__ __forceinline__ uint32_t pack2(float a, float b) {
    uint32_t r; asm("cvt.rn.bf16x2.f32 %0, %1, %2;" : "=r"(r) : "f"(b), "f"(a)); return r;
}
__device__ __forceinline__ float bflo(uint32_t v) { return __uint_as_float(v << 16); }
__device__ __forceinline__ float bfhi(uint32_t v) { return __uint_as_float(v & 0xffff0000u); }
__device__ __forceinline__ float ex2(float x) { float r; asm("ex2.approx.ftz.f32 %0, %1;" : "=f"(r) : "f"(x)); return r; }
__device__ __forceinline__ float rcpf(float x) { float r; asm("rcp.approx.ftz.f32 %0, %1;" : "=f"(r) : "f"(x)); return r; }
__device__ __forceinline__ void score2(float& a, float& b) {
    const float SCALE = 0.07216878364870322f;
    uint32_t u = pack2(a, b);
    u = pack2(bflo(u) * SCALE, bfhi(u) * SCALE);
    a = bflo(u); b = bfhi(u);
}
__device__ __forceinline__ uint32_t smem_u32(const void* p) { return (uint32_t)__cvta_generic_to_shared(p); }

__device__ __forceinline__ void mbar_init(uint32_t bar, uint32_t cnt) {
    asm volatile("mbarrier.init.shared::cta.b64 [%0], %1;" :: "r"(bar), "r"(cnt) : "memory");
}
__device__ __forceinline__ void mbar_arrive(uint32_t bar) {
    asm volatile("mbarrier.arrive.shared::cta.b64 _, [%0];" :: "r"(bar) : "memory");
}
__device__ __forceinline__ void mbar_expect(uint32_t bar, uint32_t bytes) {
    asm volatile("mbarrier.arrive.expect_tx.shared::cta.b64 _, [%0], %1;" :: "r"(bar), "r"(bytes) : "memory");
}
__device__ __forceinline__ bool mbar_try(uint32_t bar, uint32_t parity) {
    uint32_t ok;
    asm volatile("{\n\t.reg .pred p;\n\tmbarrier.try_wait.parity.shared::cta.b64 p, [%1], %2;\n\tselp.u32 %0, 1, 0, p;\n\t}"
                 : "=r"(ok) : "r"(bar), "r"(parity) : "memory");
    return ok != 0;
}
__device__ __forceinline__ bool mbar_try_cluster(uint32_t bar, uint32_t parity) {
    uint32_t ok;
    asm volatile("{\n\t.reg .pred p;\n\tmbarrier.try_wait.parity.acquire.cluster.shared::cta.b64 p, [%1], %2;\n\tselp.u32 %0, 1, 0, p;\n\t}"
                 : "=r"(ok) : "r"(bar), "r"(parity) : "memory");
    return ok != 0;
}
__device__ __forceinline__ void mbar_wait(uint32_t bar, uint32_t parity) {
    uint32_t guard = 0;
    while (!mbar_try(bar, parity)) { if (++guard > (1u << 22)) __trap(); }
}
__device__ __forceinline__ void mbar_wait_cluster(uint32_t bar, uint32_t parity) {
    uint32_t guard = 0;
    while (!mbar_try_cluster(bar, parity)) { if (++guard > (1u << 22)) __trap(); }
}
__device__ __forceinline__ void bar_sync(int id, int n) { asm volatile("bar.sync %0, %1;" :: "r"(id), "r"(n) : "memory"); }
__device__ __forceinline__ void bar_arrive(int id, int n) { asm volatile("bar.arrive %0, %1;" :: "r"(id), "r"(n) : "memory"); }
__device__ __forceinline__ void sts1(uint32_t a, uint32_t v) { asm volatile("st.shared.u32 [%0], %1;" :: "r"(a), "r"(v) : "memory"); }
__device__ __forceinline__ uint32_t lds1(uint32_t a) { uint32_t v; asm volatile("ld.shared.u32 %0, [%1];" : "=r"(v) : "r"(a) : "memory"); return v; }
__device__ __forceinline__ void fence_async() { asm volatile("fence.proxy.async.shared::cta;" ::: "memory"); }
__device__ __forceinline__ void cluster_sync() {
    asm volatile("barrier.cluster.arrive.release.aligned;\n\tbarrier.cluster.wait.acquire.aligned;" ::: "memory");
}
__device__ __forceinline__ uint32_t mapa(uint32_t a, uint32_t rank) {
    uint32_t r; asm("mapa.shared::cluster.u32 %0, %1, %2;" : "=r"(r) : "r"(a), "r"(rank)); return r;
}
__device__ __forceinline__ void st_async1(uint32_t a, uint32_t v, uint32_t bar) {
    asm volatile("st.async.weak.shared::cluster.mbarrier::complete_tx::bytes.b32 [%0], %1, [%2];" :: "r"(a), "r"(v), "r"(bar) : "memory");
}
__device__ __forceinline__ void st_async2(uint32_t a, float x, float y, uint32_t bar) {
    asm volatile("st.async.weak.shared::cluster.mbarrier::complete_tx::bytes.v2.f32 [%0], {%1,%2}, [%3];" :: "r"(a), "f"(x), "f"(y), "r"(bar) : "memory");
}
__device__ __forceinline__ void st_async4(uint32_t a, const float* c, uint32_t bar) {
    asm volatile("st.async.weak.shared::cluster.mbarrier::complete_tx::bytes.v4.f32 [%0], {%1,%2,%3,%4}, [%5];"
                 :: "r"(a), "f"(c[0]), "f"(c[1]), "f"(c[2]), "f"(c[3]), "r"(bar) : "memory");
}
__device__ __forceinline__ void bulk_g2s(uint32_t dst, const void* src, uint32_t bytes, uint32_t bar) {
    asm volatile("cp.async.bulk.shared::cluster.global.mbarrier::complete_tx::bytes [%0], [%1], %2, [%3];"
                 :: "r"(dst), "l"(src), "r"(bytes), "r"(bar) : "memory");
}
__device__ __forceinline__ void cpa16(uint32_t s, const void* g) {
    asm volatile("cp.async.cg.shared.global [%0], [%1], 16;" :: "r"(s), "l"(g) : "memory");
}
__device__ __forceinline__ void cpa_wait_all() { asm volatile("cp.async.wait_all;" ::: "memory"); }
__device__ __forceinline__ void ldsm4(uint32_t* r, uint32_t a) {
    asm volatile("ldmatrix.sync.aligned.m8n8.x4.shared.b16 {%0,%1,%2,%3}, [%4];" : "=r"(r[0]), "=r"(r[1]), "=r"(r[2]), "=r"(r[3]) : "r"(a) : "memory");
}
__device__ __forceinline__ void ldsm4t(uint32_t* r, uint32_t a) {
    asm volatile("ldmatrix.sync.aligned.m8n8.x4.trans.shared.b16 {%0,%1,%2,%3}, [%4];" : "=r"(r[0]), "=r"(r[1]), "=r"(r[2]), "=r"(r[3]) : "r"(a) : "memory");
}
__device__ __forceinline__ void stsm2t(uint32_t a, uint32_t r0, uint32_t r1) {
    asm volatile("stmatrix.sync.aligned.m8n8.x2.trans.shared.b16 [%0], {%1,%2};" :: "r"(a), "r"(r0), "r"(r1) : "memory");
}
__device__ __forceinline__ void stsm4t(uint32_t a, uint32_t r0, uint32_t r1, uint32_t r2, uint32_t r3) {
    asm volatile("stmatrix.sync.aligned.m8n8.x4.trans.shared.b16 [%0], {%1,%2,%3,%4};" :: "r"(a), "r"(r0), "r"(r1), "r"(r2), "r"(r3) : "memory");
}
__device__ __forceinline__ uint32_t movm(uint32_t v) {
    uint32_t r; asm volatile("movmatrix.sync.aligned.m8n8.trans.b16 %0, %1;" : "=r"(r) : "r"(v)); return r;
}
__device__ __forceinline__ void mma16(float* c, uint32_t a0, uint32_t a1, uint32_t a2, uint32_t a3, uint32_t b0, uint32_t b1) {
    asm volatile("mma.sync.aligned.m16n8k16.row.col.f32.bf16.bf16.f32 {%0,%1,%2,%3}, {%4,%5,%6,%7}, {%8,%9}, {%0,%1,%2,%3};"
                 : "+f"(c[0]), "+f"(c[1]), "+f"(c[2]), "+f"(c[3]) : "r"(a0), "r"(a1), "r"(a2), "r"(a3), "r"(b0), "r"(b1));
}
__device__ __forceinline__ void mma8(float* c, uint32_t a0, uint32_t a1, uint32_t b0) {
    asm volatile("mma.sync.aligned.m16n8k8.row.col.f32.bf16.bf16.f32 {%0,%1,%2,%3}, {%4,%5}, {%6}, {%0,%1,%2,%3};"
                 : "+f"(c[0]), "+f"(c[1]), "+f"(c[2]), "+f"(c[3]) : "r"(a0), "r"(a1), "r"(b0));
}
__host__ __device__ constexpr uint64_t make_desc(uint32_t saddr, uint32_t lbo, uint32_t sbo, uint32_t layout) {
    return (uint64_t)((saddr & 0x3FFFF) >> 4) | ((uint64_t)(lbo >> 4) << 16) | ((uint64_t)(sbo >> 4) << 32) | ((uint64_t)layout << 62);
}
__device__ __forceinline__ void wg_fence() { asm volatile("wgmma.fence.sync.aligned;" ::: "memory"); }
__device__ __forceinline__ void wg_commit() { asm volatile("wgmma.commit_group.sync.aligned;" ::: "memory"); }
template <int N> __device__ __forceinline__ void wg_wait() { asm volatile("wgmma.wait_group.sync.aligned %0;" :: "n"(N) : "memory"); }

#define D16(C) C(d[0]), C(d[1]), C(d[2]), C(d[3]), C(d[4]), C(d[5]), C(d[6]), C(d[7]), \
               C(d[8]), C(d[9]), C(d[10]), C(d[11]), C(d[12]), C(d[13]), C(d[14]), C(d[15])
#define DREG16 "{%0,%1,%2,%3,%4,%5,%6,%7,%8,%9,%10,%11,%12,%13,%14,%15}"
__device__ __forceinline__ void wg_rs32(float* d, const uint32_t* a, uint64_t db, bool acc) {
    if (acc)
        asm volatile("wgmma.mma_async.sync.aligned.m64n32k16.f32.bf16.bf16 " DREG16 ", {%16,%17,%18,%19}, %20, 1, 1, 1, 0;"
            : D16("+f") : "r"(a[0]), "r"(a[1]), "r"(a[2]), "r"(a[3]), "l"(db));
    else
        asm volatile("wgmma.mma_async.sync.aligned.m64n32k16.f32.bf16.bf16 " DREG16 ", {%16,%17,%18,%19}, %20, 0, 1, 1, 0;"
            : D16("=f") : "r"(a[0]), "r"(a[1]), "r"(a[2]), "r"(a[3]), "l"(db));
}
__device__ __forceinline__ void wg_ss32(float* d, uint64_t da, uint64_t db, bool acc) {
    if (acc)
        asm volatile("wgmma.mma_async.sync.aligned.m64n32k16.f32.bf16.bf16 " DREG16 ", %16, %17, 1, 1, 1, 1, 0;"
            : D16("+f") : "l"(da), "l"(db));
    else
        asm volatile("wgmma.mma_async.sync.aligned.m64n32k16.f32.bf16.bf16 " DREG16 ", %16, %17, 0, 1, 1, 1, 0;"
            : D16("=f") : "l"(da), "l"(db));
}
__device__ __forceinline__ void wg_ss8(float* d, uint64_t da, uint64_t db, bool acc) {
    if (acc)
        asm volatile("wgmma.mma_async.sync.aligned.m64n8k16.f32.bf16.bf16 {%0,%1,%2,%3}, %4, %5, 1, 1, 1, 1, 1;"
            : "+f"(d[0]), "+f"(d[1]), "+f"(d[2]), "+f"(d[3]) : "l"(da), "l"(db));
    else
        asm volatile("wgmma.mma_async.sync.aligned.m64n8k16.f32.bf16.bf16 {%0,%1,%2,%3}, %4, %5, 0, 1, 1, 1, 1;"
            : "=f"(d[0]), "=f"(d[1]), "=f"(d[2]), "=f"(d[3]) : "l"(da), "l"(db));
}
template <int OFF> __device__ __forceinline__ void ldsm4t_i(uint32_t* r, uint32_t a) {
    asm volatile("ldmatrix.sync.aligned.m8n8.x4.trans.shared.b16 {%0,%1,%2,%3}, [%4+%5];"
                 : "=r"(r[0]), "=r"(r[1]), "=r"(r[2]), "=r"(r[3]) : "r"(a), "n"(OFF) : "memory");
}

__device__ __forceinline__ uint4 ld_relaxed4(const void* p) {
    uint4 v;
    asm volatile("ld.relaxed.gpu.global.v4.u32 {%0,%1,%2,%3}, [%4];" : "=r"(v.x), "=r"(v.y), "=r"(v.z), "=r"(v.w) : "l"(p) : "memory");
    return v;
}
__device__ __forceinline__ void st_relaxed2(void* p, uint32_t a, uint32_t b) {
    asm volatile("st.relaxed.gpu.global.v2.u32 [%0], {%1,%2};" :: "l"(p), "r"(a), "r"(b) : "memory");
}
__device__ __forceinline__ void st_relaxed2_off(void* base, uint32_t off, uint32_t a, uint32_t b) {
    asm volatile("{\n\t.reg .u64 ad;\n\tcvt.u64.u32 ad, %1;\n\tadd.u64 ad, ad, %0;\n\tst.relaxed.gpu.global.v2.u32 [ad], {%2,%3};\n\t}"
                 :: "l"(base), "r"(off), "r"(a), "r"(b) : "memory");
}
__device__ __forceinline__ void st_relaxed1(void* p, uint32_t a) {
    asm volatile("st.relaxed.gpu.global.u32 [%0], %1;" :: "l"(p), "r"(a) : "memory");
}
__device__ __forceinline__ uint32_t ld_acquire1(const uint32_t* p) {
    uint32_t v; asm volatile("ld.acquire.gpu.global.u32 %0, [%1];" : "=r"(v) : "l"(p) : "memory"); return v;
}
__device__ __forceinline__ void st_release1(uint32_t* p, uint32_t a) {
    asm volatile("st.release.gpu.global.u32 [%0], %1;" :: "l"(p), "r"(a) : "memory");
}
__device__ __forceinline__ uint4 lds4(uint32_t s) {
    uint4 v; asm volatile("ld.shared.v4.u32 {%0,%1,%2,%3}, [%4];" : "=r"(v.x), "=r"(v.y), "=r"(v.z), "=r"(v.w) : "r"(s) : "memory"); return v;
}
__device__ __forceinline__ void sts4(uint32_t s, const uint4& v) {
    asm volatile("st.shared.v4.u32 [%0], {%1,%2,%3,%4};" :: "r"(s), "r"(v.x), "r"(v.y), "r"(v.z), "r"(v.w) : "memory");
}
__device__ __forceinline__ float4 lds4f(uint32_t s) {
    float4 v; asm volatile("ld.shared.v4.f32 {%0,%1,%2,%3}, [%4];" : "=f"(v.x), "=f"(v.y), "=f"(v.z), "=f"(v.w) : "r"(s) : "memory"); return v;
}
__device__ __forceinline__ uint2 lds2(uint32_t s) {
    uint2 v; asm volatile("ld.shared.v2.u32 {%0,%1}, [%2];" : "=r"(v.x), "=r"(v.y) : "r"(s) : "memory"); return v;
}
__device__ __forceinline__ float2 lds2f(uint32_t s) {
    float2 v; asm volatile("ld.shared.v2.f32 {%0,%1}, [%2];" : "=f"(v.x), "=f"(v.y) : "r"(s) : "memory"); return v;
}
__device__ __forceinline__ uint32_t clk32() { uint32_t c; asm volatile("mov.u32 %0, %%clock;" : "=r"(c) :: "memory"); return c; }
__device__ __forceinline__ uint32_t tagw(float v, uint32_t tag) { return ((__float_as_uint(v) + 8u) & ~15u) | tag; }
__device__ __forceinline__ bool ok4(const uint4& v, uint32_t tag) { return (((v.x ^ tag) | (v.y ^ tag) | (v.z ^ tag) | (v.w ^ tag)) & 15u) == 0; }
__device__ __forceinline__ bool oks(const uint4& v) { return v.x != 0xFFFFFFFFu && v.y != 0xFFFFFFFFu && v.z != 0xFFFFFFFFu && v.w != 0xFFFFFFFFu; }
__device__ __forceinline__ float uf(uint32_t x) { return __uint_as_float(x & ~15u); }

template <int NT, int BAR>
__device__ __forceinline__ void mod_chunk(const bf16* __restrict__ c, const bf16* __restrict__ wmod, int col0, int tid, float* red) {
    constexpr int RG = NT / 8, NP = DM / RG;
    const int cc = tid & 7, rg = tid >> 3;
    uint4 w[NP];
    #pragma unroll
    for (int i = 0; i < NP; i++) w[i] = __ldg((const uint4*)(wmod + (size_t)(rg + i * RG) * (6 * DM) + col0 + cc * 8));
    float a[8];
    #pragma unroll
    for (int j = 0; j < 8; j++) a[j] = 0.f;
    #pragma unroll
    for (int i = 0; i < NP; i++) {
        const float v = __bfloat162float(c[rg + i * RG]);
        const float sv = bfr(__fdividef(v, 1.0f + __expf(-v)));
        a[0] += sv * bflo(w[i].x); a[1] += sv * bfhi(w[i].x); a[2] += sv * bflo(w[i].y); a[3] += sv * bfhi(w[i].y);
        a[4] += sv * bflo(w[i].z); a[5] += sv * bfhi(w[i].z); a[6] += sv * bflo(w[i].w); a[7] += sv * bfhi(w[i].w);
    }
    #pragma unroll
    for (int j = 0; j < 8; j++) {
        a[j] += __shfl_xor_sync(0xffffffffu, a[j], 8);
        a[j] += __shfl_xor_sync(0xffffffffu, a[j], 16);
    }
    if ((tid & 31) < 8) {
        float* d = red + (tid >> 5) * 64 + cc * 8;
        *(float4*)d = make_float4(a[0], a[1], a[2], a[3]);
        *(float4*)(d + 4) = make_float4(a[4], a[5], a[6], a[7]);
    }
    bar_sync(BAR, NT);
    if (tid < 64) {
        float s = 0.f;
        #pragma unroll
        for (int i = 0; i < NT / 32; i++) s += red[i * 64 + tid];
        g_mod[col0 + tid] = bfr(s);
    }
}

__device__ __forceinline__ uint32_t hadd2(uint32_t a, uint32_t b) { uint32_t r; asm("add.rn.bf16x2 %0, %1, %2;" : "=r"(r) : "r"(a), "r"(b)); return r; }
__device__ __forceinline__ uint32_t hsub2(uint32_t a, uint32_t b) { uint32_t r; asm("sub.rn.bf16x2 %0, %1, %2;" : "=r"(r) : "r"(a), "r"(b)); return r; }
__device__ __forceinline__ uint32_t hmul2(uint32_t a, uint32_t b) { uint32_t r; asm("mul.rn.bf16x2 %0, %1, %2;" : "=r"(r) : "r"(a), "r"(b)); return r; }
__device__ __forceinline__ void ln_stats(const uint2* x, uint32_t& mb2, float& rs) {
    float v[5][4];
    float s = 0.f;
    #pragma unroll
    for (int i = 0; i < 5; i++) {
        v[i][0] = bflo(x[i].x); v[i][1] = bfhi(x[i].x); v[i][2] = bflo(x[i].y); v[i][3] = bfhi(x[i].y);
        s += (v[i][0] + v[i][1]) + (v[i][2] + v[i][3]);
    }
    #pragma unroll
    for (int o = 16; o > 0; o >>= 1) s += __shfl_xor_sync(0xffffffffu, s, o);
    const float mean = s * (1.0f / DM);
    float q0 = 0.f, q1 = 0.f;
    #pragma unroll
    for (int i = 0; i < 5; i++) {
        const float d0 = v[i][0] - mean, d1 = v[i][1] - mean, d2 = v[i][2] - mean, d3 = v[i][3] - mean;
        q0 += d0 * d0; q1 += d1 * d1; q0 += d2 * d2; q1 += d3 * d3;
    }
    float q = q0 + q1;
    #pragma unroll
    for (int o = 16; o > 0; o >>= 1) q += __shfl_xor_sync(0xffffffffu, q, o);
    mb2 = pack2(mean, mean);
    const float var = bfr(q * (1.0f / DM));
    rs = __frcp_rn(bfr(__fsqrt_rn(bfr(var + 1e-5f))));
}
__device__ __forceinline__ uint32_t ln_norm(uint32_t x, uint32_t mb2, float rs) {
    const uint32_t d = hsub2(x, mb2);
    return pack2(bflo(d) * rs, bfhi(d) * rs);
}
__device__ __forceinline__ uint32_t ln_apply(uint32_t x, uint32_t mb2, float rs, uint32_t m1, uint32_t sh) {
    return hadd2(hmul2(ln_norm(x, mb2, rs), m1), sh);
}

constexpr int SM_WV = 0;
constexpr int SM_HB = 81920;
constexpr int SM_WO = SM_HB + 40960;
constexpr int SM_QX = SM_WO + 77824;
constexpr int SM_KS = SM_QX + 4096;
constexpr int SM_QM = SM_KS + 5120;
constexpr int SM_XS = SM_QM + 1024;
constexpr int SM_MS = SM_XS + 12288;
constexpr int SM_OS = SM_MS + 3840;
constexpr int SM_PM = SM_OS + 3072;
constexpr int SM_BAR = SM_PM + 640;
constexpr int SM_CH = SM_BAR + 128;
constexpr int SM_TOTAL = SM_CH + 128;
static_assert(SM_TOTAL <= 232448, "smem");

enum { B_MEM_FULL = 0, B_MEM_FREE, B_HLO_FULL, B_HHI_FULL, B_HLO_FREE, B_HHI_FREE, B_MS, B_O, B_XS, B_O1, B_XSFREE, B_WQ, B_P0, B_WV, B_WO, B_P1 };

__device__ __forceinline__ int probe_blk(uint32_t* blk) {
    uint32_t t0 = 0xffffffffu, t1 = 0xffffffffu, acc = 0;
    for (int rep = 0; rep < 3; rep++) {
        #pragma unroll
        for (int pg = 0; pg < 2; pg++) {
            uint32_t c0 = clk32();
            uint32_t v = atomicOr(blk + pg * 1024 + acc, 0u);
            acc = (v == 0x12345678u) ? 1u : 0u;
            asm volatile("" :: "r"(acc) : "memory");
            uint32_t c1 = clk32() + acc;
            uint32_t d = c1 - c0;
            if (rep > 0) { if (pg == 0) t0 = min(t0, d); else t1 = min(t1, d); }
        }
    }
    return t1 < t0 ? 1 : 0;
}

__device__ __forceinline__ uint32_t wo_tile_off(int w) {
    if (w < 8) return w * 6144;
    if (w < 12) return 8 * 6144 + (w - 8) * 4096;
    return 8 * 6144 + 4 * 4096 + (w - 12) * 6144;
}

template <int NRES, int NPRE>
__device__ __forceinline__ void wo_phase(uint32_t sb, int w, int lane, const uint32_t (*res)[4], uint32_t parity,
                                         uint32_t tag, int tile, int h) {
    FRESH(lane);
    const int er = (lane & 7) + 8 * (lane >> 4);
    const uint32_t aaddr = sb + SM_WO + wo_tile_off(w) + er * 32 + ((((lane >> 3) & 1) ^ ((er >> 2) & 1)) << 4);
    const uint32_t baddr = sb + SM_OS + lane * 16;
    float c0[4] = {0.f, 0.f, 0.f, 0.f}, c1[4] = {0.f, 0.f, 0.f, 0.f};
    uint32_t pre[NPRE > 4 ? NPRE : 4][4];
    if (NPRE >= 4) {
        #pragma unroll
        for (int i = 0; i < 4; i++) ldsm4t(pre[i], aaddr + i * 512);
        mbar_wait(sb + SM_BAR + B_O1 * 8, parity);
        uint32_t b[2][4];
        ldsm4t(b[0], baddr);
        ldsm4t(b[1], baddr + 512);
        #pragma unroll
        for (int kp = 0; kp < 2; kp++) {
            mma16(c0, pre[2 * kp][0], pre[2 * kp][1], pre[2 * kp][2], pre[2 * kp][3], b[kp][0], b[kp][1]);
            mma16(c1, pre[2 * kp + 1][0], pre[2 * kp + 1][1], pre[2 * kp + 1][2], pre[2 * kp + 1][3], b[kp][2], b[kp][3]);
        }
    } else {
        #pragma unroll
        for (int i = 0; i < 2; i++) ldsm4t(pre[i], aaddr + i * 512);
        mbar_wait(sb + SM_BAR + B_O1 * 8, parity);
        #pragma unroll
        for (int kp = 0; kp < 2; kp++) {
            uint32_t b[4];
            ldsm4t(b, baddr + kp * 512);
            if (kp == 1) { ldsm4t(pre[0], aaddr + 2 * 512); ldsm4t(pre[1], aaddr + 3 * 512); }
            mma16(c0, pre[0][0], pre[0][1], pre[0][2], pre[0][3], b[0], b[1]);
            mma16(c1, pre[1][0], pre[1][1], pre[1][2], pre[1][3], b[2], b[3]);
        }
    }
    #pragma unroll
    for (int i = 0; i < NPRE; i++) ldsm4t(pre[i], aaddr + (4 + i) * 512);
    uint32_t off0, off1;
    {
        uint32_t ch;
        asm volatile("ld.shared.u16 %0, [%1];" : "=r"(ch) : "r"(sb + SM_CH + 2 * tile) : "memory");
        const int j = h >> 4;
        const uint32_t base = (uint32_t)((tile * 4 + j) * 8192 + (h & 15) * 256 + lane * 8);
        ch >>= j;
        off0 = base + (ch & 1) * 4096;
        off1 = base + 16384 + (ch & 256) * 16;
    }
    mbar_wait(sb + SM_BAR + B_O * 8, parity);
    if (NRES == 4) {
        uint32_t b[4][4];
        #pragma unroll
        for (int i = 0; i < 4; i++) ldsm4t(b[i], baddr + (2 + i) * 512);
        #pragma unroll
        for (int i = 0; i < 2; i++) {
            mma16(c0, res[2 * i][0], res[2 * i][1], res[2 * i][2], res[2 * i][3], b[i][0], b[i][1]);
            mma16(c1, res[2 * i + 1][0], res[2 * i + 1][1], res[2 * i + 1][2], res[2 * i + 1][3], b[i][2], b[i][3]);
        }
        #pragma unroll
        for (int i = 0; i < 2; i++) {
            mma16(c0, pre[2 * i][0], pre[2 * i][1], pre[2 * i][2], pre[2 * i][3], b[2 + i][0], b[2 + i][1]);
            mma16(c1, pre[2 * i + 1][0], pre[2 * i + 1][1], pre[2 * i + 1][2], pre[2 * i + 1][3], b[2 + i][2], b[2 + i][3]);
        }
    } else if (NPRE == 4) {
        uint32_t b[2][4];
        #pragma unroll
        for (int hh = 0; hh < 2; hh++) {
            ldsm4t(b[0], baddr + (2 + 2 * hh) * 512);
            ldsm4t(b[1], baddr + (3 + 2 * hh) * 512);
            if (hh) {
                #pragma unroll
                for (int i = 0; i < 4; i++) ldsm4t(pre[i], aaddr + (8 + i) * 512);
            }
            #pragma unroll
            for (int i = 0; i < 2; i++) {
                mma16(c0, pre[2 * i][0], pre[2 * i][1], pre[2 * i][2], pre[2 * i][3], b[i][0], b[i][1]);
                mma16(c1, pre[2 * i + 1][0], pre[2 * i + 1][1], pre[2 * i + 1][2], pre[2 * i + 1][3], b[i][2], b[i][3]);
            }
        }
    }
    st_relaxed2_off(g_buf1, off0, tagw(c0[0] + c1[0], tag), tagw(c0[1] + c1[1], tag));
    st_relaxed2_off(g_buf1, off1, tagw(c0[2] + c1[2], tag), tagw(c0[3] + c1[3], tag));
}

template <int NT, bool MASK>
__device__ __forceinline__ void softmax_core(float (*sc)[2], int g, int t, uint32_t* pb) {
    const float L2E = 1.4426950408889634f;
    #pragma unroll
    for (int j = 0; j < NT; j++) score2(sc[j][0], sc[j][1]);
    if (MASK) {
        const float NEG = -999292928.0f;
        if (2 * t > g) sc[NT - 1][0] = NEG;
        if (2 * t + 1 > g) sc[NT - 1][1] = NEG;
    }
    float m[NT];
    #pragma unroll
    for (int j = 0; j < NT; j++) m[j] = fmaxf(sc[j][0], sc[j][1]);
    float mx = m[0];
    #pragma unroll
    for (int j = 1; j < NT; j++) mx = fmaxf(mx, m[j]);
    mx = fmaxf(mx, __shfl_xor_sync(0xffffffffu, mx, 1));
    mx = fmaxf(mx, __shfl_xor_sync(0xffffffffu, mx, 2));
    float s0 = 0.f, s1 = 0.f;
    #pragma unroll
    for (int j = 0; j < NT; j++) {
        sc[j][0] = ex2((sc[j][0] - mx) * L2E); sc[j][1] = ex2((sc[j][1] - mx) * L2E);
        s0 += sc[j][0]; s1 += sc[j][1];
    }
    s0 += s1;
    s0 += __shfl_xor_sync(0xffffffffu, s0, 1);
    s0 += __shfl_xor_sync(0xffffffffu, s0, 2);
    const float iv = rcpf(s0);
    #pragma unroll
    for (int j = 0; j < NT; j++) pb[j] = pack2(sc[j][0] * iv, sc[j][1] * iv);
}
template <int NT>
__device__ __forceinline__ void xsoftmax(uint32_t a, int g, int t) {
    float sc[NT][2];
    #pragma unroll
    for (int j = 0; j < NT; j++) {
        float2 v0 = lds2f(a + j * 512), v1 = lds2f(a + j * 512 + 4096), v2 = lds2f(a + j * 512 + 8192);
        sc[j][0] = v0.x + v1.x + v2.x; sc[j][1] = v0.y + v1.y + v2.y;
    }
    uint32_t pb[NT];
    softmax_core<NT, true>(sc, g, t, pb);
    #pragma unroll
    for (int j = 0; j < NT; j += 2) {
        if (j + 1 < NT) asm volatile("st.shared.v2.u32 [%0], {%1,%2};" :: "r"(a + j * 512), "r"(pb[j]), "r"(pb[j + 1]) : "memory");
        else sts1(a + j * 512, pb[j]);
    }
}
template <int NJ>
__device__ __forceinline__ void xscores(uint32_t sb, int p, int mi, int j0, int lane) {
    FRESH(lane);
    const int r = lane & 7, cq = lane >> 3;
    const int qrow = mi * 16 + r + 8 * (cq & 1);
    uint32_t kb[NJ][8];
    float d[NJ][4];
    #pragma unroll
    for (int j = 0; j < NJ; j++) {
        ldsm4(kb[j], sb + SM_KS + ((j0 + j) * 8 + r) * 128 + ((cq ^ r) << 4));
        ldsm4(kb[j] + 4, sb + SM_KS + ((j0 + j) * 8 + r) * 128 + (((cq + 4) ^ r) << 4));
        d[j][0] = 0.f; d[j][1] = 0.f; d[j][2] = 0.f; d[j][3] = 0.f;
    }
    #pragma unroll
    for (int kt = 0; kt < 4; kt++) {
        uint32_t a[4];
        ldsm4(a, sb + SM_QX + qrow * 128 + (((2 * kt + (cq >> 1)) ^ r) << 4));
        #pragma unroll
        for (int j = 0; j < NJ; j++) mma16(d[j], a[0], a[1], a[2], a[3], kb[j][2 * kt], kb[j][2 * kt + 1]);
    }
    const uint32_t la = sb + SM_XS + p * 4096 + (mi * 3 + j0) * 512 + lane * 16;
    #pragma unroll
    for (int rk = 0; rk < 3; rk++) {
        const uint32_t ra = mapa(la, rk), rb = mapa(sb + SM_BAR + B_XS * 8, rk);
        #pragma unroll
        for (int j = 0; j < NJ; j++) st_async4(ra + j * 512, d[j], rb);
    }
}
__device__ __forceinline__ void mbar_arrive_remote(uint32_t bar) {
    asm volatile("mbarrier.arrive.relaxed.cluster.shared::cluster.b64 _, [%0];" :: "r"(bar) : "memory");
}

__device__ __forceinline__ void tma2d(uint32_t dst, const CUtensorMap* map, int c0, int c1, uint32_t bar) {
    asm volatile("cp.async.bulk.tensor.2d.shared::cluster.global.mbarrier::complete_tx::bytes [%0], [%1, {%2, %3}], [%4];"
                 :: "r"(dst), "l"(map), "r"(c0), "r"(c1), "r"(bar) : "memory");
}
__device__ __forceinline__ void tma2d_pf(const CUtensorMap* map, int c0, int c1) {
    asm volatile("cp.async.bulk.prefetch.tensor.2d.L2.global [%0, {%1, %2}];" :: "l"(map), "r"(c0), "r"(c1) : "memory");
}
__device__ __forceinline__ void bulk_pf(const void* p, uint32_t bytes) {
    asm volatile("cp.async.bulk.prefetch.L2.global [%0], %1;" :: "l"(p), "r"(bytes) : "memory");
}
struct RMaps { CUtensorMap wq, wk, wv, wo, wop; };
__device__ __forceinline__ void signal_cnt(int idx) {
    asm volatile("fence.proxy.async.global;\n\tred.release.gpu.global.add.u32 [%0], 1;" :: "l"(g_cnt + idx * 32) : "memory");
}

__global__ void __launch_bounds__(512, 1)
k_rec(const __grid_constant__ RMaps maps, const bf16* __restrict__ mem0, const bf16* __restrict__ Wo,
      const bf16* __restrict__ xin, const bf16* __restrict__ cvec, const bf16* __restrict__ wmod) {
    extern __shared__ __align__(1024) uint8_t smem_raw[];
    constexpr uint32_t SBC = 1024;
    const uint32_t sb = smem_u32(smem_raw);
    if ((sb & 0xFFFFFFu) != SBC) __trap();
    int lane = __shfl_sync(0xffffffffu, threadIdx.x & 31, threadIdx.x & 31);
    const int warp = __shfl_sync(0xffffffffu, threadIdx.x >> 5, 0), wg = warp >> 2;
    const int tid = warp * 32 + lane;
    const int b = blockIdx.x, h = b / 3, p = b % 3;
    const int g = lane >> 2, t = lane & 3;
    const int tile0 = p == 0 ? 0 : (p == 1 ? 14 : 27);
    const int ntile = p == 0 ? 14 : 13;
    const uint32_t bar = sb + SM_BAR;

    if (tid == 0) T2(100 + b);
    if (tid == 0) {
        mbar_init(bar + B_MEM_FULL * 8, 4);
        mbar_init(bar + B_MEM_FREE * 8, 12);
        mbar_init(bar + B_HLO_FULL * 8, 1);
        mbar_init(bar + B_HHI_FULL * 8, 1);
        mbar_init(bar + B_HLO_FREE * 8, 12);
        mbar_init(bar + B_HHI_FREE * 8, 12);
        mbar_init(bar + B_MS * 8, 1);
        mbar_init(bar + B_O * 8, 1);
        mbar_init(bar + B_XS * 8, 1);
        mbar_init(bar + B_O1 * 8, 4);
        mbar_init(bar + B_XSFREE * 8, 12);
        mbar_init(bar + B_WQ * 8, 1);
        mbar_init(bar + B_P0 * 8, 1);
        mbar_init(bar + B_P1 * 8, 1);
        mbar_init(bar + B_WV * 8, 1);
        mbar_init(bar + B_WO * 8, 1);
        asm volatile("fence.mbarrier_init.release.cluster;" ::: "memory");
        mbar_expect(bar + B_MS * 8, 3840);
        mbar_expect(bar + B_O * 8, 2048);
        mbar_expect(bar + B_XS * 8, 12288);
    }
    __syncwarp();
    asm volatile("barrier.cluster.arrive.relaxed.aligned;\n\tbarrier.cluster.wait.acquire.aligned;" ::: "memory");
    if (warp == 0) T3(0);

    if (tid == 480) {
        #pragma unroll 1
        for (int i = 0; i < 5; i++) {
            if (i > 0 && i <= NPACE) mbar_wait(bar + B_P0 * 8, (i - 1) & 1);
            if (i <= NPACE) mbar_expect(bar + B_P0 * 8, i == NPACE ? (5 - NPACE) * 16384 : 16384);
            tma2d(sb + SM_WO + i * 16384, &maps.wq, h * DH + p * 64, i * 128, bar + B_P0 * 8);
            if (i > 0 && i <= NPACE) mbar_wait(bar + B_P1 * 8, (i - 1) & 1);
            if (i <= NPACE) mbar_expect(bar + B_P1 * 8, i == NPACE ? (5 - NPACE) * 16384 : 16384);
            tma2d(sb + SM_WV + i * 16384, &maps.wk, h * DH + p * 64, i * 128, bar + B_P1 * 8);
        }
        mbar_wait(bar + B_P0 * 8, NPACE & 1);
        mbar_wait(bar + B_P1 * 8, NPACE & 1);
        mbar_arrive(bar + B_WQ * 8);
        #pragma unroll 1
        for (int i = 0; i < 5; i++) tma2d_pf(&maps.wv, h * DH + p * 64, i * 128);
        tma2d_pf(&maps.wop, tile0 * 16, h * DH);
    }
    __syncwarp();
    if (wg < 3) {
        const uint32_t tag = *(volatile uint32_t*)&g_epoch + 1u;
        const int seg1 = b + 1, nrow = b < NSEG - 1 ? 64 : 32;
        const bf16* xl = xin + lane * 4;
        uint4 wm[5];
        float cv[5];
        if (wg < 2 && b < 80) {
            #pragma unroll
            for (int i = 0; i < 5; i++) {
                wm[i] = __ldg((const uint4*)(wmod + (size_t)((tid >> 1) + 128 * i) * (6 * DM) + b * 16 + (tid & 1) * 8));
                cv[i] = __bfloat162float(cvec[(tid >> 1) + 128 * i]);
            }
        }
        uint2 xn[6][5];
        #pragma unroll
        for (int r = 0; r < 6; r++) {
            const int idx = warp + 12 * r, nx = idx < 32 ? idx : (idx < nrow ? b * 32 + idx : 0);
            #pragma unroll
            for (int i = 0; i < 5; i++) xn[r][i] = __ldg((const uint2*)(xl + (size_t)nx * DM + i * 128));
        }
        if (wg < 2 && b < 80) {
            float a[8];
            #pragma unroll
            for (int j = 0; j < 8; j++) a[j] = 0.f;
            #pragma unroll
            for (int i = 0; i < 5; i++) {
                const float sv = bfr(__fdividef(cv[i], 1.0f + __expf(-cv[i])));
                a[0] += sv * bflo(wm[i].x); a[1] += sv * bfhi(wm[i].x); a[2] += sv * bflo(wm[i].y); a[3] += sv * bfhi(wm[i].y);
                a[4] += sv * bflo(wm[i].z); a[5] += sv * bfhi(wm[i].z); a[6] += sv * bflo(wm[i].w); a[7] += sv * bfhi(wm[i].w);
            }
            #pragma unroll 1
            for (int o = 2; o < 32; o <<= 1) {
                #pragma unroll
                for (int j = 0; j < 8; j++) a[j] += __shfl_xor_sync(0xffffffffu, a[j], o);
            }
            if (lane < 2) {
                const uint32_t d = sb + SM_QM + warp * 64 + lane * 32;
                sts4(d, make_uint4(__float_as_uint(a[0]), __float_as_uint(a[1]), __float_as_uint(a[2]), __float_as_uint(a[3])));
                sts4(d + 16, make_uint4(__float_as_uint(a[4]), __float_as_uint(a[5]), __float_as_uint(a[6]), __float_as_uint(a[7])));
            }
            bar_sync(1, 256);
            if (tid < 8) {
                float s0 = 0.f, s1 = 0.f;
                #pragma unroll
                for (int i = 0; i < 8; i++) { const float2 v = lds2f(sb + SM_QM + i * 64 + tid * 8); s0 += v.x; s1 += v.y; }
                st_relaxed2(g_modx + (b * 8 + tid) * 2, pack2(s0, s1), tag);
            }
        }
        __syncwarp();
        #pragma unroll 1
        for (int r = 0; r < 6; r++) {
            uint32_t mb; float rs;
            ln_stats(xn[0], mb, rs);
            #pragma unroll
            for (int i = 0; i < 5; i++) {
                const uint2 nv = make_uint2(ln_norm(xn[0][i].x, mb, rs), ln_norm(xn[0][i].y, mb, rs));
                #pragma unroll
                for (int q = 0; q < 5; q++) xn[q][i] = xn[q + 1][i];
                xn[5][i] = nv;
            }
        }
        T3(12);
        if (tid < 320) {
            uint4 v; uint32_t guard = 0;
            while (true) {
                v = ld_relaxed4(g_modx + tid * 4);
                if (v.y == tag && v.w == tag) break;
                __nanosleep(50);
                if (++guard > (1u << 22)) __trap();
            }
            if (tid >= 160) { v.x = hadd2(v.x, 0x3f803f80u); v.z = hadd2(v.z, 0x3f803f80u); }
            asm volatile("st.shared.v2.u32 [%0], {%1,%2};" :: "r"(sb + SM_KS + tid * 8), "r"(v.x), "r"(v.z) : "memory");
        }
        bar_sync(2, 384);
        T3(13);
        {
            uint2 sh[5], m1[5];
            #pragma unroll
            for (int i = 0; i < 5; i++) { sh[i] = lds2(sb + SM_KS + i * 256 + lane * 8); m1[i] = lds2(sb + SM_KS + 1280 + i * 256 + lane * 8); }
            #pragma unroll
            for (int r = 0; r < 6; r++) {
                const int idx = warp + 12 * r, row = idx & 31;
                if (idx < nrow) {
                    char* dst = (idx < 32 ? (char*)smem_raw + SM_HB : (char*)g_ht + (size_t)seg1 * 40960)
                                + (lane >> 4) * 4096 + row * 128 + ((((lane >> 1) & 7) ^ (row & 7)) << 4) + (lane & 1) * 8;
                    #pragma unroll
                    for (int i = 0; i < 5; i++)
                        *(uint2*)(dst + i * 8192) = make_uint2(hadd2(hmul2(xn[r][i].x, m1[i].x), sh[i].x), hadd2(hmul2(xn[r][i].y, m1[i].y), sh[i].y));
                }
            }
        }
        fence_async();
        bar_sync(2, 384);
        T3(7);
        if (tid == 0) { mbar_arrive(bar + B_HLO_FULL * 8); mbar_arrive(bar + B_HHI_FULL * 8); }
        if (tid == 352 && b < NSEG - 1) {
            asm volatile("fence.proxy.async.global;" ::: "memory");
            st_release1(&g_hflag[seg1], tag);
        }
        __syncwarp();
    }

    if (wg < 2) {
        asm volatile("setmaxnreg.inc.sync.aligned.u32 200;");
        const int w = warp & 3;
        uint32_t wa[40][4];
        {
            mbar_wait(bar + B_WQ * 8, 0);
            if (w == 0) T3(1 + wg);
            const int r = lane & 7;
            const uint32_t wsrc = sb + (wg == 0 ? SM_WO : SM_WV) + (r + ((lane >> 4) << 3)) * 128 + (((2 * w + ((lane >> 3) & 1)) ^ r) << 4);
            #pragma unroll
            for (int kt = 0; kt < 40; kt++) ldsm4t(wa[kt], wsrc + kt * 2048);
            fence_async();
            bar_arrive(10 + wg, 256);
        }

        const uint32_t dstx = sb + (wg == 0 ? SM_QX : SM_KS + 1024);

        for (int s = -1; s < NSEG; s++) {
            const uint32_t par = s & 1;
            FRESH(lane);
            const int g = lane >> 2, t = lane & 3, tid = warp * 32 + lane;
            if (s >= 0) {
                mbar_wait(bar + B_MEM_FULL * 8, par);
                TR(0);
                float c[4][4];
                #pragma unroll
                for (int i = 0; i < 4; i++) { c[i][0] = 0.f; c[i][1] = 0.f; c[i][2] = 0.f; c[i][3] = 0.f; }
                uint32_t maddr = sb + lane * 16;
                asm volatile("" : "+r"(maddr));
                #pragma unroll
                for (int kp = 0; kp < 20; kp++) {
                    uint32_t bb[4];
                    ldsm4t(bb, maddr + (SM_HB + kp * 512));
                    mma16(c[(kp & 1) * 2], wa[2 * kp][0], wa[2 * kp][1], wa[2 * kp][2], wa[2 * kp][3], bb[0], bb[1]);
                    mma16(c[(kp & 1) * 2 + 1], wa[2 * kp + 1][0], wa[2 * kp + 1][1], wa[2 * kp + 1][2], wa[2 * kp + 1][3], bb[2], bb[3]);
                }
                {
                    const int tok = lane & 7, ch = 2 * w + ((lane >> 3) & 1);
                    stsm2t(sb + (wg == 0 ? SM_QM : SM_KS) + tok * 128 + ((ch ^ tok) << 4),
                           pack2((c[0][0] + c[1][0]) + (c[2][0] + c[3][0]), (c[0][1] + c[1][1]) + (c[2][1] + c[3][1])),
                           pack2((c[0][2] + c[1][2]) + (c[2][2] + c[3][2]), (c[0][3] + c[1][3]) + (c[2][3] + c[3][3])));
                }
                __syncwarp();
                if (lane == 0) mbar_arrive(bar + B_MEM_FREE * 8);
                TR(1);
                bar_sync(1, 256);
                if (warp < 5) {
                    const int r = lane & 7, cq = lane >> 3;
                    uint32_t a[8], kb[8];
                    ldsm4(a, sb + SM_QM + r * 128 + ((cq ^ r) << 4));
                    ldsm4(kb, sb + SM_KS + (warp * 8 + r) * 128 + ((cq ^ r) << 4));
                    ldsm4(a + 4, sb + SM_QM + r * 128 + (((cq + 4) ^ r) << 4));
                    ldsm4(kb + 4, sb + SM_KS + (warp * 8 + r) * 128 + (((cq + 4) ^ r) << 4));
                    float d0[4] = {0.f, 0.f, 0.f, 0.f}, d1[4] = {0.f, 0.f, 0.f, 0.f};
                    mma16(d0, a[0], 0u, a[1], 0u, kb[0], kb[1]);
                    mma16(d1, a[2], 0u, a[3], 0u, kb[2], kb[3]);
                    mma16(d0, a[4], 0u, a[5], 0u, kb[4], kb[5]);
                    mma16(d1, a[6], 0u, a[7], 0u, kb[6], kb[7]);
                    const uint32_t la = sb + SM_MS + p * 1280 + warp * 256 + lane * 8;
                    #pragma unroll
                    for (int rk = 0; rk < 3; rk++)
                        st_async2(mapa(la, rk), d0[0] + d1[0], d0[1] + d1[1], mapa(bar + B_MS * 8, rk));
                    bar_arrive(4, 352);
                } else if (warp < 7) {
                    xscores<1>(sb, p, warp - 5, 0, lane);
                    bar_arrive(4, 352);
                }
                TR(2);
                if (s < NSEG - 1) {
                    wo_phase<0, 4>(sb, warp, lane, nullptr, par, (uint32_t)(s % 15) + 1u, tile0 + warp, h);
                    TR(4);
                }
            }
            if (s < NSEG - 1) {
                FRESH(lane);
                const uint32_t hp = (s + 1) & 1;
                float d[16];
                const uint64_t db0 = make_desc(SBC + SM_HB, 16, 1024, 1);
                mbar_wait(bar + B_HHI_FULL * 8, hp);
                if (s < 0 && warp == 0) T3(10);
                {
                    const int r = lane & 7, mq = lane >> 3;
                    const uint32_t ha = sb + SM_HB + 9 * 4096 + (8 * (mq >> 1) + r) * 128 + (((6 + (mq & 1)) ^ r) << 4);
                    uint32_t b0[4], b1[4];
                    ldsm4(b0, ha);
                    ldsm4(b1, ha + 2048);
                    #pragma unroll
                    for (int i = 0; i < 16; i++) d[i] = 0.f;
                    mma16(d + 0, wa[39][0], wa[39][1], wa[39][2], wa[39][3], b0[0], b0[1]);
                    mma16(d + 4, wa[39][0], wa[39][1], wa[39][2], wa[39][3], b0[2], b0[3]);
                    mma16(d + 8, wa[39][0], wa[39][1], wa[39][2], wa[39][3], b1[0], b1[1]);
                    mma16(d + 12, wa[39][0], wa[39][1], wa[39][2], wa[39][3], b1[2], b1[3]);
                    asm volatile("" : "+f"(d[0]), "+f"(d[4]), "+f"(d[8]), "+f"(d[12]) :: "memory");
                }
                if (s >= 0) bar_arrive(6, 512);
                mbar_wait(bar + B_HLO_FULL * 8, hp);
                bar_sync(9, 384);
                TR(6);
                wg_fence();
                #pragma unroll
                for (int kt = 0; kt < 12; kt++) wg_rs32(d, wa[kt], db0 + (uint64_t)(((kt >> 2) * 4096 + (kt & 3) * 32) >> 4), 1);
                wg_commit();
                #pragma unroll
                for (int kt = 12; kt < 39; kt++) wg_rs32(d, wa[kt], db0 + (uint64_t)(((kt >> 2) * 4096 + (kt & 3) * 32) >> 4), 1);
                wg_commit();
                wg_wait<1>();
                if (lane == 0) mbar_arrive(bar + B_HLO_FREE * 8);
                wg_wait<0>();
                if (lane == 0) mbar_arrive(bar + B_HHI_FREE * 8);
                TR(7);
                const int mi = lane >> 3, r = lane & 7;
                #pragma unroll
                for (int jj = 0; jj < 2; jj++) {
                    const int tok = 8 * (2 * jj + (mi >> 1)) + r, ch = 2 * w + (mi & 1);
                    stsm4t(dstx + tok * 128 + ((ch ^ r) << 4),
                           pack2(d[8 * jj + 0], d[8 * jj + 1]), pack2(d[8 * jj + 2], d[8 * jj + 3]),
                           pack2(d[8 * jj + 4], d[8 * jj + 5]), pack2(d[8 * jj + 6], d[8 * jj + 7]));
                }
                bar_arrive(8, 384);
                if (s < 0 && warp == 0) T3(11);
                if (s < 0) { bar_sync(0, 512); asm volatile("griddepcontrol.launch_dependents;" ::: "memory"); }
            }
        }
    } else if (wg == 2) {
        asm volatile("setmaxnreg.dec.sync.aligned.u32 64;");
        const int w = warp & 3;
        uint32_t res[4][4];
        {
            const bf16* src = Wo + ((size_t)h * DH + ((p + 1) % 3) * 64) * DM + (tile0 + warp) * 16 + 2 * t;
            #pragma unroll
            for (int kt = 0; kt < 4; kt++) {
                res[kt][0] = __ldg((const uint32_t*)(src + (size_t)(kt * 16 + g) * DM));
                res[kt][1] = __ldg((const uint32_t*)(src + (size_t)(kt * 16 + g) * DM + 8));
                res[kt][2] = __ldg((const uint32_t*)(src + (size_t)(kt * 16 + 8 + g) * DM));
                res[kt][3] = __ldg((const uint32_t*)(src + (size_t)(kt * 16 + 8 + g) * DM + 8));
            }
            #pragma unroll
            for (int kt = 0; kt < 4; kt++) {
                #pragma unroll
                for (int i = 0; i < 4; i++) res[kt][i] = movm(res[kt][i]);
            }
        }
        bar_sync(11, 256);
        if (tid == 256) {
            fence_async();
            mbar_expect(bar + B_WV * 8, 81920);
            #pragma unroll
            for (int i = 0; i < 5; i++) tma2d(sb + SM_WV + i * 16384, &maps.wv, h * DH + p * 64, i * 128, bar + B_WV * 8);
        }
        mbar_wait(bar + B_WV * 8, 0);
        if (w == 0) T3(3);
        const uint64_t da0 = make_desc(SBC + SM_WV, 16, 1024, 1);
        uint32_t vx[8], vm0 = 0, vm1 = 0;
        #pragma unroll
        for (int i = 0; i < 8; i++) vx[i] = 0;

        for (int s = -1; s < NSEG; s++) {
            FRESH(lane);
            const int g = lane >> 2, t = lane & 3, tid = warp * 32 + lane;
            if (s >= 0) {
                const uint32_t par = s & 1;
                mbar_wait(bar + B_MEM_FULL * 8, par);
                bar_sync(4, 352);
                TR(0);
                float dv[4];
                {
                    const uint64_t dbm = make_desc(SBC + SM_HB, 128, 128, 0);
                    wg_fence();
                    #pragma unroll
                    for (int kt = 0; kt < 40; kt++) {
                        wg_ss8(dv, da0 + (uint64_t)(kt * 128), dbm + (uint64_t)(kt * 16), kt > 0);
                        wg_commit();
                        if (kt < 39) wg_wait<1>();
                    }
                    wg_commit();
                }
                TR(1);
                bar_sync(5, 160);
                TR(2);
                uint32_t pb[5];
                #pragma unroll
                for (int j = 0; j < 5; j++) pb[j] = lds1(sb + SM_PM + j * 128 + lane * 4);
                float o0[4] = {0.f, 0.f, 0.f, 0.f}, o1[4] = {0.f, 0.f, 0.f, 0.f}, o2[4] = {0.f, 0.f, 0.f, 0.f};
                wg_wait<0>();
                TR(3);
                mma16(o0, vx[0], vx[1], vx[2], vx[3], pb[1], pb[2]);
                mma16(o1, vx[4], vx[5], vx[6], vx[7], pb[3], pb[4]);
                vm0 = pack2(dv[0], dv[1]); vm1 = pack2(dv[2], dv[3]);
                mma8(o2, vm0, vm1, pb[0]);
                if (s < NSEG - 1) {
                    const uint32_t q0 = pack2(o0[0] + o1[0] + o2[0], o0[1] + o1[1] + o2[1]), q1 = pack2(o0[2] + o1[2] + o2[2], o0[3] + o1[3] + o2[3]);
                    const uint32_t la = sb + SM_OS + (w * 16 + g) * 16 + t * 4;
                    #pragma unroll
                    for (int i = 1; i < 3; i++) {
                        const uint32_t rk = (p + i) % 3;
                        const uint32_t ra = mapa(la + (3 - i) * 1024, rk), rb = mapa(bar + B_O * 8, rk);
                        st_async1(ra, q0, rb);
                        st_async1(ra + 128, q1, rb);
                    }
                    sts1(la, q0);
                    sts1(la + 128, q1);
                    __syncwarp();
                    if (lane == 0) { mbar_arrive(bar + B_O1 * 8); mbar_arrive(bar + B_MEM_FREE * 8); }
                }
                TR(5);
                if (s < NSEG - 1) {
                    wo_phase<4, 4>(sb, warp, lane, res, par, (uint32_t)(s % 15) + 1u, tile0 + warp, h);
                    TR(4);
                    if (tid == 256) mbar_expect(bar + B_O * 8, 2048);
                }
                if (s < NSEG - 1) bar_sync(6, 512);
            }
            uint32_t vn[8];
            #pragma unroll
            for (int i = 0; i < 8; i++) vn[i] = 0;
            if (s < NSEG - 1) {
            float d[16];
            const uint32_t hp = (s + 1) & 1;
            const uint64_t db0 = make_desc(SBC + SM_HB, 16, 1024, 1);
            mbar_wait(bar + B_HHI_FULL * 8, hp);
            TR(6);
            wg_fence();
            #pragma unroll
            for (int kt = 12; kt < 40; kt++) wg_ss32(d, da0 + (uint64_t)(kt * 128), db0 + (uint64_t)(((kt >> 2) * 4096 + (kt & 3) * 32) >> 4), kt > 12);
            wg_commit();
            mbar_wait(bar + B_HLO_FULL * 8, hp);
            wg_fence();
            #pragma unroll
            for (int kt = 0; kt < 9; kt++) wg_ss32(d, da0 + (uint64_t)(kt * 128), db0 + (uint64_t)(((kt >> 2) * 4096 + (kt & 3) * 32) >> 4), 1);
            wg_commit();
            #pragma unroll
            for (int kt = 9; kt < 12; kt++) wg_ss32(d, da0 + (uint64_t)(kt * 128), db0 + (uint64_t)(((kt >> 2) * 4096 + (kt & 3) * 32) >> 4), 1);
            wg_commit();
            wg_wait<1>();
            bar_arrive(9, 384);
            wg_wait<0>();
            if (lane == 0) mbar_arrive(bar + B_HLO_FREE * 8);
            TR(7);
            if (lane == 0) mbar_arrive(bar + B_HHI_FREE * 8);
            #pragma unroll
            for (int i = 0; i < 8; i++) vn[i] = pack2(d[2 * i], d[2 * i + 1]);
            }
            if (s >= 0) {
                {
                    FRESH(lane);
                    mbar_wait(bar + B_XS * 8, s & 1);
                    if (w == 0 && lane == 0) mbar_expect(bar + B_XS * 8, 12288);
                    const uint32_t a = sb + SM_XS + (w >> 1) * 1536 + lane * 16 + (w & 1) * 8;
                    if (w == 0) xsoftmax<2>(a, lane >> 2, lane & 3);
                    else if (w == 1) xsoftmax<3>(a, lane >> 2, lane & 3);
                    else if (w == 2) xsoftmax<4>(a, lane >> 2, lane & 3);
                    else xsoftmax<5>(a, lane >> 2, lane & 3);
                }
                TR(8);
                bar_sync(7, 128);
                FRESH(lane);
                bf16* orow = g_ox + (size_t)(s * 32 + (lane >> 2)) * HD + h * DH + p * 64 + w * 16 + 2 * (lane & 3);
                {
                    const uint32_t pa = sb + SM_XS + lane * 16;
                    #pragma unroll
                    for (int mi = 0; mi < 2; mi++) {
                        float oa[4] = {0.f, 0.f, 0.f, 0.f}, ob[4] = {0.f, 0.f, 0.f, 0.f};
                        if (mi == 0) {
                            const uint4 p0 = lds4(pa);
                            const uint32_t p3 = lds1(pa + 1024 + 8);
                            mma8(oa, vm0, vm1, p0.x);
                            mma8(ob, vm0, vm1, p0.z);
                            mma16(oa, vx[0], vx[1], vx[2], vx[3], p0.y, 0u);
                            mma16(ob, vx[0], vx[1], vx[2], vx[3], p0.w, p3);
                        } else {
                            const uint4 p1 = lds4(pa + 1536), p2 = lds4(pa + 2560);
                            const uint32_t p4 = lds1(pa + 3584 + 8);
                            mma8(oa, vm0, vm1, p1.x);
                            mma8(ob, vm0, vm1, p1.z);
                            mma16(oa, vx[0], vx[1], vx[2], vx[3], p1.y, p2.x);
                            mma16(ob, vx[0], vx[1], vx[2], vx[3], p1.w, p2.z);
                            mma16(oa, vx[4], vx[5], vx[6], vx[7], p2.y, 0u);
                            mma16(ob, vx[4], vx[5], vx[6], vx[7], p2.w, p4);
                            if (lane < 3) mbar_arrive_remote(mapa(bar + B_XSFREE * 8, lane));
                        }
                        const uint32_t u0 = movm(pack2(oa[0], oa[1])), u1 = movm(pack2(oa[2], oa[3]));
                        const uint32_t u2 = movm(pack2(ob[0], ob[1])), u3 = movm(pack2(ob[2], ob[3]));
                        bf16* dst = orow + (size_t)(16 * mi) * HD;
                        *(uint32_t*)dst = u0;
                        *(uint32_t*)(dst + 8) = u1;
                        *(uint32_t*)(dst + 8 * HD) = u2;
                        *(uint32_t*)(dst + 8 * HD + 8) = u3;
                    }
                }
                TR(9);
                if (s == NSEG - 1) {
                    bar_sync(7, 128);
                    if (w == 3 && lane == 0) { signal_cnt(C_REC + 15); T2(400 + b); }
                    break;
                }
            }
            #pragma unroll
            for (int i = 0; i < 8; i++) vx[i] = vn[i];
            if (s >= 0) mbar_wait_cluster(bar + B_XSFREE * 8, s & 1);
            bar_sync(8, 384);
            TR(10);
            if (w < 3) xscores<2>(sb, p, w > 0, w == 2 ? 3 : 1, lane);
            else if ((s & 3) == 3 && s >= 0 && lane == 0) signal_cnt(C_REC + (s >> 2));
            __syncwarp();
            TR(11);
            if (s < 0) { bar_sync(0, 512); asm volatile("griddepcontrol.launch_dependents;" ::: "memory"); }
        }
    } else {
        asm volatile("setmaxnreg.dec.sync.aligned.u32 48;");
        const int w = warp & 3, lt = tid & 127;
        const uint32_t epoch = *(volatile uint32_t*)&g_epoch + 1u;
        if (b == 91) { if (lt < C_NUM) g_cnt[lt * 32] = 0u; __threadfence(); }
        if (b < 80) {
            #pragma unroll
            for (int i = 0; i < 2; i++) {
                const int idx = lt + i * 128, sl = idx >> 6, pg = (idx >> 5) & 1, wd = idx & 31;
                st_relaxed1(g_buf2 + (sl * 3 + (b >> 5)) * 2048 + pg * 1024 + (b & 31) * 32 + wd, 0xFFFFFFFFu);
            }
            __threadfence();
        }
        if (lane == 0 && w < 3) {
            int c = 0;
            if (w == 0) c = probe_blk(g_buf2 + 640 + (b & 31) * 8);
            else if (b < 80) c = probe_blk(g_buf1 + (b * 2 + (w - 1)) * 2048);
            else if (b < 92 && w == 1) c = probe_blk(g_buf2 + (b - 80) * 2048 + 960);
            asm volatile("st.shared.u8 [%0], %1;" :: "r"(sb + SM_CH + 96 + w), "r"(c) : "memory");
        }
        if (w == 0) T3(4);
        bar_sync(3, 128);
        uint32_t selmask;
        {
            const uint32_t c3 = lds1(sb + SM_CH + 96);
            const uint32_t cr = c3 & 1u, c1 = (c3 >> 8) & 1u, c2 = (c3 >> 16) & 1u;
            if (lt == 0 && b < 92) st_release1(&g_choice[b], (epoch << 2) | (b < 80 ? (c1 | (c2 << 1)) : (c1 ^ cr)));
            bar_sync(10, 256);
            if (w == 3) {
                if (lane == 0) { fence_async(); mbar_expect(bar + B_WO * 8, ntile * 6144 - 8192); }
                __syncwarp();
                if (lane < ntile) {
                    #pragma unroll
                    for (int e3 = 0; e3 < 3; e3++) {
                        const bool part = lane >= 8 && lane < 12;
                        if (part && e3 == 1) continue;
                        tma2d(sb + SM_WO + wo_tile_off(lane) + ((part && e3 == 2) ? 1 : e3) * 2048, &maps.wo,
                              (tile0 + lane) * 16, h * DH + ((e3 + p) % 3) * 64, bar + B_WO * 8);
                    }
                }
                __syncwarp();
            }
            if (w == 0) T3(5);
            if (lt < 92) {
                uint32_t v, guard = 0;
                while (true) {
                    v = ld_acquire1(&g_choice[lt]);
                    if ((v >> 2) == (epoch & 0x3fffffffu)) break;
                    __nanosleep(100);
                    if (++guard > (1u << 22)) __trap();
                }
                asm volatile("st.shared.u8 [%0], %1;" :: "r"(sb + SM_CH + lt), "r"(v & 3u) : "memory");
            }
            if (w == 0) T3(6);
            bar_sync(3, 128);
            selmask = (c1 << 12) | (c2 << 13);
            for (int i = 0; i < 12; i++) {
                uint32_t c; asm volatile("ld.shared.u8 %0, [%1];" : "=r"(c) : "r"(sb + SM_CH + 80 + i) : "memory");
                selmask |= ((c ^ cr) & 1u) << i;
            }
        }
        mbar_wait(bar + B_WO * 8, 0);
        if (w == 0) T3(8);
        bar_sync(0, 512);
        if (w == 0) T3(9);
        asm volatile("griddepcontrol.launch_dependents;" ::: "memory");
        const bool has_tile = (12 + w) < ntile;
        for (int s = 0; s < NSEG; s++) {
            const uint32_t par = s & 1;
            FRESH(lane);
            const int g = lane >> 2, t = lane & 3, lt = w * 32 + lane;
            if (s == 0) {
                mbar_wait(bar + B_HLO_FREE * 8, par);
                for (int k = lt; k < DM; k += 128) {
                    uint32_t v[4];
                    #pragma unroll
                    for (int i = 0; i < 4; i++) {
                        uint32_t lo = *(const uint16_t*)(mem0 + (2 * i) * DM + k), hi = *(const uint16_t*)(mem0 + (2 * i + 1) * DM + k);
                        v[i] = lo | (hi << 16);
                    }
                    asm volatile("st.shared.v4.u32 [%0], {%1,%2,%3,%4};" :: "r"(sb + SM_HB + k * 16), "r"(v[0]), "r"(v[1]), "r"(v[2]), "r"(v[3]) : "memory");
                }
            } else {
                const int sl = s & 3;
                const char* q = (const char*)g_buf2 + sl * 3 * 8192 + lt * 16;
                const uint32_t sm = selmask >> (sl * 3);
                const char* q0 = q + (sm & 1) * 4096;
                const char* q1 = q + 8192 + (sm & 2) * 2048;
                const char* q2 = q + 16384 + (sm & 4) * 1024;
                const uint32_t dst = sb + SM_HB + lt * 16;
                uint32_t guard = 0;
                mbar_wait(bar + B_HLO_FREE * 8, par);
                TR(10);
                while (true) {
                    const uint4 v0 = ld_relaxed4(q0), v1 = ld_relaxed4(q0 + 2048), v2 = ld_relaxed4(q1), v3 = ld_relaxed4(q1 + 2048), v4 = ld_relaxed4(q2);
                    sts4(dst, v0); sts4(dst + 2048, v1); sts4(dst + 4096, v2); sts4(dst + 6144, v3); sts4(dst + 8192, v4);
                    if (__all_sync(0xffffffffu, oks(v0) && oks(v1) && oks(v2) && oks(v3) && oks(v4))) break;
                    if (++guard > (1u << 22)) __trap();
                }
            }
            fence_async();
            __syncwarp();
            if (lane == 0) mbar_arrive(bar + B_MEM_FULL * 8);
            if (b == 0 && lt == 0) T2(300 + s);
            if (s == 0 && lt == 0) T2(200 + b);
            TR(0);
            if (w == 2) {
                mbar_wait(bar + B_MS * 8, par);
                TR(1);
                if (lane == 0) mbar_expect(bar + B_MS * 8, 3840);
                uint32_t pb[5];
                float sc[5][2];
                {
                    const uint32_t a = sb + SM_MS + lane * 8;
                    float2 u[5], v[5];
                    #pragma unroll
                    for (int j = 0; j < 5; j++) { u[j] = lds2f(a + j * 256); v[j] = lds2f(a + j * 256 + 1280); }
                    #pragma unroll
                    for (int j = 0; j < 5; j++) { sc[j][0] = u[j].x + v[j].x; sc[j][1] = u[j].y + v[j].y; }
                    #pragma unroll
                    for (int j = 0; j < 5; j++) u[j] = lds2f(a + j * 256 + 2560);
                    #pragma unroll
                    for (int j = 0; j < 5; j++) { sc[j][0] += u[j].x; sc[j][1] += u[j].y; }
                }
                softmax_core<5, false>(sc, g, t, pb);
                #pragma unroll
                for (int j = 0; j < 5; j++) sts1(sb + SM_PM + j * 128 + lane * 4, pb[j]);
                bar_arrive(5, 160);
                TR(2);
            }
            const uint32_t tag = (uint32_t)(s % 15) + 1u;
            if (s < NSEG - 1) {
                if (w == 3) {
                    const char* src = (const char*)g_ht + (size_t)(s + 1) * 40960;
                    if (s == 0) {
                        uint32_t guard = 0;
                        while (true) {
                            const uint32_t f0 = lane > 0 ? ld_acquire1(&g_hflag[lane]) : epoch, f1 = ld_acquire1(&g_hflag[32 + lane]);
                            if (__all_sync(0xffffffffu, f0 == epoch && f1 == epoch)) break;
                            if (++guard > (1u << 22)) __trap();
                        }
                        asm volatile("fence.proxy.async.global;" ::: "memory");
                    }
                    mbar_wait(bar + B_HHI_FREE * 8, par);
                    if (lane == 0) {
                        mbar_expect(bar + B_HHI_FULL * 8, 28672);
                        bulk_g2s(sb + SM_HB + 12288, src + 12288, 28672, sb + SM_BAR + B_HHI_FULL * 8);
                    }
                    mbar_wait(bar + B_MEM_FREE * 8, par);
                    if (lane == 0) {
                        mbar_expect(bar + B_HLO_FULL * 8, 12288);
                        bulk_g2s(sb + SM_HB, src, 12288, sb + SM_BAR + B_HLO_FULL * 8);
                    }
                    __syncwarp();
                }
                if (has_tile) wo_phase<0, 4>(sb, warp, lane, nullptr, par, tag, tile0 + warp, h);
                TR(4);
                bar_sync(6, 512);
            }
            if (s < NSEG - 1) {
                { const uint32_t c0 = clk32(); while (clk32() - c0 < H1_DELAY); }
                if (b < 80) {
                    FRESH(lane);
                    const char* rin0 = (const char*)g_buf1 + (size_t)(b * 2) * 8192 + ((selmask >> 12) & 1) * 4096 + (lane >> 2) * 256 + w * 64 + (lane & 3) * 16;
                    const char* rin1 = (const char*)g_buf1 + (size_t)(b * 2 + 1) * 8192 + ((selmask >> 13) & 1) * 4096 + (lane >> 2) * 256 + w * 64 + (lane & 3) * 16;
                    const int col = b * 8 + 2 * w + ((lane >> 1) & 1), wd = 2 * (lane & 1) + (lane >> 4);
                    const int sl = (lane & 8) ? ((s + 3) & 3) : ((s + 1) & 3);
                    uint32_t* dst = g_buf2 + (sl * 3 + (col >> 8)) * 2048 + ((lane >> 2) & 1) * 1024 + (col & 255) * 4 + wd;
                    asm volatile("" : "+l"(dst));
                    uint4 v0, v1, v2, v3;
                    uint32_t guard = 0;
                    while (true) {
                        v0 = ld_relaxed4(rin0); v1 = ld_relaxed4(rin0 + 2048);
                        v2 = ld_relaxed4(rin1); v3 = ld_relaxed4(rin1 + 2048);
                        if (__all_sync(0xffffffffu, ok4(v0, tag) && ok4(v1, tag) && ok4(v2, tag) && ok4(v3, tag))) break;
                        if (++guard > (1u << 22)) __trap();
                    }
                    TR(11);
                    const float a0 = (uf(v0.x) + uf(v1.x)) + (uf(v2.x) + uf(v3.x)), a1 = (uf(v0.y) + uf(v1.y)) + (uf(v2.y) + uf(v3.y));
                    const float a2 = (uf(v0.z) + uf(v1.z)) + (uf(v2.z) + uf(v3.z)), a3 = (uf(v0.w) + uf(v1.w)) + (uf(v2.w) + uf(v3.w));
                    const bool u16 = lane & 16;
                    float m0 = (u16 ? a2 : a0) + __shfl_xor_sync(0xffffffffu, u16 ? a0 : a2, 16);
                    float m1 = (u16 ? a3 : a1) + __shfl_xor_sync(0xffffffffu, u16 ? a1 : a3, 16);
                    m0 += __shfl_xor_sync(0xffffffffu, m0, 8); m1 += __shfl_xor_sync(0xffffffffu, m1, 8);
                    m0 += __shfl_xor_sync(0xffffffffu, m0, 4); m1 += __shfl_xor_sync(0xffffffffu, m1, 4);
                    st_relaxed1(dst, (lane & 8) ? 0xFFFFFFFFu : pack2(m0, m1));
                    TR(12);
                }
            }
        }
    }
    cluster_sync();
}

constexpr int G_STAGES = 6;
constexpr int G_STAGE_BYTES = 32768;
constexpr int G_SMEM = G_STAGES * G_STAGE_BYTES + 1024 + 256 + 2048 + 10240;

__device__ __forceinline__ void wg_ss128(float* d, uint64_t da, uint64_t db, int sc) {
    asm volatile("{\n\t.reg .pred p;\n\tsetp.ne.b32 p, %66, 0;\n\t"
        "wgmma.mma_async.sync.aligned.m64n128k16.f32.bf16.bf16 "
        "{%0,%1,%2,%3,%4,%5,%6,%7,%8,%9,%10,%11,%12,%13,%14,%15,%16,%17,%18,%19,%20,%21,%22,%23,%24,%25,%26,%27,%28,%29,%30,%31,"
        "%32,%33,%34,%35,%36,%37,%38,%39,%40,%41,%42,%43,%44,%45,%46,%47,%48,%49,%50,%51,%52,%53,%54,%55,%56,%57,%58,%59,%60,%61,%62,%63}, "
        "%64, %65, p, 1, 1, 0, 1;\n\t}"
        : "+f"(d[0]), "+f"(d[1]), "+f"(d[2]), "+f"(d[3]), "+f"(d[4]), "+f"(d[5]), "+f"(d[6]), "+f"(d[7]),
          "+f"(d[8]), "+f"(d[9]), "+f"(d[10]), "+f"(d[11]), "+f"(d[12]), "+f"(d[13]), "+f"(d[14]), "+f"(d[15]),
          "+f"(d[16]), "+f"(d[17]), "+f"(d[18]), "+f"(d[19]), "+f"(d[20]), "+f"(d[21]), "+f"(d[22]), "+f"(d[23]),
          "+f"(d[24]), "+f"(d[25]), "+f"(d[26]), "+f"(d[27]), "+f"(d[28]), "+f"(d[29]), "+f"(d[30]), "+f"(d[31]),
          "+f"(d[32]), "+f"(d[33]), "+f"(d[34]), "+f"(d[35]), "+f"(d[36]), "+f"(d[37]), "+f"(d[38]), "+f"(d[39]),
          "+f"(d[40]), "+f"(d[41]), "+f"(d[42]), "+f"(d[43]), "+f"(d[44]), "+f"(d[45]), "+f"(d[46]), "+f"(d[47]),
          "+f"(d[48]), "+f"(d[49]), "+f"(d[50]), "+f"(d[51]), "+f"(d[52]), "+f"(d[53]), "+f"(d[54]), "+f"(d[55]),
          "+f"(d[56]), "+f"(d[57]), "+f"(d[58]), "+f"(d[59]), "+f"(d[60]), "+f"(d[61]), "+f"(d[62]), "+f"(d[63])
        : "l"(da), "l"(db), "r"(sc));
}

#define SP0_LAST 12
#define SP2_LAST 6
enum { J_MOD = 0, J_G0, J_LN, J_G1, J_G2, J_FIN, J_END };
__host__ __device__ constexpr int sp0(int b) { return b >= 15 ? SP0_LAST : 3; }
__host__ __device__ constexpr int sp2(int b) { return b >= 15 ? SP2_LAST : 3; }
__host__ __device__ constexpr int njr(int b) { return b >= 15 ? 16 : 8; }
struct JobTab { uint32_t n; uint32_t j[1200]; };
constexpr uint32_t mkjob(int ty, int b, int n, int k0, int nk, int ks) {
    return (uint32_t)(ty | (b << 3) | (n << 7) | (k0 << 11) | (nk << 18) | (ks << 25));
}
constexpr void add_jobs(JobTab& t, int ty, int b) {
    if (b < 0) return;
    if (ty == J_G0) { for (int ks = 0; ks < sp0(b); ks++) for (int n = 0; n < 5; n++) t.j[t.n++] = mkjob(ty, b, n, ks * (96 / sp0(b)), 96 / sp0(b), ks); }
    else if (ty == J_G2) { for (int ks = 0; ks < sp2(b); ks++) for (int n = 0; n < 5; n++) t.j[t.n++] = mkjob(ty, b, n, ks * (24 / sp2(b)), 24 / sp2(b), ks); }
    else if (ty == J_G1) { for (int n = 0; n < 12; n++) t.j[t.n++] = mkjob(ty, b, n, 0, 10, 0); }
    else { for (int n = 0; n < njr(b); n++) t.j[t.n++] = mkjob(ty, b, n, 0, 16 / njr(b), ty == J_LN ? sp0(b) : sp2(b)); }
}
constexpr JobTab make_tab() {
    JobTab t = {};
    for (int i = 20; i < 60; i++) t.j[t.n++] = mkjob(J_MOD, 0, 0, i, 0, 0);
    for (int b = 0; b < 15; b++) {
        add_jobs(t, J_G0, b); add_jobs(t, J_G1, b - 1); add_jobs(t, J_FIN, b - 2); add_jobs(t, J_G2, b - 1); add_jobs(t, J_LN, b);
    }
    add_jobs(t, J_FIN, 13); add_jobs(t, J_G1, 14);
    add_jobs(t, J_G0, 15); add_jobs(t, J_G2, 14); add_jobs(t, J_LN, 15); add_jobs(t, J_FIN, 14);
    add_jobs(t, J_G1, 15); add_jobs(t, J_G2, 15); add_jobs(t, J_FIN, 15);
    return t;
}
__constant__ JobTab c_jobs = make_tab();

__device__ __forceinline__ bool cnt_ge(int idx, uint32_t target) { return ld_acquire1(g_cnt + idx * 32) >= target; }
__device__ __forceinline__ void cnt_wait(int idx, uint32_t target) {
    uint32_t guard = 0;
    while (!cnt_ge(idx, target)) { __nanosleep(64); if (++guard > (1u << 22)) __trap(); }
}

struct SMaps { CUtensorMap ox, wo, h2, w1, act, w2; };

__global__ void __launch_bounds__(384, 1)
k_side(const __grid_constant__ SMaps maps, const bf16* __restrict__ xin, const bf16* __restrict__ cvec,
       const bf16* __restrict__ wmod, bf16* __restrict__ outp) {
    extern __shared__ uint8_t smem_raw[];
    const uint32_t sb = (smem_u32(smem_raw) + 1023u) & ~1023u;
    const uint32_t bars = sb + G_STAGES * G_STAGE_BYTES;
    float* red = (float*)(smem_raw + (bars + 256 - smem_u32(smem_raw)));
    const int tid = threadIdx.x, lane = tid & 31, wg = tid >> 7;
    if (tid == 0) T2(500 + blockIdx.x);
    if (tid == 0) {
        for (int i = 0; i < G_STAGES; i++) { mbar_init(bars + i * 8, 1); mbar_init(bars + 64 + i * 8, 8); }
        for (int i = 0; i < 2; i++) { mbar_init(bars + 128 + i * 8, 1); mbar_init(bars + 144 + i * 8, 8); }
        asm volatile("fence.mbarrier_init.release.cluster;" ::: "memory");
    }
    __syncthreads();
    if (wg == 0) {
        if (tid == 0) {
            uint32_t st = 0, ph = 1;
            for (uint32_t it = 0;; it++) {
                const uint32_t ji = atomicAdd(g_cnt + C_Q * 32, 1u);
                const uint32_t job = ji < c_jobs.n ? c_jobs.j[ji] : (uint32_t)J_END;
                if (ji == 0) g_epoch = g_epoch + 1u;
                const int ty = job & 7, b = (job >> 3) & 15, n = (job >> 7) & 15, k0 = (job >> 11) & 127, nk = (job >> 18) & 127;
                const uint32_t sl = it & 1;
                mbar_wait(bars + 144 + sl * 8, ((it >> 1) & 1) ^ 1);
                sts1(bars + 160 + sl * 4, job);
                if (ty == J_G0 || ty == J_G1 || ty == J_G2) {
                    if (b >= PRING && ty != J_G1) cnt_wait((ty == J_G0 ? C_LN : C_FIN) + b - PRING, njr(b - PRING));
                    mbar_arrive(bars + 128 + sl * 8);
                    const CUtensorMap* mA = ty == J_G0 ? &maps.ox : (ty == J_G1 ? &maps.h2 : &maps.act);
                    const CUtensorMap* mB = ty == J_G0 ? &maps.wo : (ty == J_G1 ? &maps.w1 : &maps.w2);
                    const int didx = ty == J_G0 ? C_REC + b : (ty == J_G1 ? C_LN + b : C_G1 + b);
                    const uint32_t dtgt = ty == J_G0 ? 96u : (ty == J_G1 ? (uint32_t)njr(b) : 12u);
                    int pre = 0;
                    if (!cnt_ge(didx, dtgt)) {
                        pre = nk < G_STAGES ? nk : G_STAGES;
                        uint32_t s2 = st, p2 = ph;
                        for (int i = 0; i < pre; i++) {
                            mbar_wait(bars + 64 + s2 * 8, p2);
                            const uint32_t a = sb + s2 * G_STAGE_BYTES;
                            mbar_expect(bars + s2 * 8, G_STAGE_BYTES);
                            tma2d(a + 16384, mB, n * 128, (k0 + i) * 64, bars + s2 * 8);
                            tma2d(a + 16384 + 8192, mB, n * 128 + 64, (k0 + i) * 64, bars + s2 * 8);
                            if (++s2 == G_STAGES) { s2 = 0; p2 ^= 1; }
                        }
                        cnt_wait(didx, dtgt);
                    }
                    asm volatile("fence.proxy.async.global;" ::: "memory");
                    T2(1024 + ji * 4 + 1);
                    for (int i = 0; i < nk; i++) {
                        const uint32_t a = sb + st * G_STAGE_BYTES;
                        if (i >= pre) {
                            mbar_wait(bars + 64 + st * 8, ph);
                            mbar_expect(bars + st * 8, G_STAGE_BYTES);
                        }
                        tma2d(a, mA, (k0 + i) * 64, b * 128, bars + st * 8);
                        if (i >= pre) {
                            tma2d(a + 16384, mB, n * 128, (k0 + i) * 64, bars + st * 8);
                            tma2d(a + 16384 + 8192, mB, n * 128 + 64, (k0 + i) * 64, bars + st * 8);
                        }
                        if (++st == G_STAGES) { st = 0; ph ^= 1; }
                    }
                } else {
                    if (ty == J_LN) { bulk_pf(xin + (size_t)(b * 128 + n * nk * 8) * DM, nk * 8 * DM * 2); cnt_wait(C_MOD, 40u); cnt_wait(C_G0 + b, 5u * sp0(b)); }
                    else if (ty == J_FIN) cnt_wait(C_G2 + b, 5u * sp2(b));
                    if (ji < 1200) T2(1024 + ji * 4 + 1);
                    mbar_arrive(bars + 128 + sl * 8);
                    if (ty == J_END) break;
                }
            }
        }
    } else {
        const int cw = wg - 1, ct = tid - 128, cwarp = ct >> 5;
        uint32_t st = 0, ph = 0;
        uint2* smod = (uint2*)(red + 512);
        bool have_mod = false;
        auto load_mod = [&]() {
            for (int i = ct; i < DM; i += 256) {
                const float4 m = __ldcg((const float4*)(g_mod + 2 * DM + i * 4));
                const float o = (i >= 320 && i < 480) ? 1.0f : 0.0f;
                smod[i] = make_uint2(pack2(m.x + o, m.y + o), pack2(m.z + o, m.w + o));
            }
            bar_sync(1, 256);
            have_mod = true;
        };
        {
            if (ct == 0) red[0] = cnt_ge(C_MOD, 40u) ? 1.0f : 0.0f;
            bar_sync(1, 256);
            const bool rdy = red[0] != 0.0f;
            bar_sync(1, 256);
            if (rdy) load_mod();
        }
        for (uint32_t it = 0;; it++) {
            const uint32_t sl = it & 1;
            mbar_wait(bars + 128 + sl * 8, (it >> 1) & 1);
            const uint32_t job = lds1(bars + 160 + sl * 4);
            __syncwarp();
            if (lane == 0) mbar_arrive(bars + 144 + sl * 8);
            const int ty = job & 7, b = (job >> 3) & 15, n = (job >> 7) & 15, k0 = (job >> 11) & 127, nk = (job >> 18) & 127, ks = (job >> 25) & 15;
            if (ty == J_END) break;
            int sig = -1;
            if (ty == J_G0 || ty == J_G1 || ty == J_G2) {
                float d[64];
                #pragma unroll
                for (int i = 0; i < 64; i++) d[i] = 0.f;
                uint32_t pst = 0;
                for (int kb = 0; kb < nk; kb++) {
                    mbar_wait(bars + st * 8, ph);
                    const uint32_t a = sb + st * G_STAGE_BYTES;
                    const uint64_t da = make_desc(a + cw * 8192, 16, 1024, 1);
                    const uint64_t db = make_desc(a + 16384, 8192, 1024, 1);
                    wg_fence();
                    #pragma unroll
                    for (int k = 0; k < 4; k++) wg_ss128(d, da + (uint64_t)(k * 2), db + (uint64_t)(k * 128), 1);
                    wg_commit();
                    if (kb > 0) {
                        wg_wait<1>();
                        if (lane == 0) mbar_arrive(bars + 64 + pst * 8);
                    }
                    pst = st;
                    if (++st == G_STAGES) { st = 0; ph ^= 1; }
                }
                wg_wait<0>();
                if (lane == 0) mbar_arrive(bars + 64 + pst * 8);
                const int g = lane >> 2, t = lane & 3;
                if (ty == J_G1) {
                    #pragma unroll
                    for (int hf = 0; hf < 2; hf++) {
                        bf16* o = g_act + (size_t)(b * 128 + cwarp * 16 + g + 8 * hf) * FF + n * 128 + 8 * t;
                        #pragma unroll
                        for (int q = 0; q < 4; q++) {
                            uint32_t u[4];
                            #pragma unroll
                            for (int i = 0; i < 4; i++) {
                                const float a0 = bfr(d[4 * (4 * q + i) + 2 * hf]), a1 = bfr(d[4 * (4 * q + i) + 2 * hf + 1]);
                                u[i] = pack2(__fdividef(a0, 1.0f + __expf(-a0)), __fdividef(a1, 1.0f + __expf(-a1)));
                            }
                            const bool o1 = t & 1, o2 = t & 2;
                            uint32_t x0 = __shfl_xor_sync(0xffffffffu, o1 ? u[0] : u[1], 1), x1 = __shfl_xor_sync(0xffffffffu, o1 ? u[2] : u[3], 1);
                            if (o1) { u[0] = x0; u[2] = x1; } else { u[1] = x0; u[3] = x1; }
                            x0 = __shfl_xor_sync(0xffffffffu, o2 ? u[0] : u[2], 2); x1 = __shfl_xor_sync(0xffffffffu, o2 ? u[1] : u[3], 2);
                            if (o2) { u[0] = x0; u[1] = x1; } else { u[2] = x0; u[3] = x1; }
                            *(uint4*)(o + q * 32) = make_uint4(u[0], u[1], u[2], u[3]);
                        }
                    }
                    sig = C_G1 + b;
                } else {
                    float* o = (ty == J_G0 ? g_p0 : g_p2) + ((size_t)((b % PRING) * PMAX + ks) * 128 + cwarp * 16 + g) * DM + n * 128 + 2 * t;
                    #pragma unroll
                    for (int hf = 0; hf < 2; hf++) {
                        #pragma unroll
                        for (int j = 0; j < 16; j++)
                            *(float2*)(o + hf * 8 * DM + j * 8) = make_float2(d[4 * j + 2 * hf], d[4 * j + 2 * hf + 1]);
                    }
                    sig = (ty == J_G0 ? C_G0 : C_G2) + b;
                }
            } else if (ty == J_MOD) {
                mod_chunk<256, 2>(cvec, wmod, k0 * 64, ct, red);
                sig = C_MOD;
            } else {
                const bool ln = ty == J_LN;
                if (!have_mod) load_mod();
                const uint2* gm = smod + (ln ? 0 : 480) + lane;
                for (int r = 0; r < nk; r++) {
                    const int lr = (n * nk + r) * 8 + cwarp, row = b * 128 + lr;
                    const float* pp = (ln ? g_p0 : g_p2) + ((size_t)((b % PRING) * PMAX) * 128 + lr) * DM + lane * 4;
                    const bf16* xs = (ln ? xin : (const bf16*)g_x1) + (size_t)row * DM + lane * 4;
                    float v[5][4];
                    uint2 xv[5];
                    #pragma unroll
                    for (int i = 0; i < 5; i++) {
                        xv[i] = __ldcg((const uint2*)(xs + i * 128));
                        v[i][0] = 0.f; v[i][1] = 0.f; v[i][2] = 0.f; v[i][3] = 0.f;
                    }
                    if (ks == 3) {
                        float4 a[3][5];
                        #pragma unroll
                        for (int q = 0; q < 3; q++) {
                            #pragma unroll
                            for (int i = 0; i < 5; i++) a[q][i] = __ldcg((const float4*)(pp + (size_t)q * 128 * DM + i * 128));
                        }
                        #pragma unroll
                        for (int q = 0; q < 3; q++) {
                            #pragma unroll
                            for (int i = 0; i < 5; i++) { v[i][0] += a[q][i].x; v[i][1] += a[q][i].y; v[i][2] += a[q][i].z; v[i][3] += a[q][i].w; }
                        }
                    } else {
                        for (int q0 = 0; q0 < ks; q0 += 6) {
                            float4 a[6][5];
                            #pragma unroll
                            for (int q = 0; q < 6; q++) {
                                #pragma unroll
                                for (int i = 0; i < 5; i++) a[q][i] = __ldcg((const float4*)(pp + (size_t)(q0 + q) * 128 * DM + i * 128));
                            }
                            #pragma unroll
                            for (int q = 0; q < 6; q++) {
                                #pragma unroll
                                for (int i = 0; i < 5; i++) { v[i][0] += a[q][i].x; v[i][1] += a[q][i].y; v[i][2] += a[q][i].z; v[i][3] += a[q][i].w; }
                            }
                        }
                    }
                    bf16* dst = (ln ? (bf16*)g_x1 : outp) + (size_t)row * DM + lane * 4;
                    #pragma unroll
                    for (int i = 0; i < 5; i++) {
                        const uint2 gg = gm[i * 32];
                        xv[i].x = hadd2(xv[i].x, hmul2(gg.x, pack2(v[i][0], v[i][1])));
                        xv[i].y = hadd2(xv[i].y, hmul2(gg.y, pack2(v[i][2], v[i][3])));
                        *(uint2*)(dst + i * 128) = xv[i];
                    }
                    if (ln) {
                        uint32_t mb; float rs;
                        ln_stats(xv, mb, rs);
                        #pragma unroll
                        for (int i = 0; i < 5; i++) {
                            const uint2 sh = gm[160 + i * 32], m1 = gm[320 + i * 32];
                            *(uint2*)(g_h2 + (size_t)row * DM + lane * 4 + i * 128) =
                                make_uint2(ln_apply(xv[i].x, mb, rs, m1.x, sh.x), ln_apply(xv[i].y, mb, rs, m1.y, sh.y));
                        }
                    }
                }
                if (ln) sig = C_LN + b; else if (b < 16 - PRING) sig = C_FIN + b;
            }
            if (sig >= 0) {
                bar_sync(1, 256);
                if (ct == 0) signal_cnt(sig);
            }
            if (ct == 0) T2(1024 + ji * 4 + 2);
        }
    }
}

typedef CUresult (*EncodeFn)(CUtensorMap*, CUtensorMapDataType, cuuint32_t, void*, const cuuint64_t*, const cuuint64_t*,
                             const cuuint32_t*, const cuuint32_t*, CUtensorMapInterleave, CUtensorMapSwizzle,
                             CUtensorMapL2promotion, CUtensorMapFloatOOBfill);

static void make_map(EncodeFn fn, CUtensorMap* m, const void* ptr, uint64_t inner, uint64_t outer, uint32_t bi, uint32_t bo,
                     CUtensorMapSwizzle sw = CU_TENSOR_MAP_SWIZZLE_128B) {
    cuuint64_t dims[2] = {inner, outer};
    cuuint64_t strides[1] = {inner * 2};
    cuuint32_t box[2] = {bi, bo};
    cuuint32_t es[2] = {1, 1};
    fn(m, CU_TENSOR_MAP_DATA_TYPE_BFLOAT16, 2, (void*)ptr, dims, strides, box, es, CU_TENSOR_MAP_INTERLEAVE_NONE,
       sw, CU_TENSOR_MAP_L2_PROMOTION_L2_256B, CU_TENSOR_MAP_FLOAT_OOB_FILL_NONE);
}

extern "C" void kernel_launch(void* const* d_in, const int* in_sizes, int n_in, void* d_out, int out_size) {
    const bf16* x = (const bf16*)d_in[0];
    const bf16* mem0 = (const bf16*)d_in[1];
    const bf16* Wq = (const bf16*)d_in[2];
    const bf16* Wk = (const bf16*)d_in[3];
    const bf16* Wv = (const bf16*)d_in[4];
    const bf16* Wo = (const bf16*)d_in[5];
    const bf16* w1 = (const bf16*)d_in[8];
    const bf16* w2 = (const bf16*)d_in[9];
    const bf16* c = (const bf16*)d_in[10];
    const bf16* wmod = (const bf16*)d_in[11];
    bf16* out = (bf16*)d_out;

    static EncodeFn enc = nullptr;
    static void *p_ox, *p_x1, *p_h2, *p_act;
    if (!enc) {
        cudaDriverEntryPointQueryResult qr;
        void* f = nullptr;
        cudaGetDriverEntryPoint("cuTensorMapEncodeTiled", &f, cudaEnableDefault, &qr);
        enc = (EncodeFn)f;
        cudaGetSymbolAddress(&p_ox, g_ox);
        cudaGetSymbolAddress(&p_x1, g_x1);
        cudaGetSymbolAddress(&p_h2, g_h2);
        cudaGetSymbolAddress(&p_act, g_act);
        cudaFuncSetAttribute(k_rec, cudaFuncAttributeMaxDynamicSharedMemorySize, SM_TOTAL);
        cudaFuncSetAttribute(k_side, cudaFuncAttributeMaxDynamicSharedMemorySize, G_SMEM);
    }
    RMaps rm;
    make_map(enc, &rm.wq, Wq, HD, DM, 64, 128);
    make_map(enc, &rm.wk, Wk, HD, DM, 64, 128);
    make_map(enc, &rm.wv, Wv, HD, DM, 64, 128);
    make_map(enc, &rm.wo, Wo, DM, HD, 16, 64, CU_TENSOR_MAP_SWIZZLE_32B);
    make_map(enc, &rm.wop, Wo, DM, HD, 224, 192, CU_TENSOR_MAP_SWIZZLE_NONE);
    SMaps m;
    make_map(enc, &m.ox, p_ox, HD, SEQ, 64, 128);
    make_map(enc, &m.wo, Wo, DM, HD, 64, 64);
    make_map(enc, &m.h2, p_h2, DM, SEQ, 64, 128);
    make_map(enc, &m.w1, w1, FF, DM, 64, 64);
    make_map(enc, &m.act, p_act, FF, SEQ, 64, 128);
    make_map(enc, &m.w2, w2, DM, FF, 64, 64);

    cudaStream_t st = cudaStreamPerThread;
    {
        cudaLaunchConfig_t cfg = {};
        cfg.gridDim = dim3(96); cfg.blockDim = dim3(512); cfg.dynamicSmemBytes = SM_TOTAL; cfg.stream = st;
        cudaLaunchAttribute at[2];
        at[0].id = cudaLaunchAttributeClusterDimension;
        at[0].val.clusterDim.x = 3; at[0].val.clusterDim.y = 1; at[0].val.clusterDim.z = 1;
        cfg.attrs = at; cfg.numAttrs = 1;
        cudaLaunchKernelEx(&cfg, k_rec, rm, mem0, Wo, x, c, wmod);
    }
    {
        cudaLaunchConfig_t cfg = {};
        cfg.gridDim = dim3(SIDE_CTAS); cfg.blockDim = dim3(384); cfg.dynamicSmemBytes = G_SMEM; cfg.stream = st;
        cudaLaunchAttribute at[1];
        at[0].id = cudaLaunchAttributeProgrammaticStreamSerialization;
        at[0].val.programmaticStreamSerializationAllowed = 1;
        cfg.attrs = at; cfg.numAttrs = 1;
        cudaLaunchKernelEx(&cfg, k_side, m, x, c, wmod, out);
    }
}
```

```cpp
#include <cuda_runtime.h>
#include <cuda_bf16.h>
#include <cuda.h>
#include <stdint.h>

typedef __nv_bfloat16 bf16;
#define VX_THROTTLE 1
#define H1_DELAY 400
#define H1_BACK 0
#define VM_THROTTLE 1
#define PRE_TRIG 0
#define NPACE 3
#define PF_LATE 1
#define SIDE_CTAS 132

constexpr int SEQ = 2048, DM = 640, NH = 32, DH = 192, NSEG = 64, FF = 1536, HD = NH * DH;

__device__ __align__(128) float g_mod[6 * DM];
__device__ __align__(1024) bf16 g_ht[(size_t)SEQ * DM];
__device__ __align__(1024) bf16 g_ox[(size_t)SEQ * HD];
__device__ __align__(1024) bf16 g_x1[(size_t)SEQ * DM];
__device__ __align__(1024) bf16 g_h2[(size_t)SEQ * DM];
__device__ __align__(1024) bf16 g_act[(size_t)SEQ * FF];
__device__ __align__(8192) uint32_t g_buf1[80 * 2 * 2048];
__device__ __align__(8192) uint32_t g_buf2[4 * 3 * 2048];
__device__ uint32_t g_choice[128];
__device__ uint32_t g_epoch;
__device__ uint32_t g_hflag[64];
__device__ __align__(128) uint32_t g_modx[2 * DM];
#define T2(i)
#define T3(i)
enum { C_Q = 0, C_MOD = 1, C_REC = 2, C_G0 = 18, C_LN = 34, C_G1 = 50, C_G2 = 66, C_FIN = 82, C_NUM = 98 };
__device__ __align__(128) uint32_t g_cnt[C_NUM * 32];
constexpr int PMAX = 12;
constexpr int PRING = 4;
__device__ __align__(1024) float g_p0[(size_t)PRING * PMAX * 128 * DM];
__device__ __align__(1024) float g_p2[(size_t)PRING * PMAX * 128 * DM];
#define TR(k)

#define FRESH(x) asm volatile("" : "+r"(x))
__device__ __forceinline__ float bfr(float x) { uint32_t r; asm("cvt.rn.bf16x2.f32 %0, %1, %2;" : "=r"(r) : "f"(x), "f"(0.0f)); return __uint_as_float(r); }
__device__ __forceinline__ uint32_t pack2(float a, float b) {
    uint32_t r; asm("cvt.rn.bf16x2.f32 %0, %1, %2;" : "=r"(r) : "f"(b), "f"(a)); return r;
}
__device__ __forceinline__ float bflo(uint32_t v) { return __uint_as_float(v << 16); }
__device__ __forceinline__ float bfhi(uint32_t v) { return __uint_as_float(v & 0xffff0000u); }
__device__ __forceinline__ float ex2(float x) { float r; asm("ex2.approx.ftz.f32 %0, %1;" : "=f"(r) : "f"(x)); return r; }
__device__ __forceinline__ float rcpf(float x) { float r; asm("rcp.approx.ftz.f32 %0, %1;" : "=f"(r) : "f"(x)); return r; }
__device__ __forceinline__ void score2(float& a, float& b) {
    const float SCALE = 0.07216878364870322f;
    uint32_t u = pack2(a, b);
    u = pack2(bflo(u) * SCALE, bfhi(u) * SCALE);
    a = bflo(u); b = bfhi(u);
}
__device__ __forceinline__ uint32_t smem_u32(const void* p) { return (uint32_t)__cvta_generic_to_shared(p); }

__device__ __forceinline__ void mbar_init(uint32_t bar, uint32_t cnt) {
    asm volatile("mbarrier.init.shared::cta.b64 [%0], %1;" :: "r"(bar), "r"(cnt) : "memory");
}
__device__ __forceinline__ void mbar_arrive(uint32_t bar) {
    asm volatile("mbarrier.arrive.shared::cta.b64 _, [%0];" :: "r"(bar) : "memory");
}
__device__ __forceinline__ void mbar_expect(uint32_t bar, uint32_t bytes) {
    asm volatile("mbarrier.arrive.expect_tx.shared::cta.b64 _, [%0], %1;" :: "r"(bar), "r"(bytes) : "memory");
}
__device__ __forceinline__ bool mbar_try(uint32_t bar, uint32_t parity) {
    uint32_t ok;
    asm volatile("{\n\t.reg .pred p;\n\tmbarrier.try_wait.parity.shared::cta.b64 p, [%1], %2;\n\tselp.u32 %0, 1, 0, p;\n\t}"
                 : "=r"(ok) : "r"(bar), "r"(parity) : "memory");
    return ok != 0;
}
__device__ __forceinline__ bool mbar_try_cluster(uint32_t bar, uint32_t parity) {
    uint32_t ok;
    asm volatile("{\n\t.reg .pred p;\n\tmbarrier.try_wait.parity.acquire.cluster.shared::cta.b64 p, [%1], %2;\n\tselp.u32 %0, 1, 0, p;\n\t}"
                 : "=r"(ok) : "r"(bar), "r"(parity) : "memory");
    return ok != 0;
}
__device__ __forceinline__ void mbar_wait(uint32_t bar, uint32_t parity) {
    uint32_t guard = 0;
    while (!mbar_try(bar, parity)) { if (++guard > (1u << 22)) __trap(); }
}
__device__ __forceinline__ void mbar_wait_cluster(uint32_t bar, uint32_t parity) {
    uint32_t guard = 0;
    while (!mbar_try_cluster(bar, parity)) { if (++guard > (1u << 22)) __trap(); }
}
__device__ __forceinline__ void bar_sync(int id, int n) { asm volatile("bar.sync %0, %1;" :: "r"(id), "r"(n) : "memory"); }
__device__ __forceinline__ void bar_arrive(int id, int n) { asm volatile("bar.arrive %0, %1;" :: "r"(id), "r"(n) : "memory"); }
__device__ __forceinline__ void sts1(uint32_t a, uint32_t v) { asm volatile("st.shared.u32 [%0], %1;" :: "r"(a), "r"(v) : "memory"); }
__device__ __forceinline__ uint32_t lds1(uint32_t a) { uint32_t v; asm volatile("ld.shared.u32 %0, [%1];" : "=r"(v) : "r"(a) : "memory"); return v; }
__device__ __forceinline__ void fence_async() { asm volatile("fence.proxy.async.shared::cta;" ::: "memory"); }
__device__ __forceinline__ void cluster_sync() {
    asm volatile("barrier.cluster.arrive.release.aligned;\n\tbarrier.cluster.wait.acquire.aligned;" ::: "memory");
}
__device__ __forceinline__ uint32_t mapa(uint32_t a, uint32_t rank) {
    uint32_t r; asm("mapa.shared::cluster.u32 %0, %1, %2;" : "=r"(r) : "r"(a), "r"(rank)); return r;
}
__device__ __forceinline__ void st_async1(uint32_t a, uint32_t v, uint32_t bar) {
    asm volatile("st.async.weak.shared::cluster.mbarrier::complete_tx::bytes.b32 [%0], %1, [%2];" :: "r"(a), "r"(v), "r"(bar) : "memory");
}
__device__ __forceinline__ void st_async2(uint32_t a, float x, float y, uint32_t bar) {
    asm volatile("st.async.weak.shared::cluster.mbarrier::complete_tx::bytes.v2.f32 [%0], {%1,%2}, [%3];" :: "r"(a), "f"(x), "f"(y), "r"(bar) : "memory");
}
__device__ __forceinline__ void st_async4(uint32_t a, const float* c, uint32_t bar) {
    asm volatile("st.async.weak.shared::cluster.mbarrier::complete_tx::bytes.v4.f32 [%0], {%1,%2,%3,%4}, [%5];"
                 :: "r"(a), "f"(c[0]), "f"(c[1]), "f"(c[2]), "f"(c[3]), "r"(bar) : "memory");
}
__device__ __forceinline__ void bulk_g2s(uint32_t dst, const void* src, uint32_t bytes, uint32_t bar) {
    asm volatile("cp.async.bulk.shared::cluster.global.mbarrier::complete_tx::bytes [%0], [%1], %2, [%3];"
                 :: "r"(dst), "l"(src), "r"(bytes), "r"(bar) : "memory");
}
__device__ __forceinline__ void cpa16(uint32_t s, const void* g) {
    asm volatile("cp.async.cg.shared.global [%0], [%1], 16;" :: "r"(s), "l"(g) : "memory");
}
__device__ __forceinline__ void cpa_wait_all() { asm volatile("cp.async.wait_all;" ::: "memory"); }
__device__ __forceinline__ void ldsm4(uint32_t* r, uint32_t a) {
    asm volatile("ldmatrix.sync.aligned.m8n8.x4.shared.b16 {%0,%1,%2,%3}, [%4];" : "=r"(r[0]), "=r"(r[1]), "=r"(r[2]), "=r"(r[3]) : "r"(a) : "memory");
}
__device__ __forceinline__ void ldsm4t(uint32_t* r, uint32_t a) {
    asm volatile("ldmatrix.sync.aligned.m8n8.x4.trans.shared.b16 {%0,%1,%2,%3}, [%4];" : "=r"(r[0]), "=r"(r[1]), "=r"(r[2]), "=r"(r[3]) : "r"(a) : "memory");
}
__device__ __forceinline__ void stsm2t(uint32_t a, uint32_t r0, uint32_t r1) {
    asm volatile("stmatrix.sync.aligned.m8n8.x2.trans.shared.b16 [%0], {%1,%2};" :: "r"(a), "r"(r0), "r"(r1) : "memory");
}
__device__ __forceinline__ void stsm4t(uint32_t a, uint32_t r0, uint32_t r1, uint32_t r2, uint32_t r3) {
    asm volatile("stmatrix.sync.aligned.m8n8.x4.trans.shared.b16 [%0], {%1,%2,%3,%4};" :: "r"(a), "r"(r0), "r"(r1), "r"(r2), "r"(r3) : "memory");
}
__device__ __forceinline__ uint32_t movm(uint32_t v) {
    uint32_t r; asm volatile("movmatrix.sync.aligned.m8n8.trans.b16 %0, %1;" : "=r"(r) : "r"(v)); return r;
}
__device__ __forceinline__ void mma16(float* c, uint32_t a0, uint32_t a1, uint32_t a2, uint32_t a3, uint32_t b0, uint32_t b1) {
    asm volatile("mma.sync.aligned.m16n8k16.row.col.f32.bf16.bf16.f32 {%0,%1,%2,%3}, {%4,%5,%6,%7}, {%8,%9}, {%0,%1,%2,%3};"
                 : "+f"(c[0]), "+f"(c[1]), "+f"(c[2]), "+f"(c[3]) : "r"(a0), "r"(a1), "r"(a2), "r"(a3), "r"(b0), "r"(b1));
}
__device__ __forceinline__ void mma8(float* c, uint32_t a0, uint32_t a1, uint32_t b0) {
    asm volatile("mma.sync.aligned.m16n8k8.row.col.f32.bf16.bf16.f32 {%0,%1,%2,%3}, {%4,%5}, {%6}, {%0,%1,%2,%3};"
                 : "+f"(c[0]), "+f"(c[1]), "+f"(c[2]), "+f"(c[3]) : "r"(a0), "r"(a1), "r"(b0));
}
__host__ __device__ constexpr uint64_t make_desc(uint32_t saddr, uint32_t lbo, uint32_t sbo, uint32_t layout) {
    return (uint64_t)((saddr & 0x3FFFF) >> 4) | ((uint64_t)(lbo >> 4) << 16) | ((uint64_t)(sbo >> 4) << 32) | ((uint64_t)layout << 62);
}
__device__ __forceinline__ void wg_fence() { asm volatile("wgmma.fence.sync.aligned;" ::: "memory"); }
__device__ __forceinline__ void wg_commit() { asm volatile("wgmma.commit_group.sync.aligned;" ::: "memory"); }
template <int N> __device__ __forceinline__ void wg_wait() { asm volatile("wgmma.wait_group.sync.aligned %0;" :: "n"(N) : "memory"); }

#define D16(C) C(d[0]), C(d[1]), C(d[2]), C(d[3]), C(d[4]), C(d[5]), C(d[6]), C(d[7]), \
               C(d[8]), C(d[9]), C(d[10]), C(d[11]), C(d[12]), C(d[13]), C(d[14]), C(d[15])
#define DREG16 "{%0,%1,%2,%3,%4,%5,%6,%7,%8,%9,%10,%11,%12,%13,%14,%15}"
__device__ __forceinline__ void wg_rs32(float* d, const uint32_t* a, uint64_t db, bool acc) {
    if (acc)
        asm volatile("wgmma.mma_async.sync.aligned.m64n32k16.f32.bf16.bf16 " DREG16 ", {%16,%17,%18,%19}, %20, 1, 1, 1, 0;"
            : D16("+f") : "r"(a[0]), "r"(a[1]), "r"(a[2]), "r"(a[3]), "l"(db));
    else
        asm volatile("wgmma.mma_async.sync.aligned.m64n32k16.f32.bf16.bf16 " DREG16 ", {%16,%17,%18,%19}, %20, 0, 1, 1, 0;"
            : D16("=f") : "r"(a[0]), "r"(a[1]), "r"(a[2]), "r"(a[3]), "l"(db));
}
__device__ __forceinline__ void wg_ss32(float* d, uint64_t da, uint64_t db, bool acc) {
    if (acc)
        asm volatile("wgmma.mma_async.sync.aligned.m64n32k16.f32.bf16.bf16 " DREG16 ", %16, %17, 1, 1, 1, 1, 0;"
            : D16("+f") : "l"(da), "l"(db));
    else
        asm volatile("wgmma.mma_async.sync.aligned.m64n32k16.f32.bf16.bf16 " DREG16 ", %16, %17, 0, 1, 1, 1, 0;"
            : D16("=f") : "l"(da), "l"(db));
}
__device__ __forceinline__ void wg_ss8(float* d, uint64_t da, uint64_t db, bool acc) {
    if (acc)
        asm volatile("wgmma.mma_async.sync.aligned.m64n8k16.f32.bf16.bf16 {%0,%1,%2,%3}, %4, %5, 1, 1, 1, 1, 1;"
            : "+f"(d[0]), "+f"(d[1]), "+f"(d[2]), "+f"(d[3]) : "l"(da), "l"(db));
    else
        asm volatile("wgmma.mma_async.sync.aligned.m64n8k16.f32.bf16.bf16 {%0,%1,%2,%3}, %4, %5, 0, 1, 1, 1, 1;"
            : "=f"(d[0]), "=f"(d[1]), "=f"(d[2]), "=f"(d[3]) : "l"(da), "l"(db));
}
template <int OFF> __device__ __forceinline__ void ldsm4t_i(uint32_t* r, uint32_t a) {
    asm volatile("ldmatrix.sync.aligned.m8n8.x4.trans.shared.b16 {%0,%1,%2,%3}, [%4+%5];"
                 : "=r"(r[0]), "=r"(r[1]), "=r"(r[2]), "=r"(r[3]) : "r"(a), "n"(OFF) : "memory");
}

__device__ __forceinline__ uint4 ld_relaxed4(const void* p) {
    uint4 v;
    asm volatile("ld.relaxed.gpu.global.v4.u32 {%0,%1,%2,%3}, [%4];" : "=r"(v.x), "=r"(v.y), "=r"(v.z), "=r"(v.w) : "l"(p) : "memory");
    return v;
}
__device__ __forceinline__ void st_relaxed2(void* p, uint32_t a, uint32_t b) {
    asm volatile("st.relaxed.gpu.global.v2.u32 [%0], {%1,%2};" :: "l"(p), "r"(a), "r"(b) : "memory");
}
__device__ __forceinline__ void st_relaxed2_off(void* base, uint32_t off, uint32_t a, uint32_t b) {
    asm volatile("{\n\t.reg .u64 ad;\n\tcvt.u64.u32 ad, %1;\n\tadd.u64 ad, ad, %0;\n\tst.relaxed.gpu.global.v2.u32 [ad], {%2,%3};\n\t}"
                 :: "l"(base), "r"(off), "r"(a), "r"(b) : "memory");
}
__device__ __forceinline__ void st_relaxed1(void* p, uint32_t a) {
    asm volatile("st.relaxed.gpu.global.u32 [%0], %1;" :: "l"(p), "r"(a) : "memory");
}
__device__ __forceinline__ uint32_t ld_acquire1(const uint32_t* p) {
    uint32_t v; asm volatile("ld.acquire.gpu.global.u32 %0, [%1];" : "=r"(v) : "l"(p) : "memory"); return v;
}
__device__ __forceinline__ void st_release1(uint32_t* p, uint32_t a) {
    asm volatile("st.release.gpu.global.u32 [%0], %1;" :: "l"(p), "r"(a) : "memory");
}
__device__ __forceinline__ uint4 lds4(uint32_t s) {
    uint4 v; asm volatile("ld.shared.v4.u32 {%0,%1,%2,%3}, [%4];" : "=r"(v.x), "=r"(v.y), "=r"(v.z), "=r"(v.w) : "r"(s) : "memory"); return v;
}
__device__ __forceinline__ void sts4(uint32_t s, const uint4& v) {
    asm volatile("st.shared.v4.u32 [%0], {%1,%2,%3,%4};" :: "r"(s), "r"(v.x), "r"(v.y), "r"(v.z), "r"(v.w) : "memory");
}
__device__ __forceinline__ float4 lds4f(uint32_t s) {
    float4 v; asm volatile("ld.shared.v4.f32 {%0,%1,%2,%3}, [%4];" : "=f"(v.x), "=f"(v.y), "=f"(v.z), "=f"(v.w) : "r"(s) : "memory"); return v;
}
__device__ __forceinline__ uint2 lds2(uint32_t s) {
    uint2 v; asm volatile("ld.shared.v2.u32 {%0,%1}, [%2];" : "=r"(v.x), "=r"(v.y) : "r"(s) : "memory"); return v;
}
__device__ __forceinline__ float2 lds2f(uint32_t s) {
    float2 v; asm volatile("ld.shared.v2.f32 {%0,%1}, [%2];" : "=f"(v.x), "=f"(v.y) : "r"(s) : "memory"); return v;
}
__device__ __forceinline__ uint32_t clk32() { uint32_t c; asm volatile("mov.u32 %0, %%clock;" : "=r"(c) :: "memory"); return c; }
__device__ __forceinline__ uint32_t tagw(float v, uint32_t tag) { return ((__float_as_uint(v) + 8u) & ~15u) | tag; }
__device__ __forceinline__ bool ok4(const uint4& v, uint32_t tag) { return (((v.x ^ tag) | (v.y ^ tag) | (v.z ^ tag) | (v.w ^ tag)) & 15u) == 0; }
__device__ __forceinline__ bool oks(const uint4& v) { return v.x != 0xFFFFFFFFu && v.y != 0xFFFFFFFFu && v.z != 0xFFFFFFFFu && v.w != 0xFFFFFFFFu; }
__device__ __forceinline__ float uf(uint32_t x) { return __uint_as_float(x & ~15u); }

template <int NT, int BAR>
__device__ __forceinline__ void mod_chunk(const bf16* __restrict__ c, const bf16* __restrict__ wmod, int col0, int tid, float* red) {
    constexpr int RG = NT / 8, NP = DM / RG;
    const int cc = tid & 7, rg = tid >> 3;
    uint4 w[NP];
    #pragma unroll
    for (int i = 0; i < NP; i++) w[i] = __ldg((const uint4*)(wmod + (size_t)(rg + i * RG) * (6 * DM) + col0 + cc * 8));
    float a[8];
    #pragma unroll
    for (int j = 0; j < 8; j++) a[j] = 0.f;
    #pragma unroll
    for (int i = 0; i < NP; i++) {
        const float v = __bfloat162float(c[rg + i * RG]);
        const float sv = bfr(__fdividef(v, 1.0f + __expf(-v)));
        a[0] += sv * bflo(w[i].x); a[1] += sv * bfhi(w[i].x); a[2] += sv * bflo(w[i].y); a[3] += sv * bfhi(w[i].y);
        a[4] += sv * bflo(w[i].z); a[5] += sv * bfhi(w[i].z); a[6] += sv * bflo(w[i].w); a[7] += sv * bfhi(w[i].w);
    }
    #pragma unroll
    for (int j = 0; j < 8; j++) {
        a[j] += __shfl_xor_sync(0xffffffffu, a[j], 8);
        a[j] += __shfl_xor_sync(0xffffffffu, a[j], 16);
    }
    if ((tid & 31) < 8) {
        float* d = red + (tid >> 5) * 64 + cc * 8;
        *(float4*)d = make_float4(a[0], a[1], a[2], a[3]);
        *(float4*)(d + 4) = make_float4(a[4], a[5], a[6], a[7]);
    }
    bar_sync(BAR, NT);
    if (tid < 64) {
        float s = 0.f;
        #pragma unroll
        for (int i = 0; i < NT / 32; i++) s += red[i * 64 + tid];
        g_mod[col0 + tid] = bfr(s);
    }
}

__device__ __forceinline__ uint32_t hadd2(uint32_t a, uint32_t b) { uint32_t r; asm("add.rn.bf16x2 %0, %1, %2;" : "=r"(r) : "r"(a), "r"(b)); return r; }
__device__ __forceinline__ uint32_t hsub2(uint32_t a, uint32_t b) { uint32_t r; asm("sub.rn.bf16x2 %0, %1, %2;" : "=r"(r) : "r"(a), "r"(b)); return r; }
__device__ __forceinline__ uint32_t hmul2(uint32_t a, uint32_t b) { uint32_t r; asm("mul.rn.bf16x2 %0, %1, %2;" : "=r"(r) : "r"(a), "r"(b)); return r; }
__device__ __forceinline__ void ln_stats(const uint2* x, uint32_t& mb2, float& rs) {
    float v[5][4];
    float s = 0.f;
    #pragma unroll
    for (int i = 0; i < 5; i++) {
        v[i][0] = bflo(x[i].x); v[i][1] = bfhi(x[i].x); v[i][2] = bflo(x[i].y); v[i][3] = bfhi(x[i].y);
        s += (v[i][0] + v[i][1]) + (v[i][2] + v[i][3]);
    }
    #pragma unroll
    for (int o = 16; o > 0; o >>= 1) s += __shfl_xor_sync(0xffffffffu, s, o);
    const float mean = s * (1.0f / DM);
    float q0 = 0.f, q1 = 0.f;
    #pragma unroll
    for (int i = 0; i < 5; i++) {
        const float d0 = v[i][0] - mean, d1 = v[i][1] - mean, d2 = v[i][2] - mean, d3 = v[i][3] - mean;
        q0 += d0 * d0; q1 += d1 * d1; q0 += d2 * d2; q1 += d3 * d3;
    }
    float q = q0 + q1;
    #pragma unroll
    for (int o = 16; o > 0; o >>= 1) q += __shfl_xor_sync(0xffffffffu, q, o);
    mb2 = pack2(mean, mean);
    const float var = bfr(q * (1.0f / DM));
    rs = __frcp_rn(bfr(__fsqrt_rn(bfr(var + 1e-5f))));
}
__device__ __forceinline__ uint32_t ln_norm(uint32_t x, uint32_t mb2, float rs) {
    const uint32_t d = hsub2(x, mb2);
    return pack2(bflo(d) * rs, bfhi(d) * rs);
}
__device__ __forceinline__ uint32_t ln_apply(uint32_t x, uint32_t mb2, float rs, uint32_t m1, uint32_t sh) {
    return hadd2(hmul2(ln_norm(x, mb2, rs), m1), sh);
}

constexpr int SM_WV = 0;
constexpr int SM_HB = 81920;
constexpr int SM_WO = SM_HB + 40960;
constexpr int SM_QX = SM_WO + 77824;
constexpr int SM_KS = SM_QX + 4096;
constexpr int SM_QM = SM_KS + 5120;
constexpr int SM_XS = SM_QM + 1024;
constexpr int SM_MS = SM_XS + 12288;
constexpr int SM_OS = SM_MS + 3840;
constexpr int SM_PM = SM_OS + 3072;
constexpr int SM_BAR = SM_PM + 640;
constexpr int SM_CH = SM_BAR + 128;
constexpr int SM_TOTAL = SM_CH + 128;
static_assert(SM_TOTAL <= 232448, "smem");

enum { B_MEM_FULL = 0, B_MEM_FREE, B_HLO_FULL, B_HHI_FULL, B_HLO_FREE, B_HHI_FREE, B_MS, B_O, B_XS, B_O1, B_XSFREE, B_WQ, B_P0, B_WV, B_WO, B_P1 };

__device__ __forceinline__ int probe_blk(uint32_t* blk) {
    uint32_t t0 = 0xffffffffu, t1 = 0xffffffffu, acc = 0;
    for (int rep = 0; rep < 3; rep++) {
        #pragma unroll
        for (int pg = 0; pg < 2; pg++) {
            uint32_t c0 = clk32();
            uint32_t v = atomicOr(blk + pg * 1024 + acc, 0u);
            acc = (v == 0x12345678u) ? 1u : 0u;
            asm volatile("" :: "r"(acc) : "memory");
            uint32_t c1 = clk32() + acc;
            uint32_t d = c1 - c0;
            if (rep > 0) { if (pg == 0) t0 = min(t0, d); else t1 = min(t1, d); }
        }
    }
    return t1 < t0 ? 1 : 0;
}

__device__ __forceinline__ uint32_t wo_tile_off(int w) {
    if (w < 8) return w * 6144;
    if (w < 12) return 8 * 6144 + (w - 8) * 4096;
    return 8 * 6144 + 4 * 4096 + (w - 12) * 6144;
}

template <int NRES, int NPRE>
__device__ __forceinline__ void wo_phase(uint32_t sb, int w, int lane, const uint32_t (*res)[4], uint32_t parity,
                                         uint32_t tag, int tile, int h) {
    FRESH(lane);
    const int er = (lane & 7) + 8 * (lane >> 4);
    const uint32_t aaddr = sb + SM_WO + wo_tile_off(w) + er * 32 + ((((lane >> 3) & 1) ^ ((er >> 2) & 1)) << 4);
    const uint32_t baddr = sb + SM_OS + lane * 16;
    float c0[4] = {0.f, 0.f, 0.f, 0.f}, c1[4] = {0.f, 0.f, 0.f, 0.f};
    uint32_t pre[NPRE > 4 ? NPRE : 4][4];
    if (NPRE >= 4) {
        #pragma unroll
        for (int i = 0; i < 4; i++) ldsm4t(pre[i], aaddr + i * 512);
        mbar_wait(sb + SM_BAR + B_O1 * 8, parity);
        uint32_t b[2][4];
        ldsm4t(b[0], baddr);
        ldsm4t(b[1], baddr + 512);
        #pragma unroll
        for (int kp = 0; kp < 2; kp++) {
            mma16(c0, pre[2 * kp][0], pre[2 * kp][1], pre[2 * kp][2], pre[2 * kp][3], b[kp][0], b[kp][1]);
            mma16(c1, pre[2 * kp + 1][0], pre[2 * kp + 1][1], pre[2 * kp + 1][2], pre[2 * kp + 1][3], b[kp][2], b[kp][3]);
        }
    } else {
        #pragma unroll
        for (int i = 0; i < 2; i++) ldsm4t(pre[i], aaddr + i * 512);
        mbar_wait(sb + SM_BAR + B_O1 * 8, parity);
        #pragma unroll
        for (int kp = 0; kp < 2; kp++) {
            uint32_t b[4];
            ldsm4t(b, baddr + kp * 512);
            if (kp == 1) { ldsm4t(pre[0], aaddr + 2 * 512); ldsm4t(pre[1], aaddr + 3 * 512); }
            mma16(c0, pre[0][0], pre[0][1], pre[0][2], pre[0][3], b[0], b[1]);
            mma16(c1, pre[1][0], pre[1][1], pre[1][2], pre[1][3], b[2], b[3]);
        }
    }
    #pragma unroll
    for (int i = 0; i < NPRE; i++) ldsm4t(pre[i], aaddr + (4 + i) * 512);
    uint32_t off0, off1;
    {
        uint32_t ch;
        asm volatile("ld.shared.u16 %0, [%1];" : "=r"(ch) : "r"(sb + SM_CH + 2 * tile) : "memory");
        const int j = h >> 4;
        const uint32_t base = (uint32_t)((tile * 4 + j) * 8192 + (h & 15) * 256 + lane * 8);
        ch >>= j;
        off0 = base + (ch & 1) * 4096;
        off1 = base + 16384 + (ch & 256) * 16;
    }
    mbar_wait(sb + SM_BAR + B_O * 8, parity);
    if (NRES == 4) {
        uint32_t b[4][4];
        #pragma unroll
        for (int i = 0; i < 4; i++) ldsm4t(b[i], baddr + (2 + i) * 512);
        #pragma unroll
        for (int i = 0; i < 2; i++) {
            mma16(c0, res[2 * i][0], res[2 * i][1], res[2 * i][2], res[2 * i][3], b[i][0], b[i][1]);
            mma16(c1, res[2 * i + 1][0], res[2 * i + 1][1], res[2 * i + 1][2], res[2 * i + 1][3], b[i][2], b[i][3]);
        }
        #pragma unroll
        for (int i = 0; i < 2; i++) {
            mma16(c0, pre[2 * i][0], pre[2 * i][1], pre[2 * i][2], pre[2 * i][3], b[2 + i][0], b[2 + i][1]);
            mma16(c1, pre[2 * i + 1][0], pre[2 * i + 1][1], pre[2 * i + 1][2], pre[2 * i + 1][3], b[2 + i][2], b[2 + i][3]);
        }
    } else if (NPRE == 4) {
        uint32_t b[2][4];
        #pragma unroll
        for (int hh = 0; hh < 2; hh++) {
            ldsm4t(b[0], baddr + (2 + 2 * hh) * 512);
            ldsm4t(b[1], baddr + (3 + 2 * hh) * 512);
            if (hh) {
                #pragma unroll
                for (int i = 0; i < 4; i++) ldsm4t(pre[i], aaddr + (8 + i) * 512);
            }
            #pragma unroll
            for (int i = 0; i < 2; i++) {
                mma16(c0, pre[2 * i][0], pre[2 * i][1], pre[2 * i][2], pre[2 * i][3], b[i][0], b[i][1]);
                mma16(c1, pre[2 * i + 1][0], pre[2 * i + 1][1], pre[2 * i + 1][2], pre[2 * i + 1][3], b[i][2], b[i][3]);
            }
        }
    }
    st_relaxed2_off(g_buf1, off0, tagw(c0[0] + c1[0], tag), tagw(c0[1] + c1[1], tag));
    st_relaxed2_off(g_buf1, off1, tagw(c0[2] + c1[2], tag), tagw(c0[3] + c1[3], tag));
}

template <int NT, bool MASK>
__device__ __forceinline__ void softmax_core(float (*sc)[2], int g, int t, uint32_t* pb) {
    const float L2E = 1.4426950408889634f;
    #pragma unroll
    for (int j = 0; j < NT; j++) score2(sc[j][0], sc[j][1]);
    if (MASK) {
        const float NEG = -999292928.0f;
        if (2 * t > g) sc[NT - 1][0] = NEG;
        if (2 * t + 1 > g) sc[NT - 1][1] = NEG;
    }
    float m[NT];
    #pragma unroll
    for (int j = 0; j < NT; j++) m[j] = fmaxf(sc[j][0], sc[j][1]);
    float mx = m[0];
    #pragma unroll
    for (int j = 1; j < NT; j++) mx = fmaxf(mx, m[j]);
    mx = fmaxf(mx, __shfl_xor_sync(0xffffffffu, mx, 1));
    mx = fmaxf(mx, __shfl_xor_sync(0xffffffffu, mx, 2));
    float s0 = 0.f, s1 = 0.f;
    #pragma unroll
    for (int j = 0; j < NT; j++) {
        sc[j][0] = ex2((sc[j][0] - mx) * L2E); sc[j][1] = ex2((sc[j][1] - mx) * L2E);
        s0 += sc[j][0]; s1 += sc[j][1];
    }
    s0 += s1;
    s0 += __shfl_xor_sync(0xffffffffu, s0, 1);
    s0 += __shfl_xor_sync(0xffffffffu, s0, 2);
    const float iv = rcpf(s0);
    #pragma unroll
    for (int j = 0; j < NT; j++) pb[j] = pack2(sc[j][0] * iv, sc[j][1] * iv);
}
template <int NT>
__device__ __forceinline__ void xsoftmax(uint32_t a, int g, int t) {
    float sc[NT][2];
    #pragma unroll
    for (int j = 0; j < NT; j++) {
        float2 v0 = lds2f(a + j * 512), v1 = lds2f(a + j * 512 + 4096), v2 = lds2f(a + j * 512 + 8192);
        sc[j][0] = v0.x + v1.x + v2.x; sc[j][1] = v0.y + v1.y + v2.y;
    }
    uint32_t pb[NT];
    softmax_core<NT, true>(sc, g, t, pb);
    #pragma unroll
    for (int j = 0; j < NT; j += 2) {
        if (j + 1 < NT) asm volatile("st.shared.v2.u32 [%0], {%1,%2};" :: "r"(a + j * 512), "r"(pb[j]), "r"(pb[j + 1]) : "memory");
        else sts1(a + j * 512, pb[j]);
    }
}
template <int NJ>
__device__ __forceinline__ void xscores(uint32_t sb, int p, int mi, int j0, int lane) {
    FRESH(lane);
    const int r = lane & 7, cq = lane >> 3;
    const int qrow = mi * 16 + r + 8 * (cq & 1);
    uint32_t kb[NJ][8];
    float d[NJ][4];
    #pragma unroll
    for (int j = 0; j < NJ; j++) {
        ldsm4(kb[j], sb + SM_KS + ((j0 + j) * 8 + r) * 128 + ((cq ^ r) << 4));
        ldsm4(kb[j] + 4, sb + SM_KS + ((j0 + j) * 8 + r) * 128 + (((cq + 4) ^ r) << 4));
        d[j][0] = 0.f; d[j][1] = 0.f; d[j][2] = 0.f; d[j][3] = 0.f;
    }
    #pragma unroll
    for (int kt = 0; kt < 4; kt++) {
        uint32_t a[4];
        ldsm4(a, sb + SM_QX + qrow * 128 + (((2 * kt + (cq >> 1)) ^ r) << 4));
        #pragma unroll
        for (int j = 0; j < NJ; j++) mma16(d[j], a[0], a[1], a[2], a[3], kb[j][2 * kt], kb[j][2 * kt + 1]);
    }
    const uint32_t la = sb + SM_XS + p * 4096 + (mi * 3 + j0) * 512 + lane * 16;
    #pragma unroll
    for (int rk = 0; rk < 3; rk++) {
        const uint32_t ra = mapa(la, rk), rb = mapa(sb + SM_BAR + B_XS * 8, rk);
        #pragma unroll
        for (int j = 0; j < NJ; j++) st_async4(ra + j * 512, d[j], rb);
    }
}
__device__ __forceinline__ void mbar_arrive_remote(uint32_t bar) {
    asm volatile("mbarrier.arrive.relaxed.cluster.shared::cluster.b64 _, [%0];" :: "r"(bar) : "memory");
}

__device__ __forceinline__ void tma2d(uint32_t dst, const CUtensorMap* map, int c0, int c1, uint32_t bar) {
    asm volatile("cp.async.bulk.tensor.2d.shared::cluster.global.mbarrier::complete_tx::bytes [%0], [%1, {%2, %3}], [%4];"
                 :: "r"(dst), "l"(map), "r"(c0), "r"(c1), "r"(bar) : "memory");
}
__device__ __forceinline__ void tma2d_pf(const CUtensorMap* map, int c0, int c1) {
    asm volatile("cp.async.bulk.prefetch.tensor.2d.L2.global [%0, {%1, %2}];" :: "l"(map), "r"(c0), "r"(c1) : "memory");
}
__device__ __forceinline__ void bulk_pf(const void* p, uint32_t bytes) {
    asm volatile("cp.async.bulk.prefetch.L2.global [%0], %1;" :: "l"(p), "r"(bytes) : "memory");
}
struct RMaps { CUtensorMap wq, wk, wv, wo, wop; };
__device__ __forceinline__ void signal_cnt(int idx) {
    asm volatile("fence.proxy.async.global;\n\tred.release.gpu.global.add.u32 [%0], 1;" :: "l"(g_cnt + idx * 32) : "memory");
}

__device__ __noinline__ void pro_ln(uint32_t sb, const bf16* __restrict__ xin, const bf16* __restrict__ cvec, const bf16* __restrict__ wmod) {
    extern __shared__ __align__(1024) uint8_t smem_raw[];
    const int tid = threadIdx.x, lane = tid & 31, warp = tid >> 5, wg = tid >> 7, b = blockIdx.x;
    const uint32_t bar = sb + SM_BAR;
    {
        const uint32_t tag = *(volatile uint32_t*)&g_epoch + 1u;
        const int seg1 = b + 1, nrow = b < NSEG - 1 ? 64 : 32;
        const bf16* xl = xin + lane * 4;
        const int wv = threadIdx.x >> 5;
        uint4 wm[5];
        float cv[5];
        if (wg < 2 && b < 80) {
            #pragma unroll
            for (int i = 0; i < 5; i++) {
                wm[i] = __ldg((const uint4*)(wmod + (size_t)((tid >> 1) + 128 * i) * (6 * DM) + b * 16 + (tid & 1) * 8));
                cv[i] = __bfloat162float(cvec[(tid >> 1) + 128 * i]);
            }
        }
        uint2 xn[6][5];
        #pragma unroll
        for (int r = 0; r < 6; r++) {
            const int idx = wv + 12 * r, nx = idx < 32 ? idx : (idx < nrow ? b * 32 + idx : 0);
            #pragma unroll
            for (int i = 0; i < 5; i++) xn[r][i] = __ldg((const uint2*)(xl + (size_t)nx * DM + i * 128));
        }
        if (wg < 2 && b < 80) {
            float a[8];
            #pragma unroll
            for (int j = 0; j < 8; j++) a[j] = 0.f;
            #pragma unroll
            for (int i = 0; i < 5; i++) {
                const float sv = bfr(__fdividef(cv[i], 1.0f + __expf(-cv[i])));
                a[0] += sv * bflo(wm[i].x); a[1] += sv * bfhi(wm[i].x); a[2] += sv * bflo(wm[i].y); a[3] += sv * bfhi(wm[i].y);
                a[4] += sv * bflo(wm[i].z); a[5] += sv * bfhi(wm[i].z); a[6] += sv * bflo(wm[i].w); a[7] += sv * bfhi(wm[i].w);
            }
            #pragma unroll 1
            for (int o = 2; o < 32; o <<= 1) {
                #pragma unroll
                for (int j = 0; j < 8; j++) a[j] += __shfl_xor_sync(0xffffffffu, a[j], o);
            }
            if (lane < 2) {
                const uint32_t d = sb + SM_QM + warp * 64 + lane * 32;
                sts4(d, make_uint4(__float_as_uint(a[0]), __float_as_uint(a[1]), __float_as_uint(a[2]), __float_as_uint(a[3])));
                sts4(d + 16, make_uint4(__float_as_uint(a[4]), __float_as_uint(a[5]), __float_as_uint(a[6]), __float_as_uint(a[7])));
            }
            bar_sync(1, 256);
            if (tid < 8) {
                float s0 = 0.f, s1 = 0.f;
                #pragma unroll
                for (int i = 0; i < 8; i++) { const float2 v = lds2f(sb + SM_QM + i * 64 + tid * 8); s0 += v.x; s1 += v.y; }
                st_relaxed2(g_modx + (b * 8 + tid) * 2, pack2(s0, s1), tag);
            }
        }
        __syncwarp();
        #pragma unroll 1
        for (int r = 0; r < 6; r++) {
            uint32_t mb; float rs;
            ln_stats(xn[0], mb, rs);
            #pragma unroll
            for (int i = 0; i < 5; i++) {
                const uint2 nv = make_uint2(ln_norm(xn[0][i].x, mb, rs), ln_norm(xn[0][i].y, mb, rs));
                #pragma unroll
                for (int q = 0; q < 5; q++) xn[q][i] = xn[q + 1][i];
                xn[5][i] = nv;
            }
        }
        T3(12);
        if (tid < 320) {
            uint4 v; uint32_t guard = 0;
            while (true) {
                v = ld_relaxed4(g_modx + tid * 4);
                if (v.y == tag && v.w == tag) break;
                __nanosleep(50);
                if (++guard > (1u << 22)) __trap();
            }
            if (tid >= 160) { v.x = hadd2(v.x, 0x3f803f80u); v.z = hadd2(v.z, 0x3f803f80u); }
            asm volatile("st.shared.v2.u32 [%0], {%1,%2};" :: "r"(sb + SM_KS + tid * 8), "r"(v.x), "r"(v.z) : "memory");
        }
        bar_sync(2, 384);
        T3(13);
        {
            uint2 sh[5], m1[5];
            #pragma unroll
            for (int i = 0; i < 5; i++) { sh[i] = lds2(sb + SM_KS + i * 256 + lane * 8); m1[i] = lds2(sb + SM_KS + 1280 + i * 256 + lane * 8); }
            #pragma unroll 1
            for (int idx = wv; idx < nrow; idx += 12) {
                const int row = idx & 31;
                char* dst = (idx < 32 ? (char*)smem_raw + SM_HB : (char*)g_ht + (size_t)seg1 * 40960)
                            + (lane >> 4) * 4096 + row * 128 + ((((lane >> 1) & 7) ^ (row & 7)) << 4) + (lane & 1) * 8;
                #pragma unroll
                for (int i = 0; i < 5; i++) {
                    *(uint2*)(dst + i * 8192) = make_uint2(hadd2(hmul2(xn[0][i].x, m1[i].x), sh[i].x), hadd2(hmul2(xn[0][i].y, m1[i].y), sh[i].y));
                    #pragma unroll
                    for (int q = 0; q < 5; q++) xn[q][i] = xn[q + 1][i];
                }
            }
            __syncwarp();
        }
        fence_async();
        bar_sync(2, 384);
        T3(7);
        if (tid == 0) { mbar_arrive(bar + B_HLO_FULL * 8); mbar_arrive(bar + B_HHI_FULL * 8); }
        if (tid == 352 && b < NSEG - 1) {
            asm volatile("fence.proxy.async.global;" ::: "memory");
            st_release1(&g_hflag[seg1], tag);
        }
        __syncwarp();
    }
}

__global__ void __launch_bounds__(512, 1)
k_rec(const __grid_constant__ RMaps maps, const bf16* __restrict__ mem0, const bf16* __restrict__ Wo,
      const bf16* __restrict__ xin, const bf16* __restrict__ cvec, const bf16* __restrict__ wmod) {
    extern __shared__ __align__(1024) uint8_t smem_raw[];
    constexpr uint32_t SBC = 1024;
    const uint32_t sb = smem_u32(smem_raw);
    if ((sb & 0xFFFFFFu) != SBC) __trap();
    int lane = __shfl_sync(0xffffffffu, threadIdx.x & 31, threadIdx.x & 31);
    const int warp = __shfl_sync(0xffffffffu, threadIdx.x >> 5, 0), wg = warp >> 2;
    const int tid = warp * 32 + lane;
    const int b = blockIdx.x, h = b / 3, p = b % 3;
    const int g = lane >> 2, t = lane & 3;
    const int tile0 = p == 0 ? 0 : (p == 1 ? 14 : 27);
    const int ntile = p == 0 ? 14 : 13;
    const uint32_t bar = sb + SM_BAR;

    if (tid == 0) T2(100 + b);
    if (tid == 0) {
        mbar_init(bar + B_MEM_FULL * 8, 4);
        mbar_init(bar + B_MEM_FREE * 8, 12);
        mbar_init(bar + B_HLO_FULL * 8, 1);
        mbar_init(bar + B_HHI_FULL * 8, 1);
        mbar_init(bar + B_HLO_FREE * 8, 12);
        mbar_init(bar + B_HHI_FREE * 8, 12);
        mbar_init(bar + B_MS * 8, 1);
        mbar_init(bar + B_O * 8, 1);
        mbar_init(bar + B_XS * 8, 1);
        mbar_init(bar + B_O1 * 8, 4);
        mbar_init(bar + B_XSFREE * 8, 12);
        mbar_init(bar + B_WQ * 8, 1);
        mbar_init(bar + B_P0 * 8, 1);
        mbar_init(bar + B_P1 * 8, 1);
        mbar_init(bar + B_WV * 8, 1);
        mbar_init(bar + B_WO * 8, 1);
        asm volatile("fence.mbarrier_init.release.cluster;" ::: "memory");
        mbar_expect(bar + B_MS * 8, 3840);
        mbar_expect(bar + B_O * 8, 2048);
        mbar_expect(bar + B_XS * 8, 12288);
    }
    __syncwarp();
    asm volatile("barrier.cluster.arrive.relaxed.aligned;\n\tbarrier.cluster.wait.acquire.aligned;" ::: "memory");
    if (warp == 0) T3(0);

    if (tid == 480) {
        #pragma unroll 1
        for (int i = 0; i < 5; i++) {
            if (i > 0 && i <= NPACE) mbar_wait(bar + B_P0 * 8, (i - 1) & 1);
            if (i <= NPACE) mbar_expect(bar + B_P0 * 8, i == NPACE ? (5 - NPACE) * 16384 : 16384);
            tma2d(sb + SM_WO + i * 16384, &maps.wq, h * DH + p * 64, i * 128, bar + B_P0 * 8);
            if (i > 0 && i <= NPACE) mbar_wait(bar + B_P1 * 8, (i - 1) & 1);
            if (i <= NPACE) mbar_expect(bar + B_P1 * 8, i == NPACE ? (5 - NPACE) * 16384 : 16384);
            tma2d(sb + SM_WV + i * 16384, &maps.wk, h * DH + p * 64, i * 128, bar + B_P1 * 8);
        }
        mbar_wait(bar + B_P0 * 8, NPACE & 1);
        mbar_wait(bar + B_P1 * 8, NPACE & 1);
        mbar_arrive(bar + B_WQ * 8);
        #pragma unroll 1
        for (int i = 0; i < 5; i++) tma2d_pf(&maps.wv, h * DH + p * 64, i * 128);
        tma2d_pf(&maps.wop, tile0 * 16, h * DH);
    }
    __syncwarp();
    if (wg < 3) pro_ln(sb, xin, cvec, wmod);

    if (wg < 2) {
        asm volatile("setmaxnreg.inc.sync.aligned.u32 200;");
        const int w = warp & 3;
        uint32_t wa[40][4];
        {
            mbar_wait(bar + B_WQ * 8, 0);
            if (w == 0) T3(1 + wg);
            const int r = lane & 7;
            const uint32_t wsrc = sb + (wg == 0 ? SM_WO : SM_WV) + (r + ((lane >> 4) << 3)) * 128 + (((2 * w + ((lane >> 3) & 1)) ^ r) << 4);
            #pragma unroll
            for (int kt = 0; kt < 40; kt++) ldsm4t(wa[kt], wsrc + kt * 2048);
            fence_async();
            bar_arrive(10 + wg, 256);
        }

        const uint32_t dstx = sb + (wg == 0 ? SM_QX : SM_KS + 1024);

        for (int s = -1; s < NSEG; s++) {
            const uint32_t par = s & 1;
            FRESH(lane);
            const int g = lane >> 2, t = lane & 3, tid = warp * 32 + lane;
            if (s >= 0) {
                mbar_wait(bar + B_MEM_FULL * 8, par);
                TR(0);
                float c[4][4];
                #pragma unroll
                for (int i = 0; i < 4; i++) { c[i][0] = 0.f; c[i][1] = 0.f; c[i][2] = 0.f; c[i][3] = 0.f; }
                uint32_t maddr = sb + lane * 16;
                asm volatile("" : "+r"(maddr));
                #pragma unroll
                for (int kp = 0; kp < 20; kp++) {
                    uint32_t bb[4];
                    ldsm4t(bb, maddr + (SM_HB + kp * 512));
                    mma16(c[(kp & 1) * 2], wa[2 * kp][0], wa[2 * kp][1], wa[2 * kp][2], wa[2 * kp][3], bb[0], bb[1]);
                    mma16(c[(kp & 1) * 2 + 1], wa[2 * kp + 1][0], wa[2 * kp + 1][1], wa[2 * kp + 1][2], wa[2 * kp + 1][3], bb[2], bb[3]);
                }
                {
                    const int tok = lane & 7, ch = 2 * w + ((lane >> 3) & 1);
                    stsm2t(sb + (wg == 0 ? SM_QM : SM_KS) + tok * 128 + ((ch ^ tok) << 4),
                           pack2((c[0][0] + c[1][0]) + (c[2][0] + c[3][0]), (c[0][1] + c[1][1]) + (c[2][1] + c[3][1])),
                           pack2((c[0][2] + c[1][2]) + (c[2][2] + c[3][2]), (c[0][3] + c[1][3]) + (c[2][3] + c[3][3])));
                }
                __syncwarp();
                if (lane == 0) mbar_arrive(bar + B_MEM_FREE * 8);
                TR(1);
                bar_sync(1, 256);
                if (warp < 5) {
                    const int r = lane & 7, cq = lane >> 3;
                    uint32_t a[8], kb[8];
                    ldsm4(a, sb + SM_QM + r * 128 + ((cq ^ r) << 4));
                    ldsm4(kb, sb + SM_KS + (warp * 8 + r) * 128 + ((cq ^ r) << 4));
                    ldsm4(a + 4, sb + SM_QM + r * 128 + (((cq + 4) ^ r) << 4));
                    ldsm4(kb + 4, sb + SM_KS + (warp * 8 + r) * 128 + (((cq + 4) ^ r) << 4));
                    float d0[4] = {0.f, 0.f, 0.f, 0.f}, d1[4] = {0.f, 0.f, 0.f, 0.f};
                    mma16(d0, a[0], 0u, a[1], 0u, kb[0], kb[1]);
                    mma16(d1, a[2], 0u, a[3], 0u, kb[2], kb[3]);
                    mma16(d0, a[4], 0u, a[5], 0u, kb[4], kb[5]);
                    mma16(d1, a[6], 0u, a[7], 0u, kb[6], kb[7]);
                    const uint32_t la = sb + SM_MS + p * 1280 + warp * 256 + lane * 8;
                    #pragma unroll
                    for (int rk = 0; rk < 3; rk++)
                        st_async2(mapa(la, rk), d0[0] + d1[0], d0[1] + d1[1], mapa(bar + B_MS * 8, rk));
                    bar_arrive(4, 352);
                } else if (warp < 7) {
                    xscores<1>(sb, p, warp - 5, 0, lane);
                    bar_arrive(4, 352);
                }
                TR(2);
                if (s < NSEG - 1) {
                    wo_phase<0, 4>(sb, warp, lane, nullptr, par, (uint32_t)(s % 15) + 1u, tile0 + warp, h);
                    TR(4);
                }
            }
            if (s < NSEG - 1) {
                FRESH(lane);
                const uint32_t hp = (s + 1) & 1;
                float d[16];
                const uint64_t db0 = make_desc(SBC + SM_HB, 16, 1024, 1);
                mbar_wait(bar + B_HHI_FULL * 8, hp);
                if (s < 0 && warp == 0) T3(10);
                {
                    const int r = lane & 7, mq = lane >> 3;
                    const uint32_t ha = sb + SM_HB + 9 * 4096 + (8 * (mq >> 1) + r) * 128 + (((6 + (mq & 1)) ^ r) << 4);
                    uint32_t b0[4], b1[4];
                    ldsm4(b0, ha);
                    ldsm4(b1, ha + 2048);
                    #pragma unroll
                    for (int i = 0; i < 16; i++) d[i] = 0.f;
                    mma16(d + 0, wa[39][0], wa[39][1], wa[39][2], wa[39][3], b0[0], b0[1]);
                    mma16(d + 4, wa[39][0], wa[39][1], wa[39][2], wa[39][3], b0[2], b0[3]);
                    mma16(d + 8, wa[39][0], wa[39][1], wa[39][2], wa[39][3], b1[0], b1[1]);
                    mma16(d + 12, wa[39][0], wa[39][1], wa[39][2], wa[39][3], b1[2], b1[3]);
                    asm volatile("" : "+f"(d[0]), "+f"(d[4]), "+f"(d[8]), "+f"(d[12]) :: "memory");
                }
                if (s >= 0) bar_arrive(6, 512);
                mbar_wait(bar + B_HLO_FULL * 8, hp);
                bar_sync(9, 384);
                TR(6);
                wg_fence();
                #pragma unroll
                for (int kt = 0; kt < 12; kt++) wg_rs32(d, wa[kt], db0 + (uint64_t)(((kt >> 2) * 4096 + (kt & 3) * 32) >> 4), 1);
                wg_commit();
                #pragma unroll
                for (int kt = 12; kt < 39; kt++) wg_rs32(d, wa[kt], db0 + (uint64_t)(((kt >> 2) * 4096 + (kt & 3) * 32) >> 4), 1);
                wg_commit();
                wg_wait<1>();
                if (lane == 0) mbar_arrive(bar + B_HLO_FREE * 8);
                wg_wait<0>();
                if (lane == 0) mbar_arrive(bar + B_HHI_FREE * 8);
                TR(7);
                const int mi = lane >> 3, r = lane & 7;
                #pragma unroll
                for (int jj = 0; jj < 2; jj++) {
                    const int tok = 8 * (2 * jj + (mi >> 1)) + r, ch = 2 * w + (mi & 1);
                    stsm4t(dstx + tok * 128 + ((ch ^ r) << 4),
                           pack2(d[8 * jj + 0], d[8 * jj + 1]), pack2(d[8 * jj + 2], d[8 * jj + 3]),
                           pack2(d[8 * jj + 4], d[8 * jj + 5]), pack2(d[8 * jj + 6], d[8 * jj + 7]));
                }
                bar_arrive(8, 384);
                if (s < 0 && warp == 0) T3(11);
                if (s < 0) { bar_sync(0, 512); asm volatile("griddepcontrol.launch_dependents;" ::: "memory"); }
            }
        }
    } else if (wg == 2) {
        asm volatile("setmaxnreg.dec.sync.aligned.u32 64;");
        const int w = warp & 3;
        uint32_t res[4][4];
        {
            const bf16* src = Wo + ((size_t)h * DH + ((p + 1) % 3) * 64) * DM + (tile0 + warp) * 16 + 2 * t;
            #pragma unroll
            for (int kt = 0; kt < 4; kt++) {
                res[kt][0] = __ldg((const uint32_t*)(src + (size_t)(kt * 16 + g) * DM));
                res[kt][1] = __ldg((const uint32_t*)(src + (size_t)(kt * 16 + g) * DM + 8));
                res[kt][2] = __ldg((const uint32_t*)(src + (size_t)(kt * 16 + 8 + g) * DM));
                res[kt][3] = __ldg((const uint32_t*)(src + (size_t)(kt * 16 + 8 + g) * DM + 8));
            }
            #pragma unroll
            for (int kt = 0; kt < 4; kt++) {
                #pragma unroll
                for (int i = 0; i < 4; i++) res[kt][i] = movm(res[kt][i]);
            }
        }
        bar_sync(11, 256);
        if (tid == 256) {
            fence_async();
            mbar_expect(bar + B_WV * 8, 81920);
            #pragma unroll
            for (int i = 0; i < 5; i++) tma2d(sb + SM_WV + i * 16384, &maps.wv, h * DH + p * 64, i * 128, bar + B_WV * 8);
        }
        mbar_wait(bar + B_WV * 8, 0);
        if (w == 0) T3(3);
        const uint64_t da0 = make_desc(SBC + SM_WV, 16, 1024, 1);
        uint32_t vx[8], vm0 = 0, vm1 = 0;
        #pragma unroll
        for (int i = 0; i < 8; i++) vx[i] = 0;

        for (int s = -1; s < NSEG; s++) {
            FRESH(lane);
            const int g = lane >> 2, t = lane & 3, tid = warp * 32 + lane;
            if (s >= 0) {
                const uint32_t par = s & 1;
                mbar_wait(bar + B_MEM_FULL * 8, par);
                bar_sync(4, 352);
                TR(0);
                float dv[4];
                {
                    const uint64_t dbm = make_desc(SBC + SM_HB, 128, 128, 0);
                    wg_fence();
                    #pragma unroll
                    for (int kt = 0; kt < 40; kt++) {
                        wg_ss8(dv, da0 + (uint64_t)(kt * 128), dbm + (uint64_t)(kt * 16), kt > 0);
                        wg_commit();
                        if (kt < 39) wg_wait<1>();
                    }
                    wg_commit();
                }
                TR(1);
                bar_sync(5, 160);
                TR(2);
                uint32_t pb[5];
                #pragma unroll
                for (int j = 0; j < 5; j++) pb[j] = lds1(sb + SM_PM + j * 128 + lane * 4);
                float o0[4] = {0.f, 0.f, 0.f, 0.f}, o1[4] = {0.f, 0.f, 0.f, 0.f}, o2[4] = {0.f, 0.f, 0.f, 0.f};
                wg_wait<0>();
                TR(3);
                mma16(o0, vx[0], vx[1], vx[2], vx[3], pb[1], pb[2]);
                mma16(o1, vx[4], vx[5], vx[6], vx[7], pb[3], pb[4]);
                vm0 = pack2(dv[0], dv[1]); vm1 = pack2(dv[2], dv[3]);
                mma8(o2, vm0, vm1, pb[0]);
                if (s < NSEG - 1) {
                    const uint32_t q0 = pack2(o0[0] + o1[0] + o2[0], o0[1] + o1[1] + o2[1]), q1 = pack2(o0[2] + o1[2] + o2[2], o0[3] + o1[3] + o2[3]);
                    const uint32_t la = sb + SM_OS + (w * 16 + g) * 16 + t * 4;
                    #pragma unroll
                    for (int i = 1; i < 3; i++) {
                        const uint32_t rk = (p + i) % 3;
                        const uint32_t ra = mapa(la + (3 - i) * 1024, rk), rb = mapa(bar + B_O * 8, rk);
                        st_async1(ra, q0, rb);
                        st_async1(ra + 128, q1, rb);
                    }
                    sts1(la, q0);
                    sts1(la + 128, q1);
                    __syncwarp();
                    if (lane == 0) { mbar_arrive(bar + B_O1 * 8); mbar_arrive(bar + B_MEM_FREE * 8); }
                }
                TR(5);
                if (s < NSEG - 1) {
                    wo_phase<4, 4>(sb, warp, lane, res, par, (uint32_t)(s % 15) + 1u, tile0 + warp, h);
                    TR(4);
                    if (tid == 256) mbar_expect(bar + B_O * 8, 2048);
                }
                if (s < NSEG - 1) bar_sync(6, 512);
            }
            uint32_t vn[8];
            #pragma unroll
            for (int i = 0; i < 8; i++) vn[i] = 0;
            if (s < NSEG - 1) {
            float d[16];
            const uint32_t hp = (s + 1) & 1;
            const uint64_t db0 = make_desc(SBC + SM_HB, 16, 1024, 1);
            mbar_wait(bar + B_HHI_FULL * 8, hp);
            TR(6);
            wg_fence();
            #pragma unroll
            for (int kt = 12; kt < 40; kt++) wg_ss32(d, da0 + (uint64_t)(kt * 128), db0 + (uint64_t)(((kt >> 2) * 4096 + (kt & 3) * 32) >> 4), kt > 12);
            wg_commit();
            mbar_wait(bar + B_HLO_FULL * 8, hp);
            wg_fence();
            #pragma unroll
            for (int kt = 0; kt < 9; kt++) wg_ss32(d, da0 + (uint64_t)(kt * 128), db0 + (uint64_t)(((kt >> 2) * 4096 + (kt & 3) * 32) >> 4), 1);
            wg_commit();
            #pragma unroll
            for (int kt = 9; kt < 12; kt++) wg_ss32(d, da0 + (uint64_t)(kt * 128), db0 + (uint64_t)(((kt >> 2) * 4096 + (kt & 3) * 32) >> 4), 1);
            wg_commit();
            wg_wait<1>();
            bar_arrive(9, 384);
            wg_wait<0>();
            if (lane == 0) mbar_arrive(bar + B_HLO_FREE * 8);
            TR(7);
            if (lane == 0) mbar_arrive(bar + B_HHI_FREE * 8);
            #pragma unroll
            for (int i = 0; i < 8; i++) vn[i] = pack2(d[2 * i], d[2 * i + 1]);
            }
            if (s >= 0) {
                {
                    FRESH(lane);
                    mbar_wait(bar + B_XS * 8, s & 1);
                    if (w == 0 && lane == 0) mbar_expect(bar + B_XS * 8, 12288);
                    const uint32_t a = sb + SM_XS + (w >> 1) * 1536 + lane * 16 + (w & 1) * 8;
                    if (w == 0) xsoftmax<2>(a, lane >> 2, lane & 3);
                    else if (w == 1) xsoftmax<3>(a, lane >> 2, lane & 3);
                    else if (w == 2) xsoftmax<4>(a, lane >> 2, lane & 3);
                    else xsoftmax<5>(a, lane >> 2, lane & 3);
                }
                TR(8);
                bar_sync(7, 128);
                FRESH(lane);
                bf16* orow = g_ox + (size_t)(s * 32 + (lane >> 2)) * HD + h * DH + p * 64 + w * 16 + 2 * (lane & 3);
                {
                    const uint32_t pa = sb + SM_XS + lane * 16;
                    #pragma unroll
                    for (int mi = 0; mi < 2; mi++) {
                        float oa[4] = {0.f, 0.f, 0.f, 0.f}, ob[4] = {0.f, 0.f, 0.f, 0.f};
                        if (mi == 0) {
                            const uint4 p0 = lds4(pa);
                            const uint32_t p3 = lds1(pa + 1024 + 8);
                            mma8(oa, vm0, vm1, p0.x);
                            mma8(ob, vm0, vm1, p0.z);
                            mma16(oa, vx[0], vx[1], vx[2], vx[3], p0.y, 0u);
                            mma16(ob, vx[0], vx[1], vx[2], vx[3], p0.w, p3);
                        } else {
                            const uint4 p1 = lds4(pa + 1536), p2 = lds4(pa + 2560);
                            const uint32_t p4 = lds1(pa + 3584 + 8);
                            mma8(oa, vm0, vm1, p1.x);
                            mma8(ob, vm0, vm1, p1.z);
                            mma16(oa, vx[0], vx[1], vx[2], vx[3], p1.y, p2.x);
                            mma16(ob, vx[0], vx[1], vx[2], vx[3], p1.w, p2.z);
                            mma16(oa, vx[4], vx[5], vx[6], vx[7], p2.y, 0u);
                            mma16(ob, vx[4], vx[5], vx[6], vx[7], p2.w, p4);
                            if (lane < 3) mbar_arrive_remote(mapa(bar + B_XSFREE * 8, lane));
                        }
                        const uint32_t u0 = movm(pack2(oa[0], oa[1])), u1 = movm(pack2(oa[2], oa[3]));
                        const uint32_t u2 = movm(pack2(ob[0], ob[1])), u3 = movm(pack2(ob[2], ob[3]));
                        bf16* dst = orow + (size_t)(16 * mi) * HD;
                        *(uint32_t*)dst = u0;
                        *(uint32_t*)(dst + 8) = u1;
                        *(uint32_t*)(dst + 8 * HD) = u2;
                        *(uint32_t*)(dst + 8 * HD + 8) = u3;
                    }
                }
                TR(9);
                if (s == NSEG - 1) {
                    bar_sync(7, 128);
                    if (w == 3 && lane == 0) { signal_cnt(C_REC + 15); T2(400 + b); }
                    break;
                }
            }
            #pragma unroll
            for (int i = 0; i < 8; i++) vx[i] = vn[i];
            if (s >= 0) mbar_wait_cluster(bar + B_XSFREE * 8, s & 1);
            bar_sync(8, 384);
            TR(10);
            if (w < 3) xscores<2>(sb, p, w > 0, w == 2 ? 3 : 1, lane);
            else if ((s & 3) == 3 && s >= 0 && lane == 0) signal_cnt(C_REC + (s >> 2));
            __syncwarp();
            TR(11);
            if (s < 0) { bar_sync(0, 512); asm volatile("griddepcontrol.launch_dependents;" ::: "memory"); }
        }
    } else {
        asm volatile("setmaxnreg.dec.sync.aligned.u32 48;");
        const int w = warp & 3, lt = tid & 127;
        const uint32_t epoch = *(volatile uint32_t*)&g_epoch + 1u;
        if (b == 91) { if (lt < C_NUM) g_cnt[lt * 32] = 0u; __threadfence(); }
        if (b < 80) {
            #pragma unroll
            for (int i = 0; i < 2; i++) {
                const int idx = lt + i * 128, sl = idx >> 6, pg = (idx >> 5) & 1, wd = idx & 31;
                st_relaxed1(g_buf2 + (sl * 3 + (b >> 5)) * 2048 + pg * 1024 + (b & 31) * 32 + wd, 0xFFFFFFFFu);
            }
            __threadfence();
        }
        if (lane == 0 && w < 3) {
            int c = 0;
            if (w == 0) c = probe_blk(g_buf2 + 640 + (b & 31) * 8);
            else if (b < 80) c = probe_blk(g_buf1 + (b * 2 + (w - 1)) * 2048);
            else if (b < 92 && w == 1) c = probe_blk(g_buf2 + (b - 80) * 2048 + 960);
            asm volatile("st.shared.u8 [%0], %1;" :: "r"(sb + SM_CH + 96 + w), "r"(c) : "memory");
        }
        if (w == 0) T3(4);
        bar_sync(3, 128);
        uint32_t selmask;
        {
            const uint32_t c3 = lds1(sb + SM_CH + 96);
            const uint32_t cr = c3 & 1u, c1 = (c3 >> 8) & 1u, c2 = (c3 >> 16) & 1u;
            if (lt == 0 && b < 92) st_release1(&g_choice[b], (epoch << 2) | (b < 80 ? (c1 | (c2 << 1)) : (c1 ^ cr)));
            bar_sync(10, 256);
            if (w == 3) {
                if (lane == 0) { fence_async(); mbar_expect(bar + B_WO * 8, ntile * 6144 - 8192); }
                __syncwarp();
                if (lane < ntile) {
                    #pragma unroll
                    for (int e3 = 0; e3 < 3; e3++) {
                        const bool part = lane >= 8 && lane < 12;
                        if (part && e3 == 1) continue;
                        tma2d(sb + SM_WO + wo_tile_off(lane) + ((part && e3 == 2) ? 1 : e3) * 2048, &maps.wo,
                              (tile0 + lane) * 16, h * DH + ((e3 + p) % 3) * 64, bar + B_WO * 8);
                    }
                }
                __syncwarp();
            }
            if (w == 0) T3(5);
            if (lt < 92) {
                uint32_t v, guard = 0;
                while (true) {
                    v = ld_acquire1(&g_choice[lt]);
                    if ((v >> 2) == (epoch & 0x3fffffffu)) break;
                    __nanosleep(100);
                    if (++guard > (1u << 22)) __trap();
                }
                asm volatile("st.shared.u8 [%0], %1;" :: "r"(sb + SM_CH + lt), "r"(v & 3u) : "memory");
            }
            if (w == 0) T3(6);
            bar_sync(3, 128);
            selmask = (c1 << 12) | (c2 << 13);
            for (int i = 0; i < 12; i++) {
                uint32_t c; asm volatile("ld.shared.u8 %0, [%1];" : "=r"(c) : "r"(sb + SM_CH + 80 + i) : "memory");
                selmask |= ((c ^ cr) & 1u) << i;
            }
        }
        mbar_wait(bar + B_WO * 8, 0);
        if (w == 0) T3(8);
        bar_sync(0, 512);
        if (w == 0) T3(9);
        asm volatile("griddepcontrol.launch_dependents;" ::: "memory");
        const bool has_tile = (12 + w) < ntile;
        for (int s = 0; s < NSEG; s++) {
            const uint32_t par = s & 1;
            FRESH(lane);
            const int g = lane >> 2, t = lane & 3, lt = w * 32 + lane;
            if (s == 0) {
                mbar_wait(bar + B_HLO_FREE * 8, par);
                for (int k = lt; k < DM; k += 128) {
                    uint32_t v[4];
                    #pragma unroll
                    for (int i = 0; i < 4; i++) {
                        uint32_t lo = *(const uint16_t*)(mem0 + (2 * i) * DM + k), hi = *(const uint16_t*)(mem0 + (2 * i + 1) * DM + k);
                        v[i] = lo | (hi << 16);
                    }
                    asm volatile("st.shared.v4.u32 [%0], {%1,%2,%3,%4};" :: "r"(sb + SM_HB + k * 16), "r"(v[0]), "r"(v[1]), "r"(v[2]), "r"(v[3]) : "memory");
                }
            } else {
                const int sl = s & 3;
                const char* q = (const char*)g_buf2 + sl * 3 * 8192 + lt * 16;
                const uint32_t sm = selmask >> (sl * 3);
                const char* q0 = q + (sm & 1) * 4096;
                const char* q1 = q + 8192 + (sm & 2) * 2048;
                const char* q2 = q + 16384 + (sm & 4) * 1024;
                const uint32_t dst = sb + SM_HB + lt * 16;
                uint32_t guard = 0;
                mbar_wait(bar + B_HLO_FREE * 8, par);
                TR(10);
                while (true) {
                    const uint4 v0 = ld_relaxed4(q0), v1 = ld_relaxed4(q0 + 2048), v2 = ld_relaxed4(q1), v3 = ld_relaxed4(q1 + 2048), v4 = ld_relaxed4(q2);
                    sts4(dst, v0); sts4(dst + 2048, v1); sts4(dst + 4096, v2); sts4(dst + 6144, v3); sts4(dst + 8192, v4);
                    if (__all_sync(0xffffffffu, oks(v0) && oks(v1) && oks(v2) && oks(v3) && oks(v4))) break;
                    if (++guard > (1u << 22)) __trap();
                }
            }
            fence_async();
            __syncwarp();
            if (lane == 0) mbar_arrive(bar + B_MEM_FULL * 8);
            if (b == 0 && lt == 0) T2(300 + s);
            if (s == 0 && lt == 0) T2(200 + b);
            TR(0);
            if (w == 2) {
                mbar_wait(bar + B_MS * 8, par);
                TR(1);
                if (lane == 0) mbar_expect(bar + B_MS * 8, 3840);
                uint32_t pb[5];
                float sc[5][2];
                {
                    const uint32_t a = sb + SM_MS + lane * 8;
                    float2 u[5], v[5];
                    #pragma unroll
                    for (int j = 0; j < 5; j++) { u[j] = lds2f(a + j * 256); v[j] = lds2f(a + j * 256 + 1280); }
                    #pragma unroll
                    for (int j = 0; j < 5; j++) { sc[j][0] = u[j].x + v[j].x; sc[j][1] = u[j].y + v[j].y; }
                    #pragma unroll
                    for (int j = 0; j < 5; j++) u[j] = lds2f(a + j * 256 + 2560);
                    #pragma unroll
                    for (int j = 0; j < 5; j++) { sc[j][0] += u[j].x; sc[j][1] += u[j].y; }
                }
                softmax_core<5, false>(sc, g, t, pb);
                #pragma unroll
                for (int j = 0; j < 5; j++) sts1(sb + SM_PM + j * 128 + lane * 4, pb[j]);
                bar_arrive(5, 160);
                TR(2);
            }
            const uint32_t tag = (uint32_t)(s % 15) + 1u;
            if (s < NSEG - 1) {
                if (w == 3) {
                    const char* src = (const char*)g_ht + (size_t)(s + 1) * 40960;
                    if (s == 0) {
                        uint32_t guard = 0;
                        while (true) {
                            const uint32_t f0 = lane > 0 ? ld_acquire1(&g_hflag[lane]) : epoch, f1 = ld_acquire1(&g_hflag[32 + lane]);
                            if (__all_sync(0xffffffffu, f0 == epoch && f1 == epoch)) break;
                            if (++guard > (1u << 22)) __trap();
                        }
                        asm volatile("fence.proxy.async.global;" ::: "memory");
                    }
                    mbar_wait(bar + B_HHI_FREE * 8, par);
                    if (lane == 0) {
                        mbar_expect(bar + B_HHI_FULL * 8, 28672);
                        bulk_g2s(sb + SM_HB + 12288, src + 12288, 28672, sb + SM_BAR + B_HHI_FULL * 8);
                    }
                    mbar_wait(bar + B_MEM_FREE * 8, par);
                    if (lane == 0) {
                        mbar_expect(bar + B_HLO_FULL * 8, 12288);
                        bulk_g2s(sb + SM_HB, src, 12288, sb + SM_BAR + B_HLO_FULL * 8);
                    }
                    __syncwarp();
                }
                if (has_tile) wo_phase<0, 4>(sb, warp, lane, nullptr, par, tag, tile0 + warp, h);
                TR(4);
                bar_sync(6, 512);
            }
            if (s < NSEG - 1) {
                { const uint32_t c0 = clk32(); while (clk32() - c0 < H1_DELAY); }
                if (b < 80) {
                    FRESH(lane);
                    const char* rin0 = (const char*)g_buf1 + (size_t)(b * 2) * 8192 + ((selmask >> 12) & 1) * 4096 + (lane >> 2) * 256 + w * 64 + (lane & 3) * 16;
                    const char* rin1 = (const char*)g_buf1 + (size_t)(b * 2 + 1) * 8192 + ((selmask >> 13) & 1) * 4096 + (lane >> 2) * 256 + w * 64 + (lane & 3) * 16;
                    const int col = b * 8 + 2 * w + ((lane >> 1) & 1), wd = 2 * (lane & 1) + (lane >> 4);
                    const int sl = (lane & 8) ? ((s + 3) & 3) : ((s + 1) & 3);
                    uint32_t* dst = g_buf2 + (sl * 3 + (col >> 8)) * 2048 + ((lane >> 2) & 1) * 1024 + (col & 255) * 4 + wd;
                    asm volatile("" : "+l"(dst));
                    uint4 v0, v1, v2, v3;
                    uint32_t guard = 0;
                    while (true) {
                        v0 = ld_relaxed4(rin0); v1 = ld_relaxed4(rin0 + 2048);
                        v2 = ld_relaxed4(rin1); v3 = ld_relaxed4(rin1 + 2048);
                        if (__all_sync(0xffffffffu, ok4(v0, tag) && ok4(v1, tag) && ok4(v2, tag) && ok4(v3, tag))) break;
                        if (++guard > (1u << 22)) __trap();
                    }
                    TR(11);
                    const float a0 = (uf(v0.x) + uf(v1.x)) + (uf(v2.x) + uf(v3.x)), a1 = (uf(v0.y) + uf(v1.y)) + (uf(v2.y) + uf(v3.y));
                    const float a2 = (uf(v0.z) + uf(v1.z)) + (uf(v2.z) + uf(v3.z)), a3 = (uf(v0.w) + uf(v1.w)) + (uf(v2.w) + uf(v3.w));
                    const bool u16 = lane & 16;
                    float m0 = (u16 ? a2 : a0) + __shfl_xor_sync(0xffffffffu, u16 ? a0 : a2, 16);
                    float m1 = (u16 ? a3 : a1) + __shfl_xor_sync(0xffffffffu, u16 ? a1 : a3, 16);
                    m0 += __shfl_xor_sync(0xffffffffu, m0, 8); m1 += __shfl_xor_sync(0xffffffffu, m1, 8);
                    m0 += __shfl_xor_sync(0xffffffffu, m0, 4); m1 += __shfl_xor_sync(0xffffffffu, m1, 4);
                    st_relaxed1(dst, (lane & 8) ? 0xFFFFFFFFu : pack2(m0, m1));
                    TR(12);
                }
            }
        }
    }
    cluster_sync();
}

constexpr int G_STAGES = 6;
constexpr int G_STAGE_BYTES = 32768;
constexpr int G_SMEM = G_STAGES * G_STAGE_BYTES + 1024 + 256 + 2048 + 10240;

__device__ __forceinline__ void wg_ss128(float* d, uint64_t da, uint64_t db, int sc) {
    asm volatile("{\n\t.reg .pred p;\n\tsetp.ne.b32 p, %66, 0;\n\t"
        "wgmma.mma_async.sync.aligned.m64n128k16.f32.bf16.bf16 "
        "{%0,%1,%2,%3,%4,%5,%6,%7,%8,%9,%10,%11,%12,%13,%14,%15,%16,%17,%18,%19,%20,%21,%22,%23,%24,%25,%26,%27,%28,%29,%30,%31,"
        "%32,%33,%34,%35,%36,%37,%38,%39,%40,%41,%42,%43,%44,%45,%46,%47,%48,%49,%50,%51,%52,%53,%54,%55,%56,%57,%58,%59,%60,%61,%62,%63}, "
        "%64, %65, p, 1, 1, 0, 1;\n\t}"
        : "+f"(d[0]), "+f"(d[1]), "+f"(d[2]), "+f"(d[3]), "+f"(d[4]), "+f"(d[5]), "+f"(d[6]), "+f"(d[7]),
          "+f"(d[8]), "+f"(d[9]), "+f"(d[10]), "+f"(d[11]), "+f"(d[12]), "+f"(d[13]), "+f"(d[14]), "+f"(d[15]),
          "+f"(d[16]), "+f"(d[17]), "+f"(d[18]), "+f"(d[19]), "+f"(d[20]), "+f"(d[21]), "+f"(d[22]), "+f"(d[23]),
          "+f"(d[24]), "+f"(d[25]), "+f"(d[26]), "+f"(d[27]), "+f"(d[28]), "+f"(d[29]), "+f"(d[30]), "+f"(d[31]),
          "+f"(d[32]), "+f"(d[33]), "+f"(d[34]), "+f"(d[35]), "+f"(d[36]), "+f"(d[37]), "+f"(d[38]), "+f"(d[39]),
          "+f"(d[40]), "+f"(d[41]), "+f"(d[42]), "+f"(d[43]), "+f"(d[44]), "+f"(d[45]), "+f"(d[46]), "+f"(d[47]),
          "+f"(d[48]), "+f"(d[49]), "+f"(d[50]), "+f"(d[51]), "+f"(d[52]), "+f"(d[53]), "+f"(d[54]), "+f"(d[55]),
          "+f"(d[56]), "+f"(d[57]), "+f"(d[58]), "+f"(d[59]), "+f"(d[60]), "+f"(d[61]), "+f"(d[62]), "+f"(d[63])
        : "l"(da), "l"(db), "r"(sc));
}

#define SP0_LAST 12
#define SP2_LAST 6
enum { J_MOD = 0, J_G0, J_LN, J_G1, J_G2, J_FIN, J_END };
__host__ __device__ constexpr int sp0(int b) { return b >= 15 ? SP0_LAST : 3; }
__host__ __device__ constexpr int sp2(int b) { return b >= 15 ? SP2_LAST : 3; }
__host__ __device__ constexpr int njr(int b) { return b >= 15 ? 16 : 8; }
struct JobTab { uint32_t n; uint32_t j[1200]; };
constexpr uint32_t mkjob(int ty, int b, int n, int k0, int nk, int ks) {
    return (uint32_t)(ty | (b << 3) | (n << 7) | (k0 << 11) | (nk << 18) | (ks << 25));
}
constexpr void add_jobs(JobTab& t, int ty, int b) {
    if (b < 0) return;
    if (ty == J_G0) { for (int ks = 0; ks < sp0(b); ks++) for (int n = 0; n < 5; n++) t.j[t.n++] = mkjob(ty, b, n, ks * (96 / sp0(b)), 96 / sp0(b), ks); }
    else if (ty == J_G2) { for (int ks = 0; ks < sp2(b); ks++) for (int n = 0; n < 5; n++) t.j[t.n++] = mkjob(ty, b, n, ks * (24 / sp2(b)), 24 / sp2(b), ks); }
    else if (ty == J_G1) { for (int n = 0; n < 12; n++) t.j[t.n++] = mkjob(ty, b, n, 0, 10, 0); }
    else { for (int n = 0; n < njr(b); n++) t.j[t.n++] = mkjob(ty, b, n, 0, 16 / njr(b), ty == J_LN ? sp0(b) : sp2(b)); }
}
constexpr JobTab make_tab() {
    JobTab t = {};
    for (int i = 20; i < 60; i++) t.j[t.n++] = mkjob(J_MOD, 0, 0, i, 0, 0);
    for (int b = 0; b < 15; b++) {
        add_jobs(t, J_G0, b); add_jobs(t, J_G1, b - 1); add_jobs(t, J_FIN, b - 2); add_jobs(t, J_G2, b - 1); add_jobs(t, J_LN, b);
    }
    add_jobs(t, J_FIN, 13); add_jobs(t, J_G1, 14);
    add_jobs(t, J_G0, 15); add_jobs(t, J_G2, 14); add_jobs(t, J_LN, 15); add_jobs(t, J_FIN, 14);
    add_jobs(t, J_G1, 15); add_jobs(t, J_G2, 15); add_jobs(t, J_FIN, 15);
    return t;
}
__constant__ JobTab c_jobs = make_tab();

__device__ __forceinline__ bool cnt_ge(int idx, uint32_t target) { return ld_acquire1(g_cnt + idx * 32) >= target; }
__device__ __forceinline__ void cnt_wait(int idx, uint32_t target) {
    uint32_t guard = 0;
    while (!cnt_ge(idx, target)) { __nanosleep(64); if (++guard > (1u << 22)) __trap(); }
}

struct SMaps { CUtensorMap ox, wo, h2, w1, act, w2; };

__global__ void __launch_bounds__(384, 1)
k_side(const __grid_constant__ SMaps maps, const bf16* __restrict__ xin, const bf16* __restrict__ cvec,
       const bf16* __restrict__ wmod, bf16* __restrict__ outp) {
    extern __shared__ uint8_t smem_raw[];
    const uint32_t sb = (smem_u32(smem_raw) + 1023u) & ~1023u;
    const uint32_t bars = sb + G_STAGES * G_STAGE_BYTES;
    float* red = (float*)(smem_raw + (bars + 256 - smem_u32(smem_raw)));
    const int tid = threadIdx.x, lane = tid & 31, wg = tid >> 7;
    if (tid == 0) T2(500 + blockIdx.x);
    if (tid == 0) {
        for (int i = 0; i < G_STAGES; i++) { mbar_init(bars + i * 8, 1); mbar_init(bars + 64 + i * 8, 8); }
        for (int i = 0; i < 2; i++) { mbar_init(bars + 128 + i * 8, 1); mbar_init(bars + 144 + i * 8, 8); }
        asm volatile("fence.mbarrier_init.release.cluster;" ::: "memory");
    }
    __syncthreads();
    if (wg == 0) {
        if (tid == 0) {
            uint32_t st = 0, ph = 1;
            for (uint32_t it = 0;; it++) {
                const uint32_t ji = atomicAdd(g_cnt + C_Q * 32, 1u);
                const uint32_t job = ji < c_jobs.n ? c_jobs.j[ji] : (uint32_t)J_END;
                if (ji == 0) g_epoch = g_epoch + 1u;
                const int ty = job & 7, b = (job >> 3) & 15, n = (job >> 7) & 15, k0 = (job >> 11) & 127, nk = (job >> 18) & 127;
                const uint32_t sl = it & 1;
                mbar_wait(bars + 144 + sl * 8, ((it >> 1) & 1) ^ 1);
                sts1(bars + 160 + sl * 4, job);
                if (ty == J_G0 || ty == J_G1 || ty == J_G2) {
                    if (b >= PRING && ty != J_G1) cnt_wait((ty == J_G0 ? C_LN : C_FIN) + b - PRING, njr(b - PRING));
                    mbar_arrive(bars + 128 + sl * 8);
                    const CUtensorMap* mA = ty == J_G0 ? &maps.ox : (ty == J_G1 ? &maps.h2 : &maps.act);
                    const CUtensorMap* mB = ty == J_G0 ? &maps.wo : (ty == J_G1 ? &maps.w1 : &maps.w2);
                    const int didx = ty == J_G0 ? C_REC + b : (ty == J_G1 ? C_LN + b : C_G1 + b);
                    const uint32_t dtgt = ty == J_G0 ? 96u : (ty == J_G1 ? (uint32_t)njr(b) : 12u);
                    int pre = 0;
                    if (!cnt_ge(didx, dtgt)) {
                        pre = nk < G_STAGES ? nk : G_STAGES;
                        uint32_t s2 = st, p2 = ph;
                        for (int i = 0; i < pre; i++) {
                            mbar_wait(bars + 64 + s2 * 8, p2);
                            const uint32_t a = sb + s2 * G_STAGE_BYTES;
                            mbar_expect(bars + s2 * 8, G_STAGE_BYTES);
                            tma2d(a + 16384, mB, n * 128, (k0 + i) * 64, bars + s2 * 8);
                            tma2d(a + 16384 + 8192, mB, n * 128 + 64, (k0 + i) * 64, bars + s2 * 8);
                            if (++s2 == G_STAGES) { s2 = 0; p2 ^= 1; }
                        }
                        cnt_wait(didx, dtgt);
                    }
                    asm volatile("fence.proxy.async.global;" ::: "memory");
                    T2(1024 + ji * 4 + 1);
                    for (int i = 0; i < nk; i++) {
                        const uint32_t a = sb + st * G_STAGE_BYTES;
                        if (i >= pre) {
                            mbar_wait(bars + 64 + st * 8, ph);
                            mbar_expect(bars + st * 8, G_STAGE_BYTES);
                        }
                        tma2d(a, mA, (k0 + i) * 64, b * 128, bars + st * 8);
                        if (i >= pre) {
                            tma2d(a + 16384, mB, n * 128, (k0 + i) * 64, bars + st * 8);
                            tma2d(a + 16384 + 8192, mB, n * 128 + 64, (k0 + i) * 64, bars + st * 8);
                        }
                        if (++st == G_STAGES) { st = 0; ph ^= 1; }
                    }
                } else {
                    if (ty == J_LN) { bulk_pf(xin + (size_t)(b * 128 + n * nk * 8) * DM, nk * 8 * DM * 2); cnt_wait(C_MOD, 40u); cnt_wait(C_G0 + b, 5u * sp0(b)); }
                    else if (ty == J_FIN) cnt_wait(C_G2 + b, 5u * sp2(b));
                    if (ji < 1200) T2(1024 + ji * 4 + 1);
                    mbar_arrive(bars + 128 + sl * 8);
                    if (ty == J_END) break;
                }
            }
        }
    } else {
        const int cw = wg - 1, ct = tid - 128, cwarp = ct >> 5;
        uint32_t st = 0, ph = 0;
        uint2* smod = (uint2*)(red + 512);
        bool have_mod = false;
        auto load_mod = [&]() {
            for (int i = ct; i < DM; i += 256) {
                const float4 m = __ldcg((const float4*)(g_mod + 2 * DM + i * 4));
                const float o = (i >= 320 && i < 480) ? 1.0f : 0.0f;
                smod[i] = make_uint2(pack2(m.x + o, m.y + o), pack2(m.z + o, m.w + o));
            }
            bar_sync(1, 256);
            have_mod = true;
        };
        {
            if (ct == 0) red[0] = cnt_ge(C_MOD, 40u) ? 1.0f : 0.0f;
            bar_sync(1, 256);
            const bool rdy = red[0] != 0.0f;
            bar_sync(1, 256);
            if (rdy) load_mod();
        }
        for (uint32_t it = 0;; it++) {
            const uint32_t sl = it & 1;
            mbar_wait(bars + 128 + sl * 8, (it >> 1) & 1);
            const uint32_t job = lds1(bars + 160 + sl * 4);
            __syncwarp();
            if (lane == 0) mbar_arrive(bars + 144 + sl * 8);
            const int ty = job & 7, b = (job >> 3) & 15, n = (job >> 7) & 15, k0 = (job >> 11) & 127, nk = (job >> 18) & 127, ks = (job >> 25) & 15;
            if (ty == J_END) break;
            int sig = -1;
            if (ty == J_G0 || ty == J_G1 || ty == J_G2) {
                float d[64];
                #pragma unroll
                for (int i = 0; i < 64; i++) d[i] = 0.f;
                uint32_t pst = 0;
                for (int kb = 0; kb < nk; kb++) {
                    mbar_wait(bars + st * 8, ph);
                    const uint32_t a = sb + st * G_STAGE_BYTES;
                    const uint64_t da = make_desc(a + cw * 8192, 16, 1024, 1);
                    const uint64_t db = make_desc(a + 16384, 8192, 1024, 1);
                    wg_fence();
                    #pragma unroll
                    for (int k = 0; k < 4; k++) wg_ss128(d, da + (uint64_t)(k * 2), db + (uint64_t)(k * 128), 1);
                    wg_commit();
                    if (kb > 0) {
                        wg_wait<1>();
                        if (lane == 0) mbar_arrive(bars + 64 + pst * 8);
                    }
                    pst = st;
                    if (++st == G_STAGES) { st = 0; ph ^= 1; }
                }
                wg_wait<0>();
                if (lane == 0) mbar_arrive(bars + 64 + pst * 8);
                const int g = lane >> 2, t = lane & 3;
                if (ty == J_G1) {
                    #pragma unroll
                    for (int hf = 0; hf < 2; hf++) {
                        bf16* o = g_act + (size_t)(b * 128 + cwarp * 16 + g + 8 * hf) * FF + n * 128 + 8 * t;
                        #pragma unroll
                        for (int q = 0; q < 4; q++) {
                            uint32_t u[4];
                            #pragma unroll
                            for (int i = 0; i < 4; i++) {
                                const float a0 = bfr(d[4 * (4 * q + i) + 2 * hf]), a1 = bfr(d[4 * (4 * q + i) + 2 * hf + 1]);
                                u[i] = pack2(__fdividef(a0, 1.0f + __expf(-a0)), __fdividef(a1, 1.0f + __expf(-a1)));
                            }
                            const bool o1 = t & 1, o2 = t & 2;
                            uint32_t x0 = __shfl_xor_sync(0xffffffffu, o1 ? u[0] : u[1], 1), x1 = __shfl_xor_sync(0xffffffffu, o1 ? u[2] : u[3], 1);
                            if (o1) { u[0] = x0; u[2] = x1; } else { u[1] = x0; u[3] = x1; }
                            x0 = __shfl_xor_sync(0xffffffffu, o2 ? u[0] : u[2], 2); x1 = __shfl_xor_sync(0xffffffffu, o2 ? u[1] : u[3], 2);
                            if (o2) { u[0] = x0; u[1] = x1; } else { u[2] = x0; u[3] = x1; }
                            *(uint4*)(o + q * 32) = make_uint4(u[0], u[1], u[2], u[3]);
                        }
                    }
                    sig = C_G1 + b;
                } else {
                    float* o = (ty == J_G0 ? g_p0 : g_p2) + ((size_t)((b % PRING) * PMAX + ks) * 128 + cwarp * 16 + g) * DM + n * 128 + 2 * t;
                    #pragma unroll
                    for (int hf = 0; hf < 2; hf++) {
                        #pragma unroll
                        for (int j = 0; j < 16; j++)
                            *(float2*)(o + hf * 8 * DM + j * 8) = make_float2(d[4 * j + 2 * hf], d[4 * j + 2 * hf + 1]);
                    }
                    sig = (ty == J_G0 ? C_G0 : C_G2) + b;
                }
            } else if (ty == J_MOD) {
                mod_chunk<256, 2>(cvec, wmod, k0 * 64, ct, red);
                sig = C_MOD;
            } else {
                const bool ln = ty == J_LN;
                if (!have_mod) load_mod();
                const uint2* gm = smod + (ln ? 0 : 480) + lane;
                for (int r = 0; r < nk; r++) {
                    const int lr = (n * nk + r) * 8 + cwarp, row = b * 128 + lr;
                    const float* pp = (ln ? g_p0 : g_p2) + ((size_t)((b % PRING) * PMAX) * 128 + lr) * DM + lane * 4;
                    const bf16* xs = (ln ? xin : (const bf16*)g_x1) + (size_t)row * DM + lane * 4;
                    float v[5][4];
                    uint2 xv[5];
                    #pragma unroll
                    for (int i = 0; i < 5; i++) {
                        xv[i] = __ldcg((const uint2*)(xs + i * 128));
                        v[i][0] = 0.f; v[i][1] = 0.f; v[i][2] = 0.f; v[i][3] = 0.f;
                    }
                    if (ks == 3) {
                        float4 a[3][5];
                        #pragma unroll
                        for (int q = 0; q < 3; q++) {
                            #pragma unroll
                            for (int i = 0; i < 5; i++) a[q][i] = __ldcg((const float4*)(pp + (size_t)q * 128 * DM + i * 128));
                        }
                        #pragma unroll
                        for (int q = 0; q < 3; q++) {
                            #pragma unroll
                            for (int i = 0; i < 5; i++) { v[i][0] += a[q][i].x; v[i][1] += a[q][i].y; v[i][2] += a[q][i].z; v[i][3] += a[q][i].w; }
                        }
                    } else {
                        for (int q0 = 0; q0 < ks; q0 += 6) {
                            float4 a[6][5];
                            #pragma unroll
                            for (int q = 0; q < 6; q++) {
                                #pragma unroll
                                for (int i = 0; i < 5; i++) a[q][i] = __ldcg((const float4*)(pp + (size_t)(q0 + q) * 128 * DM + i * 128));
                            }
                            #pragma unroll
                            for (int q = 0; q < 6; q++) {
                                #pragma unroll
                                for (int i = 0; i < 5; i++) { v[i][0] += a[q][i].x; v[i][1] += a[q][i].y; v[i][2] += a[q][i].z; v[i][3] += a[q][i].w; }
                            }
                        }
                    }
                    bf16* dst = (ln ? (bf16*)g_x1 : outp) + (size_t)row * DM + lane * 4;
                    #pragma unroll
                    for (int i = 0; i < 5; i++) {
                        const uint2 gg = gm[i * 32];
                        xv[i].x = hadd2(xv[i].x, hmul2(gg.x, pack2(v[i][0], v[i][1])));
                        xv[i].y = hadd2(xv[i].y, hmul2(gg.y, pack2(v[i][2], v[i][3])));
                        *(uint2*)(dst + i * 128) = xv[i];
                    }
                    if (ln) {
                        uint32_t mb; float rs;
                        ln_stats(xv, mb, rs);
                        #pragma unroll
                        for (int i = 0; i < 5; i++) {
                            const uint2 sh = gm[160 + i * 32], m1 = gm[320 + i * 32];
                            *(uint2*)(g_h2 + (size_t)row * DM + lane * 4 + i * 128) =
                                make_uint2(ln_apply(xv[i].x, mb, rs, m1.x, sh.x), ln_apply(xv[i].y, mb, rs, m1.y, sh.y));
                        }
                    }
                }
                if (ln) sig = C_LN + b; else if (b < 16 - PRING) sig = C_FIN + b;
            }
            if (sig >= 0) {
                bar_sync(1, 256);
                if (ct == 0) signal_cnt(sig);
            }
            if (ct == 0) T2(1024 + ji * 4 + 2);
        }
    }
}

typedef CUresult (*EncodeFn)(CUtensorMap*, CUtensorMapDataType, cuuint32_t, void*, const cuuint64_t*, const cuuint64_t*,
                             const cuuint32_t*, const cuuint32_t*, CUtensorMapInterleave, CUtensorMapSwizzle,
                             CUtensorMapL2promotion, CUtensorMapFloatOOBfill);

static void make_map(EncodeFn fn, CUtensorMap* m, const void* ptr, uint64_t inner, uint64_t outer, uint32_t bi, uint32_t bo,
                     CUtensorMapSwizzle sw = CU_TENSOR_MAP_SWIZZLE_128B) {
    cuuint64_t dims[2] = {inner, outer};
    cuuint64_t strides[1] = {inner * 2};
    cuuint32_t box[2] = {bi, bo};
    cuuint32_t es[2] = {1, 1};
    fn(m, CU_TENSOR_MAP_DATA_TYPE_BFLOAT16, 2, (void*)ptr, dims, strides, box, es, CU_TENSOR_MAP_INTERLEAVE_NONE,
       sw, CU_TENSOR_MAP_L2_PROMOTION_L2_256B, CU_TENSOR_MAP_FLOAT_OOB_FILL_NONE);
}

extern "C" void kernel_launch(void* const* d_in, const int* in_sizes, int n_in, void* d_out, int out_size) {
    const bf16* x = (const bf16*)d_in[0];
    const bf16* mem0 = (const bf16*)d_in[1];
    const bf16* Wq = (const bf16*)d_in[2];
    const bf16* Wk = (const bf16*)d_in[3];
    const bf16* Wv = (const bf16*)d_in[4];
    const bf16* Wo = (const bf16*)d_in[5];
    const bf16* w1 = (const bf16*)d_in[8];
    const bf16* w2 = (const bf16*)d_in[9];
    const bf16* c = (const bf16*)d_in[10];
    const bf16* wmod = (const bf16*)d_in[11];
    bf16* out = (bf16*)d_out;

    static EncodeFn enc = nullptr;
    static void *p_ox, *p_x1, *p_h2, *p_act;
    if (!enc) {
        cudaDriverEntryPointQueryResult qr;
        void* f = nullptr;
        cudaGetDriverEntryPoint("cuTensorMapEncodeTiled", &f, cudaEnableDefault, &qr);
        enc = (EncodeFn)f;
        cudaGetSymbolAddress(&p_ox, g_ox);
        cudaGetSymbolAddress(&p_x1, g_x1);
        cudaGetSymbolAddress(&p_h2, g_h2);
        cudaGetSymbolAddress(&p_act, g_act);
        cudaFuncSetAttribute(k_rec, cudaFuncAttributeMaxDynamicSharedMemorySize, SM_TOTAL);
        cudaFuncSetAttribute(k_side, cudaFuncAttributeMaxDynamicSharedMemorySize, G_SMEM);
    }
    RMaps rm;
    make_map(enc, &rm.wq, Wq, HD, DM, 64, 128);
    make_map(enc, &rm.wk, Wk, HD, DM, 64, 128);
    make_map(enc, &rm.wv, Wv, HD, DM, 64, 128);
    make_map(enc, &rm.wo, Wo, DM, HD, 16, 64, CU_TENSOR_MAP_SWIZZLE_32B);
    make_map(enc, &rm.wop, Wo, DM, HD, 224, 192, CU_TENSOR_MAP_SWIZZLE_NONE);
    SMaps m;
    make_map(enc, &m.ox, p_ox, HD, SEQ, 64, 128);
    make_map(enc, &m.wo, Wo, DM, HD, 64, 64);
    make_map(enc, &m.h2, p_h2, DM, SEQ, 64, 128);
    make_map(enc, &m.w1, w1, FF, DM, 64, 64);
    make_map(enc, &m.act, p_act, FF, SEQ, 64, 128);
    make_map(enc, &m.w2, w2, DM, FF, 64, 64);

    cudaStream_t st = cudaStreamPerThread;
    {
        cudaLaunchConfig_t cfg = {};
        cfg.gridDim = dim3(96); cfg.blockDim = dim3(512); cfg.dynamicSmemBytes = SM_TOTAL; cfg.stream = st;
        cudaLaunchAttribute at[2];
        at[0].id = cudaLaunchAttributeClusterDimension;
        at[0].val.clusterDim.x = 3; at[0].val.clusterDim.y = 1; at[0].val.clusterDim.z = 1;
        cfg.attrs = at; cfg.numAttrs = 1;
        cudaLaunchKernelEx(&cfg, k_rec, rm, mem0, Wo, x, c, wmod);
    }
    {
        cudaLaunchConfig_t cfg = {};
        cfg.gridDim = dim3(SIDE_CTAS); cfg.blockDim = dim3(384); cfg.dynamicSmemBytes = G_SMEM; cfg.stream = st;
        cudaLaunchAttribute at[1];
        at[0].id = cudaLaunchAttributeProgrammaticStreamSerialization;
        at[0].val.programmaticStreamSerializationAllowed = 1;
        cfg.attrs = at; cfg.numAttrs = 1;
        cudaLaunchKernelEx(&cfg, k_side, m, x, c, wmod, out);
    }
}
```

```cpp
#include <cuda_runtime.h>
#include <cuda_bf16.h>
#include <cuda.h>
#include <stdint.h>

typedef __nv_bfloat16 bf16;
#define VX_THROTTLE 1
#define H1_DELAY 470
#define H1_BACK 0
#define VM_THROTTLE 1
#define PRE_TRIG 0
#define NPACE 4
#define PF_LATE 1
#define SEL1 1
#define SEL2 1
#define H2_DELAY 0
#define H2_EARLY 0
#define V_FIRST 16
#define V_AHEAD 16
#define SIDE_CTAS 132

constexpr int SEQ = 2048, DM = 640, NH = 32, DH = 192, NSEG = 64, FF = 1536, HD = NH * DH;

__device__ __align__(128) float g_mod[6 * DM];
__device__ __align__(1024) bf16 g_ht[(size_t)SEQ * DM];
__device__ __align__(1024) bf16 g_ox[(size_t)SEQ * HD];
__device__ __align__(1024) bf16 g_x1[(size_t)SEQ * DM];
__device__ __align__(1024) bf16 g_h2[(size_t)SEQ * DM];
__device__ __align__(1024) bf16 g_act[(size_t)SEQ * FF];
__device__ __align__(8192) uint32_t g_buf1[80 * 2 * 2048];
__device__ __align__(8192) uint32_t g_buf2[4 * 3 * 2048];
__device__ uint32_t g_choice[128];
__device__ uint32_t g_epoch;
__device__ uint32_t g_hflag[64];
__device__ __align__(1024) uint4 g_vx[(size_t)NSEG * 96 * 256];
__device__ __align__(128) uint32_t g_modx[2 * DM];
#define T2(i)
#define T3(i)
enum { C_Q = 0, C_MOD = 1, C_REC = 2, C_G0 = 18, C_LN = 34, C_G1 = 50, C_G2 = 66, C_FIN = 82, C_V = 98, C_H = 114, C_NUM = 115 };
__device__ __align__(128) uint32_t g_cnt[C_NUM * 32];
constexpr int PMAX = 12;
constexpr int PRING = 4;
__device__ __align__(1024) float g_p0[(size_t)PRING * PMAX * 128 * DM];
__device__ __align__(1024) float g_p2[(size_t)PRING * PMAX * 128 * DM];
#define TR(k)

#define FRESH(x) asm volatile("" : "+r"(x))
__device__ __forceinline__ float bfr(float x) { uint32_t r; asm("cvt.rn.bf16x2.f32 %0, %1, %2;" : "=r"(r) : "f"(x), "f"(0.0f)); return __uint_as_float(r); }
__device__ __forceinline__ uint32_t pack2(float a, float b) {
    uint32_t r; asm("cvt.rn.bf16x2.f32 %0, %1, %2;" : "=r"(r) : "f"(b), "f"(a)); return r;
}
__device__ __forceinline__ float bflo(uint32_t v) { return __uint_as_float(v << 16); }
__device__ __forceinline__ float bfhi(uint32_t v) { return __uint_as_float(v & 0xffff0000u); }
__device__ __forceinline__ float ex2(float x) { float r; asm("ex2.approx.ftz.f32 %0, %1;" : "=f"(r) : "f"(x)); return r; }
__device__ __forceinline__ float rcpf(float x) { float r; asm("rcp.approx.ftz.f32 %0, %1;" : "=f"(r) : "f"(x)); return r; }
__device__ __forceinline__ void score2(float& a, float& b) {
    const float SCALE = 0.07216878364870322f;
    uint32_t u = pack2(a, b);
    u = pack2(bflo(u) * SCALE, bfhi(u) * SCALE);
    a = bflo(u); b = bfhi(u);
}
__device__ __forceinline__ uint32_t smem_u32(const void* p) { return (uint32_t)__cvta_generic_to_shared(p); }

__device__ __forceinline__ void mbar_init(uint32_t bar, uint32_t cnt) {
    asm volatile("mbarrier.init.shared::cta.b64 [%0], %1;" :: "r"(bar), "r"(cnt) : "memory");
}
__device__ __forceinline__ void mbar_arrive(uint32_t bar) {
    asm volatile("mbarrier.arrive.shared::cta.b64 _, [%0];" :: "r"(bar) : "memory");
}
__device__ __forceinline__ void mbar_expect(uint32_t bar, uint32_t bytes) {
    asm volatile("mbarrier.arrive.expect_tx.shared::cta.b64 _, [%0], %1;" :: "r"(bar), "r"(bytes) : "memory");
}
__device__ __forceinline__ bool mbar_try(uint32_t bar, uint32_t parity) {
    uint32_t ok;
    asm volatile("{\n\t.reg .pred p;\n\tmbarrier.try_wait.parity.shared::cta.b64 p, [%1], %2;\n\tselp.u32 %0, 1, 0, p;\n\t}"
                 : "=r"(ok) : "r"(bar), "r"(parity) : "memory");
    return ok != 0;
}
__device__ __forceinline__ bool mbar_try_cluster(uint32_t bar, uint32_t parity) {
    uint32_t ok;
    asm volatile("{\n\t.reg .pred p;\n\tmbarrier.try_wait.parity.acquire.cluster.shared::cta.b64 p, [%1], %2;\n\tselp.u32 %0, 1, 0, p;\n\t}"
                 : "=r"(ok) : "r"(bar), "r"(parity) : "memory");
    return ok != 0;
}
__device__ __forceinline__ void mbar_wait(uint32_t bar, uint32_t parity) {
    uint32_t guard = 0;
    while (!mbar_try(bar, parity)) { if (++guard > (1u << 22)) __trap(); }
}
__device__ __forceinline__ void mbar_wait_cluster(uint32_t bar, uint32_t parity) {
    uint32_t guard = 0;
    while (!mbar_try_cluster(bar, parity)) { if (++guard > (1u << 22)) __trap(); }
}
__device__ __forceinline__ void bar_sync(int id, int n) { asm volatile("bar.sync %0, %1;" :: "r"(id), "r"(n) : "memory"); }
__device__ __forceinline__ void bar_arrive(int id, int n) { asm volatile("bar.arrive %0, %1;" :: "r"(id), "r"(n) : "memory"); }
__device__ __forceinline__ void sts1(uint32_t a, uint32_t v) { asm volatile("st.shared.u32 [%0], %1;" :: "r"(a), "r"(v) : "memory"); }
__device__ __forceinline__ uint32_t lds1(uint32_t a) { uint32_t v; asm volatile("ld.shared.u32 %0, [%1];" : "=r"(v) : "r"(a) : "memory"); return v; }
__device__ __forceinline__ void fence_async() { asm volatile("fence.proxy.async.shared::cta;" ::: "memory"); }
__device__ __forceinline__ void cluster_sync() {
    asm volatile("barrier.cluster.arrive.release.aligned;\n\tbarrier.cluster.wait.acquire.aligned;" ::: "memory");
}
__device__ __forceinline__ uint32_t mapa(uint32_t a, uint32_t rank) {
    uint32_t r; asm("mapa.shared::cluster.u32 %0, %1, %2;" : "=r"(r) : "r"(a), "r"(rank)); return r;
}
__device__ __forceinline__ void st_async1(uint32_t a, uint32_t v, uint32_t bar) {
    asm volatile("st.async.weak.shared::cluster.mbarrier::complete_tx::bytes.b32 [%0], %1, [%2];" :: "r"(a), "r"(v), "r"(bar) : "memory");
}
__device__ __forceinline__ void st_async2(uint32_t a, float x, float y, uint32_t bar) {
    asm volatile("st.async.weak.shared::cluster.mbarrier::complete_tx::bytes.v2.f32 [%0], {%1,%2}, [%3];" :: "r"(a), "f"(x), "f"(y), "r"(bar) : "memory");
}
__device__ __forceinline__ void st_async4(uint32_t a, const float* c, uint32_t bar) {
    asm volatile("st.async.weak.shared::cluster.mbarrier::complete_tx::bytes.v4.f32 [%0], {%1,%2,%3,%4}, [%5];"
                 :: "r"(a), "f"(c[0]), "f"(c[1]), "f"(c[2]), "f"(c[3]), "r"(bar) : "memory");
}
__device__ __forceinline__ void bulk_g2s(uint32_t dst, const void* src, uint32_t bytes, uint32_t bar) {
    asm volatile("cp.async.bulk.shared::cluster.global.mbarrier::complete_tx::bytes [%0], [%1], %2, [%3];"
                 :: "r"(dst), "l"(src), "r"(bytes), "r"(bar) : "memory");
}
__device__ __forceinline__ void cpa16(uint32_t s, const void* g) {
    asm volatile("cp.async.cg.shared.global [%0], [%1], 16;" :: "r"(s), "l"(g) : "memory");
}
__device__ __forceinline__ void cpa_wait_all() { asm volatile("cp.async.wait_all;" ::: "memory"); }
__device__ __forceinline__ void ldsm4(uint32_t* r, uint32_t a) {
    asm volatile("ldmatrix.sync.aligned.m8n8.x4.shared.b16 {%0,%1,%2,%3}, [%4];" : "=r"(r[0]), "=r"(r[1]), "=r"(r[2]), "=r"(r[3]) : "r"(a) : "memory");
}
__device__ __forceinline__ void ldsm4t(uint32_t* r, uint32_t a) {
    asm volatile("ldmatrix.sync.aligned.m8n8.x4.trans.shared.b16 {%0,%1,%2,%3}, [%4];" : "=r"(r[0]), "=r"(r[1]), "=r"(r[2]), "=r"(r[3]) : "r"(a) : "memory");
}
__device__ __forceinline__ void stsm2t(uint32_t a, uint32_t r0, uint32_t r1) {
    asm volatile("stmatrix.sync.aligned.m8n8.x2.trans.shared.b16 [%0], {%1,%2};" :: "r"(a), "r"(r0), "r"(r1) : "memory");
}
__device__ __forceinline__ void stsm4t(uint32_t a, uint32_t r0, uint32_t r1, uint32_t r2, uint32_t r3) {
    asm volatile("stmatrix.sync.aligned.m8n8.x4.trans.shared.b16 [%0], {%1,%2,%3,%4};" :: "r"(a), "r"(r0), "r"(r1), "r"(r2), "r"(r3) : "memory");
}
__device__ __forceinline__ uint32_t movm(uint32_t v) {
    uint32_t r; asm volatile("movmatrix.sync.aligned.m8n8.trans.b16 %0, %1;" : "=r"(r) : "r"(v)); return r;
}
__device__ __forceinline__ void mma16(float* c, uint32_t a0, uint32_t a1, uint32_t a2, uint32_t a3, uint32_t b0, uint32_t b1) {
    asm volatile("mma.sync.aligned.m16n8k16.row.col.f32.bf16.bf16.f32 {%0,%1,%2,%3}, {%4,%5,%6,%7}, {%8,%9}, {%0,%1,%2,%3};"
                 : "+f"(c[0]), "+f"(c[1]), "+f"(c[2]), "+f"(c[3]) : "r"(a0), "r"(a1), "r"(a2), "r"(a3), "r"(b0), "r"(b1));
}
__device__ __forceinline__ void mma8(float* c, uint32_t a0, uint32_t a1, uint32_t b0) {
    asm volatile("mma.sync.aligned.m16n8k8.row.col.f32.bf16.bf16.f32 {%0,%1,%2,%3}, {%4,%5}, {%6}, {%0,%1,%2,%3};"
                 : "+f"(c[0]), "+f"(c[1]), "+f"(c[2]), "+f"(c[3]) : "r"(a0), "r"(a1), "r"(b0));
}
__host__ __device__ constexpr uint64_t make_desc(uint32_t saddr, uint32_t lbo, uint32_t sbo, uint32_t layout) {
    return (uint64_t)((saddr & 0x3FFFF) >> 4) | ((uint64_t)(lbo >> 4) << 16) | ((uint64_t)(sbo >> 4) << 32) | ((uint64_t)layout << 62);
}
__device__ __forceinline__ void wg_fence() { asm volatile("wgmma.fence.sync.aligned;" ::: "memory"); }
__device__ __forceinline__ void wg_commit() { asm volatile("wgmma.commit_group.sync.aligned;" ::: "memory"); }
template <int N> __device__ __forceinline__ void wg_wait() { asm volatile("wgmma.wait_group.sync.aligned %0;" :: "n"(N) : "memory"); }

#define D16(C) C(d[0]), C(d[1]), C(d[2]), C(d[3]), C(d[4]), C(d[5]), C(d[6]), C(d[7]), \
               C(d[8]), C(d[9]), C(d[10]), C(d[11]), C(d[12]), C(d[13]), C(d[14]), C(d[15])
#define DREG16 "{%0,%1,%2,%3,%4,%5,%6,%7,%8,%9,%10,%11,%12,%13,%14,%15}"
__device__ __forceinline__ void wg_rs32(float* d, const uint32_t* a, uint64_t db, bool acc) {
    if (acc)
        asm volatile("wgmma.mma_async.sync.aligned.m64n32k16.f32.bf16.bf16 " DREG16 ", {%16,%17,%18,%19}, %20, 1, 1, 1, 0;"
            : D16("+f") : "r"(a[0]), "r"(a[1]), "r"(a[2]), "r"(a[3]), "l"(db));
    else
        asm volatile("wgmma.mma_async.sync.aligned.m64n32k16.f32.bf16.bf16 " DREG16 ", {%16,%17,%18,%19}, %20, 0, 1, 1, 0;"
            : D16("=f") : "r"(a[0]), "r"(a[1]), "r"(a[2]), "r"(a[3]), "l"(db));
}
__device__ __forceinline__ void wg_ss32(float* d, uint64_t da, uint64_t db, bool acc) {
    if (acc)
        asm volatile("wgmma.mma_async.sync.aligned.m64n32k16.f32.bf16.bf16 " DREG16 ", %16, %17, 1, 1, 1, 1, 0;"
            : D16("+f") : "l"(da), "l"(db));
    else
        asm volatile("wgmma.mma_async.sync.aligned.m64n32k16.f32.bf16.bf16 " DREG16 ", %16, %17, 0, 1, 1, 1, 0;"
            : D16("=f") : "l"(da), "l"(db));
}
__device__ __forceinline__ void wg_ss8(float* d, uint64_t da, uint64_t db, bool acc) {
    if (acc)
        asm volatile("wgmma.mma_async.sync.aligned.m64n8k16.f32.bf16.bf16 {%0,%1,%2,%3}, %4, %5, 1, 1, 1, 1, 1;"
            : "+f"(d[0]), "+f"(d[1]), "+f"(d[2]), "+f"(d[3]) : "l"(da), "l"(db));
    else
        asm volatile("wgmma.mma_async.sync.aligned.m64n8k16.f32.bf16.bf16 {%0,%1,%2,%3}, %4, %5, 0, 1, 1, 1, 1;"
            : "=f"(d[0]), "=f"(d[1]), "=f"(d[2]), "=f"(d[3]) : "l"(da), "l"(db));
}
template <int OFF> __device__ __forceinline__ void ldsm4t_i(uint32_t* r, uint32_t a) {
    asm volatile("ldmatrix.sync.aligned.m8n8.x4.trans.shared.b16 {%0,%1,%2,%3}, [%4+%5];"
                 : "=r"(r[0]), "=r"(r[1]), "=r"(r[2]), "=r"(r[3]) : "r"(a), "n"(OFF) : "memory");
}

__device__ __forceinline__ uint4 ld_relaxed4(const void* p) {
    uint4 v;
    asm volatile("ld.relaxed.gpu.global.v4.u32 {%0,%1,%2,%3}, [%4];" : "=r"(v.x), "=r"(v.y), "=r"(v.z), "=r"(v.w) : "l"(p) : "memory");
    return v;
}
__device__ __forceinline__ void st_relaxed2(void* p, uint32_t a, uint32_t b) {
    asm volatile("st.relaxed.gpu.global.v2.u32 [%0], {%1,%2};" :: "l"(p), "r"(a), "r"(b) : "memory");
}
__device__ __forceinline__ void st_relaxed2_off(void* base, uint32_t off, uint32_t a, uint32_t b) {
    asm volatile("{\n\t.reg .u64 ad;\n\tcvt.u64.u32 ad, %1;\n\tadd.u64 ad, ad, %0;\n\tst.relaxed.gpu.global.v2.u32 [ad], {%2,%3};\n\t}"
                 :: "l"(base), "r"(off), "r"(a), "r"(b) : "memory");
}
__device__ __forceinline__ void st_relaxed1(void* p, uint32_t a) {
    asm volatile("st.relaxed.gpu.global.u32 [%0], %1;" :: "l"(p), "r"(a) : "memory");
}
__device__ __forceinline__ uint32_t ld_acquire1(const uint32_t* p) {
    uint32_t v; asm volatile("ld.acquire.gpu.global.u32 %0, [%1];" : "=r"(v) : "l"(p) : "memory"); return v;
}
__device__ __forceinline__ void st_release1(uint32_t* p, uint32_t a) {
    asm volatile("st.release.gpu.global.u32 [%0], %1;" :: "l"(p), "r"(a) : "memory");
}
__device__ __forceinline__ uint4 lds4(uint32_t s) {
    uint4 v; asm volatile("ld.shared.v4.u32 {%0,%1,%2,%3}, [%4];" : "=r"(v.x), "=r"(v.y), "=r"(v.z), "=r"(v.w) : "r"(s) : "memory"); return v;
}
__device__ __forceinline__ void sts4(uint32_t s, const uint4& v) {
    asm volatile("st.shared.v4.u32 [%0], {%1,%2,%3,%4};" :: "r"(s), "r"(v.x), "r"(v.y), "r"(v.z), "r"(v.w) : "memory");
}
__device__ __forceinline__ float4 lds4f(uint32_t s) {
    float4 v; asm volatile("ld.shared.v4.f32 {%0,%1,%2,%3}, [%4];" : "=f"(v.x), "=f"(v.y), "=f"(v.z), "=f"(v.w) : "r"(s) : "memory"); return v;
}
__device__ __forceinline__ uint2 lds2(uint32_t s) {
    uint2 v; asm volatile("ld.shared.v2.u32 {%0,%1}, [%2];" : "=r"(v.x), "=r"(v.y) : "r"(s) : "memory"); return v;
}
__device__ __forceinline__ float2 lds2f(uint32_t s) {
    float2 v; asm volatile("ld.shared.v2.f32 {%0,%1}, [%2];" : "=f"(v.x), "=f"(v.y) : "r"(s) : "memory"); return v;
}
__device__ __forceinline__ uint32_t clk32() { uint32_t c; asm volatile("mov.u32 %0, %%clock;" : "=r"(c) :: "memory"); return c; }
__device__ __forceinline__ uint32_t tagw(float v, uint32_t tag) { return ((__float_as_uint(v) + 8u) & ~15u) | tag; }
__device__ __forceinline__ bool ok4(const uint4& v, uint32_t tag) { return (((v.x ^ tag) | (v.y ^ tag) | (v.z ^ tag) | (v.w ^ tag)) & 15u) == 0; }
__device__ __forceinline__ bool oks(const uint4& v) { return v.x != 0xFFFFFFFFu && v.y != 0xFFFFFFFFu && v.z != 0xFFFFFFFFu && v.w != 0xFFFFFFFFu; }
__device__ __forceinline__ float uf(uint32_t x) { return __uint_as_float(x & ~15u); }

template <int NT, int BAR>
__device__ __forceinline__ void mod_chunk(const bf16* __restrict__ c, const bf16* __restrict__ wmod, int col0, int tid, float* red) {
    constexpr int RG = NT / 8, NP = DM / RG;
    const int cc = tid & 7, rg = tid >> 3;
    uint4 w[NP];
    #pragma unroll
    for (int i = 0; i < NP; i++) w[i] = __ldg((const uint4*)(wmod + (size_t)(rg + i * RG) * (6 * DM) + col0 + cc * 8));
    float a[8];
    #pragma unroll
    for (int j = 0; j < 8; j++) a[j] = 0.f;
    #pragma unroll
    for (int i = 0; i < NP; i++) {
        const float v = __bfloat162float(c[rg + i * RG]);
        const float sv = bfr(__fdividef(v, 1.0f + __expf(-v)));
        a[0] += sv * bflo(w[i].x); a[1] += sv * bfhi(w[i].x); a[2] += sv * bflo(w[i].y); a[3] += sv * bfhi(w[i].y);
        a[4] += sv * bflo(w[i].z); a[5] += sv * bfhi(w[i].z); a[6] += sv * bflo(w[i].w); a[7] += sv * bfhi(w[i].w);
    }
    #pragma unroll
    for (int j = 0; j < 8; j++) {
        a[j] += __shfl_xor_sync(0xffffffffu, a[j], 8);
        a[j] += __shfl_xor_sync(0xffffffffu, a[j], 16);
    }
    if ((tid & 31) < 8) {
        float* d = red + (tid >> 5) * 64 + cc * 8;
        *(float4*)d = make_float4(a[0], a[1], a[2], a[3]);
        *(float4*)(d + 4) = make_float4(a[4], a[5], a[6], a[7]);
    }
    bar_sync(BAR, NT);
    if (tid < 64) {
        float s = 0.f;
        #pragma unroll
        for (int i = 0; i < NT / 32; i++) s += red[i * 64 + tid];
        g_mod[col0 + tid] = bfr(s);
    }
}

__device__ __forceinline__ uint32_t hadd2(uint32_t a, uint32_t b) { uint32_t r; asm("add.rn.bf16x2 %0, %1, %2;" : "=r"(r) : "r"(a), "r"(b)); return r; }
__device__ __forceinline__ uint32_t hsub2(uint32_t a, uint32_t b) { uint32_t r; asm("sub.rn.bf16x2 %0, %1, %2;" : "=r"(r) : "r"(a), "r"(b)); return r; }
__device__ __forceinline__ uint32_t hmul2(uint32_t a, uint32_t b) { uint32_t r; asm("mul.rn.bf16x2 %0, %1, %2;" : "=r"(r) : "r"(a), "r"(b)); return r; }
__device__ __forceinline__ void ln_stats(const uint2* x, uint32_t& mb2, float& rs) {
    float v[5][4];
    float s = 0.f;
    #pragma unroll
    for (int i = 0; i < 5; i++) {
        v[i][0] = bflo(x[i].x); v[i][1] = bfhi(x[i].x); v[i][2] = bflo(x[i].y); v[i][3] = bfhi(x[i].y);
        s += (v[i][0] + v[i][1]) + (v[i][2] + v[i][3]);
    }
    #pragma unroll
    for (int o = 16; o > 0; o >>= 1) s += __shfl_xor_sync(0xffffffffu, s, o);
    const float mean = s * (1.0f / DM);
    float q0 = 0.f, q1 = 0.f;
    #pragma unroll
    for (int i = 0; i < 5; i++) {
        const float d0 = v[i][0] - mean, d1 = v[i][1] - mean, d2 = v[i][2] - mean, d3 = v[i][3] - mean;
        q0 += d0 * d0; q1 += d1 * d1; q0 += d2 * d2; q1 += d3 * d3;
    }
    float q = q0 + q1;
    #pragma unroll
    for (int o = 16; o > 0; o >>= 1) q += __shfl_xor_sync(0xffffffffu, q, o);
    mb2 = pack2(mean, mean);
    const float var = bfr(q * (1.0f / DM));
    rs = __frcp_rn(bfr(__fsqrt_rn(bfr(var + 1e-5f))));
}
__device__ __forceinline__ uint32_t ln_norm(uint32_t x, uint32_t mb2, float rs) {
    const uint32_t d = hsub2(x, mb2);
    return pack2(bflo(d) * rs, bfhi(d) * rs);
}
__device__ __forceinline__ uint32_t ln_apply(uint32_t x, uint32_t mb2, float rs, uint32_t m1, uint32_t sh) {
    return hadd2(hmul2(ln_norm(x, mb2, rs), m1), sh);
}

constexpr int SM_WV = 0;
constexpr int SM_HB = 81920;
constexpr int SM_WO = SM_HB + 40960;
constexpr int SM_QX = SM_WO + 77824;
constexpr int SM_KS = SM_QX + 4096;
constexpr int SM_QM = SM_KS + 5120;
constexpr int SM_XS = SM_QM + 1024;
constexpr int SM_MS = SM_XS + 12288;
constexpr int SM_OS = SM_MS + 3840;
constexpr int SM_PM = SM_OS + 3072;
constexpr int SM_BAR = SM_PM + 640;
constexpr int SM_CH = SM_BAR + 128;
constexpr int SM_TOTAL = SM_CH + 128;
static_assert(SM_TOTAL <= 232448, "smem");

enum { B_MEM_FULL = 0, B_MEM_FREE, B_HLO_FULL, B_HHI_FULL, B_HLO_FREE, B_HHI_FREE, B_MS, B_O, B_XS, B_O1, B_XSFREE, B_WQ, B_P0, B_WV, B_WO, B_P1 };

__device__ __forceinline__ int probe_blk(uint32_t* blk) {
    uint32_t t0 = 0xffffffffu, t1 = 0xffffffffu, acc = 0;
    for (int rep = 0; rep < 3; rep++) {
        #pragma unroll
        for (int pg = 0; pg < 2; pg++) {
            uint32_t c0 = clk32();
            uint32_t v = atomicOr(blk + pg * 1024 + acc, 0u);
            acc = (v == 0x12345678u) ? 1u : 0u;
            asm volatile("" :: "r"(acc) : "memory");
            uint32_t c1 = clk32() + acc;
            uint32_t d = c1 - c0;
            if (rep > 0) { if (pg == 0) t0 = min(t0, d); else t1 = min(t1, d); }
        }
    }
    return t1 < t0 ? 1 : 0;
}

__device__ __forceinline__ uint32_t wo_tile_off(int w) {
    if (w < 8) return w * 6144;
    if (w < 12) return 8 * 6144 + (w - 8) * 4096;
    return 8 * 6144 + 4 * 4096 + (w - 12) * 6144;
}

template <int NRES, int NPRE>
__device__ __forceinline__ void wo_phase(uint32_t sb, int w, int lane, const uint32_t (*res)[4], uint32_t parity,
                                         uint32_t tag, int tile, int h) {
    FRESH(lane);
    const int er = (lane & 7) + 8 * (lane >> 4);
    const uint32_t aaddr = sb + SM_WO + wo_tile_off(w) + er * 32 + ((((lane >> 3) & 1) ^ ((er >> 2) & 1)) << 4);
    const uint32_t baddr = sb + SM_OS + lane * 16;
    float c0[4] = {0.f, 0.f, 0.f, 0.f}, c1[4] = {0.f, 0.f, 0.f, 0.f};
    uint32_t pre[NPRE > 4 ? NPRE : 4][4];
    if (NPRE >= 4) {
        #pragma unroll
        for (int i = 0; i < 4; i++) ldsm4t(pre[i], aaddr + i * 512);
        mbar_wait(sb + SM_BAR + B_O1 * 8, parity);
        uint32_t b[2][4];
        ldsm4t(b[0], baddr);
        ldsm4t(b[1], baddr + 512);
        #pragma unroll
        for (int kp = 0; kp < 2; kp++) {
            mma16(c0, pre[2 * kp][0], pre[2 * kp][1], pre[2 * kp][2], pre[2 * kp][3], b[kp][0], b[kp][1]);
            mma16(c1, pre[2 * kp + 1][0], pre[2 * kp + 1][1], pre[2 * kp + 1][2], pre[2 * kp + 1][3], b[kp][2], b[kp][3]);
        }
    } else {
        #pragma unroll
        for (int i = 0; i < 2; i++) ldsm4t(pre[i], aaddr + i * 512);
        mbar_wait(sb + SM_BAR + B_O1 * 8, parity);
        #pragma unroll
        for (int kp = 0; kp < 2; kp++) {
            uint32_t b[4];
            ldsm4t(b, baddr + kp * 512);
            if (kp == 1) { ldsm4t(pre[0], aaddr + 2 * 512); ldsm4t(pre[1], aaddr + 3 * 512); }
            mma16(c0, pre[0][0], pre[0][1], pre[0][2], pre[0][3], b[0], b[1]);
            mma16(c1, pre[1][0], pre[1][1], pre[1][2], pre[1][3], b[2], b[3]);
        }
    }
    #pragma unroll
    for (int i = 0; i < NPRE; i++) ldsm4t(pre[i], aaddr + (4 + i) * 512);
    uint32_t off0, off1;
    {
        uint32_t ch;
        asm volatile("ld.shared.u16 %0, [%1];" : "=r"(ch) : "r"(sb + SM_CH + 2 * tile) : "memory");
        const int j = h >> 4;
        const uint32_t base = (uint32_t)((tile * 4 + j) * 8192 + (h & 15) * 256 + lane * 8);
        ch >>= j;
        off0 = base + (ch & 1) * 4096;
        off1 = base + 16384 + (ch & 256) * 16;
    }
    mbar_wait(sb + SM_BAR + B_O * 8, parity);
    if (NRES == 4) {
        uint32_t b[4][4];
        #pragma unroll
        for (int i = 0; i < 4; i++) ldsm4t(b[i], baddr + (2 + i) * 512);
        #pragma unroll
        for (int i = 0; i < 2; i++) {
            mma16(c0, res[2 * i][0], res[2 * i][1], res[2 * i][2], res[2 * i][3], b[i][0], b[i][1]);
            mma16(c1, res[2 * i + 1][0], res[2 * i + 1][1], res[2 * i + 1][2], res[2 * i + 1][3], b[i][2], b[i][3]);
        }
        #pragma unroll
        for (int i = 0; i < 2; i++) {
            mma16(c0, pre[2 * i][0], pre[2 * i][1], pre[2 * i][2], pre[2 * i][3], b[2 + i][0], b[2 + i][1]);
            mma16(c1, pre[2 * i + 1][0], pre[2 * i + 1][1], pre[2 * i + 1][2], pre[2 * i + 1][3], b[2 + i][2], b[2 + i][3]);
        }
    } else if (NPRE == 4) {
        uint32_t b[2][4];
        #pragma unroll
        for (int hh = 0; hh < 2; hh++) {
            ldsm4t(b[0], baddr + (2 + 2 * hh) * 512);
            ldsm4t(b[1], baddr + (3 + 2 * hh) * 512);
            if (hh) {
                #pragma unroll
                for (int i = 0; i < 4; i++) ldsm4t(pre[i], aaddr + (8 + i) * 512);
            }
            #pragma unroll
            for (int i = 0; i < 2; i++) {
                mma16(c0, pre[2 * i][0], pre[2 * i][1], pre[2 * i][2], pre[2 * i][3], b[i][0], b[i][1]);
                mma16(c1, pre[2 * i + 1][0], pre[2 * i + 1][1], pre[2 * i + 1][2], pre[2 * i + 1][3], b[i][2], b[i][3]);
            }
        }
    }
    st_relaxed2_off(g_buf1, off0, tagw(c0[0] + c1[0], tag), tagw(c0[1] + c1[1], tag));
    st_relaxed2_off(g_buf1, off1, tagw(c0[2] + c1[2], tag), tagw(c0[3] + c1[3], tag));
}

template <int NT, bool MASK>
__device__ __forceinline__ void softmax_core(float (*sc)[2], int g, int t, uint32_t* pb) {
    const float L2E = 1.4426950408889634f;
    #pragma unroll
    for (int j = 0; j < NT; j++) score2(sc[j][0], sc[j][1]);
    if (MASK) {
        const float NEG = -999292928.0f;
        if (2 * t > g) sc[NT - 1][0] = NEG;
        if (2 * t + 1 > g) sc[NT - 1][1] = NEG;
    }
    float m[NT];
    #pragma unroll
    for (int j = 0; j < NT; j++) m[j] = fmaxf(sc[j][0], sc[j][1]);
    float mx = m[0];
    #pragma unroll
    for (int j = 1; j < NT; j++) mx = fmaxf(mx, m[j]);
    mx = fmaxf(mx, __shfl_xor_sync(0xffffffffu, mx, 1));
    mx = fmaxf(mx, __shfl_xor_sync(0xffffffffu, mx, 2));
    float s0 = 0.f, s1 = 0.f;
    #pragma unroll
    for (int j = 0; j < NT; j++) {
        sc[j][0] = ex2((sc[j][0] - mx) * L2E); sc[j][1] = ex2((sc[j][1] - mx) * L2E);
        s0 += sc[j][0]; s1 += sc[j][1];
    }
    s0 += s1;
    s0 += __shfl_xor_sync(0xffffffffu, s0, 1);
    s0 += __shfl_xor_sync(0xffffffffu, s0, 2);
    const float iv = rcpf(s0);
    #pragma unroll
    for (int j = 0; j < NT; j++) pb[j] = pack2(sc[j][0] * iv, sc[j][1] * iv);
}
template <int NT>
__device__ __forceinline__ void xsoftmax(uint32_t a, int g, int t) {
    float sc[NT][2];
    #pragma unroll
    for (int j = 0; j < NT; j++) {
        float2 v0 = lds2f(a + j * 512), v1 = lds2f(a + j * 512 + 4096), v2 = lds2f(a + j * 512 + 8192);
        sc[j][0] = v0.x + v1.x + v2.x; sc[j][1] = v0.y + v1.y + v2.y;
    }
    uint32_t pb[NT];
    softmax_core<NT, true>(sc, g, t, pb);
    #pragma unroll
    for (int j = 0; j < NT; j += 2) {
        if (j + 1 < NT) asm volatile("st.shared.v2.u32 [%0], {%1,%2};" :: "r"(a + j * 512), "r"(pb[j]), "r"(pb[j + 1]) : "memory");
        else sts1(a + j * 512, pb[j]);
    }
}
template <int NJ>
__device__ __forceinline__ void xscores(uint32_t sb, int p, int mi, int j0, int lane) {
    FRESH(lane);
    const int r = lane & 7, cq = lane >> 3;
    const int qrow = mi * 16 + r + 8 * (cq & 1);
    uint32_t kb[NJ][8];
    float d[NJ][4];
    #pragma unroll
    for (int j = 0; j < NJ; j++) {
        ldsm4(kb[j], sb + SM_KS + ((j0 + j) * 8 + r) * 128 + ((cq ^ r) << 4));
        ldsm4(kb[j] + 4, sb + SM_KS + ((j0 + j) * 8 + r) * 128 + (((cq + 4) ^ r) << 4));
        d[j][0] = 0.f; d[j][1] = 0.f; d[j][2] = 0.f; d[j][3] = 0.f;
    }
    #pragma unroll
    for (int kt = 0; kt < 4; kt++) {
        uint32_t a[4];
        ldsm4(a, sb + SM_QX + qrow * 128 + (((2 * kt + (cq >> 1)) ^ r) << 4));
        #pragma unroll
        for (int j = 0; j < NJ; j++) mma16(d[j], a[0], a[1], a[2], a[3], kb[j][2 * kt], kb[j][2 * kt + 1]);
    }
    const uint32_t la = sb + SM_XS + p * 4096 + (mi * 3 + j0) * 512 + lane * 16;
    #pragma unroll
    for (int rk = 0; rk < 3; rk++) {
        const uint32_t ra = mapa(la, rk), rb = mapa(sb + SM_BAR + B_XS * 8, rk);
        #pragma unroll
        for (int j = 0; j < NJ; j++) st_async4(ra + j * 512, d[j], rb);
    }
}
__device__ __forceinline__ void mbar_arrive_remote(uint32_t bar) {
    asm volatile("mbarrier.arrive.relaxed.cluster.shared::cluster.b64 _, [%0];" :: "r"(bar) : "memory");
}

__device__ __forceinline__ void tma2d(uint32_t dst, const CUtensorMap* map, int c0, int c1, uint32_t bar) {
    asm volatile("cp.async.bulk.tensor.2d.shared::cluster.global.mbarrier::complete_tx::bytes [%0], [%1, {%2, %3}], [%4];"
                 :: "r"(dst), "l"(map), "r"(c0), "r"(c1), "r"(bar) : "memory");
}
__device__ __forceinline__ void tma2d_pf(const CUtensorMap* map, int c0, int c1) {
    asm volatile("cp.async.bulk.prefetch.tensor.2d.L2.global [%0, {%1, %2}];" :: "l"(map), "r"(c0), "r"(c1) : "memory");
}
__device__ __forceinline__ void bulk_pf(const void* p, uint32_t bytes) {
    asm volatile("cp.async.bulk.prefetch.L2.global [%0], %1;" :: "l"(p), "r"(bytes) : "memory");
}
struct RMaps { CUtensorMap wq, wk, wv, wo, wop; };
__device__ __forceinline__ void signal_cnt(int idx) {
    asm volatile("fence.proxy.async.global;\n\tred.release.gpu.global.add.u32 [%0], 1;" :: "l"(g_cnt + idx * 32) : "memory");
}

__device__ __forceinline__ void pro_ln(uint32_t sb, uint32_t tag, const bf16* __restrict__ xin, const bf16* __restrict__ cvec, const bf16* __restrict__ wmod) {
    extern __shared__ __align__(1024) uint8_t smem_raw[];
    const int tid = threadIdx.x, lane = tid & 31, warp = tid >> 5, wg = tid >> 7, b = blockIdx.x;
    const uint32_t bar = sb + SM_BAR;
    {
        const int seg1 = b + 1, nrow = b < NSEG - 1 ? 64 : 32;
        const bf16* xl = xin + lane * 4;
        const int wv = threadIdx.x >> 5;
        uint4 wm[5];
        float cv[5];
        if (wg < 2 && b < 80) {
            #pragma unroll
            for (int i = 0; i < 5; i++) {
                wm[i] = __ldg((const uint4*)(wmod + (size_t)((tid >> 1) + 128 * i) * (6 * DM) + b * 16 + (tid & 1) * 8));
                cv[i] = __bfloat162float(cvec[(tid >> 1) + 128 * i]);
            }
        }
        uint2 xn[6][5];
        #pragma unroll
        for (int r = 0; r < 6; r++) {
            const int idx = wv + 12 * r, nx = idx < 32 ? idx : (idx < nrow ? b * 32 + idx : 0);
            #pragma unroll
            for (int i = 0; i < 5; i++) xn[r][i] = __ldg((const uint2*)(xl + (size_t)nx * DM + i * 128));
        }
        if (wg < 2 && b < 80) {
            float a[8];
            #pragma unroll
            for (int j = 0; j < 8; j++) a[j] = 0.f;
            #pragma unroll
            for (int i = 0; i < 5; i++) {
                const float sv = bfr(__fdividef(cv[i], 1.0f + __expf(-cv[i])));
                a[0] += sv * bflo(wm[i].x); a[1] += sv * bfhi(wm[i].x); a[2] += sv * bflo(wm[i].y); a[3] += sv * bfhi(wm[i].y);
                a[4] += sv * bflo(wm[i].z); a[5] += sv * bfhi(wm[i].z); a[6] += sv * bflo(wm[i].w); a[7] += sv * bfhi(wm[i].w);
            }
            #pragma unroll 1
            for (int o = 2; o < 32; o <<= 1) {
                #pragma unroll
                for (int j = 0; j < 8; j++) a[j] += __shfl_xor_sync(0xffffffffu, a[j], o);
            }
            if (lane < 2) {
                const uint32_t d = sb + SM_QM + warp * 64 + lane * 32;
                sts4(d, make_uint4(__float_as_uint(a[0]), __float_as_uint(a[1]), __float_as_uint(a[2]), __float_as_uint(a[3])));
                sts4(d + 16, make_uint4(__float_as_uint(a[4]), __float_as_uint(a[5]), __float_as_uint(a[6]), __float_as_uint(a[7])));
            }
            bar_sync(1, 256);
            if (tid < 8) {
                float s0 = 0.f, s1 = 0.f;
                #pragma unroll
                for (int i = 0; i < 8; i++) { const float2 v = lds2f(sb + SM_QM + i * 64 + tid * 8); s0 += v.x; s1 += v.y; }
                st_relaxed2(g_modx + (b * 8 + tid) * 2, pack2(s0, s1), tag);
            }
        }
        __syncwarp();
        #pragma unroll 1
        for (int r = 0; r < 6; r++) {
            uint32_t mb; float rs;
            ln_stats(xn[0], mb, rs);
            #pragma unroll
            for (int i = 0; i < 5; i++) {
                const uint2 nv = make_uint2(ln_norm(xn[0][i].x, mb, rs), ln_norm(xn[0][i].y, mb, rs));
                #pragma unroll
                for (int q = 0; q < 5; q++) xn[q][i] = xn[q + 1][i];
                xn[5][i] = nv;
            }
        }
        T3(12);
        if (tid < 320) {
            uint4 v; uint32_t guard = 0;
            while (true) {
                v = ld_relaxed4(g_modx + tid * 4);
                if (v.y == tag && v.w == tag) break;
                __nanosleep(50);
                if (++guard > (1u << 22)) __trap();
            }
            if (tid >= 160) { v.x = hadd2(v.x, 0x3f803f80u); v.z = hadd2(v.z, 0x3f803f80u); }
            asm volatile("st.shared.v2.u32 [%0], {%1,%2};" :: "r"(sb + SM_KS + tid * 8), "r"(v.x), "r"(v.z) : "memory");
        }
        bar_sync(2, 384);
        T3(13);
        {
            uint2 sh[5], m1[5];
            #pragma unroll
            for (int i = 0; i < 5; i++) { sh[i] = lds2(sb + SM_KS + i * 256 + lane * 8); m1[i] = lds2(sb + SM_KS + 1280 + i * 256 + lane * 8); }
            #pragma unroll 1
            for (int idx = wv; idx < nrow; idx += 12) {
                const int row = idx & 31;
                char* dst = (idx < 32 ? (char*)smem_raw + SM_HB : (char*)g_ht + (size_t)seg1 * 40960)
                            + (lane >> 4) * 4096 + row * 128 + ((((lane >> 1) & 7) ^ (row & 7)) << 4) + (lane & 1) * 8;
                #pragma unroll
                for (int i = 0; i < 5; i++) {
                    *(uint2*)(dst + i * 8192) = make_uint2(hadd2(hmul2(xn[0][i].x, m1[i].x), sh[i].x), hadd2(hmul2(xn[0][i].y, m1[i].y), sh[i].y));
                    #pragma unroll
                    for (int q = 0; q < 5; q++) xn[q][i] = xn[q + 1][i];
                }
            }
            __syncwarp();
        }
        fence_async();
        bar_sync(2, 384);
        T3(7);
        if (tid == 0) { mbar_arrive(bar + B_HLO_FULL * 8); mbar_arrive(bar + B_HHI_FULL * 8); }
        if (tid == 352 && b < NSEG - 1) {
            asm volatile("fence.proxy.async.global;" ::: "memory");
            st_release1(&g_hflag[seg1], tag);
        }
        __syncwarp();
    }
}

__global__ void __launch_bounds__(512, 1)
k_rec(const __grid_constant__ RMaps maps, const bf16* __restrict__ mem0, const bf16* __restrict__ Wo,
      const bf16* __restrict__ xin, const bf16* __restrict__ cvec, const bf16* __restrict__ wmod) {
    extern __shared__ __align__(1024) uint8_t smem_raw[];
    constexpr uint32_t SBC = 1024;
    const uint32_t sb = smem_u32(smem_raw);
    if ((sb & 0xFFFFFFu) != SBC) __trap();
    int lane = __shfl_sync(0xffffffffu, threadIdx.x & 31, threadIdx.x & 31);
    const int warp = __shfl_sync(0xffffffffu, threadIdx.x >> 5, 0), wg = warp >> 2;
    const int tid = warp * 32 + lane;
    const int b = blockIdx.x, h = b / 3, p = b % 3;
    const int g = lane >> 2, t = lane & 3;
    const int tile0 = p == 0 ? 0 : (p == 1 ? 14 : 27);
    const int ntile = p == 0 ? 14 : 13;
    const uint32_t bar = sb + SM_BAR;

    if (tid == 0) T2(100 + b);
    const uint32_t epoch = *(volatile uint32_t*)&g_epoch + 1u;
    if (tid == 0) {
        mbar_init(bar + B_MEM_FULL * 8, 4);
        mbar_init(bar + B_MEM_FREE * 8, 12);
        mbar_init(bar + B_HLO_FULL * 8, 1);
        mbar_init(bar + B_HHI_FULL * 8, 1);
        mbar_init(bar + B_HLO_FREE * 8, 12);
        mbar_init(bar + B_HHI_FREE * 8, 12);
        mbar_init(bar + B_MS * 8, 1);
        mbar_init(bar + B_O * 8, 1);
        mbar_init(bar + B_XS * 8, 1);
        mbar_init(bar + B_O1 * 8, 4);
        mbar_init(bar + B_XSFREE * 8, 12);
        mbar_init(bar + B_WQ * 8, 1);
        mbar_init(bar + B_P0 * 8, 1);
        mbar_init(bar + B_P1 * 8, 1);
        mbar_init(bar + B_WV * 8, 1);
        mbar_init(bar + B_WO * 8, 1);
        asm volatile("fence.mbarrier_init.release.cluster;" ::: "memory");
        mbar_expect(bar + B_MS * 8, 3840);
        mbar_expect(bar + B_O * 8, 2048);
        mbar_expect(bar + B_XS * 8, 12288);
    }
    __syncwarp();
    asm volatile("barrier.cluster.arrive.relaxed.aligned;\n\tbarrier.cluster.wait.acquire.aligned;" ::: "memory");
    if (warp == 0) T3(0);

    if (tid == 480) {
        #pragma unroll 1
        for (int i = 0; i < 5; i++) {
            if (i > 0 && i <= NPACE) mbar_wait(bar + B_P0 * 8, (i - 1) & 1);
            if (i <= NPACE) mbar_expect(bar + B_P0 * 8, i == NPACE ? (5 - NPACE) * 16384 : 16384);
            tma2d(sb + SM_WO + i * 16384, &maps.wq, h * DH + p * 64, i * 128, bar + B_P0 * 8);
            if (i > 0 && i <= NPACE) mbar_wait(bar + B_P1 * 8, (i - 1) & 1);
            if (i <= NPACE) mbar_expect(bar + B_P1 * 8, i == NPACE ? (5 - NPACE) * 16384 : 16384);
            tma2d(sb + SM_WV + i * 16384, &maps.wk, h * DH + p * 64, i * 128, bar + B_P1 * 8);
        }
        mbar_wait(bar + B_P0 * 8, NPACE & 1);
        mbar_wait(bar + B_P1 * 8, NPACE & 1);
        mbar_arrive(bar + B_WQ * 8);
        #pragma unroll 1
        for (int i = 0; i < 5; i++) tma2d_pf(&maps.wv, h * DH + p * 64, i * 128);
        tma2d_pf(&maps.wop, tile0 * 16, h * DH);
    }
    __syncwarp();
    if (wg < 3) pro_ln(sb, epoch, xin, cvec, wmod);

    if (wg < 2) {
        asm volatile("setmaxnreg.inc.sync.aligned.u32 200;");
        const int w = warp & 3;
        uint32_t wa[40][4];
        {
            mbar_wait(bar + B_WQ * 8, 0);
            if (w == 0) T3(1 + wg);
            const int r = lane & 7;
            const uint32_t wsrc = sb + (wg == 0 ? SM_WO : SM_WV) + (r + ((lane >> 4) << 3)) * 128 + (((2 * w + ((lane >> 3) & 1)) ^ r) << 4);
            #pragma unroll
            for (int kt = 0; kt < 40; kt++) ldsm4t(wa[kt], wsrc + kt * 2048);
            fence_async();
            bar_arrive(10 + wg, 256);
        }

        const uint32_t dstx = sb + (wg == 0 ? SM_QX : SM_KS + 1024);

        for (int s = -1; s < NSEG; s++) {
            const uint32_t par = s & 1;
            FRESH(lane);
            const int g = lane >> 2, t = lane & 3, tid = warp * 32 + lane;
            if (s >= 0) {
                mbar_wait(bar + B_MEM_FULL * 8, par);
                TR(0);
                float c[4][4];
                #pragma unroll
                for (int i = 0; i < 4; i++) { c[i][0] = 0.f; c[i][1] = 0.f; c[i][2] = 0.f; c[i][3] = 0.f; }
                uint32_t maddr = sb + lane * 16;
                asm volatile("" : "+r"(maddr));
                #pragma unroll
                for (int kp = 0; kp < 20; kp++) {
                    uint32_t bb[4];
                    ldsm4t(bb, maddr + (SM_HB + kp * 512));
                    mma16(c[(kp & 1) * 2], wa[2 * kp][0], wa[2 * kp][1], wa[2 * kp][2], wa[2 * kp][3], bb[0], bb[1]);
                    mma16(c[(kp & 1) * 2 + 1], wa[2 * kp + 1][0], wa[2 * kp + 1][1], wa[2 * kp + 1][2], wa[2 * kp + 1][3], bb[2], bb[3]);
                }
                {
                    const int tok = lane & 7, ch = 2 * w + ((lane >> 3) & 1);
                    stsm2t(sb + (wg == 0 ? SM_QM : SM_KS) + tok * 128 + ((ch ^ tok) << 4),
                           pack2((c[0][0] + c[1][0]) + (c[2][0] + c[3][0]), (c[0][1] + c[1][1]) + (c[2][1] + c[3][1])),
                           pack2((c[0][2] + c[1][2]) + (c[2][2] + c[3][2]), (c[0][3] + c[1][3]) + (c[2][3] + c[3][3])));
                }
                __syncwarp();
                if (lane == 0) mbar_arrive(bar + B_MEM_FREE * 8);
                TR(1);
                bar_sync(1, 256);
                if (warp < 5) {
                    const int r = lane & 7, cq = lane >> 3;
                    uint32_t a[8], kb[8];
                    ldsm4(a, sb + SM_QM + r * 128 + ((cq ^ r) << 4));
                    ldsm4(kb, sb + SM_KS + (warp * 8 + r) * 128 + ((cq ^ r) << 4));
                    ldsm4(a + 4, sb + SM_QM + r * 128 + (((cq + 4) ^ r) << 4));
                    ldsm4(kb + 4, sb + SM_KS + (warp * 8 + r) * 128 + (((cq + 4) ^ r) << 4));
                    float d0[4] = {0.f, 0.f, 0.f, 0.f}, d1[4] = {0.f, 0.f, 0.f, 0.f};
                    mma16(d0, a[0], 0u, a[1], 0u, kb[0], kb[1]);
                    mma16(d1, a[2], 0u, a[3], 0u, kb[2], kb[3]);
                    mma16(d0, a[4], 0u, a[5], 0u, kb[4], kb[5]);
                    mma16(d1, a[6], 0u, a[7], 0u, kb[6], kb[7]);
                    const uint32_t la = sb + SM_MS + p * 1280 + warp * 256 + lane * 8;
                    #pragma unroll
                    for (int rk = 0; rk < 3; rk++)
                        st_async2(mapa(la, rk), d0[0] + d1[0], d0[1] + d1[1], mapa(bar + B_MS * 8, rk));
                    bar_arrive(4, 352);
                } else if (warp < 7) {
                    xscores<1>(sb, p, warp - 5, 0, lane);
                    bar_arrive(4, 352);
                }
                TR(2);
                if (s < NSEG - 1) {
                    wo_phase<0, 4>(sb, warp, lane, nullptr, par, (uint32_t)(s % 15) + 1u, tile0 + warp, h);
                    TR(4);
                }
            }
            if (s < NSEG - 1) {
                FRESH(lane);
                const uint32_t hp = (s + 1) & 1;
                float d[16];
                const uint64_t db0 = make_desc(SBC + SM_HB, 16, 1024, 1);
                mbar_wait(bar + B_HHI_FULL * 8, hp);
                if (s < 0 && warp == 0) T3(10);
                {
                    const int r = lane & 7, mq = lane >> 3;
                    const uint32_t ha = sb + SM_HB + 9 * 4096 + (8 * (mq >> 1) + r) * 128 + (((6 + (mq & 1)) ^ r) << 4);
                    uint32_t b0[4], b1[4];
                    ldsm4(b0, ha);
                    ldsm4(b1, ha + 2048);
                    #pragma unroll
                    for (int i = 0; i < 16; i++) d[i] = 0.f;
                    mma16(d + 0, wa[39][0], wa[39][1], wa[39][2], wa[39][3], b0[0], b0[1]);
                    mma16(d + 4, wa[39][0], wa[39][1], wa[39][2], wa[39][3], b0[2], b0[3]);
                    mma16(d + 8, wa[39][0], wa[39][1], wa[39][2], wa[39][3], b1[0], b1[1]);
                    mma16(d + 12, wa[39][0], wa[39][1], wa[39][2], wa[39][3], b1[2], b1[3]);
                    asm volatile("" : "+f"(d[0]), "+f"(d[4]), "+f"(d[8]), "+f"(d[12]) :: "memory");
                }
                if (s >= 0) bar_arrive(6, 512);
                mbar_wait(bar + B_HLO_FULL * 8, hp);
                bar_sync(9, 384);
                TR(6);
                wg_fence();
                #pragma unroll
                for (int kt = 0; kt < 12; kt++) wg_rs32(d, wa[kt], db0 + (uint64_t)(((kt >> 2) * 4096 + (kt & 3) * 32) >> 4), 1);
                wg_commit();
                #pragma unroll
                for (int kt = 12; kt < 39; kt++) wg_rs32(d, wa[kt], db0 + (uint64_t)(((kt >> 2) * 4096 + (kt & 3) * 32) >> 4), 1);
                wg_commit();
                wg_wait<1>();
                if (lane == 0) mbar_arrive(bar + B_HLO_FREE * 8);
                if ((s & 3) == 0 && s > 0 && warp == 7 && lane == 0) signal_cnt(C_REC + (s >> 2) - 1);
                __syncwarp();
                wg_wait<0>();
                if (lane == 0) mbar_arrive(bar + B_HHI_FREE * 8);
                TR(7);
                const int mi = lane >> 3, r = lane & 7;
                #pragma unroll
                for (int jj = 0; jj < 2; jj++) {
                    const int tok = 8 * (2 * jj + (mi >> 1)) + r, ch = 2 * w + (mi & 1);
                    stsm4t(dstx + tok * 128 + ((ch ^ r) << 4),
                           pack2(d[8 * jj + 0], d[8 * jj + 1]), pack2(d[8 * jj + 2], d[8 * jj + 3]),
                           pack2(d[8 * jj + 4], d[8 * jj + 5]), pack2(d[8 * jj + 6], d[8 * jj + 7]));
                }
                bar_arrive(8, 384);
                if (s < 0 && warp == 0) T3(11);
                if (s < 0) { bar_sync(0, 512); asm volatile("griddepcontrol.launch_dependents;" ::: "memory"); }
            }
        }
    } else if (wg == 2) {
        asm volatile("setmaxnreg.dec.sync.aligned.u32 64;");
        const int w = warp & 3;
        uint32_t res[4][4];
        {
            const bf16* src = Wo + ((size_t)h * DH + ((p + 1) % 3) * 64) * DM + (tile0 + warp) * 16 + 2 * t;
            #pragma unroll
            for (int kt = 0; kt < 4; kt++) {
                res[kt][0] = __ldg((const uint32_t*)(src + (size_t)(kt * 16 + g) * DM));
                res[kt][1] = __ldg((const uint32_t*)(src + (size_t)(kt * 16 + g) * DM + 8));
                res[kt][2] = __ldg((const uint32_t*)(src + (size_t)(kt * 16 + 8 + g) * DM));
                res[kt][3] = __ldg((const uint32_t*)(src + (size_t)(kt * 16 + 8 + g) * DM + 8));
            }
            #pragma unroll
            for (int kt = 0; kt < 4; kt++) {
                #pragma unroll
                for (int i = 0; i < 4; i++) res[kt][i] = movm(res[kt][i]);
            }
        }
        bar_sync(11, 256);
        if (tid == 256) {
            fence_async();
            mbar_expect(bar + B_WV * 8, 81920);
            #pragma unroll
            for (int i = 0; i < 5; i++) tma2d(sb + SM_WV + i * 16384, &maps.wv, h * DH + p * 64, i * 128, bar + B_WV * 8);
        }
        mbar_wait(bar + B_WV * 8, 0);
        if (w == 0) T3(3);
        const uint64_t da0 = make_desc(SBC + SM_WV, 16, 1024, 1);
        uint32_t vx[8], vm0 = 0, vm1 = 0;
        #pragma unroll
        for (int i = 0; i < 8; i++) vx[i] = 0;

        for (int s = -1; s < NSEG; s++) {
            FRESH(lane);
            const int g = lane >> 2, t = lane & 3, tid = warp * 32 + lane;
            if (s >= 0) {
                const uint32_t par = s & 1;
                mbar_wait(bar + B_MEM_FULL * 8, par);
                bar_sync(4, 352);
                TR(0);
                float dv[4];
                {
                    const uint64_t dbm = make_desc(SBC + SM_HB, 128, 128, 0);
                    wg_fence();
                    #pragma unroll
                    for (int kt = 0; kt < 40; kt++) {
                        wg_ss8(dv, da0 + (uint64_t)(kt * 128), dbm + (uint64_t)(kt * 16), kt > 0);
                        wg_commit();
                        if (kt < 39) wg_wait<1>();
                    }
                    wg_commit();
                }
                TR(1);
                bar_sync(5, 160);
                TR(2);
                uint32_t pb[5];
                #pragma unroll
                for (int j = 0; j < 5; j++) pb[j] = lds1(sb + SM_PM + j * 128 + lane * 4);
                float o0[4] = {0.f, 0.f, 0.f, 0.f}, o1[4] = {0.f, 0.f, 0.f, 0.f}, o2[4] = {0.f, 0.f, 0.f, 0.f};
                wg_wait<0>();
                TR(3);
                mma16(o0, vx[0], vx[1], vx[2], vx[3], pb[1], pb[2]);
                mma16(o1, vx[4], vx[5], vx[6], vx[7], pb[3], pb[4]);
                vm0 = pack2(dv[0], dv[1]); vm1 = pack2(dv[2], dv[3]);
                mma8(o2, vm0, vm1, pb[0]);
                if (s < NSEG - 1) {
                    const uint32_t q0 = pack2(o0[0] + o1[0] + o2[0], o0[1] + o1[1] + o2[1]), q1 = pack2(o0[2] + o1[2] + o2[2], o0[3] + o1[3] + o2[3]);
                    const uint32_t la = sb + SM_OS + (w * 16 + g) * 16 + t * 4;
                    #pragma unroll
                    for (int i = 1; i < 3; i++) {
                        const uint32_t rk = (p + i) % 3;
                        const uint32_t ra = mapa(la + (3 - i) * 1024, rk), rb = mapa(bar + B_O * 8, rk);
                        st_async1(ra, q0, rb);
                        st_async1(ra + 128, q1, rb);
                    }
                    sts1(la, q0);
                    sts1(la + 128, q1);
                    __syncwarp();
                    if (lane == 0) { mbar_arrive(bar + B_O1 * 8); mbar_arrive(bar + B_MEM_FREE * 8); }
                }
                TR(5);
                if (s < NSEG - 1) {
                    wo_phase<4, 4>(sb, warp, lane, res, par, (uint32_t)(s % 15) + 1u, tile0 + warp, h);
                    TR(4);
                    if (tid == 256) mbar_expect(bar + B_O * 8, 2048);
                }
                if (s < NSEG - 1) bar_sync(6, 512);
            }
            uint32_t vn[8];
            #pragma unroll
            for (int i = 0; i < 8; i++) vn[i] = 0;
            if (V_FIRST < 16 && s >= 0 && s < NSEG - 1 && lds1(sb + SM_CH + 112) > (uint32_t)((s + 1) >> 2)) {
                const uint4* src = g_vx + ((size_t)(s + 1) * 96 + b) * 256 + w * 32 + lane;
                const uint4 u0 = ld_relaxed4(src), u1 = ld_relaxed4(src + 128);
                bar_arrive(9, 384);
                if (lane == 0) { mbar_arrive(bar + B_HLO_FREE * 8); mbar_arrive(bar + B_HHI_FREE * 8); }
                vn[0] = u0.x; vn[1] = u0.y; vn[2] = u0.z; vn[3] = u0.w; vn[4] = u1.x; vn[5] = u1.y; vn[6] = u1.z; vn[7] = u1.w;
            } else if (s < NSEG - 1) {
            float d[16];
            const uint32_t hp = (s + 1) & 1;
            const uint64_t db0 = make_desc(SBC + SM_HB, 16, 1024, 1);
            mbar_wait(bar + B_HHI_FULL * 8, hp);
            TR(6);
            wg_fence();
            #pragma unroll
            for (int kt = 12; kt < 40; kt++) wg_ss32(d, da0 + (uint64_t)(kt * 128), db0 + (uint64_t)(((kt >> 2) * 4096 + (kt & 3) * 32) >> 4), kt > 12);
            wg_commit();
            mbar_wait(bar + B_HLO_FULL * 8, hp);
            wg_fence();
            #pragma unroll
            for (int kt = 0; kt < 9; kt++) wg_ss32(d, da0 + (uint64_t)(kt * 128), db0 + (uint64_t)(((kt >> 2) * 4096 + (kt & 3) * 32) >> 4), 1);
            wg_commit();
            #pragma unroll
            for (int kt = 9; kt < 12; kt++) wg_ss32(d, da0 + (uint64_t)(kt * 128), db0 + (uint64_t)(((kt >> 2) * 4096 + (kt & 3) * 32) >> 4), 1);
            wg_commit();
            wg_wait<1>();
            bar_arrive(9, 384);
            wg_wait<0>();
            if (lane == 0) mbar_arrive(bar + B_HLO_FREE * 8);
            TR(7);
            if (lane == 0) mbar_arrive(bar + B_HHI_FREE * 8);
            #pragma unroll
            for (int i = 0; i < 8; i++) vn[i] = pack2(d[2 * i], d[2 * i + 1]);
            }
            if (s >= 0) {
                {
                    FRESH(lane);
                    mbar_wait(bar + B_XS * 8, s & 1);
                    if (w == 0 && lane == 0) mbar_expect(bar + B_XS * 8, 12288);
                    const uint32_t a = sb + SM_XS + (w >> 1) * 1536 + lane * 16 + (w & 1) * 8;
                    if (w == 0) xsoftmax<2>(a, lane >> 2, lane & 3);
                    else if (w == 1) xsoftmax<3>(a, lane >> 2, lane & 3);
                    else if (w == 2) xsoftmax<4>(a, lane >> 2, lane & 3);
                    else xsoftmax<5>(a, lane >> 2, lane & 3);
                }
                TR(8);
                bar_sync(7, 128);
                FRESH(lane);
                bf16* orow = g_ox + (size_t)(s * 32 + (lane >> 2)) * HD + h * DH + p * 64 + w * 16 + 2 * (lane & 3);
                {
                    const uint32_t pa = sb + SM_XS + lane * 16;
                    #pragma unroll
                    for (int mi = 0; mi < 2; mi++) {
                        float oa[4] = {0.f, 0.f, 0.f, 0.f}, ob[4] = {0.f, 0.f, 0.f, 0.f};
                        if (mi == 0) {
                            const uint4 p0 = lds4(pa);
                            const uint32_t p3 = lds1(pa + 1024 + 8);
                            mma8(oa, vm0, vm1, p0.x);
                            mma8(ob, vm0, vm1, p0.z);
                            mma16(oa, vx[0], vx[1], vx[2], vx[3], p0.y, 0u);
                            mma16(ob, vx[0], vx[1], vx[2], vx[3], p0.w, p3);
                        } else {
                            const uint4 p1 = lds4(pa + 1536), p2 = lds4(pa + 2560);
                            const uint32_t p4 = lds1(pa + 3584 + 8);
                            mma8(oa, vm0, vm1, p1.x);
                            mma8(ob, vm0, vm1, p1.z);
                            mma16(oa, vx[0], vx[1], vx[2], vx[3], p1.y, p2.x);
                            mma16(ob, vx[0], vx[1], vx[2], vx[3], p1.w, p2.z);
                            mma16(oa, vx[4], vx[5], vx[6], vx[7], p2.y, 0u);
                            mma16(ob, vx[4], vx[5], vx[6], vx[7], p2.w, p4);
                            if (lane < 3) mbar_arrive_remote(mapa(bar + B_XSFREE * 8, lane));
                        }
                        const uint32_t u0 = movm(pack2(oa[0], oa[1])), u1 = movm(pack2(oa[2], oa[3]));
                        const uint32_t u2 = movm(pack2(ob[0], ob[1])), u3 = movm(pack2(ob[2], ob[3]));
                        bf16* dst = orow + (size_t)(16 * mi) * HD;
                        *(uint32_t*)dst = u0;
                        *(uint32_t*)(dst + 8) = u1;
                        *(uint32_t*)(dst + 8 * HD) = u2;
                        *(uint32_t*)(dst + 8 * HD + 8) = u3;
                    }
                }
                TR(9);
                if (s == NSEG - 1) {
                    bar_sync(7, 128);
                    if (w == 3 && lane == 0) { signal_cnt(C_REC + 15); T2(400 + b); }
                    break;
                }
            }
            #pragma unroll
            for (int i = 0; i < 8; i++) vx[i] = vn[i];
            if (s >= 0) mbar_wait_cluster(bar + B_XSFREE * 8, s & 1);
            bar_sync(8, 384);
            TR(10);
            if (w < 3) xscores<2>(sb, p, w > 0, w == 2 ? 3 : 1, lane);
            TR(11);
            if (s < 0) { bar_sync(0, 512); asm volatile("griddepcontrol.launch_dependents;" ::: "memory"); }
        }
    } else {
        asm volatile("setmaxnreg.dec.sync.aligned.u32 48;");
        const int w = warp & 3, lt = tid & 127;
        if (b == 91) { if (lt < C_NUM) g_cnt[lt * 32] = 0u; __threadfence(); }
        if (b < 80) {
            #pragma unroll
            for (int i = 0; i < 2; i++) {
                const int idx = lt + i * 128, sl = idx >> 6, pg = (idx >> 5) & 1, wd = idx & 31;
                st_relaxed1(g_buf2 + (sl * 3 + (b >> 5)) * 2048 + pg * 1024 + (b & 31) * 32 + wd, 0xFFFFFFFFu);
            }
            __threadfence();
        }
        if (lane == 0 && w < 3) {
            int c = 0;
            if (w == 0) c = probe_blk(g_buf2 + 640 + (b & 31) * 8);
            else if (b < 80) c = probe_blk(g_buf1 + (b * 2 + (w - 1)) * 2048);
            else if (b < 92 && w == 1) c = probe_blk(g_buf2 + (b - 80) * 2048 + 960);
            asm volatile("st.shared.u8 [%0], %1;" :: "r"(sb + SM_CH + 96 + w), "r"(c) : "memory");
        }
        if (w == 0) T3(4);
        bar_sync(3, 128);
        uint32_t selmask;
        {
            const uint32_t c3 = lds1(sb + SM_CH + 96);
            const uint32_t cr = c3 & 1u, c1 = (c3 >> 8) & 1u, c2 = (c3 >> 16) & 1u;
            if (lt == 0 && b < 92) st_release1(&g_choice[b], (epoch << 2) | (b < 80 ? (c1 | (c2 << 1)) : (c1 ^ cr)));
            bar_sync(10, 256);
            if (w == 3) {
                if (lane == 0) { fence_async(); mbar_expect(bar + B_WO * 8, ntile * 6144 - 8192); }
                __syncwarp();
                if (lane < ntile) {
                    #pragma unroll
                    for (int e3 = 0; e3 < 3; e3++) {
                        const bool part = lane >= 8 && lane < 12;
                        if (part && e3 == 1) continue;
                        tma2d(sb + SM_WO + wo_tile_off(lane) + ((part && e3 == 2) ? 1 : e3) * 2048, &maps.wo,
                              (tile0 + lane) * 16, h * DH + ((e3 + p) % 3) * 64, bar + B_WO * 8);
                    }
                }
                __syncwarp();
            }
            if (w == 0) T3(5);
            if (lt < 92) {
                uint32_t v, guard = 0;
                while (true) {
                    v = ld_acquire1(&g_choice[lt]);
                    if ((v >> 2) == (epoch & 0x3fffffffu)) break;
                    __nanosleep(100);
                    if (++guard > (1u << 22)) __trap();
                }
                asm volatile("st.shared.u8 [%0], %1;" :: "r"(sb + SM_CH + lt), "r"(v & 3u) : "memory");
            }
            if (w == 0) T3(6);
            bar_sync(3, 128);
            selmask = (c1 << 12) | (c2 << 13);
            for (int i = 0; i < 12; i++) {
                uint32_t c; asm volatile("ld.shared.u8 %0, [%1];" : "=r"(c) : "r"(sb + SM_CH + 80 + i) : "memory");
                selmask |= ((c ^ cr) & 1u) << i;
            }
        }
        mbar_wait(bar + B_WO * 8, 0);
        if (w == 0) T3(8);
        bar_sync(0, 512);
        if (w == 0) T3(9);
        asm volatile("griddepcontrol.launch_dependents;" ::: "memory");
        const bool has_tile = (12 + w) < ntile;
        uint32_t t6 = 0;
        for (int s = 0; s < NSEG; s++) {
            const uint32_t par = s & 1;
            FRESH(lane);
            const int g = lane >> 2, t = lane & 3, lt = w * 32 + lane;
            if (s == 0) {
                mbar_wait(bar + B_HLO_FREE * 8, par);
                for (int k = lt; k < DM; k += 128) {
                    uint32_t v[4];
                    #pragma unroll
                    for (int i = 0; i < 4; i++) {
                        uint32_t lo = *(const uint16_t*)(mem0 + (2 * i) * DM + k), hi = *(const uint16_t*)(mem0 + (2 * i + 1) * DM + k);
                        v[i] = lo | (hi << 16);
                    }
                    asm volatile("st.shared.v4.u32 [%0], {%1,%2,%3,%4};" :: "r"(sb + SM_HB + k * 16), "r"(v[0]), "r"(v[1]), "r"(v[2]), "r"(v[3]) : "memory");
                }
            } else {
                const int sl = s & 3;
                const char* q = (const char*)g_buf2 + sl * 3 * 8192 + lt * 16;
                const uint32_t sm = selmask >> (sl * 3);
                const char* q0 = q + (sm & 1) * 4096;
                const char* q1 = q + 8192 + (sm & 2) * 2048;
                const char* q2 = q + 16384 + (sm & 4) * 1024;
                const uint32_t dst = sb + SM_HB + lt * 16;
                uint32_t guard = 0;
                if (!H2_EARLY) mbar_wait(bar + B_HLO_FREE * 8, par);
                TR(10);
                {
                    uint4 v0 = ld_relaxed4(q0), v1 = ld_relaxed4(q0 + 2048), v2 = ld_relaxed4(q1), v3 = ld_relaxed4(q1 + 2048), v4 = ld_relaxed4(q2);
                    while (true) {
                        const bool k0 = oks(v0), k1 = oks(v1), k2 = oks(v2), k3 = oks(v3), k4 = oks(v4);
                        if (__all_sync(0xffffffffu, k0 && k1 && k2 && k3 && k4)) break;
                        if (!k0) v0 = ld_relaxed4(q0);
                        if (!k1) v1 = ld_relaxed4(q0 + 2048);
                        if (!k2) v2 = ld_relaxed4(q1);
                        if (!k3) v3 = ld_relaxed4(q1 + 2048);
                        if (!k4) v4 = ld_relaxed4(q2);
                        if (++guard > (1u << 22)) __trap();
                    }
                    if (H2_EARLY) mbar_wait(bar + B_HLO_FREE * 8, par);
                    sts4(dst, v0); sts4(dst + 2048, v1); sts4(dst + 4096, v2); sts4(dst + 6144, v3); sts4(dst + 8192, v4);
                }
            }
            fence_async();
            __syncwarp();
            if (lane == 0) mbar_arrive(bar + B_MEM_FULL * 8);
            if (b == 0 && lt == 0) T2(300 + s);
            if (s == 0 && lt == 0) T2(200 + b);
            TR(0);
            if (w == 2) {
                mbar_wait(bar + B_MS * 8, par);
                TR(1);
                if (lane == 0) mbar_expect(bar + B_MS * 8, 3840);
                uint32_t pb[5];
                float sc[5][2];
                {
                    const uint32_t a = sb + SM_MS + lane * 8;
                    float2 u[5], v[5];
                    #pragma unroll
                    for (int j = 0; j < 5; j++) { u[j] = lds2f(a + j * 256); v[j] = lds2f(a + j * 256 + 1280); }
                    #pragma unroll
                    for (int j = 0; j < 5; j++) { sc[j][0] = u[j].x + v[j].x; sc[j][1] = u[j].y + v[j].y; }
                    #pragma unroll
                    for (int j = 0; j < 5; j++) u[j] = lds2f(a + j * 256 + 2560);
                    #pragma unroll
                    for (int j = 0; j < 5; j++) { sc[j][0] += u[j].x; sc[j][1] += u[j].y; }
                }
                softmax_core<5, false>(sc, g, t, pb);
                #pragma unroll
                for (int j = 0; j < 5; j++) sts1(sb + SM_PM + j * 128 + lane * 4, pb[j]);
                bar_arrive(5, 160);
                TR(2);
            }
            const uint32_t tag = (uint32_t)(s % 15) + 1u;
            if (s < NSEG - 1) {
                if (w == 3) {
                    const char* src = (const char*)g_ht + (size_t)(s + 1) * 40960;
                    if (s == 0) {
                        uint32_t guard = 0;
                        while (true) {
                            const uint32_t f0 = lane > 0 ? ld_acquire1(&g_hflag[lane]) : epoch, f1 = ld_acquire1(&g_hflag[32 + lane]);
                            if (__all_sync(0xffffffffu, f0 == epoch && f1 == epoch)) break;
                            if (++guard > (1u << 22)) __trap();
                        }
                        asm volatile("fence.proxy.async.global;" ::: "memory");
                        __syncwarp();
                        if (V_FIRST < 16 && b == 95 && lane == 0) signal_cnt(C_H);
                        __syncwarp();
                    }
                    mbar_wait(bar + B_HHI_FREE * 8, par);
                    if (lane == 0) {
                        mbar_expect(bar + B_HHI_FULL * 8, 28672);
                        bulk_g2s(sb + SM_HB + 12288, src + 12288, 28672, sb + SM_BAR + B_HHI_FULL * 8);
                        const uint32_t vb = (s + 1) >> 2;
                        if (V_FIRST < 16 && (s == 0 || lds1(sb + SM_CH + 112) <= vb))
                            sts1(sb + SM_CH + 112, ld_acquire1(g_cnt + (C_V + vb) * 32) >= 48u ? vb + 1 : 0u);
                    }
                    mbar_wait(bar + B_MEM_FREE * 8, par);
                    if (lane == 0) {
                        mbar_expect(bar + B_HLO_FULL * 8, 12288);
                        bulk_g2s(sb + SM_HB, src, 12288, sb + SM_BAR + B_HLO_FULL * 8);
                    }
                    __syncwarp();
                }
                if (has_tile) wo_phase<0, 4>(sb, warp, lane, nullptr, par, tag, tile0 + warp, h);
                TR(4);
                bar_sync(6, 512);
            }
            if (s < NSEG - 1) {
                t6 = clk32();
                while (clk32() - t6 < H1_DELAY);
                if (b < 80) {
                    FRESH(lane);
                    const char* rin0 = (const char*)g_buf1 + (size_t)(b * 2) * 8192 + ((selmask >> 12) & 1) * 4096 + (lane >> 2) * 256 + w * 64 + (lane & 3) * 16;
                    const char* rin1 = (const char*)g_buf1 + (size_t)(b * 2 + 1) * 8192 + ((selmask >> 13) & 1) * 4096 + (lane >> 2) * 256 + w * 64 + (lane & 3) * 16;
                    const int col = b * 8 + 2 * w + ((lane >> 1) & 1), wd = 2 * (lane & 1) + (lane >> 4);
                    const int sl = (lane & 8) ? ((s + 3) & 3) : ((s + 1) & 3);
                    uint32_t* dst = g_buf2 + (sl * 3 + (col >> 8)) * 2048 + ((lane >> 2) & 1) * 1024 + (col & 255) * 4 + wd;
                    asm volatile("" : "+l"(dst));
                    uint4 v0, v1, v2, v3;
                    uint32_t guard = 0;
                    v0 = ld_relaxed4(rin0); v1 = ld_relaxed4(rin0 + 2048);
                    v2 = ld_relaxed4(rin1); v3 = ld_relaxed4(rin1 + 2048);
                    while (true) {
                        const bool k0 = ok4(v0, tag), k1 = ok4(v1, tag), k2 = ok4(v2, tag), k3 = ok4(v3, tag);
                        if (__all_sync(0xffffffffu, k0 && k1 && k2 && k3)) break;
                        if (!k0) v0 = ld_relaxed4(rin0);
                        if (!k1) v1 = ld_relaxed4(rin0 + 2048);
                        if (!k2) v2 = ld_relaxed4(rin1);
                        if (!k3) v3 = ld_relaxed4(rin1 + 2048);
                        if (++guard > (1u << 22)) __trap();
                    }
                    TR(11);
                    const float a0 = (uf(v0.x) + uf(v1.x)) + (uf(v2.x) + uf(v3.x)), a1 = (uf(v0.y) + uf(v1.y)) + (uf(v2.y) + uf(v3.y));
                    const float a2 = (uf(v0.z) + uf(v1.z)) + (uf(v2.z) + uf(v3.z)), a3 = (uf(v0.w) + uf(v1.w)) + (uf(v2.w) + uf(v3.w));
                    const bool u16 = lane & 16;
                    float m0 = (u16 ? a2 : a0) + __shfl_xor_sync(0xffffffffu, u16 ? a0 : a2, 16);
                    float m1 = (u16 ? a3 : a1) + __shfl_xor_sync(0xffffffffu, u16 ? a1 : a3, 16);
                    m0 += __shfl_xor_sync(0xffffffffu, m0, 8); m1 += __shfl_xor_sync(0xffffffffu, m1, 8);
                    m0 += __shfl_xor_sync(0xffffffffu, m0, 4); m1 += __shfl_xor_sync(0xffffffffu, m1, 4);
                    st_relaxed1(dst, (lane & 8) ? 0xFFFFFFFFu : pack2(m0, m1));
                    TR(12);
                }
            }
        }
    }
    cluster_sync();
}

constexpr int G_STAGES = 6;
constexpr int G_STAGE_BYTES = 32768;
constexpr int G_SMEM = G_STAGES * G_STAGE_BYTES + 1024 + 256 + 2048 + 5120 + 20480;

template <int TA, int TB>
__device__ __forceinline__ void wg_ss128(float* d, uint64_t da, uint64_t db, int sc) {
    asm volatile("{\n\t.reg .pred p;\n\tsetp.ne.b32 p, %66, 0;\n\t"
        "wgmma.mma_async.sync.aligned.m64n128k16.f32.bf16.bf16 "
        "{%0,%1,%2,%3,%4,%5,%6,%7,%8,%9,%10,%11,%12,%13,%14,%15,%16,%17,%18,%19,%20,%21,%22,%23,%24,%25,%26,%27,%28,%29,%30,%31,"
        "%32,%33,%34,%35,%36,%37,%38,%39,%40,%41,%42,%43,%44,%45,%46,%47,%48,%49,%50,%51,%52,%53,%54,%55,%56,%57,%58,%59,%60,%61,%62,%63}, "
        "%64, %65, p, 1, 1, %67, %68;\n\t}"
        : "+f"(d[0]), "+f"(d[1]), "+f"(d[2]), "+f"(d[3]), "+f"(d[4]), "+f"(d[5]), "+f"(d[6]), "+f"(d[7]),
          "+f"(d[8]), "+f"(d[9]), "+f"(d[10]), "+f"(d[11]), "+f"(d[12]), "+f"(d[13]), "+f"(d[14]), "+f"(d[15]),
          "+f"(d[16]), "+f"(d[17]), "+f"(d[18]), "+f"(d[19]), "+f"(d[20]), "+f"(d[21]), "+f"(d[22]), "+f"(d[23]),
          "+f"(d[24]), "+f"(d[25]), "+f"(d[26]), "+f"(d[27]), "+f"(d[28]), "+f"(d[29]), "+f"(d[30]), "+f"(d[31]),
          "+f"(d[32]), "+f"(d[33]), "+f"(d[34]), "+f"(d[35]), "+f"(d[36]), "+f"(d[37]), "+f"(d[38]), "+f"(d[39]),
          "+f"(d[40]), "+f"(d[41]), "+f"(d[42]), "+f"(d[43]), "+f"(d[44]), "+f"(d[45]), "+f"(d[46]), "+f"(d[47]),
          "+f"(d[48]), "+f"(d[49]), "+f"(d[50]), "+f"(d[51]), "+f"(d[52]), "+f"(d[53]), "+f"(d[54]), "+f"(d[55]),
          "+f"(d[56]), "+f"(d[57]), "+f"(d[58]), "+f"(d[59]), "+f"(d[60]), "+f"(d[61]), "+f"(d[62]), "+f"(d[63])
        : "l"(da), "l"(db), "r"(sc), "n"(TA), "n"(TB));
}

#define SP0_LAST 12
#define SP2_LAST 6
#define SP0_14 3
#define SP2_14 3
#define NJ_REG 16
#define NJ_14 16
#define HB1 14
#define HB2 14
#define ORD 1
#define G0F 36
enum { J_MOD = 0, J_G0, J_LN, J_G1, J_G2, J_FIN, J_END, J_V };
__host__ __device__ constexpr int sp0(int b) { return b >= 15 ? SP0_LAST : (b == 14 ? SP0_14 : 3); }
__host__ __device__ constexpr int sp2(int b) { return b >= 15 ? SP2_LAST : (b == 14 ? SP2_14 : 3); }
__host__ __device__ constexpr int njr(int b) { return sp0(b) > 3 ? 16 * (sp0(b) / 3) : (b >= 14 ? NJ_14 : NJ_REG); }
__host__ __device__ constexpr int njf(int b) { return sp2(b) > 3 ? 16 * (sp2(b) / 3) : (b >= 14 ? NJ_14 : NJ_REG); }
__host__ __device__ constexpr int ng0(int b) { return (b >= 15 && 5 * sp0(b) > G0F) ? 10 * sp0(b) - G0F : 5 * sp0(b); }
struct JobTab { uint32_t n; uint32_t j[1790]; };
constexpr uint32_t mkjob(int ty, int b, int n, int k0, int nk, int ks) {
    return (uint32_t)(ty | (b << 3) | (n << 7) | (k0 << 11) | (nk << 18) | (ks << 25));
}
constexpr void add_jobs(JobTab& t, int ty, int b) {
    if (b < 0 || b > 15) return;
    if (ty == J_V) { for (int n = 0; n < 48; n++) t.j[t.n++] = mkjob(ty, b, 0, n, 10, 0); return; }
    if (ty == J_G0) { for (int ks = 0; ks < sp0(b); ks++) for (int n = 0; n < 5; n++) {
        const int hf = b >= 15 && ks * 5 + n >= G0F;
        for (int h = hf; h <= 2 * hf; h++) t.j[t.n++] = mkjob(ty, b, n, ks * (96 / sp0(b)), 96 / sp0(b), ks) | ((uint32_t)h << 29); } }
    else if (ty == J_G2) { for (int h = (b >= HB2); h <= 2 * (b >= HB2); h++) for (int ks = 0; ks < sp2(b); ks++) for (int n = 0; n < 5; n++)
        t.j[t.n++] = mkjob(ty, b, n, ks * (24 / sp2(b)), 24 / sp2(b), ks) | ((uint32_t)h << 29); }
    else if (ty == J_G1) { for (int h = (b >= HB1); h <= 2 * (b >= HB1); h++) for (int n = 0; n < 12; n++) t.j[t.n++] = mkjob(ty, b, n, 0, 10, 0) | ((uint32_t)h << 29); }
    else { for (int n = 0; n < (ty == J_LN ? njr(b) : njf(b)); n++) t.j[t.n++] = mkjob(ty, b, 0, n, (ty == J_LN ? njr(b) : njf(b)) > 8 ? 1 : 2, ty == J_LN ? sp0(b) : sp2(b)); }
}
constexpr JobTab make_tab() {
    JobTab t = {};
    for (int b = V_FIRST; b < V_AHEAD; b++) add_jobs(t, J_V, b);
    for (int i = 20; i < 60; i++) t.j[t.n++] = mkjob(J_MOD, 0, 0, i, 0, 0);
    for (int b = 0; b < 15; b++) {
        add_jobs(t, J_V, b + V_AHEAD);
        add_jobs(t, J_G0, b); add_jobs(t, J_G1, b - 1); add_jobs(t, J_FIN, b - 2); add_jobs(t, J_G2, b - 1); if (!ORD || b < 14) add_jobs(t, J_LN, b);
    }
    if (ORD) {
        if (ORD == 2) add_jobs(t, J_FIN, 13);
        add_jobs(t, J_G0, 15); add_jobs(t, J_LN, 14); if (ORD == 1) add_jobs(t, J_FIN, 13);
        if (ORD == 4) { add_jobs(t, J_LN, 15); add_jobs(t, J_G1, 14); add_jobs(t, J_G1, 15); add_jobs(t, J_G2, 14); }
        else { add_jobs(t, J_G1, 14); add_jobs(t, J_LN, 15); add_jobs(t, J_G2, 14); add_jobs(t, J_G1, 15); }
        if (ORD >= 3) add_jobs(t, J_FIN, 13);
        add_jobs(t, J_FIN, 14); add_jobs(t, J_G2, 15); add_jobs(t, J_FIN, 15);
        return t;
    }
    add_jobs(t, J_FIN, 13); add_jobs(t, J_G1, 14);
    add_jobs(t, J_G0, 15); add_jobs(t, J_G2, 14); add_jobs(t, J_LN, 15); add_jobs(t, J_FIN, 14);
    add_jobs(t, J_G1, 15); add_jobs(t, J_G2, 15); add_jobs(t, J_FIN, 15);
    return t;
}
__constant__ JobTab c_jobs = make_tab();

__device__ __forceinline__ bool cnt_ge(int idx, uint32_t target) { return ld_acquire1(g_cnt + idx * 32) >= target; }
__device__ __forceinline__ void cnt_wait(int idx, uint32_t target) {
    uint32_t guard = 0;
    while (!cnt_ge(idx, target)) { __nanosleep(64); if (++guard > (1u << 22)) __trap(); }
}

template <int TV>
__device__ __forceinline__ void mainloop(float* d, uint32_t sb, uint32_t bars, int cw, int lane, int nk, uint32_t& st, uint32_t& ph) {
    uint32_t pst = 0;
    for (int kb = 0; kb < nk; kb++) {
        mbar_wait(bars + st * 8, ph);
        const uint32_t a = sb + st * G_STAGE_BYTES;
        const uint64_t da = make_desc(a + (TV ? 16384 : 0) + cw * 8192, 16, 1024, 1);
        const uint64_t db = TV ? make_desc(a, 16, 1024, 1) : make_desc(a + 16384, 8192, 1024, 1);
        wg_fence();
        #pragma unroll
        for (int k = 0; k < 4; k++) wg_ss128<TV, 1 - TV>(d, da + (uint64_t)(k * (TV ? 128 : 2)), db + (uint64_t)(k * (TV ? 2 : 128)), 1);
        wg_commit();
        if (kb > 0) {
            wg_wait<1>();
            if (lane == 0) mbar_arrive(bars + 64 + pst * 8);
        }
        pst = st;
        if (++st == G_STAGES) { st = 0; ph ^= 1; }
    }
    wg_wait<0>();
    if (lane == 0) mbar_arrive(bars + 64 + pst * 8);
}
struct SMaps { CUtensorMap ox, wo, h2, w1, act, w2, wv, h2h, acth, oxh; };

__global__ void __launch_bounds__(384, 1)
k_side(const __grid_constant__ SMaps maps, const bf16* __restrict__ xin, const bf16* __restrict__ cvec,
       const bf16* __restrict__ wmod, bf16* __restrict__ outp) {
    extern __shared__ uint8_t smem_raw[];
    const uint32_t sb = (smem_u32(smem_raw) + 1023u) & ~1023u;
    const uint32_t bars = sb + G_STAGES * G_STAGE_BYTES;
    float* red = (float*)(smem_raw + (bars + 256 - smem_u32(smem_raw)));
    const int tid = threadIdx.x, lane = tid & 31, wg = tid >> 7;
    if (tid == 0) T2(500 + blockIdx.x);
    if (tid == 0) {
        for (int i = 0; i < G_STAGES; i++) { mbar_init(bars + i * 8, 1); mbar_init(bars + 64 + i * 8, 8); }
        for (int i = 0; i < 2; i++) { mbar_init(bars + 128 + i * 8, 1); mbar_init(bars + 144 + i * 8, 8); }
        asm volatile("fence.mbarrier_init.release.cluster;" ::: "memory");
    }
    __syncthreads();
    if (wg == 0) {
        if (tid == 0) {
            uint32_t st = 0, ph = 1;
            bool have_h = false;
            for (uint32_t it = 0;; it++) {
                const uint32_t ji = atomicAdd(g_cnt + C_Q * 32, 1u);
                const uint32_t job = ji < c_jobs.n ? c_jobs.j[ji] : (uint32_t)J_END;
                if (ji == 0) g_epoch = g_epoch + 1u;
                const int ty = job & 7, b = (job >> 3) & 15, n = (job >> 7) & 15, k0 = (job >> 11) & 127, nk = (job >> 18) & 127;
                const uint32_t sl = it & 1;
                mbar_wait(bars + 144 + sl * 8, ((it >> 1) & 1) ^ 1);
                sts1(bars + 160 + sl * 4, job);
                if (ty == J_V) {
                    mbar_arrive(bars + 128 + sl * 8);
                    if (!have_h) { cnt_wait(C_H, 1u); asm volatile("fence.proxy.async.global;" ::: "memory"); have_h = true; }
                    T2(1024 + ji * 4 + 1);
                    for (int i = 0; i < 10; i++) {
                        const uint32_t a = sb + st * G_STAGE_BYTES;
                        mbar_wait(bars + 64 + st * 8, ph);
                        mbar_expect(bars + st * 8, G_STAGE_BYTES);
                        #pragma unroll
                        for (int q = 0; q < 4; q++) bulk_g2s(a + q * 4096, (const char*)g_ht + (size_t)(b * 4 + q) * 40960 + i * 4096, 4096, bars + st * 8);
                        tma2d(a + 16384, &maps.wv, k0 * 128, i * 64, bars + st * 8);
                        tma2d(a + 16384 + 8192, &maps.wv, k0 * 128 + 64, i * 64, bars + st * 8);
                        if (++st == G_STAGES) { st = 0; ph ^= 1; }
                    }
                } else if (ty == J_G0 || ty == J_G1 || ty == J_G2) {
                    if (b >= PRING && ty != J_G1) cnt_wait((ty == J_G0 ? C_LN : C_FIN) + b - PRING, njr(b - PRING));
                    mbar_arrive(bars + 128 + sl * 8);
                    const uint32_t hm = job >> 29, hoff = hm >> 1, txb = hm ? G_STAGE_BYTES - 8192 : G_STAGE_BYTES;
                    const CUtensorMap* mA = ty == J_G0 ? (hm ? &maps.oxh : &maps.ox) : (ty == J_G1 ? (hm ? &maps.h2h : &maps.h2) : (hm ? &maps.acth : &maps.act));
                    const CUtensorMap* mB = ty == J_G0 ? &maps.wo : (ty == J_G1 ? &maps.w1 : &maps.w2);
                    const int didx = ty == J_G0 ? C_REC + b : (ty == J_G1 ? C_LN + b : C_G1 + b);
                    const uint32_t dtgt = ty == J_G0 ? 96u : (ty == J_G1 ? (uint32_t)njr(b) : (b >= HB1 ? 24u : 12u));
                    int pre = 0;
                    if (!cnt_ge(didx, dtgt)) {
                        pre = nk < G_STAGES ? nk : G_STAGES;
                        uint32_t s2 = st, p2 = ph;
                        for (int i = 0; i < pre; i++) {
                            mbar_wait(bars + 64 + s2 * 8, p2);
                            const uint32_t a = sb + s2 * G_STAGE_BYTES;
                            mbar_expect(bars + s2 * 8, txb);
                            tma2d(a + 16384, mB, n * 128, (k0 + i) * 64, bars + s2 * 8);
                            tma2d(a + 16384 + 8192, mB, n * 128 + 64, (k0 + i) * 64, bars + s2 * 8);
                            if (++s2 == G_STAGES) { s2 = 0; p2 ^= 1; }
                        }
                        cnt_wait(didx, dtgt);
                    }
                    asm volatile("fence.proxy.async.global;" ::: "memory");
                    T2(1024 + ji * 4 + 1);
                    for (int i = 0; i < nk; i++) {
                        const uint32_t a = sb + st * G_STAGE_BYTES;
                        if (i >= pre) {
                            mbar_wait(bars + 64 + st * 8, ph);
                            mbar_expect(bars + st * 8, txb);
                        }
                        tma2d(a + hoff * 8192, mA, (k0 + i) * 64, b * 128 + hoff * 64, bars + st * 8);
                        if (i >= pre) {
                            tma2d(a + 16384, mB, n * 128, (k0 + i) * 64, bars + st * 8);
                            tma2d(a + 16384 + 8192, mB, n * 128 + 64, (k0 + i) * 64, bars + st * 8);
                        }
                        if (++st == G_STAGES) { st = 0; ph ^= 1; }
                    }
                } else {
                    if (ty == J_LN) { const int rj = 128 / njr(b); bulk_pf(xin + (size_t)(b * 128 + k0 * rj) * DM, rj * DM * 2); cnt_wait(C_MOD, 40u); cnt_wait(C_G0 + b, (uint32_t)ng0(b)); }
                    else if (ty == J_FIN) cnt_wait(C_G2 + b, (b >= HB2 ? 10u : 5u) * sp2(b));
                    if (ji < 1790) T2(1024 + ji * 4 + 1);
                    mbar_arrive(bars + 128 + sl * 8);
                    if (ty == J_END) break;
                }
            }
        }
    } else {
        const int cw = wg - 1, ct = tid - 128, cwarp = ct >> 5;
        uint32_t st = 0, ph = 0;
        uint2* smod = (uint2*)(red + 512);
        bool have_mod = false;
        auto load_mod = [&]() {
            for (int i = ct; i < DM; i += 256) {
                const float4 m = __ldcg((const float4*)(g_mod + 2 * DM + i * 4));
                const float o = (i >= 320 && i < 480) ? 1.0f : 0.0f;
                smod[i] = make_uint2(pack2(m.x + o, m.y + o), pack2(m.z + o, m.w + o));
            }
            bar_sync(1, 256);
            have_mod = true;
        };
        {
            if (ct == 0) red[0] = cnt_ge(C_MOD, 40u) ? 1.0f : 0.0f;
            bar_sync(1, 256);
            const bool rdy = red[0] != 0.0f;
            bar_sync(1, 256);
            if (rdy) load_mod();
        }
        for (uint32_t it = 0;; it++) {
            const uint32_t sl = it & 1;
            mbar_wait(bars + 128 + sl * 8, (it >> 1) & 1);
            const uint32_t job = __shfl_sync(0xffffffffu, lds1(bars + 160 + sl * 4), 0);
            __syncwarp();
            if (lane == 0) mbar_arrive(bars + 144 + sl * 8);
            const int ty = job & 7, b = (job >> 3) & 15, n = (job >> 7) & 15, k0 = (job >> 11) & 127, nk = (job >> 18) & 127, ks = (job >> 25) & 15;
            if (ty == J_END) break;
            int sig = -1;
            if ((job >> 29) && (int)(job >> 30) != cw) {
                for (int kb = 0; kb < nk; kb++) {
                    mbar_wait(bars + st * 8, ph);
                    if (lane == 0) mbar_arrive(bars + 64 + st * 8);
                    if (++st == G_STAGES) { st = 0; ph ^= 1; }
                }
                sig = (ty == J_G0 ? C_G0 : (ty == J_G1 ? C_G1 : C_G2)) + b;
            } else if (ty == J_G0 || ty == J_G1 || ty == J_G2 || ty == J_V) {
                float d[64];
                #pragma unroll
                for (int i = 0; i < 64; i++) d[i] = 0.f;
                if (ty == J_V) mainloop<1>(d, sb, bars, cw, lane, nk, st, ph);
                else mainloop<0>(d, sb, bars, cw, lane, nk, st, ph);
                const int g = lane >> 2, t = lane & 3;
                if (ty == J_V) {
                    uint4* o = g_vx + ((size_t)(b * 4) * 96 + k0 * 2 + cw) * 256 + (ct & 127);
                    #pragma unroll
                    for (int q = 0; q < 8; q++)
                        o[(q >> 1) * 96 * 256 + (q & 1) * 128] = make_uint4(pack2(d[8 * q], d[8 * q + 1]), pack2(d[8 * q + 2], d[8 * q + 3]),
                                                                            pack2(d[8 * q + 4], d[8 * q + 5]), pack2(d[8 * q + 6], d[8 * q + 7]));
                    sig = C_V + b;
                } else if (ty == J_G1) {
                    #pragma unroll
                    for (int hf = 0; hf < 2; hf++) {
                        bf16* o = g_act + (size_t)(b * 128 + cwarp * 16 + g + 8 * hf) * FF + n * 128 + 8 * t;
                        #pragma unroll
                        for (int q = 0; q < 4; q++) {
                            uint32_t u[4];
                            #pragma unroll
                            for (int i = 0; i < 4; i++) {
                                const float a0 = bfr(d[4 * (4 * q + i) + 2 * hf]), a1 = bfr(d[4 * (4 * q + i) + 2 * hf + 1]);
                                u[i] = pack2(__fdividef(a0, 1.0f + __expf(-a0)), __fdividef(a1, 1.0f + __expf(-a1)));
                            }
                            const bool o1 = t & 1, o2 = t & 2;
                            uint32_t x0 = __shfl_xor_sync(0xffffffffu, o1 ? u[0] : u[1], 1), x1 = __shfl_xor_sync(0xffffffffu, o1 ? u[2] : u[3], 1);
                            if (o1) { u[0] = x0; u[2] = x1; } else { u[1] = x0; u[3] = x1; }
                            x0 = __shfl_xor_sync(0xffffffffu, o2 ? u[0] : u[2], 2); x1 = __shfl_xor_sync(0xffffffffu, o2 ? u[1] : u[3], 2);
                            if (o2) { u[0] = x0; u[1] = x1; } else { u[2] = x0; u[3] = x1; }
                            *(uint4*)(o + q * 32) = make_uint4(u[0], u[1], u[2], u[3]);
                        }
                    }
                    sig = C_G1 + b;
                } else {
                    float* o = (ty == J_G0 ? g_p0 : g_p2) + ((size_t)((b % PRING) * PMAX + ks) * 128 + cwarp * 16 + g) * DM + n * 128 + 2 * t;
                    #pragma unroll
                    for (int hf = 0; hf < 2; hf++) {
                        #pragma unroll
                        for (int j = 0; j < 16; j++)
                            *(float2*)(o + hf * 8 * DM + j * 8) = make_float2(d[4 * j + 2 * hf], d[4 * j + 2 * hf + 1]);
                    }
                    sig = (ty == J_G0 ? C_G0 : C_G2) + b;
                }
            } else if (ty == J_MOD) {
                mod_chunk<256, 2>(cvec, wmod, k0 * 64, ct, red);
                sig = C_MOD;
            } else {
                const bool ln = ty == J_LN;
                if (!have_mod) load_mod();
                const uint2* gm = smod + (ln ? 0 : 480) + lane;
                const int wpr = ks / 3, rpj = 8 / wpr, sub = cwarp % wpr;
                float4* rbuf = (float4*)(red + 512 + 1280) + lane;
                for (int r = 0; r < nk; r++) {
                    const int lr = (k0 * nk + r) * rpj + cwarp / wpr, row = b * 128 + lr;
                    const float* pp = (ln ? g_p0 : g_p2) + ((size_t)((b % PRING) * PMAX + sub * 3) * 128 + lr) * DM + lane * 4;
                    const bf16* xs = (ln ? xin : (const bf16*)g_x1) + (size_t)row * DM + lane * 4;
                    float v[5][4];
                    uint2 xv[5];
                    float4 a[3][5];
                    #pragma unroll
                    for (int q = 0; q < 3; q++) {
                        #pragma unroll
                        for (int i = 0; i < 5; i++) a[q][i] = __ldcg((const float4*)(pp + (size_t)q * 128 * DM + i * 128));
                    }
                    #pragma unroll
                    for (int i = 0; i < 5; i++) xv[i] = __ldcg((const uint2*)(xs + i * 128));
                    if (wpr > 1) bar_sync(1, 256);
                    #pragma unroll
                    for (int i = 0; i < 5; i++) {
                        v[i][0] = a[0][i].x + a[1][i].x + a[2][i].x; v[i][1] = a[0][i].y + a[1][i].y + a[2][i].y;
                        v[i][2] = a[0][i].z + a[1][i].z + a[2][i].z; v[i][3] = a[0][i].w + a[1][i].w + a[2][i].w;
                    }
                    if (wpr > 1) {
                        if (sub) {
                            #pragma unroll
                            for (int i = 0; i < 5; i++) rbuf[cwarp * 160 + i * 32] = make_float4(v[i][0], v[i][1], v[i][2], v[i][3]);
                        }
                        bar_sync(1, 256);
                        if (sub) continue;
                        for (int q = 1; q < wpr; q++) {
                            #pragma unroll
                            for (int i = 0; i < 5; i++) {
                                const float4 e = rbuf[(cwarp + q) * 160 + i * 32];
                                v[i][0] += e.x; v[i][1] += e.y; v[i][2] += e.z; v[i][3] += e.w;
                            }
                        }
                    }
                    bf16* dst = (ln ? (bf16*)g_x1 : outp) + (size_t)row * DM + lane * 4;
                    #pragma unroll
                    for (int i = 0; i < 5; i++) {
                        const uint2 gg = gm[i * 32];
                        xv[i].x = hadd2(xv[i].x, hmul2(gg.x, pack2(v[i][0], v[i][1])));
                        xv[i].y = hadd2(xv[i].y, hmul2(gg.y, pack2(v[i][2], v[i][3])));
                        *(uint2*)(dst + i * 128) = xv[i];
                    }
                    if (ln) {
                        uint32_t mb; float rs;
                        ln_stats(xv, mb, rs);
                        #pragma unroll
                        for (int i = 0; i < 5; i++) {
                            const uint2 sh = gm[160 + i * 32], m1 = gm[320 + i * 32];
                            *(uint2*)(g_h2 + (size_t)row * DM + lane * 4 + i * 128) =
                                make_uint2(ln_apply(xv[i].x, mb, rs, m1.x, sh.x), ln_apply(xv[i].y, mb, rs, m1.y, sh.y));
                        }
                    }
                }
                if (ln) sig = C_LN + b; else if (b < 16 - PRING) sig = C_FIN + b;
            }
            if (sig >= 0) {
                bar_sync(1, 256);
                if (ct == 0) signal_cnt(sig);
            }
            if (ct == 0) T2(1024 + ji * 4 + 2);
        }
    }
}

typedef CUresult (*EncodeFn)(CUtensorMap*, CUtensorMapDataType, cuuint32_t, void*, const cuuint64_t*, const cuuint64_t*,
                             const cuuint32_t*, const cuuint32_t*, CUtensorMapInterleave, CUtensorMapSwizzle,
                             CUtensorMapL2promotion, CUtensorMapFloatOOBfill);

static void make_map(EncodeFn fn, CUtensorMap* m, const void* ptr, uint64_t inner, uint64_t outer, uint32_t bi, uint32_t bo,
                     CUtensorMapSwizzle sw = CU_TENSOR_MAP_SWIZZLE_128B) {
    cuuint64_t dims[2] = {inner, outer};
    cuuint64_t strides[1] = {inner * 2};
    cuuint32_t box[2] = {bi, bo};
    cuuint32_t es[2] = {1, 1};
    fn(m, CU_TENSOR_MAP_DATA_TYPE_BFLOAT16, 2, (void*)ptr, dims, strides, box, es, CU_TENSOR_MAP_INTERLEAVE_NONE,
       sw, CU_TENSOR_MAP_L2_PROMOTION_L2_256B, CU_TENSOR_MAP_FLOAT_OOB_FILL_NONE);
}

extern "C" void kernel_launch(void* const* d_in, const int* in_sizes, int n_in, void* d_out, int out_size) {
    const bf16* x = (const bf16*)d_in[0];
    const bf16* mem0 = (const bf16*)d_in[1];
    const bf16* Wq = (const bf16*)d_in[2];
    const bf16* Wk = (const bf16*)d_in[3];
    const bf16* Wv = (const bf16*)d_in[4];
    const bf16* Wo = (const bf16*)d_in[5];
    const bf16* w1 = (const bf16*)d_in[8];
    const bf16* w2 = (const bf16*)d_in[9];
    const bf16* c = (const bf16*)d_in[10];
    const bf16* wmod = (const bf16*)d_in[11];
    bf16* out = (bf16*)d_out;

    static EncodeFn enc = nullptr;
    static void *p_ox, *p_x1, *p_h2, *p_act;
    if (!enc) {
        cudaDriverEntryPointQueryResult qr;
        void* f = nullptr;
        cudaGetDriverEntryPoint("cuTensorMapEncodeTiled", &f, cudaEnableDefault, &qr);
        enc = (EncodeFn)f;
        cudaGetSymbolAddress(&p_ox, g_ox);
        cudaGetSymbolAddress(&p_x1, g_x1);
        cudaGetSymbolAddress(&p_h2, g_h2);
        cudaGetSymbolAddress(&p_act, g_act);
        cudaFuncSetAttribute(k_rec, cudaFuncAttributeMaxDynamicSharedMemorySize, SM_TOTAL);
        cudaFuncSetAttribute(k_side, cudaFuncAttributeMaxDynamicSharedMemorySize, G_SMEM);
    }
    RMaps rm;
    make_map(enc, &rm.wq, Wq, HD, DM, 64, 128);
    make_map(enc, &rm.wk, Wk, HD, DM, 64, 128);
    make_map(enc, &rm.wv, Wv, HD, DM, 64, 128);
    make_map(enc, &rm.wo, Wo, DM, HD, 16, 64, CU_TENSOR_MAP_SWIZZLE_32B);
    make_map(enc, &rm.wop, Wo, DM, HD, 224, 192, CU_TENSOR_MAP_SWIZZLE_NONE);
    SMaps m;
    make_map(enc, &m.ox, p_ox, HD, SEQ, 64, 128);
    make_map(enc, &m.oxh, p_ox, HD, SEQ, 64, 64);
    make_map(enc, &m.wv, Wv, HD, DM, 64, 64);
    make_map(enc, &m.wo, Wo, DM, HD, 64, 64);
    make_map(enc, &m.h2, p_h2, DM, SEQ, 64, 128);
    make_map(enc, &m.w1, w1, FF, DM, 64, 64);
    make_map(enc, &m.act, p_act, FF, SEQ, 64, 128);
    make_map(enc, &m.h2h, p_h2, DM, SEQ, 64, 64);
    make_map(enc, &m.acth, p_act, FF, SEQ, 64, 64);
    make_map(enc, &m.w2, w2, DM, FF, 64, 64);

    cudaStream_t st = cudaStreamPerThread;
    {
        cudaLaunchConfig_t cfg = {};
        cfg.gridDim = dim3(96); cfg.blockDim = dim3(512); cfg.dynamicSmemBytes = SM_TOTAL; cfg.stream = st;
        cudaLaunchAttribute at[2];
        at[0].id = cudaLaunchAttributeClusterDimension;
        at[0].val.clusterDim.x = 3; at[0].val.clusterDim.y = 1; at[0].val.clusterDim.z = 1;
        cfg.attrs = at; cfg.numAttrs = 1;
        cudaLaunchKernelEx(&cfg, k_rec, rm, mem0, Wo, x, c, wmod);
    }
    {
        cudaLaunchConfig_t cfg = {};
        cfg.gridDim = dim3(SIDE_CTAS); cfg.blockDim = dim3(384); cfg.dynamicSmemBytes = G_SMEM; cfg.stream = st;
        cudaLaunchAttribute at[1];
        at[0].id = cudaLaunchAttributeProgrammaticStreamSerialization;
        at[0].val.programmaticStreamSerializationAllowed = 1;
        cfg.attrs = at; cfg.numAttrs = 1;
        cudaLaunchKernelEx(&cfg, k_side, m, x, c, wmod, out);
    }
}
```
